```python
import torch

def _softmax(x, axis=-1):
    return torch.softmax(x, dim=axis)

def _gelu(x):
    return torch.nn.functional.gelu(x, approximate='tanh')

def _silu(x):
    return torch.nn.functional.silu(x)

def _sigmoid(x):
    return torch.sigmoid(x)

def _layernorm(x, axis=-1, eps=1e-05):
    m = x.mean(dim=axis, keepdim=True)
    v = x.var(dim=axis, keepdim=True, unbiased=False)
    return (x - m) / torch.sqrt(v + eps)

def _scatter_add(tgt, idx, src, axis=0):
    return tgt.clone().index_add_(axis, idx, src)

def _segment_sum(src, seg, n):
    out = torch.zeros((n,) + src.shape[1:], dtype=src.dtype)
    return out.index_add_(0, seg, src)

def _pad(x, pw):
    flat = tuple((v for pair in reversed(pw) for v in pair))
    return torch.nn.functional.pad(x, flat)
kernel_name = 'adaLN_cond__spectral_gfnet__mixer_token_mlp__prompt'

def setup_inputs():

    _w = lambda a: (lambda t: t.to(torch.bfloat16) if t.is_floating_point() else t)(torch.as_tensor(a))

    def _A_setup():
        B, S, D = (1, 2048, 576)
        Df = D // 2 + 1
        return {'x': _w((lambda *s: torch.randn(*s, dtype=torch.bfloat16) * 0.05)(B, S, D)), 'w_r': _w((lambda *s: torch.randn(*s, dtype=torch.bfloat16) * 1.6)(S, Df) * 0.02), 'w_i': _w((lambda *s: torch.randn(*s, dtype=torch.bfloat16) * 1.6)(S, Df) * 0.02)}
    _A_in = _A_setup()

    def _B_setup():
        B, S, D, F = (1, 2048, 576, 4608)
        return {'x': _w((lambda *s: torch.randn(*s, dtype=torch.bfloat16) * 0.05)(B, S, D)), 'w1': _w((lambda *s: torch.randn(*s, dtype=torch.bfloat16) * 0.8)(S, F) * S ** (-0.5)), 'b1': _w((lambda *s: torch.randn(*s, dtype=torch.bfloat16) * 12.8)(F) * 0.02), 'w2': _w((lambda *s: torch.randn(*s, dtype=torch.bfloat16) * 0.2)(F, S) * F ** (-0.5)), 'b2': _w((lambda *s: torch.randn(*s, dtype=torch.bfloat16) * 1.6)(S) * 0.02)}
    _B_in = _B_setup()
    return {'A_x': _A_in['x'], 'A_w_r': _A_in['w_r'], 'A_w_i': _A_in['w_i'], 'B_x': _B_in['x'], 'B_w1': _B_in['w1'], 'B_b1': _B_in['b1'], 'B_w2': _B_in['w2'], 'B_b2': _B_in['b2'], 'c': _w((lambda *s: torch.randn(*s, dtype=torch.bfloat16) * 0.1)(1, 576) * 8.0), 'w_mod': _w((lambda *s: torch.randn(*s, dtype=torch.bfloat16) * 0.1)(576, 6 * 576) * 576 ** (-0.5) * 8.0)}

def reference(A_x, A_w_r, A_w_i, B_x, B_w1, B_b1, B_w2, B_b2, c, w_mod):

    def _A_ref(x, w_r, w_i):
        B, S, D = x.shape
        X = (lambda x, axes=(-2, -1): torch.fft.rfft2(x.float(), dim=axes))(x, axes=(-2, -1))
        W = w_r + 1j * w_i
        X = X * W
        y = (lambda x, s, axes=(-2, -1): torch.fft.irfft2(x, s=s, dim=axes).to(torch.bfloat16))(X, (S, D), axes=(-2, -1))
        return y

    def _B_ref(x, w1, b1, w2, b2):
        B, S, D = x.shape
        h = _layernorm(x, axis=-1)
        u = torch.einsum('bsd,sf->bdf', h, w1) + b1
        u = _gelu(u)
        y = torch.einsum('bdf,fs->bds', u, w2) + b2
        return (lambda x, *d: x.permute(*d))(y, 0, 2, 1)
    x = A_x
    mod = (_silu(c) @ w_mod).reshape(c.shape[0], 6, 1, -1)
    sa, ca, ga, sb, cb, gb = (mod[:, 0].clone(), mod[:, 1].clone(), mod[:, 2].clone(), mod[:, 3].clone(), mod[:, 4].clone(), mod[:, 5].clone())
    h = _layernorm(x, axis=-1) * (1 + ca) + sa
    x = x + ga * _A_ref(h, A_w_r, A_w_i)
    h = _layernorm(x, axis=-1) * (1 + cb) + sb
    x = x + gb * _B_ref(h, B_w1, B_b1, B_w2, B_b2)
    return x
```

```cpp
#include <cuda_runtime.h>
#include <cuda_bf16.h>
#include <cuda_fp16.h>
#include <cuda.h>
#include <stdint.h>

namespace {

constexpr int S_ = 2048, D_ = 576, F_ = 4608;
constexpr int NCTA = 132, NTHR = 512;
constexpr int TP = 4640;
constexpr int SPEC_P = 296;
constexpr int NST = 6;
constexpr int A_BYTES = 16384, B_BYTES = 18432;
constexpr int IT_P2 = 32, IT_G2 = 40, IT_END = 76;
constexpr int SPIN_LIMIT = 1 << 22;

constexpr int OFF_A = 0;
constexpr int OFF_B = NST * A_BYTES;
constexpr int OFF_P = OFF_B + NST * B_BYTES;
constexpr int OFF_BAR = OFF_P;
constexpr int OFF_MISC = OFF_P + 256;
constexpr int OFF_GB = OFF_P + 384;
constexpr int OFF_P2R = OFF_P + 1536;
constexpr int SMEM_BYTES = OFF_P2R + 9216 + 1024;
constexpr int QA = 15, QB = 11, QC = 15;
constexpr int TAB_BYTES = (QA + QB + QC) * 512;
constexpr int OFF_TAB = OFF_B;
constexpr int OFF_SPEC = OFF_TAB + TAB_BYTES;
constexpr int OFF_STAGE = OFF_SPEC + 19072;
constexpr int OFF_WRAW = OFF_STAGE + 18432;
constexpr int OFF_B3 = OFF_WRAW + 24576;
constexpr int OFF_MODA = OFF_B3 + 4096;
constexpr int OFF_MODC = OFF_MODA + 2560;
constexpr int OFF_RED = OFF_MODC + 3584;
static_assert(OFF_RED + 1280 <= OFF_P, "scratch overflow");
static_assert(OFF_WRAW % 128 == 0 && OFF_STAGE % 128 == 0, "align");
constexpr int BAR_FULL = 0, BAR_EMPTY = 6, BAR_TAB = 12, BAR_W = 13, BAR_P2GO = 14, BAR_G2GO = 15, BAR_P2R = 16,
              BAR_CANSEND = 17, BAR_RECV = 18, BAR_ROLE = 19;

struct Cos1152 { double c[1152]; };
constexpr double cx_cos(double x) { double t = 1, s = 1; for (int i = 1; i < 14; i++) { t *= -x * x / ((2 * i - 1) * (2 * i)); s += t; } return s; }
constexpr Cos1152 make_cos() {
    Cos1152 r{};
    for (int i = 0; i <= 288; i++) {
        double v = (i == 288) ? 0.0 : cx_cos(3.14159265358979323846 * 2.0 * i / 1152.0);
        r.c[i] = v; r.c[576 - i] = -v; r.c[576 + i] = -v; r.c[(1152 - i) % 1152] = v;
    }
    return r;
}
constexpr uint32_t cx_f2h(double v) {
    uint32_t s = v < 0 ? 0x8000u : 0u; double a = v < 0 ? -v : v;
    if (a < 1e-9) return 0;
    int e = 0;
    while (a >= 2.0) { a *= 0.5; e++; }
    while (a < 1.0 && e > -14) { a *= 2.0; e--; }
    double m = a * 1024.0; uint32_t mi = (uint32_t)m; double fr = m - mi;
    if (fr > 0.5 || (fr == 0.5 && (mi & 1))) mi++;
    return s | (uint32_t)(((e + 14) << 10) + mi);
}
struct Tab { uint32_t w[(QA + QB + QC) * 128]; };
constexpr Tab make_tab() {
    Tab t{};
    Cos1152 ct = make_cos();
    auto C = [&](int num, int den) { return ct.c[(num % den) * (1152 / den)]; };
    auto Sn = [&](int num, int den) { return ct.c[((num % den) * (1152 / den) + 864) % 1152]; };
    auto put = [&](int q0, int idx, int lane, double lo, double hi) { t.w[((q0 + idx / 4) * 32 + lane) * 4 + idx % 4] = cx_f2h(lo) | (cx_f2h(hi) << 16); };
    for (int lane = 0; lane < 32; lane++) {
        const int g = lane >> 2, q = lane & 3;
        for (int mt = 0; mt < 3; mt++) {
            const int ka = 8 * mt + g;
            for (int r = 0; r < 10; r++) {
                const int im = r & 1, i0 = (r >> 1) * 2;
                double v[2] = {0, 0};
                for (int e = 0; e < 2; e++) { int i = i0 + e, d1 = 4 * i + q; if (i < 9 && ka <= 18) v[e] = (im ? -Sn(ka * d1, 36) : C(ka * d1, 36)) / 8; }
                put(0, mt * 10 + r, lane, v[0], v[1]);
            }
            for (int v = 0; v < 2; v++) {
                const int d2 = 4 * q + v;
                put(0, 30 + (mt * 2 + v) * 2, lane, C(ka * d2, 576) * 4 / 3, C(ka * (d2 + 2), 576) * 4 / 3);
                put(0, 31 + (mt * 2 + v) * 2, lane, Sn(ka * d2, 576) * 4 / 3, Sn(ka * (d2 + 2), 576) * 4 / 3);
            }
        }
        for (int v = 0; v < 2; v++) for (int nt = 0; nt < 4; nt++) {
            const int kb = 2 * (g >> 1) + (nt & 1) + 8 * (nt >> 1), part = g & 1; const double sg = kb >= 8 ? -1 : 1;
            double b0[2] = {0, 0}, b1[2] = {0, 0};
            for (int e = 0; e < 2; e++) { int d2 = 4 * q + 2 * e + v; double c = C(kb * d2, 16) / 4, s = Sn(kb * d2, 16) / 4;
                b0[e] = part ? -sg * s : c; b1[e] = part ? sg * c : s; }
            put(0, 42 + (v * 4 + nt) * 2, lane, b0[0], b0[1]); put(0, 43 + (v * 4 + nt) * 2, lane, b1[0], b1[1]);
        }
        for (int part = 0; part < 2; part++) for (int ks = 0; ks < 2; ks++) for (int a = 0; a < 4; a++) {
            const int ka = g + 8 * (a & 1), ja = q + 4 * (2 * ks + (a >> 1)); const double c = C(ka * ja, 16) / 4, s = Sn(ka * ja, 16) / 4;
            put(QA, (part * 2 + ks) * 4 + a, lane, part ? -s : c, part ? c : s);
        }
        for (int h = 0; h < 2; h++) {
            put(QA, 16 + 2 * h, lane, C((g + 8 * h) * (2 * q), 128) / 2, C((g + 8 * h) * (2 * q + 1), 128) / 2);
            put(QA, 17 + 2 * h, lane, Sn((g + 8 * h) * (2 * q), 128) / 2, Sn((g + 8 * h) * (2 * q + 1), 128) / 2);
            put(QA, 23 + 2 * h, lane, C(g * (8 * h + 2 * q), 128), C(g * (8 * h + 2 * q + 1), 128));
            put(QA, 24 + 2 * h, lane, Sn(g * (8 * h + 2 * q), 128), Sn(g * (8 * h + 2 * q + 1), 128));
            for (int nt = 0; nt < 4; nt++) {
                const int ja = 4 * nt + (g >> 1), part = g & 1; double b0[2] = {0, 0}, b1[2] = {0, 0};
                for (int e = 0; e < 2; e++) { int ka = 8 * h + 2 * q + e; double c = C(ja * ka, 16) / 4, s = Sn(ja * ka, 16) / 4;
                    b0[e] = part ? s : c; b1[e] = part ? c : -s; }
                put(QA, 27 + (h * 4 + nt) * 2, lane, b0[0], b0[1]); put(QA, 28 + (h * 4 + nt) * 2, lane, b1[0], b1[1]);
            }
        }
        put(QA, 20, lane, C(g * 2 * q, 8) / 2, C(g * (2 * q + 1), 8) / 2);
        put(QA, 21, lane, Sn(g * 2 * q, 8) / 2, Sn(g * (2 * q + 1), 8) / 2);
        put(QA, 22, lane, -Sn(g * 2 * q, 8) / 2, -Sn(g * (2 * q + 1), 8) / 2);
        for (int m2 = 0; m2 < 2; m2++) {
            const int d2 = 2 * g + m2;
            for (int ks = 0; ks < 2; ks++) for (int a = 0; a < 4; a++) {
                const int kb = 2 * q + (a >> 1) + 8 * ks; const double sg = ks ? -1 : 1, c = C(d2 * kb, 16) / 4, s = Sn(d2 * kb, 16) / 4;
                put(QA + QB, (m2 * 2 + ks) * 4 + a, lane, (a & 1) ? s : c, (a & 1) ? sg * c : -sg * s);
            }
            for (int mt = 0; mt < 3; mt++) {
                const int ka = 8 * mt + 2 * q;
                put(QA + QB, 16 + (m2 * 3 + mt) * 2, lane, C(ka * d2, 576) * 4 / 3, C((ka + 1) * d2, 576) * 4 / 3);
                put(QA + QB, 17 + (m2 * 3 + mt) * 2, lane, Sn(ka * d2, 576) * 4 / 3, Sn((ka + 1) * d2, 576) * 4 / 3);
            }
        }
        for (int mt = 0; mt < 3; mt++) for (int nt = 0; nt < 5; nt++) {
            const int i = 2 * nt + (g & 1), d1 = 4 * i + (g >> 1); double b0[2] = {0, 0}, b1[2] = {0, 0};
            for (int e = 0; e < 2; e++) { int ka = 8 * mt + 2 * q + e;
                if (ka <= 18 && i < 9) { double wt = (ka == 0 || ka == 18) ? 0.125 : 0.25; b0[e] = wt * C(ka * d1, 36); b1[e] = -wt * Sn(ka * d1, 36); } }
            put(QA + QB, 28 + (mt * 5 + nt) * 2, lane, b0[0], b0[1]); put(QA + QB, 29 + (mt * 5 + nt) * 2, lane, b1[0], b1[1]);
        }
    }
    return t;
}
__device__ __align__(128) const Tab g_tab = make_tab();

__device__ __align__(128) uint32_t g_T[128 * TP];
__device__ __align__(128) uint4 g_h3[128 * 1152];
__device__ __align__(128) uint4 g_U[72 * 4 * 1152];
__device__ __align__(128) uint32_t g_mod[3456];
__device__ __align__(128) uint32_t g_cnt[20 * 32];
__device__ __align__(128) uint32_t g_slot[96];
constexpr int CNT_EPOCH = 0, CNT_H3 = 1, CNT_U1 = 2, CNT_U2 = 10;
#define PROFT(i) do {} while (0)
#define PROF0(i) do {} while (0)

__device__ __forceinline__ void mbar_init(uint32_t bar, uint32_t cnt) { asm volatile("mbarrier.init.shared::cta.b64 [%0], %1;" :: "r"(bar), "r"(cnt) : "memory"); }
__device__ __forceinline__ void mbar_expect(uint32_t bar, uint32_t bytes) { asm volatile("mbarrier.arrive.expect_tx.shared::cta.b64 _, [%0], %1;" :: "r"(bar), "r"(bytes) : "memory"); }
__device__ __forceinline__ void mbar_arrive(uint32_t bar) { asm volatile("mbarrier.arrive.shared::cta.b64 _, [%0];" :: "r"(bar) : "memory"); }
__device__ __forceinline__ void mbar_arrive_n(uint32_t bar, uint32_t n) { asm volatile("mbarrier.arrive.shared::cta.b64 _, [%0], %1;" :: "r"(bar), "r"(n) : "memory"); }
__device__ __forceinline__ void mbar_arrive_remote(uint32_t rbar) { asm volatile("mbarrier.arrive.release.cluster.shared::cluster.b64 _, [%0];" :: "r"(rbar) : "memory"); }
__device__ __forceinline__ void mbar_wait(uint32_t bar, uint32_t parity) {
    uint32_t ok; int it = 0;
    do { asm volatile("{.reg .pred p; mbarrier.try_wait.parity.shared::cta.b64 p, [%1], %2; selp.u32 %0, 1, 0, p;}" : "=r"(ok) : "r"(bar), "r"(parity) : "memory");
         if (++it > SPIN_LIMIT) __trap(); } while (!ok);
}
__device__ __forceinline__ void mbar_wait_cluster(uint32_t bar, uint32_t parity) {
    uint32_t ok; int it = 0;
    do { asm volatile("{.reg .pred p; mbarrier.try_wait.parity.acquire.cluster.shared::cta.b64 p, [%1], %2; selp.u32 %0, 1, 0, p;}" : "=r"(ok) : "r"(bar), "r"(parity) : "memory");
         if (++it > SPIN_LIMIT) __trap(); } while (!ok);
}
__device__ __forceinline__ uint32_t mapa(uint32_t a, uint32_t rank) { uint32_t r; asm("mapa.shared::cluster.u32 %0, %1, %2;" : "=r"(r) : "r"(a), "r"(rank)); return r; }
__device__ __forceinline__ void bar_sync(int id, int n) { asm volatile("bar.sync %0, %1;" :: "r"(id), "r"(n) : "memory"); }
__device__ __forceinline__ void bulk_load(uint32_t dst, const void* src, uint32_t bytes, uint32_t bar) {
    asm volatile("cp.async.bulk.shared::cluster.global.mbarrier::complete_tx::bytes [%0], [%1], %2, [%3];" :: "r"(dst), "l"(src), "r"(bytes), "r"(bar) : "memory"); }
__device__ __forceinline__ void tma2(uint32_t dst, const CUtensorMap* m, int c0, int c1, uint32_t bar) {
    asm volatile("cp.async.bulk.tensor.2d.shared::cluster.global.mbarrier::complete_tx::bytes [%0], [%1, {%3, %4}], [%2];" :: "r"(dst), "l"(m), "r"(bar), "r"(c0), "r"(c1) : "memory"); }
__device__ __forceinline__ void tma3(uint32_t dst, const CUtensorMap* m, int c0, int c1, int c2, uint32_t bar) {
    asm volatile("cp.async.bulk.tensor.3d.shared::cluster.global.mbarrier::complete_tx::bytes [%0], [%1, {%3, %4, %5}], [%2];" :: "r"(dst), "l"(m), "r"(bar), "r"(c0), "r"(c1), "r"(c2) : "memory"); }
__device__ __forceinline__ void tma4(uint32_t dst, const CUtensorMap* m, int c0, int c1, int c2, int c3, uint32_t bar) {
    asm volatile("cp.async.bulk.tensor.4d.shared::cluster.global.mbarrier::complete_tx::bytes [%0], [%1, {%3, %4, %5, %6}], [%2];" :: "r"(dst), "l"(m), "r"(bar), "r"(c0), "r"(c1), "r"(c2), "r"(c3) : "memory"); }
__device__ __forceinline__ void l2_prefetch(const void* p, uint32_t bytes) { asm volatile("cp.async.bulk.prefetch.L2.global [%0], %1;" :: "l"(p), "r"(bytes) : "memory"); }
__device__ __forceinline__ void fence_proxy_async() { asm volatile("fence.proxy.async;" ::: "memory"); }
__device__ __forceinline__ uint4 lds128(uint32_t a) { uint4 v; asm volatile("ld.shared.v4.u32 {%0,%1,%2,%3}, [%4];" : "=r"(v.x), "=r"(v.y), "=r"(v.z), "=r"(v.w) : "r"(a) : "memory"); return v; }
__device__ __forceinline__ uint32_t lds32(uint32_t a) { uint32_t v; asm volatile("ld.shared.u32 %0, [%1];" : "=r"(v) : "r"(a) : "memory"); return v; }
__device__ __forceinline__ uint32_t lds16(uint32_t a) { uint16_t v; asm volatile("ld.shared.u16 %0, [%1];" : "=h"(v) : "r"(a) : "memory"); return v; }
__device__ __forceinline__ void sts128(uint32_t a, uint4 v) { asm volatile("st.shared.v4.u32 [%0], {%1,%2,%3,%4};" :: "r"(a), "r"(v.x), "r"(v.y), "r"(v.z), "r"(v.w) : "memory"); }
__device__ __forceinline__ void sts32(uint32_t a, uint32_t v) { asm volatile("st.shared.u32 [%0], %1;" :: "r"(a), "r"(v) : "memory"); }
__device__ __forceinline__ void sts16(uint32_t a, uint32_t v) { asm volatile("st.shared.u16 [%0], %1;" :: "r"(a), "h"((uint16_t)v) : "memory"); }
__device__ __forceinline__ uint4 ldx128(const void* p) {
    uint4 v; asm volatile("{.reg .b128 t; .reg .b64 a, b; ld.relaxed.gpu.global.b128 t, [%4]; mov.b128 {a, b}, t; mov.b64 {%0,%1}, a; mov.b64 {%2,%3}, b;}"
        : "=r"(v.x), "=r"(v.y), "=r"(v.z), "=r"(v.w) : "l"(p) : "memory"); return v; }
__device__ __forceinline__ void stx128(void* p, uint4 v) {
    asm volatile("{.reg .b128 t; .reg .b64 a, b; mov.b64 a, {%1,%2}; mov.b64 b, {%3,%4}; mov.b128 t, {a, b}; st.relaxed.gpu.global.b128 [%0], t;}"
        :: "l"(p), "r"(v.x), "r"(v.y), "r"(v.z), "r"(v.w) : "memory"); }
__device__ __forceinline__ uint32_t ld_relaxed(const uint32_t* p) { uint32_t v; asm volatile("ld.relaxed.gpu.global.u32 %0, [%1];" : "=r"(v) : "l"(p) : "memory"); return v; }
__device__ __forceinline__ uint32_t ld_acquire(const uint32_t* p) { uint32_t v; asm volatile("ld.acquire.gpu.global.u32 %0, [%1];" : "=r"(v) : "l"(p) : "memory"); return v; }
__device__ __forceinline__ void st_relaxed(uint32_t* p, uint32_t v) { asm volatile("st.relaxed.gpu.global.u32 [%0], %1;" :: "l"(p), "r"(v) : "memory"); }
__device__ __forceinline__ void red_release(uint32_t* p) { asm volatile("red.release.gpu.global.add.u32 [%0], 1;" :: "l"(p) : "memory"); }
__device__ __forceinline__ void wait_count(const uint32_t* p, uint32_t target) {
    int it = 0; while ((int)(ld_acquire(p) - target) < 0) { if (++it > SPIN_LIMIT) __trap(); }
}
__device__ __forceinline__ uint4 ldg_nc128(const void* p) { uint4 v; asm volatile("ld.global.nc.L1::no_allocate.v4.u32 {%0,%1,%2,%3}, [%4];" : "=r"(v.x), "=r"(v.y), "=r"(v.z), "=r"(v.w) : "l"(p)); return v; }
__device__ __forceinline__ uint32_t ldg_nc32(const void* p) { uint32_t v; asm volatile("ld.global.nc.L1::no_allocate.u32 %0, [%1];" : "=r"(v) : "l"(p)); return v; }
__device__ __forceinline__ uint32_t ldg_nc16(const void* p) { uint16_t v; asm volatile("ld.global.nc.u16 %0, [%1];" : "=h"(v) : "l"(p)); return v; }
__device__ __forceinline__ float bf_lo(uint32_t w) { return __uint_as_float(w << 16); }
__device__ __forceinline__ float bf_hi(uint32_t w) { return __uint_as_float(w & 0xFFFF0000u); }
__device__ __forceinline__ uint32_t pack_bf(float lo, float hi) { uint32_t r; asm("cvt.rn.bf16x2.f32 %0, %1, %2;" : "=r"(r) : "f"(hi), "f"(lo)); return r; }
__device__ __forceinline__ uint32_t pack_h(float lo, float hi) { uint32_t r; asm("cvt.rn.f16x2.f32 %0, %1, %2;" : "=r"(r) : "f"(hi), "f"(lo)); return r; }
__device__ __forceinline__ float bf_round(float v) { return bf_lo(pack_bf(v, 0.f)); }
__device__ __forceinline__ uint32_t hmul2(uint32_t a, uint32_t b) { uint32_t r; asm("mul.rn.f16x2 %0, %1, %2;" : "=r"(r) : "r"(a), "r"(b)); return r; }
__device__ __forceinline__ uint32_t hfma2(uint32_t a, uint32_t b, uint32_t c) { uint32_t r; asm("fma.rn.f16x2 %0, %1, %2, %3;" : "=r"(r) : "r"(a), "r"(b), "r"(c)); return r; }
__device__ __forceinline__ uint32_t hfms2(uint32_t a, uint32_t b, uint32_t c) { uint32_t r; asm("{.reg .b32 t; neg.f16x2 t, %3; fma.rn.f16x2 %0, %1, %2, t;}" : "=r"(r) : "r"(a), "r"(b), "r"(c)); return r; }
__device__ __forceinline__ void cmul_neg(uint32_t& re, uint32_t& im, uint32_t c, uint32_t s) { uint32_t a = hfma2(re, c, hmul2(im, s)), b = hfms2(im, c, hmul2(re, s)); re = a; im = b; }
__device__ __forceinline__ void cmul_pos(uint32_t& re, uint32_t& im, uint32_t c, uint32_t s) { uint32_t a = hfms2(re, c, hmul2(im, s)), b = hfma2(im, c, hmul2(re, s)); re = a; im = b; }
__device__ __forceinline__ void mma_h(uint32_t& d0, uint32_t& d1, uint32_t a0, uint32_t a1, uint32_t a2, uint32_t a3, uint32_t b0, uint32_t b1) {
    asm("mma.sync.aligned.m16n8k16.row.col.f16.f16.f16.f16 {%0,%1}, {%2,%3,%4,%5}, {%6,%7}, {%0,%1};" : "+r"(d0), "+r"(d1) : "r"(a0), "r"(a1), "r"(a2), "r"(a3), "r"(b0), "r"(b1)); }
__device__ __forceinline__ void mma_h8(uint32_t& d0, uint32_t& d1, uint32_t a0, uint32_t a1, uint32_t b0) {
    asm("mma.sync.aligned.m16n8k8.row.col.f16.f16.f16.f16 {%0,%1}, {%2,%3}, {%4}, {%0,%1};" : "+r"(d0), "+r"(d1) : "r"(a0), "r"(a1), "r"(b0)); }
__device__ __forceinline__ void mma_f(float (&d)[4], uint32_t a0, uint32_t a1, uint32_t a2, uint32_t a3, uint32_t b0, uint32_t b1) {
    asm("mma.sync.aligned.m16n8k16.row.col.f32.f16.f16.f32 {%0,%1,%2,%3}, {%4,%5,%6,%7}, {%8,%9}, {%0,%1,%2,%3};"
        : "+f"(d[0]), "+f"(d[1]), "+f"(d[2]), "+f"(d[3]) : "r"(a0), "r"(a1), "r"(a2), "r"(a3), "r"(b0), "r"(b1)); }
template <int NQ> __device__ __forceinline__ void load_tab(uint32_t (&r)[NQ * 4], uint32_t addr) {
    #pragma unroll
    for (int i = 0; i < NQ; i++) { uint4 v = lds128(addr + i * 512); r[4 * i] = v.x; r[4 * i + 1] = v.y; r[4 * i + 2] = v.z; r[4 * i + 3] = v.w; }
}
__device__ __forceinline__ void warp_sum2(float& a, float& b) {
    #pragma unroll
    for (int o = 16; o; o >>= 1) { a += __shfl_xor_sync(~0u, a, o); b += __shfl_xor_sync(~0u, b, o); }
}
__device__ __forceinline__ float gelu(float x) {
    float t = x * fmaf(x * x, 0.044715f * 0.7978845608028654f, 0.7978845608028654f), th;
    asm("tanh.approx.f32 %0, %1;" : "=f"(th) : "f"(t));
    float hx = 0.5f * x; return fmaf(hx, th, hx);
}
__device__ __forceinline__ uint64_t mkdesc(uint32_t addr, uint32_t lbo, uint32_t sbo, uint32_t swz) {
    return (uint64_t)((addr & 0x3FFFF) >> 4) | ((uint64_t)(lbo >> 4) << 16) | ((uint64_t)(sbo >> 4) << 32) | ((uint64_t)swz << 62);
}
#define WG_FENCE() asm volatile("wgmma.fence.sync.aligned;" ::: "memory")
#define WG_COMMIT() asm volatile("wgmma.commit_group.sync.aligned;" ::: "memory")
#define WG_WAIT(n) asm volatile("wgmma.wait_group.sync.aligned %0;" :: "n"(n) : "memory")
#define R4(b) "+f"(d[b]), "+f"(d[b + 1]), "+f"(d[b + 2]), "+f"(d[b + 3])
#define R12(b) R4(b), R4(b + 4), R4(b + 8)
#define R36(b) R12(b), R12(b + 12), R12(b + 24)
__device__ __forceinline__ void wgmma144(float (&d)[72], uint64_t da, uint64_t db, int acc) {
    asm volatile("{.reg .pred p; setp.ne.b32 p, %74, 0;\n"
        "wgmma.mma_async.sync.aligned.m64n144k16.f32.bf16.bf16 {%0,%1,%2,%3,%4,%5,%6,%7,%8,%9,%10,%11,%12,%13,%14,%15,%16,%17,%18,%19,%20,%21,%22,%23,"
        "%24,%25,%26,%27,%28,%29,%30,%31,%32,%33,%34,%35,%36,%37,%38,%39,%40,%41,%42,%43,%44,%45,%46,%47,"
        "%48,%49,%50,%51,%52,%53,%54,%55,%56,%57,%58,%59,%60,%61,%62,%63,%64,%65,%66,%67,%68,%69,%70,%71}, %72, %73, p, 1, 1, 1, 1;}\n"
        : R36(0), R36(36) : "l"(da), "l"(db), "r"(acc));
}
__device__ __forceinline__ void wgmma72(float (&d)[36], uint64_t da, uint64_t db, int acc) {
    asm volatile("{.reg .pred p; setp.ne.b32 p, %38, 0;\n"
        "wgmma.mma_async.sync.aligned.m64n72k16.f32.bf16.bf16 {%0,%1,%2,%3,%4,%5,%6,%7,%8,%9,%10,%11,%12,%13,%14,%15,%16,%17,%18,%19,%20,%21,%22,%23,"
        "%24,%25,%26,%27,%28,%29,%30,%31,%32,%33,%34,%35}, %36, %37, p, 1, 1, 1, 1;}\n"
        : R36(0) : "l"(da), "l"(db), "r"(acc));
}

struct Params {
    const uint16_t *x, *wr, *wi, *w1, *b1, *w2, *b2, *c, *wmod;
    uint16_t* out;
};

template <int NT> struct StripRegs { uint4 w[(1152 + NT - 1) / NT]; uint32_t c[(1152 + NT - 1) / NT]; };
template <int NT> __device__ __forceinline__ void strip_load(StripRegs<NT>& r, const Params& p, int strip, int t) {
    #pragma unroll
    for (int u = 0; u < (1152 + NT - 1) / NT; u++) {
        const int row = (t >> 1) + u * (NT / 2);
        if (row < D_) { r.w[u] = ldg_nc128(p.wmod + row * 3456 + strip * 16 + (t & 1) * 8); r.c[u] = ldg_nc16(p.c + row); }
        else { r.w[u] = make_uint4(0, 0, 0, 0); r.c[u] = 0; }
    }
}
template <int NT> __device__ __forceinline__ void strip_partial(const StripRegs<NT>& r, uint32_t red, int t) {
    float a[8] = {0, 0, 0, 0, 0, 0, 0, 0};
    #pragma unroll
    for (int u = 0; u < (1152 + NT - 1) / NT; u++) {
        const float cv = bf_lo(r.c[u]);
        const float s = bf_round(__fdividef(cv, 1.f + __expf(-cv)));
        a[0] = fmaf(s, bf_lo(r.w[u].x), a[0]); a[1] = fmaf(s, bf_hi(r.w[u].x), a[1]);
        a[2] = fmaf(s, bf_lo(r.w[u].y), a[2]); a[3] = fmaf(s, bf_hi(r.w[u].y), a[3]);
        a[4] = fmaf(s, bf_lo(r.w[u].z), a[4]); a[5] = fmaf(s, bf_hi(r.w[u].z), a[5]);
        a[6] = fmaf(s, bf_lo(r.w[u].w), a[6]); a[7] = fmaf(s, bf_hi(r.w[u].w), a[7]);
    }
    const int lane = t & 31;
    #pragma unroll
    for (int st = 0; st < 3; st++) {
        const int n = 4 >> st, o = 16 >> st; const bool up = lane & o;
        #pragma unroll
        for (int i = 0; i < n; i++) { float keep = up ? a[i + n] : a[i], send = up ? a[i] : a[i + n]; a[i] = keep + __shfl_xor_sync(~0u, send, o); }
    }
    a[0] += __shfl_xor_sync(~0u, a[0], 2);
    if (!(lane & 2)) sts32(red + ((t >> 5) * 16 + (lane & 1) * 8 + (lane >> 2)) * 4, __float_as_uint(a[0]));
}
template <int NT> __device__ __forceinline__ void strip_publish(uint32_t red, int strip, int t, uint32_t tag) {
    if (t < 16) {
        float s = 0;
        #pragma unroll
        for (int w = 0; w < NT / 32; w++) s += __uint_as_float(lds32(red + (w * 16 + t) * 4));
        st_relaxed(g_mod + strip * 16 + t, (pack_bf(0.f, s) & 0xFFFF0000u) | tag);
    }
}
__device__ __forceinline__ uint4 poll_mod(int chunk, uint32_t tag) {
    uint4 v; int it = 0;
    do { v = ldx128(g_mod + chunk * 4); if (++it > SPIN_LIMIT) __trap(); }
    while ((((v.x ^ tag) | (v.y ^ tag) | (v.z ^ tag) | (v.w ^ tag)) & 0xFFFFu) != 0);
    return v;
}
__device__ __forceinline__ void radix16(const uint4 (&V)[4], const uint32_t (&B)[16], uint4 (&o)[4]) {
    #pragma unroll
    for (int nt = 0; nt < 4; nt++) {
        o[nt] = make_uint4(0, 0, 0, 0);
        #pragma unroll
        for (int ks = 0; ks < 2; ks++) {
            const uint32_t b0 = B[(ks * 4 + nt) * 2], b1 = B[(ks * 4 + nt) * 2 + 1];
            mma_h(o[nt].x, o[nt].y, V[2 * ks].x, V[2 * ks].y, V[2 * ks + 1].x, V[2 * ks + 1].y, b0, b1);
            mma_h(o[nt].z, o[nt].w, V[2 * ks].z, V[2 * ks].w, V[2 * ks + 1].z, V[2 * ks + 1].w, b0, b1);
        }
    }
}
template <int OFF, int N> __device__ __forceinline__ void store_u_half(const float (&d)[N], char* base, float bias0, float bias1, int q) {
    #pragma unroll
    for (int h = 0; h < 2; h++) {
        const float bias = h ? bias1 : bias0;
        uint32_t w[9];
        #pragma unroll
        for (int blk = 0; blk < 9; blk++) w[blk] = pack_bf(gelu(d[OFF + 4 * blk + 2 * h] + bias), gelu(d[OFF + 4 * blk + 2 * h + 1] + bias));
        char* p = base + h * 2304;
        *(uint4*)(p + q * 128) = make_uint4(w[0], w[1], w[2], w[3]);
        *(uint4*)(p + 512 + q * 128) = make_uint4(w[4], w[5], w[6], w[7]);
        *(uint32_t*)(p + 1024 + q * 4) = w[8];
    }
}

__global__ void __cluster_dims__(2, 1, 1) __launch_bounds__(NTHR, 1)
fused_kernel(const Params p,
             const __grid_constant__ CUtensorMap tm_w1a, const __grid_constant__ CUtensorMap tm_w1b, const __grid_constant__ CUtensorMap tm_w2,
             const __grid_constant__ CUtensorMap tm_h3a, const __grid_constant__ CUtensorMap tm_h3b,
             const __grid_constant__ CUtensorMap tm_wr, const __grid_constant__ CUtensorMap tm_wi)
{
    extern __shared__ char smem_raw[];
    const uint32_t sm = ((uint32_t)__cvta_generic_to_shared(smem_raw) + 1023u) & ~1023u;
    const int tid = threadIdx.x, warp = tid >> 5, lane = tid & 31, g = lane >> 2, q = lane & 3;
    const int b = blockIdx.x;
    const uint32_t rank = b & 1;
    const uint32_t bars = sm + OFF_BAR;
    const bool rowcta = b < 128;

    StripRegs<NTHR> sr;
    strip_load<NTHR>(sr, p, b, tid);
    const uint32_t epoch = ld_relaxed(g_cnt + CNT_EPOCH * 32);
    uint32_t xw[9];
    if (rowcta) {
        const uint32_t* xr = (const uint32_t*)(p.x + (size_t)(b + 128 * warp) * D_) + 8 * q + g;
        #pragma unroll
        for (int i = 0; i < 9; i++) xw[i] = ldg_nc32(xr + 32 * i);
    }
    if (tid == 480) {
        for (int i = 0; i < NST; i++) { mbar_init(bars + 8 * (BAR_FULL + i), 2); mbar_init(bars + 8 * (BAR_EMPTY + i), 2); }
        mbar_init(bars + 8 * BAR_TAB, 1); mbar_init(bars + 8 * BAR_W, 1); mbar_init(bars + 8 * BAR_P2GO, 1); mbar_init(bars + 8 * BAR_G2GO, 1);
        mbar_init(bars + 8 * BAR_P2R, 1); mbar_init(bars + 8 * BAR_CANSEND, 2); mbar_init(bars + 8 * BAR_RECV, 1); mbar_init(bars + 8 * BAR_ROLE, 1);
        asm volatile("fence.mbarrier_init.release.cluster;" ::: "memory");
        fence_proxy_async();
        mbar_expect(bars + 8 * BAR_TAB, TAB_BYTES);
        bulk_load(sm + OFF_TAB, &g_tab, TAB_BYTES, bars + 8 * BAR_TAB);
        mbar_expect(bars + 8 * BAR_P2R, 9216);
        mbar_expect(bars + 8 * BAR_RECV, 36864);
        if (rowcta) {
            const int c0 = ((b >> 3) * 289 + (b & 7) * 36) & ~7;
            mbar_expect(bars + 8 * BAR_W, 24576);
            tma2(sm + OFF_WRAW, &tm_wr, c0, 0, bars + 8 * BAR_W);
            tma2(sm + OFF_WRAW + 12288, &tm_wi, c0, 0, bars + 8 * BAR_W);
        }
        asm volatile("prefetch.tensormap [%0];" :: "l"(&tm_w1a) : "memory"); asm volatile("prefetch.tensormap [%0];" :: "l"(&tm_h3a) : "memory");
        asm volatile("prefetch.tensormap [%0];" :: "l"(&tm_w1b) : "memory"); asm volatile("prefetch.tensormap [%0];" :: "l"(&tm_h3b) : "memory");
        asm volatile("prefetch.tensormap [%0];" :: "l"(&tm_w2) : "memory");
    }
    __syncwarp();
    asm volatile("barrier.cluster.arrive.release.aligned;" ::: "memory");
    {
        const int ks = warp >> 3, nt = (warp >> 1) & 3, in = q + 4 * (2 * ks + (warp & 1)), o = 4 * nt + (g >> 1);
        const uint32_t a = sm + OFF_B3 + ((warp >> 2) * 32 + lane) * 16 + (warp & 3) * 4;
        float s, c;
        sincospif((float)((o * (128 * in + b)) & 2047) * (1.f / 1024.f), &s, &c); s *= 0.25f; c *= 0.25f;
        sts32(a, (g & 1) ? pack_h(-s, c) : pack_h(c, s));
        sincospif((float)((in * (128 * o + b)) & 2047) * (1.f / 1024.f), &s, &c); s *= 0.25f; c *= 0.25f;
        sts32(a + 2048, (g & 1) ? pack_h(s, c) : pack_h(c, -s));
        if (tid < 160) sts128(sm + OFF_MODA + tid * 16, make_uint4(0, 0, 0, 0));
    }
    const uint32_t tag = (epoch + 1) & 0xFFFFu;
    strip_partial<NTHR>(sr, sm + OFF_RED, tid);
    PROF0(0);
    __syncthreads();
    strip_publish<NTHR>(sm + OFF_RED, b, tid, tag);
    PROF0(1);
    asm volatile("barrier.cluster.wait.acquire.aligned;" ::: "memory");
    if (tid == 448 && rank == 0) {
        uint32_t smid; asm volatile("mov.u32 %0, %%smid;" : "=r"(smid));
        const uint32_t tp = smid >> 1;
        uint32_t pr = tp < 32 ? (tp & 7) * 8 + (tp >> 3) : tp < 60 ? (1 + (tp - 32) % 7) * 8 + 4 + (tp - 32) / 7 : tp < 62 ? 4 + tp : tp < 66 ? tp - 58 : 0;
        while (atomicExch(g_slot + pr, epoch + 1) == epoch + 1) pr = pr == 65 ? 0 : pr + 1;
        sts32(sm + OFF_MISC, pr);
        asm volatile("st.shared::cluster.u32 [%0], %1;" :: "r"(mapa(sm + OFF_MISC, 1)), "r"(pr) : "memory");
        mbar_arrive(bars + 8 * BAR_ROLE);
        mbar_arrive_remote(mapa(bars + 8 * BAR_ROLE, 1));
    }
    __syncwarp();

    const int trow = 4 * (b & 7) + ((b >> 3) & 3) + 32 * (b >> 5);
    uint32_t* const tptr = g_T + (size_t)trow * TP + (warp < 9 ? q * 288 + 32 * warp + 4 * g : 4608 + 4 * q);

    if (rowcta) {
        uint32_t nb[2][5];
        {
            float s1 = 0, s2 = 0;
            #pragma unroll
            for (int i = 0; i < 9; i++) { float lo = bf_lo(xw[i]), hi = bf_hi(xw[i]); s1 += lo + hi; s2 = fmaf(lo, lo, fmaf(hi, hi, s2)); }
            warp_sum2(s1, s2);
            const float m = s1 * (1.f / D_), r = rsqrtf(fmaxf(s2 * (1.f / D_) - m * m, 0.f) + 1e-5f), mr = -m * r;
            #pragma unroll
            for (int pp = 0; pp < 5; pp++) {
                nb[0][pp] = pack_h(fmaf(bf_lo(xw[2 * pp]), r, mr), pp < 4 ? fmaf(bf_lo(xw[pp < 4 ? 2 * pp + 1 : 0]), r, mr) : 0.f);
                nb[1][pp] = pack_h(fmaf(bf_hi(xw[2 * pp]), r, mr), pp < 4 ? fmaf(bf_hi(xw[pp < 4 ? 2 * pp + 1 : 0]), r, mr) : 0.f);
            }
        }
        PROF0(2);
        uint32_t ta[QA * 4];
        mbar_wait(bars + 8 * BAR_TAB, 0);
        load_tab<QA>(ta, sm + OFF_TAB + lane * 16);
        if (tid < 288) {
            const uint4 v = poll_mod(tid, tag);
            const int isc = tid >= 144, d0 = (tid - 144 * isc) * 4, i = d0 >> 6, ln = ((d0 & 15) >> 1) * 4 + ((d0 >> 4) & 3);
            const uint32_t vv[4] = {v.x, v.y, v.z, v.w};
            #pragma unroll
            for (int e = 0; e < 4; e++) {
                float f = bf_hi(vv[e]); if (isc) f = bf_round(1.f + f);
                const int idx = (1 - isc) * 10 + (e & 1) * 5 + (i >> 1);
                sts16(sm + OFF_MODA + ((idx >> 2) * 32 + ln + (e >> 1) * 4) * 16 + (idx & 3) * 4 + (i & 1) * 2, pack_h(f, 0.f));
            }
        }
        __syncthreads();
        PROF0(3);
        {
            uint32_t md[20];
            load_tab<5>(md, sm + OFF_MODA + lane * 16);
            #pragma unroll
            for (int v = 0; v < 2; v++)
                #pragma unroll
                for (int pp = 0; pp < 5; pp++) nb[v][pp] = hfma2(nb[v][pp], md[v * 5 + pp], md[10 + v * 5 + pp]);
        }
        uint32_t re[3][2], im[3][2];
        #pragma unroll
        for (int mt = 0; mt < 3; mt++)
            #pragma unroll
            for (int v = 0; v < 2; v++) {
                re[mt][v] = 0; im[mt][v] = 0;
                mma_h8(re[mt][v], im[mt][v], ta[mt * 10 + 8], ta[mt * 10 + 9], nb[v][4]);
                mma_h(re[mt][v], im[mt][v], ta[mt * 10], ta[mt * 10 + 1], ta[mt * 10 + 2], ta[mt * 10 + 3], nb[v][0], nb[v][1]);
                mma_h(re[mt][v], im[mt][v], ta[mt * 10 + 4], ta[mt * 10 + 5], ta[mt * 10 + 6], ta[mt * 10 + 7], nb[v][2], nb[v][3]);
                cmul_neg(re[mt][v], im[mt][v], ta[30 + (mt * 2 + v) * 2], ta[31 + (mt * 2 + v) * 2]);
            }
        const uint32_t srow = sm + OFF_SPEC + warp * (SPEC_P * 4);
        #pragma unroll
        for (int nt = 0; nt < 4; nt++) {
            uint32_t o0 = 0, o1 = 0, o2 = 0, o3 = 0;
            #pragma unroll
            for (int v = 0; v < 2; v++) {
                const uint32_t b0 = ta[42 + (v * 4 + nt) * 2], b1 = ta[43 + (v * 4 + nt) * 2];
                mma_h(o0, o1, re[0][v], re[1][v], im[0][v], im[1][v], b0, b1);
                mma_h(o2, o3, re[2][v], re[2][v], im[2][v], im[2][v], b0, b1);
            }
            if (nt < 2) {
                const uint32_t a = srow + (g + 72 * q + 36 * nt) * 4;
                sts32(a, o0); sts32(a + 32, o1); if (g < 3) sts32(a + 64, o2);
            } else {
                const uint32_t a = srow + (288 - g - 72 * q - 36 * (nt - 2)) * 4;
                if (g > 0 || (q == 0 && nt == 2)) sts32(a, o0);
                sts32(a - 32, o1); if (g < 2) sts32(a - 64, o2);
            }
        }
        uint32_t b3[16];
        if (warp < 10) load_tab<4>(b3, sm + OFF_B3 + lane * 16);
        __syncthreads();
        PROF0(4);
        if (warp < 10) {
            uint4 V[4], o[4];
            #pragma unroll
            for (int u = 0; u < 4; u++) V[u] = lds128(sm + OFF_SPEC + ((q + 4 * u) * SPEC_P + 32 * warp + 4 * g) * 4);
            radix16(V, b3, o);
            if (warp < 9) {
                #pragma unroll
                for (int nt = 0; nt < 4; nt++) { o[nt].x |= 1u; stx128(tptr + nt * 1152, o[nt]); }
            } else if (g == 0) stx128(tptr, make_uint4(o[0].x | 1u, o[1].x, o[2].x, o[3].x));
        }
        PROF0(5);
    }

    int role = 0;
    if (warp >= 12) {
        const int t = tid - 384;
        StripRegs<128> s2;
        if (b < 84) strip_load<128>(s2, p, 132 + b, t);
        mbar_wait_cluster(bars + 8 * BAR_ROLE, 0);
        role = lds32(sm + OFF_MISC);
        if (role < 64) {
            const int gi = role >> 3, u = role & 7, ci = u * 2 + rank;
            if (t == 0) {
                for (int it = 0; it < NST; it++) {
                    mbar_expect(bars + 8 * (BAR_FULL + it), A_BYTES);
                    tma4(sm + OFF_A + it * A_BYTES, &tm_w1a, 0, 0, 4 * it, 9 * gi + 4 * (u >> 2) + 2 * rank, bars + 8 * (BAR_FULL + it));
                }
            }
            l2_prefetch(p.w1 + (size_t)(128 * ci + t) * F_ + 576 * gi, 1152);
        }
        if (b < 84) {
            strip_partial<128>(s2, sm + OFF_RED + 1024, t);
            bar_sync(2, 128);
            strip_publish<128>(sm + OFF_RED + 1024, 132 + b, t, tag);
        }
        for (int ch = t; ch < 576; ch += 128) {
            const uint4 v = poll_mod(288 + ch, tag);
            const int a = ch / 144, d0 = (ch - 144 * a) * 4;
            uint32_t w0 = __byte_perm(v.x, v.y, 0x7632), w1 = __byte_perm(v.z, v.w, 0x7632);
            if (a == 2) { w0 = pack_bf(1.f + bf_lo(w0), 1.f + bf_hi(w0)); w1 = pack_bf(1.f + bf_lo(w1), 1.f + bf_hi(w1)); }
            if (a < 3) {
                const int idx = a * 9 + (d0 >> 6), ln = ((d0 & 15) >> 1) * 4 + ((d0 >> 4) & 3);
                const uint32_t ad = sm + OFF_MODC + ((idx >> 2) * 32 + ln) * 16 + (idx & 3) * 4;
                sts32(ad, w0); sts32(ad + 64, w1);
            } else { sts32(sm + OFF_GB + d0 * 2, w0); sts32(sm + OFF_GB + d0 * 2 + 4, w1); }
        }
        if (b == 0) { bar_sync(2, 128); if (t == 0) st_relaxed(g_cnt + CNT_EPOCH * 32, epoch + 1); }
    } else if (b <= 128) {
        const int nw = rowcta ? 9 : 4;
        uint32_t tb[QB * 4], wre[4][2], wim[4][2];
        if (warp < nw) {
            mbar_wait(bars + 8 * BAR_TAB, 0);
            load_tab<QB>(tb, sm + OFF_TAB + QA * 512 + lane * 16);
            if (rowcta) {
                mbar_wait(bars + 8 * BAR_W, 0);
                const uint32_t wa = sm + OFF_WRAW + (g + 32 * q) * 96 + ((((b >> 3) * 289 + (b & 7) * 36) & 7) + 4 * warp) * 2;
                #pragma unroll
                for (int x = 0; x < 4; x++)
                    #pragma unroll
                    for (int h = 0; h < 2; h++) {
                        const uint32_t a = wa + h * 768 + x * 2;
                        wre[x][h] = pack_h(bf_lo(lds16(a)), bf_lo(lds16(a + 1536)));
                        wim[x][h] = pack_h(bf_lo(lds16(a + 12288)), bf_lo(lds16(a + 12288 + 1536)));
                    }
            } else {
                #pragma unroll
                for (int x = 0; x < 4; x++)
                    #pragma unroll
                    for (int h = 0; h < 2; h++) {
                        const int o = (4 * x + warp + 16 * (g + 8 * h + 32 * q)) * 289 + 288;
                        wre[x][h] = pack_h(bf_lo(ldg_nc16(p.wr + o)), bf_lo(ldg_nc16(p.wr + o + 256 * 289)));
                        wim[x][h] = pack_h(bf_lo(ldg_nc16(p.wi + o)), bf_lo(ldg_nc16(p.wi + o + 256 * 289)));
                    }
            }
        }
        uint32_t* gp[3]; uint32_t sa[3]; bool act[3];
        #pragma unroll
        for (int u = 0; u < 3; u++) {
            const int e = tid + 384 * u, row = rowcta ? e / 9 : e >> 2, i = e - row * nw;
            act[u] = row < 128;
            gp[u] = g_T + (size_t)row * TP + b * 36 + 4 * i;
            sa[u] = sm + OFF_STAGE + row * 144 + i * 16;
        }
        PROF0(6);
        {
            uint4 v[3]; bool need[3] = {act[0], act[1], act[2]}; int it = 0;
            do {
                #pragma unroll
                for (int u = 0; u < 3; u++) if (need[u]) v[u] = ldx128(gp[u]);
                #pragma unroll
                for (int u = 0; u < 3; u++) if (need[u] && (v[u].x & 1u)) { need[u] = false; sts128(sa[u], v[u]); }
                if (++it > SPIN_LIMIT) __trap();
            } while (need[0] || need[1] || need[2]);
        }
        bar_sync(1, 384);
        PROF0(7);
        if (warp < nw) {
            const uint32_t ca = sm + OFF_STAGE + lane * 144 + warp * 16;
            uint32_t V[4][4];
            #pragma unroll
            for (int u = 0; u < 4; u++) { uint4 t4 = lds128(ca + u * 4608); V[u][0] = t4.x; V[u][1] = t4.y; V[u][2] = t4.z; V[u][3] = t4.w; }
            uint32_t zr[4][2], zi[4][2];
            #pragma unroll
            for (int x = 0; x < 4; x++) {
                uint32_t r0 = 0, r1 = 0, i0 = 0, i1 = 0;
                mma_h(r0, r1, tb[0], tb[1], tb[2], tb[3], V[0][x], V[1][x]);
                mma_h(i0, i1, tb[8], tb[9], tb[10], tb[11], V[0][x], V[1][x]);
                mma_h(r0, r1, tb[4], tb[5], tb[6], tb[7], V[2][x], V[3][x]);
                mma_h(i0, i1, tb[12], tb[13], tb[14], tb[15], V[2][x], V[3][x]);
                cmul_neg(r0, i0, tb[16], tb[17]); cmul_neg(r1, i1, tb[18], tb[19]);
                uint32_t xr0 = 0, xr1 = 0, xi0 = 0, xi1 = 0;
                mma_h(xr0, xr1, r0, r1, i0, i1, tb[20], tb[21]);
                mma_h(xi0, xi1, r0, r1, i0, i1, tb[22], tb[20]);
                cmul_pos(xr0, xi0, wre[x][0], wim[x][0]); cmul_pos(xr1, xi1, wre[x][1], wim[x][1]);
                zr[x][0] = 0; zi[x][0] = 0; zr[x][1] = 0; zi[x][1] = 0;
                mma_h(zr[x][0], zi[x][0], tb[20], tb[21], tb[22], tb[20], xr0, xi0);
                mma_h(zr[x][1], zi[x][1], tb[20], tb[21], tb[22], tb[20], xr1, xi1);
                cmul_pos(zr[x][0], zi[x][0], tb[23], tb[24]); cmul_pos(zr[x][1], zi[x][1], tb[25], tb[26]);
            }
            #pragma unroll
            for (int nt = 0; nt < 4; nt++) {
                uint4 o = make_uint4(0, 0, 0, 0);
                #pragma unroll
                for (int h = 0; h < 2; h++) {
                    const uint32_t b0 = tb[27 + (h * 4 + nt) * 2], b1 = tb[28 + (h * 4 + nt) * 2];
                    mma_h(o.x, o.y, zr[0][h], zr[1][h], zi[0][h], zi[1][h], b0, b1);
                    mma_h(o.z, o.w, zr[2][h], zr[3][h], zi[2][h], zi[3][h], b0, b1);
                }
                o.x &= ~1u;
                sts128(ca + nt * 4608, o);
            }
        }
        bar_sync(1, 384);
        PROF0(8);
        #pragma unroll
        for (int u = 0; u < 3; u++) if (act[u]) stx128(gp[u], lds128(sa[u]));
        PROF0(9);
    }

    if (rowcta) {
        uint32_t tc[QC * 4];
        load_tab<QC>(tc, sm + OFF_TAB + (QA + QB) * 512 + lane * 16);
        if (warp < 10) {
            uint32_t b3[16];
            load_tab<4>(b3, sm + OFF_B3 + 2048 + lane * 16);
            uint4 V[4], o[4];
            int it = 0;
            if (warp < 9) {
                bool need[4] = {true, true, true, true};
                do {
                    #pragma unroll
                    for (int u = 0; u < 4; u++) if (need[u]) V[u] = ldx128(tptr + u * 1152);
                    #pragma unroll
                    for (int u = 0; u < 4; u++) need[u] = V[u].x & 1u;
                    if (++it > SPIN_LIMIT) __trap();
                } while (need[0] || need[1] || need[2] || need[3]);
            } else {
                uint4 v = make_uint4(0, 0, 0, 0);
                if (g == 0) do { v = ldx128(tptr); if (++it > SPIN_LIMIT) __trap(); } while (v.x & 1u);
                V[0] = make_uint4(v.x, 0, 0, 0); V[1] = make_uint4(v.y, 0, 0, 0); V[2] = make_uint4(v.z, 0, 0, 0); V[3] = make_uint4(v.w, 0, 0, 0);
            }
            __syncwarp();
            PROF0(10);
            radix16(V, b3, o);
            if (warp < 9 || g == 0) {
                #pragma unroll
                for (int nt = 0; nt < 4; nt++) sts128(sm + OFF_SPEC + ((4 * nt + q) * SPEC_P + 32 * warp + 4 * g) * 4, o[nt]);
            }
        }
        __syncthreads();
        PROF0(11);
        const uint32_t srow = sm + OFF_SPEC + warp * (SPEC_P * 4);
        uint32_t re[2][3], im[2][3];
        #pragma unroll
        for (int mt = 0; mt < 3; mt++) {
            const uint32_t a = srow + (g + 72 * q + 8 * mt) * 4, a2 = srow + (288 - g - 72 * q - 8 * mt) * 4;
            const uint32_t z0 = lds32(a), z1 = lds32(a + 144), z2 = lds32(a2), z3 = lds32(a2 - 144);
            #pragma unroll
            for (int m2 = 0; m2 < 2; m2++) {
                re[m2][mt] = 0; im[m2][mt] = 0;
                mma_h(re[m2][mt], im[m2][mt], tc[m2 * 8], tc[m2 * 8 + 1], tc[m2 * 8 + 2], tc[m2 * 8 + 3], z0, z1);
                mma_h(re[m2][mt], im[m2][mt], tc[m2 * 8 + 4], tc[m2 * 8 + 5], tc[m2 * 8 + 6], tc[m2 * 8 + 7], z2, z3);
                cmul_pos(re[m2][mt], im[m2][mt], tc[16 + (m2 * 3 + mt) * 2], tc[17 + (m2 * 3 + mt) * 2]);
            }
        }
        uint32_t md[28];
        load_tab<7>(md, sm + OFF_MODC + lane * 16);
        float y[5][4];
        #pragma unroll
        for (int nt = 0; nt < 5; nt++) {
            y[nt][0] = y[nt][1] = y[nt][2] = y[nt][3] = 0.f;
            #pragma unroll
            for (int mt = 0; mt < 3; mt++)
                mma_f(y[nt], re[0][mt], re[1][mt], im[0][mt], im[1][mt], tc[28 + (mt * 5 + nt) * 2], tc[29 + (mt * 5 + nt) * 2]);
        }
        float v0[9], v1[9], s1 = 0, s2 = 0;
        #pragma unroll
        for (int i = 0; i < 9; i++) {
            xw[i] = pack_bf(fmaf(bf_lo(md[i]), y[i >> 1][i & 1], bf_lo(xw[i])), fmaf(bf_hi(md[i]), y[i >> 1][2 + (i & 1)], bf_hi(xw[i])));
            v0[i] = bf_lo(xw[i]); v1[i] = bf_hi(xw[i]);
            s1 += v0[i] + v1[i]; s2 = fmaf(v0[i], v0[i], fmaf(v1[i], v1[i], s2));
        }
        warp_sum2(s1, s2);
        float m = s1 * (1.f / D_), r = rsqrtf(fmaxf(s2 * (1.f / D_) - m * m, 0.f) + 1e-5f), mr = -m * r;
        s1 = 0; s2 = 0;
        #pragma unroll
        for (int i = 0; i < 9; i++) {
            v0[i] = fmaf(fmaf(v0[i], r, mr), bf_lo(md[18 + i]), bf_lo(md[9 + i]));
            v1[i] = fmaf(fmaf(v1[i], r, mr), bf_hi(md[18 + i]), bf_hi(md[9 + i]));
            s1 += v0[i] + v1[i]; s2 = fmaf(v0[i], v0[i], fmaf(v1[i], v1[i], s2));
        }
        warp_sum2(s1, s2);
        m = s1 * (1.f / D_); r = rsqrtf(fmaxf(s2 * (1.f / D_) - m * m, 0.f) + 1e-5f); mr = -m * r;
        {
            const int n7 = 2 * q + (g >> 2);
            const uint32_t a = sm + OFF_STAGE + n7 * 256 + (warp >> 3) * 128 + ((warp & 7) ^ n7) * 16 + (g & 3) * 4;
            #pragma unroll
            for (int i = 0; i < 9; i++) sts32(a + i * 2048, pack_bf(fmaf(v0[i], r, mr), fmaf(v1[i], r, mr)));
        }
        __syncthreads();
        PROF0(12);
        #pragma unroll
        for (int u = 0; u < 3; u++) {
            const int e = tid + 512 * u;
            if (e < 1152) g_h3[b * 1152 + e] = lds128(sm + OFF_STAGE + ((e & ~7) | ((e ^ (e >> 4)) & 7)) * 16);
        }
        uint32_t* xo = (uint32_t*)(p.out + (size_t)(b + 128 * warp) * D_) + 8 * q + g;
        #pragma unroll
        for (int i = 0; i < 9; i++) xo[32 * i] = xw[i];
    }
    fence_proxy_async();
    __syncthreads();
    if (tid == 0 && rowcta) red_release(g_cnt + CNT_H3 * 32);
    PROF0(13);
    role = lds32(sm + OFF_MISC);
    if (role >= 64) return;

    const int gi = role >> 3, dt = role & 3, c2 = (role >> 2) & 1;
    const int wg = warp >> 2, wi = warp & 3;
    if (wg == 3) {
        if (tid == 384) {
            for (int it = NST; it < IT_END; it++) {
                const int s = it % NST; const uint32_t fb = bars + 8 * (BAR_FULL + s), dst = sm + OFF_A + s * A_BYTES;
                mbar_wait(bars + 8 * (BAR_EMPTY + s), ((it / NST) & 1) ^ 1);
                mbar_expect(fb, A_BYTES);
                if (it < IT_P2) tma4(dst, &tm_w1a, 0, 0, 4 * it, 9 * gi + 4 * c2 + 2 * rank, fb);
                else if (it < IT_G2) tma4(dst, &tm_w1b, 0, 0, 64 * rank + 8 * (it - IT_P2), 9 * gi + 8, fb);
                else { const int n = it - IT_G2, kb = n < 32 ? 36 * rank + 9 * (n >> 3) + (n & 7) : 36 * rank + 9 * (n - 32) + 8;
                       tma3(dst, &tm_w2, 0, 64 * kb, 4 * gi + 2 * c2, fb); }
            }
        } else if (tid == 416) {
            wait_count(g_cnt + CNT_H3 * 32, (epoch + 1) * 128);
            fence_proxy_async();
            PROFT(14);
            for (int it = 0; it < IT_END; it++) {
                const int s = it % NST; const uint32_t fb = bars + 8 * (BAR_FULL + s), dst = sm + OFF_B + s * B_BYTES;
                if (it == IT_G2) { wait_count(g_cnt + (CNT_U1 + dt * 2 + rank) * 32, (epoch + 1) * 32); fence_proxy_async(); PROFT(19); }
                if (it == IT_G2 + 32) { wait_count(g_cnt + (CNT_U2 + dt * 2 + rank) * 32, (epoch + 1) * 16); fence_proxy_async(); }
                if (it >= NST) mbar_wait(bars + 8 * (BAR_EMPTY + s), ((it / NST) & 1) ^ 1);
                mbar_expect(fb, B_BYTES);
                if (it < IT_P2) tma3(dst, &tm_h3a, 0, 18 * dt, 4 * it, fb);
                else if (it < IT_G2) tma3(dst, &tm_h3b, 0, 18 * dt + 9 * c2, 64 * rank + 8 * (it - IT_P2), fb);
                else { const int n = it - IT_G2, kb = n < 32 ? 36 * rank + 9 * (n >> 3) + (n & 7) : 36 * rank + 9 * (n - 32) + 8;
                       bulk_load(dst, g_U + (kb * 4 + dt) * 1152, B_BYTES, fb); }
            }
        } else if (warp == 14) {
            const int ci = (role & 7) * 2 + rank;
            for (int i = 0; i < 9; i++) {
                const int r = (16 * i + (lane & 15)) * 16 + ci + (lane >> 4) * 2304;
                l2_prefetch(p.w2 + (size_t)r * S_ + 256 * gi, 512);
                __nanosleep(700);
            }
        }
    } else if (wg == 2) {
        float d0[36], d1[36];
        const int fr = 576 * gi + 512 + 16 * wi + g;
        const float bias0 = bf_lo(ldg_nc16(p.b1 + fr)), bias1 = bf_lo(ldg_nc16(p.b1 + fr + 8));
        mbar_wait(bars + 8 * BAR_P2GO, 0);
        for (int it = IT_P2; it < IT_G2; it++) {
            const int s = it % NST;
            mbar_wait(bars + 8 * (BAR_FULL + s), (it / NST) & 1);
            if (it == IT_G2 - 1 && tid == 256) mbar_arrive(bars + 8 * BAR_G2GO);
            const uint64_t da = mkdesc(sm + OFF_A + s * A_BYTES, 8192, 1024, 1), db = mkdesc(sm + OFF_B + s * B_BYTES, 128, 256, 0);
            WG_FENCE();
            #pragma unroll
            for (int k = 0; k < 8; k += 2) {
                wgmma72(d0, da + k * 128, db + k * 144, it > IT_P2 || k > 0);
                wgmma72(d1, da + (k + 1) * 128, db + (k + 1) * 144, it > IT_P2 || k > 0);
            }
            WG_COMMIT();
            WG_WAIT(1);
            if (it > IT_P2 && tid == 256) mbar_arrive_n(bars + 8 * (BAR_EMPTY + (it - 1) % NST), 2);
        }
        WG_WAIT(0);
        if (tid == 256) { mbar_arrive_n(bars + 8 * (BAR_EMPTY + (IT_G2 - 1) % NST), 2); PROFT(18); }
        const uint32_t slot = sm + OFF_P2R + ((wi & 1) * 32 + lane) * 16;
        if ((uint32_t)(wi >> 1) != rank) {
            const uint32_t ra = mapa(slot, rank ^ 1), rb = mapa(bars + 8 * BAR_P2R, rank ^ 1);
            #pragma unroll
            for (int i = 0; i < 9; i++)
                asm volatile("st.async.weak.shared::cluster.mbarrier::complete_tx::bytes.v4.f32 [%0], {%1,%2,%3,%4}, [%5];"
                    :: "r"(ra + i * 1024), "f"(d0[4 * i] + d1[4 * i]), "f"(d0[4 * i + 1] + d1[4 * i + 1]), "f"(d0[4 * i + 2] + d1[4 * i + 2]), "f"(d0[4 * i + 3] + d1[4 * i + 3]), "r"(rb) : "memory");
        } else {
            mbar_wait_cluster(bars + 8 * BAR_P2R, 0);
            #pragma unroll
            for (int i = 0; i < 9; i++) {
                const uint4 v = lds128(slot + i * 1024);
                d0[4 * i] += d1[4 * i] + __uint_as_float(v.x); d0[4 * i + 1] += d1[4 * i + 1] + __uint_as_float(v.y);
                d0[4 * i + 2] += d1[4 * i + 2] + __uint_as_float(v.z); d0[4 * i + 3] += d1[4 * i + 3] + __uint_as_float(v.w);
            }
            store_u_half<0>(d0, (char*)(g_U + ((9 * gi + 8) * 4 + dt) * 1152) + wi * 4608 + c2 * 1152 + g * 16, bias0, bias1, q);
            fence_proxy_async();
            bar_sync(3, 64);
            if ((wi & 1) == 0 && lane == 0) red_release(g_cnt + (CNT_U2 + dt * 2 + (gi >> 2)) * 32);
        }
    } else {
        float d[72];
        const bool lead = (tid & 127) == 0;
        {
            const int fr = 576 * gi + 256 * c2 + 128 * rank + 64 * wg + 16 * wi + g;
            const float bias0 = bf_lo(ldg_nc16(p.b1 + fr)), bias1 = bf_lo(ldg_nc16(p.b1 + fr + 8));
            int s = 0, ph = 0, prev = 0;
            for (int it = 0; it < IT_P2; it++) {
                mbar_wait(bars + 8 * (BAR_FULL + s), ph);
                if (it == 0) PROF0(15);
                if (it == IT_P2 - 1 && tid == 0) mbar_arrive(bars + 8 * BAR_P2GO);
                const uint64_t da = mkdesc(sm + OFF_A + s * A_BYTES + wg * 8192, 8192, 1024, 1), db = mkdesc(sm + OFF_B + s * B_BYTES, 128, 256, 0);
                WG_FENCE();
                #pragma unroll
                for (int k = 0; k < 4; k++) wgmma144(d, da + k * 128, db + k * 288, it > 0 || k > 0);
                WG_COMMIT();
                WG_WAIT(1);
                if (it > 0 && lead) mbar_arrive(bars + 8 * (BAR_EMPTY + prev));
                prev = s; if (++s == NST) { s = 0; ph ^= 1; }
            }
            WG_WAIT(0);
            if (lead) mbar_arrive(bars + 8 * (BAR_EMPTY + prev));
            PROF0(16);
            char* ub = (char*)(g_U + ((9 * gi + 4 * c2 + 2 * rank + wg) * 4 + dt) * 1152) + wi * 4608 + g * 16;
            store_u_half<0>(d, ub, bias0, bias1, q);
            store_u_half<36>(d, ub + 1152, bias0, bias1, q);
            fence_proxy_async();
            bar_sync(4 + wg, 128);
            if (lead) red_release(g_cnt + (CNT_U1 + dt * 2 + (gi >> 2)) * 32);
            PROF0(17);
        }
        const int srow = 256 * gi + 128 * c2 + 64 * wg + 16 * wi + g + 8 * rank;
        uint16_t* const orow = p.out + (size_t)srow * D_ + 144 * dt;
        uint4 xq[4]; uint32_t xs[2];
        #pragma unroll
        for (int i = 0; i < 4; i++) xq[i] = *(const uint4*)(orow + 72 * (i >> 1) + 32 * (i & 1) + 8 * q);
        xs[0] = *(const uint32_t*)(orow + 64 + 2 * q); xs[1] = *(const uint32_t*)(orow + 136 + 2 * q);
        const float bias = bf_lo(ldg_nc16(p.b2 + srow));
        mbar_wait(bars + 8 * BAR_G2GO, 0);
        int s = IT_G2 % NST, ph = (IT_G2 / NST) & 1, prev = 0;
        for (int it = IT_G2; it < IT_END; it++) {
            mbar_wait(bars + 8 * (BAR_FULL + s), ph);
            if (it == IT_G2) PROF0(20);
            const uint64_t da = mkdesc(sm + OFF_A + s * A_BYTES + wg * 8192, 8192, 1024, 1), db = mkdesc(sm + OFF_B + s * B_BYTES, 2304, 128, 0);
            WG_FENCE();
            #pragma unroll
            for (int k = 0; k < 4; k++) wgmma144(d, da + k * 128, db + k * 288, it > IT_G2 || k > 0);
            WG_COMMIT();
            WG_WAIT(1);
            if (it > IT_G2 && lead) {
                mbar_arrive(bars + 8 * (BAR_EMPTY + prev));
                if (it == IT_END - 4) mbar_arrive_remote(mapa(bars + 8 * BAR_CANSEND, rank ^ 1));
            }
            prev = s; if (++s == NST) { s = 0; ph ^= 1; }
        }
        WG_WAIT(0);
        PROF0(21);
        static_assert((IT_END - 6) % NST == 4, "receive buffer = B slots 4 and 5");
        const uint32_t slot = sm + OFF_B + 4 * B_BYTES + tid * 16;
        mbar_wait_cluster(bars + 8 * BAR_CANSEND, 0);
        {
            const uint32_t ra = mapa(slot, rank ^ 1), rb = mapa(bars + 8 * BAR_RECV, rank ^ 1);
            #pragma unroll
            for (int i = 0; i < 9; i++) {
                const float* e = d + 8 * i;
                asm volatile("st.async.weak.shared::cluster.mbarrier::complete_tx::bytes.v4.f32 [%0], {%1,%2,%3,%4}, [%5];"
                    :: "r"(ra + i * 4096), "f"(rank ? e[0] : e[2]), "f"(rank ? e[1] : e[3]), "f"(rank ? e[4] : e[6]), "f"(rank ? e[5] : e[7]), "r"(rb) : "memory");
            }
        }
        float v[36];
        #pragma unroll
        for (int i = 0; i < 18; i++) { v[2 * i] = (rank ? d[4 * i + 2] : d[4 * i]) + bias; v[2 * i + 1] = (rank ? d[4 * i + 3] : d[4 * i + 1]) + bias; }
        uint4 gq[4]; uint32_t gs[2];
        #pragma unroll
        for (int i = 0; i < 4; i++) gq[i] = lds128(sm + OFF_GB + (144 * dt + 72 * (i >> 1) + 32 * (i & 1) + 8 * q) * 2);
        gs[0] = lds32(sm + OFF_GB + (144 * dt + 64 + 2 * q) * 2); gs[1] = lds32(sm + OFF_GB + (144 * dt + 136 + 2 * q) * 2);
        mbar_wait_cluster(bars + 8 * BAR_RECV, 0);
        PROF0(22);
        #pragma unroll
        for (int i = 0; i < 9; i++) {
            const uint4 t4 = lds128(slot + i * 4096);
            v[4 * i] += __uint_as_float(t4.x); v[4 * i + 1] += __uint_as_float(t4.y); v[4 * i + 2] += __uint_as_float(t4.z); v[4 * i + 3] += __uint_as_float(t4.w);
        }
        #define FIN(x_, g_, k_) pack_bf(fmaf(bf_lo(g_), v[k_], bf_lo(x_)), fmaf(bf_hi(g_), v[(k_) + 1], bf_hi(x_)))
        #pragma unroll
        for (int i = 0; i < 4; i++) {
            const int k0 = 18 * (i >> 1) + 8 * (i & 1);
            *(uint4*)(orow + 72 * (i >> 1) + 32 * (i & 1) + 8 * q) =
                make_uint4(FIN(xq[i].x, gq[i].x, k0), FIN(xq[i].y, gq[i].y, k0 + 2), FIN(xq[i].z, gq[i].z, k0 + 4), FIN(xq[i].w, gq[i].w, k0 + 6));
        }
        *(uint32_t*)(orow + 64 + 2 * q) = FIN(xs[0], gs[0], 16);
        *(uint32_t*)(orow + 136 + 2 * q) = FIN(xs[1], gs[1], 34);
        PROF0(23);
    }
}

typedef CUresult (*EncodeFn)(CUtensorMap*, CUtensorMapDataType, cuuint32_t, void*, const cuuint64_t*, const cuuint64_t*, const cuuint32_t*,
                             const cuuint32_t*, CUtensorMapInterleave, CUtensorMapSwizzle, CUtensorMapL2promotion, CUtensorMapFloatOOBfill);

void encode(EncodeFn fn, CUtensorMap* m, CUtensorMapDataType dt, int rank, const void* ptr, const cuuint64_t* dims, const cuuint64_t* strides,
            const cuuint32_t* box, CUtensorMapSwizzle sw) {
    const cuuint32_t es[5] = {1, 1, 1, 1, 1};
    fn(m, dt, rank, (void*)ptr, dims, strides, box, es, CU_TENSOR_MAP_INTERLEAVE_NONE, sw, CU_TENSOR_MAP_L2_PROMOTION_L2_128B, CU_TENSOR_MAP_FLOAT_OOB_FILL_NONE);
}

}

extern "C" void kernel_launch(void* const* d_in, const int* in_sizes, int n_in, void* d_out, int out_size) {
    (void)in_sizes; (void)n_in; (void)out_size;
    Params p;
    p.x = (const uint16_t*)d_in[0]; p.wr = (const uint16_t*)d_in[1]; p.wi = (const uint16_t*)d_in[2];
    p.w1 = (const uint16_t*)d_in[4]; p.b1 = (const uint16_t*)d_in[5]; p.w2 = (const uint16_t*)d_in[6]; p.b2 = (const uint16_t*)d_in[7];
    p.c = (const uint16_t*)d_in[8]; p.wmod = (const uint16_t*)d_in[9]; p.out = (uint16_t*)d_out;

    void* fnp = nullptr; cudaDriverEntryPointQueryResult qr;
    cudaGetDriverEntryPoint("cuTensorMapEncodeTiled", &fnp, cudaEnableDefault, &qr);
    EncodeFn fn = (EncodeFn)fnp;
    void* h3p = nullptr; cudaGetSymbolAddress(&h3p, g_h3);
    CUtensorMap tw1a, tw1b, tw2, th3a, th3b, twr, twi;
    {
        const cuuint64_t dims[4] = {64, 16, 128, 72}, st[3] = {128ull * F_ * 2, (cuuint64_t)F_ * 2, 128};
        const cuuint32_t ba[4] = {64, 16, 4, 2}, bb[4] = {64, 16, 8, 1};
        encode(fn, &tw1a, CU_TENSOR_MAP_DATA_TYPE_BFLOAT16, 4, p.w1, dims, st, ba, CU_TENSOR_MAP_SWIZZLE_128B);
        encode(fn, &tw1b, CU_TENSOR_MAP_DATA_TYPE_BFLOAT16, 4, p.w1, dims, st, bb, CU_TENSOR_MAP_SWIZZLE_128B);
    }
    {
        const cuuint64_t dims[3] = {64, F_, 32}, st[2] = {(cuuint64_t)S_ * 2, 128};
        const cuuint32_t bx[3] = {64, 64, 2};
        encode(fn, &tw2, CU_TENSOR_MAP_DATA_TYPE_BFLOAT16, 3, p.w2, dims, st, bx, CU_TENSOR_MAP_SWIZZLE_128B);
    }
    {
        const cuuint64_t dims[3] = {64, 72, 128}, st[2] = {256, 18432};
        const cuuint32_t ba[3] = {64, 18, 4}, bb[3] = {64, 9, 8};
        encode(fn, &th3a, CU_TENSOR_MAP_DATA_TYPE_UINT32, 3, h3p, dims, st, ba, CU_TENSOR_MAP_SWIZZLE_NONE);
        encode(fn, &th3b, CU_TENSOR_MAP_DATA_TYPE_UINT32, 3, h3p, dims, st, bb, CU_TENSOR_MAP_SWIZZLE_NONE);
    }
    {
        const cuuint64_t dims[2] = {4624, 128}, st[1] = {9248};
        const cuuint32_t bx[2] = {48, 128};
        encode(fn, &twr, CU_TENSOR_MAP_DATA_TYPE_BFLOAT16, 2, p.wr, dims, st, bx, CU_TENSOR_MAP_SWIZZLE_NONE);
        encode(fn, &twi, CU_TENSOR_MAP_DATA_TYPE_BFLOAT16, 2, p.wi, dims, st, bx, CU_TENSOR_MAP_SWIZZLE_NONE);
    }
    cudaFuncSetAttribute(fused_kernel, cudaFuncAttributeMaxDynamicSharedMemorySize, SMEM_BYTES);
    cudaLaunchConfig_t cfg = {};
    cfg.gridDim = dim3(NCTA); cfg.blockDim = dim3(NTHR); cfg.dynamicSmemBytes = SMEM_BYTES; cfg.stream = cudaStreamPerThread;
    cudaLaunchAttribute at[1];
    at[0].id = cudaLaunchAttributeCooperative; at[0].val.cooperative = 1;
    cfg.attrs = at; cfg.numAttrs = 1;
    cudaLaunchKernelEx(&cfg, fused_kernel, p, tw1a, tw1b, tw2, th3a, th3b, twr, twi);
}
```

```cpp
#include <cuda_runtime.h>
#include <cuda_bf16.h>
#include <cuda_fp16.h>
#include <cuda.h>
#include <stdint.h>

namespace {

constexpr int S_ = 2048, D_ = 576, F_ = 4608;
constexpr int NCTA = 132, NTHR = 512;
constexpr int TP = 4736;
constexpr int SPEC_P = 296;
constexpr int NST = 6;
constexpr int A_BYTES = 16384, B_BYTES = 18432;
constexpr int IT_P2 = 32, IT_G2 = 40, IT_END = 76;
constexpr int SPIN_LIMIT = 1 << 22;
#define UIDX(dt_, kh_) 0
#define UCNT 128
#define MODPAD 16
#define MODSLEEP 0
#define X2D 1300
#define NCD 0
#define CPHINT ".L2::128B"
#define NCST 17
#define NCPF 1
#define NCPACE 0
#define P2A 2
#define P2D 400
#define P2CH 1
#define A2E 1
#define A2D 100
#define W1N 8
#define W1P 100
#define W1S 0
#define XDELAY 1600
#define X1D 2300
#define PF1 0
#define PF2 1
#define X1DELAY 2500

constexpr int OFF_A = 0;
constexpr int OFF_B = NST * A_BYTES;
constexpr int OFF_P = OFF_B + NST * B_BYTES;
constexpr int OFF_BAR = OFF_P;
constexpr int OFF_MISC = OFF_P + 368;
constexpr int OFF_GB = OFF_P + 384;
constexpr int OFF_P2R = OFF_P + 1536;
constexpr int OFF_X1 = OFF_P2R;
constexpr int OFF_PROF = OFF_X1 + 18432;
constexpr int SMEM_BYTES = OFF_PROF + 512 + 1024;
constexpr int QA = 13, QB = 7, QC = 13;
constexpr int TAB_BYTES = (QA + QB + QC) * 512;
constexpr int OFF_STAGE = OFF_B;
constexpr int OFF_STX = OFF_STAGE + 16384;
constexpr int OFF_TAB = OFF_STAGE + 20480;
constexpr int OFF_SPEC = OFF_TAB + TAB_BYTES;
constexpr int OFF_WRAW = OFF_SPEC + 19072;
constexpr int OFF_B3 = OFF_WRAW + 28672;
constexpr int OFF_MODA = OFF_B3 + 4096;
constexpr int OFF_MODC = OFF_MODA + 2560;
constexpr int OFF_RED = OFF_MODC + 3584;
constexpr int OFF_SILU = OFF_RED + 768;
static_assert(OFF_SILU + 1152 <= OFF_P && 6 * 28672 <= OFF_B3, "scratch overflow");
constexpr int OFF_STRIP = OFF_A;
static_assert(OFF_WRAW % 128 == 0 && OFF_STAGE % 128 == 0 && OFF_STX % 128 == 0, "align");
constexpr int BAR_FULL = 0, BAR_EMPTY = 6, BAR_TAB = 12, BAR_W = 13, BAR_P2GO = 14, BAR_G2GO = 15, BAR_P2R = 16,
              BAR_CANSEND = 17, BAR_RECV = 18, BAR_ROLE = 19, BAR_NC = 20, BAR_TAB2 = 21, BAR_XB = 22, BAR_GB = 23, BAR_HOLD = 24, BAR_W1GO = 25, BAR_UOK = 26, BAR_STGO = 29, BAR_X = 30;

struct Cos1152 { double c[1152]; };
constexpr double cx_cos(double x) { double t = 1, s = 1; for (int i = 1; i < 14; i++) { t *= -x * x / ((2 * i - 1) * (2 * i)); s += t; } return s; }
constexpr Cos1152 make_cos() {
    Cos1152 r{};
    for (int i = 0; i <= 288; i++) {
        double v = (i == 288) ? 0.0 : cx_cos(3.14159265358979323846 * 2.0 * i / 1152.0);
        r.c[i] = v; r.c[576 - i] = -v; r.c[576 + i] = -v; r.c[(1152 - i) % 1152] = v;
    }
    return r;
}
constexpr uint32_t cx_f2h(double v) {
    uint32_t s = v < 0 ? 0x8000u : 0u; double a = v < 0 ? -v : v;
    if (a < 1e-9) return 0;
    int e = 0;
    while (a >= 2.0) { a *= 0.5; e++; }
    while (a < 1.0 && e > -14) { a *= 2.0; e--; }
    double m = a * 1024.0; uint32_t mi = (uint32_t)m; double fr = m - mi;
    if (fr > 0.5 || (fr == 0.5 && (mi & 1))) mi++;
    return s | (uint32_t)(((e + 14) << 10) + mi);
}
struct Tab { uint32_t w[(QA + QB + QC) * 128]; };
constexpr Tab make_tab() {
    Tab t{};
    Cos1152 ct = make_cos();
    auto C = [&](int num, int den) { return ct.c[(num % den) * (1152 / den)]; };
    auto Sn = [&](int num, int den) { return ct.c[((num % den) * (1152 / den) + 864) % 1152]; };
    auto put = [&](int q0, int idx, int lane, double lo, double hi) { t.w[((q0 + idx / 4) * 32 + lane) * 4 + idx % 4] = cx_f2h(lo) | (cx_f2h(hi) << 16); };
    for (int lane = 0; lane < 32; lane++) {
        const int g = lane >> 2, q = lane & 3;
        for (int mt = 0; mt < 3; mt++) {
            const int ka = 8 * mt + g;
            for (int r = 0; r < 10; r++) {
                const int im = r & 1, i0 = (r >> 1) * 2;
                double v[2] = {0, 0};
                for (int e = 0; e < 2; e++) { int i = i0 + e, d1 = 4 * i + q; if (i < 9 && ka <= 18) v[e] = (im ? -Sn(ka * d1, 36) : C(ka * d1, 36)) / 8; }
                put(0, mt * 10 + r, lane, v[0], v[1]);
            }
            for (int v = 0; v < 2; v++) {
                const int d2 = 4 * q + v;
                put(0, 30 + (mt * 2 + v) * 2, lane, C(ka * d2, 576) * 4 / 3, C(ka * (d2 + 2), 576) * 4 / 3);
                put(0, 31 + (mt * 2 + v) * 2, lane, Sn(ka * d2, 576) * 4 / 3, Sn(ka * (d2 + 2), 576) * 4 / 3);
            }
        }
        for (int v = 0; v < 2; v++) for (int nt = 0; nt < 2; nt++) {
            const int kb = 2 * (g >> 1) + nt, part = g & 1;
            double b0[2] = {0, 0}, b1[2] = {0, 0};
            for (int e = 0; e < 2; e++) { int d2 = 4 * q + 2 * e + v; double c = C(kb * d2, 16) / 4, s = Sn(kb * d2, 16) / 4;
                b0[e] = part ? -s : c; b1[e] = part ? c : s; }
            put(0, 42 + (v * 2 + nt) * 2, lane, b0[0], b0[1]); put(0, 43 + (v * 2 + nt) * 2, lane, b1[0], b1[1]);
        }
        for (int par = 0; par < 2; par++) for (int a = 0; a < 4; a++) {
            const int ja = 2 * (q + 4 * (a >> 1)) + par; const double c = C(g * ja, 16) / 4, s = Sn(g * ja, 16) / 4;
            put(QA, par * 4 + a, lane, (a & 1) ? -s : c, (a & 1) ? c : s);
        }
        for (int h = 0; h < 2; h++) {
            put(QA, 8 + 2 * h, lane, C((g + 8 * h) * (2 * q), 128) / 2, C((g + 8 * h) * (2 * q + 1), 128) / 2);
            put(QA, 9 + 2 * h, lane, Sn((g + 8 * h) * (2 * q), 128) / 2, Sn((g + 8 * h) * (2 * q + 1), 128) / 2);
            put(QA, 15 + 2 * h, lane, C(g * (8 * h + 2 * q), 128), C(g * (8 * h + 2 * q + 1), 128));
            put(QA, 16 + 2 * h, lane, Sn(g * (8 * h + 2 * q), 128), Sn(g * (8 * h + 2 * q + 1), 128));
        }
        put(QA, 12, lane, C(g * 2 * q, 8) / 2, C(g * (2 * q + 1), 8) / 2);
        put(QA, 13, lane, Sn(g * 2 * q, 8) / 2, Sn(g * (2 * q + 1), 8) / 2);
        put(QA, 14, lane, -Sn(g * 2 * q, 8) / 2, -Sn(g * (2 * q + 1), 8) / 2);
        for (int u = 0; u < 4; u++) {
            const int ja = 2 * ((g >> 1) + 4 * (u & 1)) + (u >> 1), part = g & 1; double b0[2] = {0, 0}, b1[2] = {0, 0};
            for (int e = 0; e < 2; e++) { int ka = 2 * q + e; double c = C(ja * ka, 16) / 4, s = Sn(ja * ka, 16) / 4;
                b0[e] = part ? s : c; b1[e] = part ? c : -s; }
            put(QA, 19 + u * 2, lane, b0[0], b0[1]); put(QA, 20 + u * 2, lane, b1[0], b1[1]);
        }
        for (int m2 = 0; m2 < 2; m2++) {
            const int d2 = 2 * g + m2;
            for (int a = 0; a < 4; a++) {
                const int kb = 2 * q + (a >> 1); const double c = C(d2 * kb, 16) / 4, s = Sn(d2 * kb, 16) / 4;
                put(QA + QB, m2 * 4 + a, lane, (a & 1) ? s : c, (a & 1) ? c : -s);
            }
            for (int mt = 0; mt < 3; mt++) {
                const int ka = 8 * mt + 2 * q;
                put(QA + QB, 8 + (m2 * 3 + mt) * 2, lane, C(ka * d2, 576) * 4 / 3, C((ka + 1) * d2, 576) * 4 / 3);
                put(QA + QB, 9 + (m2 * 3 + mt) * 2, lane, Sn(ka * d2, 576) * 4 / 3, Sn((ka + 1) * d2, 576) * 4 / 3);
            }
        }
        for (int mt = 0; mt < 3; mt++) for (int nt = 0; nt < 5; nt++) {
            const int i = 2 * nt + (g & 1), d1 = 4 * i + (g >> 1); double b0[2] = {0, 0}, b1[2] = {0, 0};
            for (int e = 0; e < 2; e++) { int ka = 8 * mt + 2 * q + e;
                if (ka <= 18 && i < 9) { double wt = (ka == 0 || ka == 18) ? 0.125 : 0.25; b0[e] = wt * C(ka * d1, 36); b1[e] = -wt * Sn(ka * d1, 36); } }
            put(QA + QB, 20 + (mt * 5 + nt) * 2, lane, b0[0], b0[1]); put(QA + QB, 21 + (mt * 5 + nt) * 2, lane, b1[0], b1[1]);
        }
    }
    return t;
}
__device__ __align__(128) const Tab g_tab = make_tab();

struct Scratch {
    uint32_t cnt[30 * 32];
    uint32_t slot[96];
    uint32_t mod[2304];
    uint32_t modc[896 + 288];
    uint32_t T[128 * TP];
    uint4 h3[128 * 1152];
    uint4 U[72 * 4 * 1152];
};
__device__ __align__(1024) Scratch g_scr;
#define g_cnt (p.scr->cnt)
#define g_slot (p.scr->slot)
#define g_mod (p.scr->mod)
#define g_T (p.scr->T)
#define g_h3 (p.scr->h3)
#define g_U (p.scr->U)
constexpr int CNT_EPOCH = 0, CNT_H3 = 1, CNT_X1 = 26, CNT_NC = 27, CNT_U = 2;
#define PROFT(i) do {} while (0)
#define PROFDUMP() do {} while (0)
#define PROF0(i) do {} while (0)

__device__ __forceinline__ void mbar_init(uint32_t bar, uint32_t cnt) { asm volatile("mbarrier.init.shared::cta.b64 [%0], %1;" :: "r"(bar), "r"(cnt) : "memory"); }
__device__ __forceinline__ void mbar_expect(uint32_t bar, uint32_t bytes) { asm volatile("mbarrier.arrive.expect_tx.shared::cta.b64 _, [%0], %1;" :: "r"(bar), "r"(bytes) : "memory"); }
__device__ __forceinline__ void mbar_arrive(uint32_t bar) { asm volatile("mbarrier.arrive.shared::cta.b64 _, [%0];" :: "r"(bar) : "memory"); }
__device__ __forceinline__ void mbar_arrive_n(uint32_t bar, uint32_t n) { asm volatile("mbarrier.arrive.shared::cta.b64 _, [%0], %1;" :: "r"(bar), "r"(n) : "memory"); }
__device__ __forceinline__ void mbar_arrive_remote(uint32_t rbar) { asm volatile("mbarrier.arrive.relaxed.cluster.shared::cluster.b64 _, [%0];" :: "r"(rbar) : "memory"); }
__device__ __forceinline__ void mbar_wait(uint32_t bar, uint32_t parity) {
    asm volatile("{.reg .pred p; .reg .u32 c;\n"
        "mbarrier.try_wait.parity.shared::cta.b64 p, [%0], %1;\n@p bra.uni DONE;\nmov.u32 c, 0;\n"
        "LOOP: mbarrier.try_wait.parity.shared::cta.b64 p, [%0], %1;\n@p bra.uni DONE;\n"
        "add.u32 c, c, 1;\nsetp.lt.u32 p, c, %2;\n@p bra.uni LOOP;\ntrap;\nDONE:}" :: "r"(bar), "r"(parity), "n"(SPIN_LIMIT) : "memory");
}
__device__ __forceinline__ bool mbar_test(uint32_t bar, uint32_t parity) {
    uint32_t ok; asm volatile("{.reg .pred p; mbarrier.test_wait.parity.shared::cta.b64 p, [%1], %2; selp.u32 %0, 1, 0, p;}" : "=r"(ok) : "r"(bar), "r"(parity) : "memory"); return ok; }
__device__ __forceinline__ uint32_t mapa(uint32_t a, uint32_t rank) { uint32_t r; asm("mapa.shared::cluster.u32 %0, %1, %2;" : "=r"(r) : "r"(a), "r"(rank)); return r; }
__device__ __forceinline__ uint32_t clk32() { uint32_t r; asm volatile("mov.u32 %0, %%clock;" : "=r"(r)); return r; }
__device__ __forceinline__ void hb() {
    asm volatile("{.reg .b32 a, b; .reg .pred p; mma.sync.aligned.m16n8k8.row.col.f16.f16.f16.f16 {a, b}, {%0,%0}, {%0}, {%0,%0};\n"
                 "setp.ne.u32 p, a, 0; @p trap;}" :: "r"(0));
}
__device__ __forceinline__ void spin_until(uint32_t t) { while (__any_sync(~0u, (int)(clk32() - t) < 0)) hb(); }
__device__ __forceinline__ bool elect() { uint32_t r; asm volatile("{.reg .pred p; elect.sync _|p, 0xffffffff; selp.u32 %0, 1, 0, p;}" : "=r"(r)); return r; }
__device__ __forceinline__ void bar_sync(int id, int n) { asm volatile("bar.sync %0, %1;" :: "r"(id), "r"(n) : "memory"); }
__device__ __forceinline__ void bulk_load(uint32_t dst, const void* src, uint32_t bytes, uint32_t bar) {
    asm volatile("cp.async.bulk.shared::cluster.global.mbarrier::complete_tx::bytes [%0], [%1], %2, [%3];" :: "r"(dst), "l"(src), "r"(bytes), "r"(bar) : "memory"); }
__device__ __forceinline__ void tma2(uint32_t dst, const CUtensorMap* m, int c0, int c1, uint32_t bar) {
    asm volatile("cp.async.bulk.tensor.2d.shared::cluster.global.mbarrier::complete_tx::bytes [%0], [%1, {%3, %4}], [%2];" :: "r"(dst), "l"(m), "r"(bar), "r"(c0), "r"(c1) : "memory"); }
__device__ __forceinline__ void tma3(uint32_t dst, const CUtensorMap* m, int c0, int c1, int c2, uint32_t bar) {
    asm volatile("cp.async.bulk.tensor.3d.shared::cluster.global.mbarrier::complete_tx::bytes [%0], [%1, {%3, %4, %5}], [%2];" :: "r"(dst), "l"(m), "r"(bar), "r"(c0), "r"(c1), "r"(c2) : "memory"); }
__device__ __forceinline__ void tma4(uint32_t dst, const CUtensorMap* m, int c0, int c1, int c2, int c3, uint32_t bar) {
    asm volatile("cp.async.bulk.tensor.4d.shared::cluster.global.mbarrier::complete_tx::bytes [%0], [%1, {%3, %4, %5, %6}], [%2];" :: "r"(dst), "l"(m), "r"(bar), "r"(c0), "r"(c1), "r"(c2), "r"(c3) : "memory"); }
__device__ __forceinline__ void fence_async_g() { asm volatile("fence.proxy.async.global;" ::: "memory"); }
__device__ __forceinline__ void fence_async_s() { asm volatile("fence.proxy.async.shared::cta;" ::: "memory"); }
__device__ __forceinline__ uint4 lds128(uint32_t a) { uint4 v; asm volatile("ld.shared.v4.u32 {%0,%1,%2,%3}, [%4];" : "=r"(v.x), "=r"(v.y), "=r"(v.z), "=r"(v.w) : "r"(a) : "memory"); return v; }
__device__ __forceinline__ uint32_t lds32(uint32_t a) { uint32_t v; asm volatile("ld.shared.u32 %0, [%1];" : "=r"(v) : "r"(a) : "memory"); return v; }
__device__ __forceinline__ void sts128(uint32_t a, uint4 v) { asm volatile("st.shared.v4.u32 [%0], {%1,%2,%3,%4};" :: "r"(a), "r"(v.x), "r"(v.y), "r"(v.z), "r"(v.w) : "memory"); }
__device__ __forceinline__ void sts32(uint32_t a, uint32_t v) { asm volatile("st.shared.u32 [%0], %1;" :: "r"(a), "r"(v) : "memory"); }
__device__ __forceinline__ void sts16(uint32_t a, uint32_t v) { asm volatile("st.shared.u16 [%0], %1;" :: "r"(a), "h"((uint16_t)v) : "memory"); }
__device__ __forceinline__ uint4 ldx128(const void* p) {
    uint4 v; asm volatile("{.reg .b128 t; .reg .b64 a, b; ld.relaxed.gpu.global.b128 t, [%4]; mov.b128 {a, b}, t; mov.b64 {%0,%1}, a; mov.b64 {%2,%3}, b;}"
        : "=r"(v.x), "=r"(v.y), "=r"(v.z), "=r"(v.w) : "l"(p) : "memory"); return v; }
__device__ __forceinline__ void stx128(void* p, uint4 v) {
    asm volatile("{.reg .b128 t; .reg .b64 a, b; mov.b64 a, {%1,%2}; mov.b64 b, {%3,%4}; mov.b128 t, {a, b}; st.relaxed.gpu.global.b128 [%0], t;}"
        :: "l"(p), "r"(v.x), "r"(v.y), "r"(v.z), "r"(v.w) : "memory"); }
__device__ __forceinline__ uint32_t ld_relaxed(const uint32_t* p) { uint32_t v; asm volatile("ld.relaxed.gpu.global.u32 %0, [%1];" : "=r"(v) : "l"(p) : "memory"); return v; }
__device__ __forceinline__ uint32_t ld_acquire(const uint32_t* p) { uint32_t v; asm volatile("ld.acquire.gpu.global.u32 %0, [%1];" : "=r"(v) : "l"(p) : "memory"); return v; }
__device__ __forceinline__ void st_relaxed(uint32_t* p, uint32_t v) { asm volatile("st.relaxed.gpu.global.u32 [%0], %1;" :: "l"(p), "r"(v) : "memory"); }
__device__ __forceinline__ void red_release(uint32_t* p) { asm volatile("red.release.gpu.global.add.u32 [%0], 1;" :: "l"(p) : "memory"); }
__device__ __forceinline__ void wait_count(const uint32_t* p, uint32_t target) {
    int it = 0; while ((int)(ld_acquire(p) - target) < 0) { if (++it > SPIN_LIMIT) __trap(); }
}
__device__ __forceinline__ uint32_t ldg_nc32(const void* p) { uint32_t v; asm volatile("ld.global.nc.L1::no_allocate.u32 %0, [%1];" : "=r"(v) : "l"(p)); return v; }
__device__ __forceinline__ uint32_t ldg_nc16(const void* p) { uint16_t v; asm volatile("ld.global.nc.u16 %0, [%1];" : "=h"(v) : "l"(p)); return v; }
__device__ __forceinline__ float bf_lo(uint32_t w) { return __uint_as_float(w << 16); }
__device__ __forceinline__ float bf_hi(uint32_t w) { return __uint_as_float(w & 0xFFFF0000u); }
__device__ __forceinline__ uint32_t pack_bf(float lo, float hi) { uint32_t r; asm("cvt.rn.bf16x2.f32 %0, %1, %2;" : "=r"(r) : "f"(hi), "f"(lo)); return r; }
__device__ __forceinline__ uint32_t pack_h(float lo, float hi) { uint32_t r; asm("cvt.rn.f16x2.f32 %0, %1, %2;" : "=r"(r) : "f"(hi), "f"(lo)); return r; }
__device__ __forceinline__ float bf_round(float v) { return bf_lo(pack_bf(v, 0.f)); }
__device__ __forceinline__ uint32_t hmul2(uint32_t a, uint32_t b) { uint32_t r; asm("mul.rn.f16x2 %0, %1, %2;" : "=r"(r) : "r"(a), "r"(b)); return r; }
__device__ __forceinline__ uint32_t hfma2(uint32_t a, uint32_t b, uint32_t c) { uint32_t r; asm("fma.rn.f16x2 %0, %1, %2, %3;" : "=r"(r) : "r"(a), "r"(b), "r"(c)); return r; }
__device__ __forceinline__ uint32_t hfms2(uint32_t a, uint32_t b, uint32_t c) { uint32_t r; asm("{.reg .b32 t; neg.f16x2 t, %3; fma.rn.f16x2 %0, %1, %2, t;}" : "=r"(r) : "r"(a), "r"(b), "r"(c)); return r; }
__device__ __forceinline__ uint32_t hadd2(uint32_t a, uint32_t b) { uint32_t r; asm("add.rn.f16x2 %0, %1, %2;" : "=r"(r) : "r"(a), "r"(b)); return r; }
__device__ __forceinline__ uint32_t hsub2(uint32_t a, uint32_t b) { uint32_t r; asm("sub.rn.f16x2 %0, %1, %2;" : "=r"(r) : "r"(a), "r"(b)); return r; }
__device__ __forceinline__ void cmul_neg(uint32_t& re, uint32_t& im, uint32_t c, uint32_t s) { uint32_t a = hfma2(re, c, hmul2(im, s)), b = hfms2(im, c, hmul2(re, s)); re = a; im = b; }
__device__ __forceinline__ void cmul_pos(uint32_t& re, uint32_t& im, uint32_t c, uint32_t s) { uint32_t a = hfms2(re, c, hmul2(im, s)), b = hfma2(im, c, hmul2(re, s)); re = a; im = b; }
__device__ __forceinline__ void mma_h(uint32_t& d0, uint32_t& d1, uint32_t a0, uint32_t a1, uint32_t a2, uint32_t a3, uint32_t b0, uint32_t b1) {
    asm("mma.sync.aligned.m16n8k16.row.col.f16.f16.f16.f16 {%0,%1}, {%2,%3,%4,%5}, {%6,%7}, {%0,%1};" : "+r"(d0), "+r"(d1) : "r"(a0), "r"(a1), "r"(a2), "r"(a3), "r"(b0), "r"(b1)); }
__device__ __forceinline__ void mma_h8(uint32_t& d0, uint32_t& d1, uint32_t a0, uint32_t a1, uint32_t b0) {
    asm("mma.sync.aligned.m16n8k8.row.col.f16.f16.f16.f16 {%0,%1}, {%2,%3}, {%4}, {%0,%1};" : "+r"(d0), "+r"(d1) : "r"(a0), "r"(a1), "r"(b0)); }
__device__ __forceinline__ void mma_f(float (&d)[4], uint32_t a0, uint32_t a1, uint32_t a2, uint32_t a3, uint32_t b0, uint32_t b1) {
    asm("mma.sync.aligned.m16n8k16.row.col.f32.f16.f16.f32 {%0,%1,%2,%3}, {%4,%5,%6,%7}, {%8,%9}, {%0,%1,%2,%3};"
        : "+f"(d[0]), "+f"(d[1]), "+f"(d[2]), "+f"(d[3]) : "r"(a0), "r"(a1), "r"(a2), "r"(a3), "r"(b0), "r"(b1)); }
template <int NQ> __device__ __forceinline__ void load_tab(uint32_t (&r)[NQ * 4], uint32_t addr) {
    #pragma unroll
    for (int i = 0; i < NQ; i++) { uint4 v = lds128(addr + i * 512); r[4 * i] = v.x; r[4 * i + 1] = v.y; r[4 * i + 2] = v.z; r[4 * i + 3] = v.w; }
}
__device__ __forceinline__ void warp_sum2(float& a, float& b) {
    #pragma unroll
    for (int o = 16; o; o >>= 1) { a += __shfl_xor_sync(~0u, a, o); b += __shfl_xor_sync(~0u, b, o); }
}
__device__ __forceinline__ float gelu2(float x) {
    float t = x * fmaf(x * x, 0.044715f * 0.7978845608028654f, 0.7978845608028654f), th;
    asm volatile("tanh.approx.f32 %0, %1;" : "=f"(th) : "f"(t));
    return fmaf(x, th, x);
}
__device__ __forceinline__ uint32_t desc_lo(uint32_t addr, uint32_t lbo) { return ((addr & 0x3FFFF) >> 4) | ((lbo >> 4) << 16); }
constexpr uint32_t DHI_A = (1024 >> 4) | (1u << 30), DHI_H3 = 256 >> 4, DHI_U = 128 >> 4;
#define WG_FENCE() asm volatile("wgmma.fence.sync.aligned;" ::: "memory")
#define WG_COMMIT() asm volatile("wgmma.commit_group.sync.aligned;" ::: "memory")
#define WG_WAIT(n) asm volatile("wgmma.wait_group.sync.aligned %0;" :: "n"(n) : "memory")
#define R4(b) "+f"(d[b]), "+f"(d[b + 1]), "+f"(d[b + 2]), "+f"(d[b + 3])
#define R12(b) R4(b), R4(b + 4), R4(b + 8)
#define R36(b) R12(b), R12(b + 12), R12(b + 24)
template <uint32_t BHI> __device__ __forceinline__ void wgmma144(float (&d)[72], uint32_t da, uint32_t db, int acc) {
    asm volatile("{.reg .pred p; .reg .b64 a, b; setp.ne.b32 p, %74, 0; mov.b64 a, {%72, %75}; mov.b64 b, {%73, %76};\n"
        "wgmma.mma_async.sync.aligned.m64n144k16.f32.bf16.bf16 {%0,%1,%2,%3,%4,%5,%6,%7,%8,%9,%10,%11,%12,%13,%14,%15,%16,%17,%18,%19,%20,%21,%22,%23,"
        "%24,%25,%26,%27,%28,%29,%30,%31,%32,%33,%34,%35,%36,%37,%38,%39,%40,%41,%42,%43,%44,%45,%46,%47,"
        "%48,%49,%50,%51,%52,%53,%54,%55,%56,%57,%58,%59,%60,%61,%62,%63,%64,%65,%66,%67,%68,%69,%70,%71}, a, b, p, 1, 1, 1, 1;}\n"
        : R36(0), R36(36) : "r"(da), "r"(db), "r"(acc), "n"(DHI_A), "n"(BHI));
}
__device__ __forceinline__ void wgmma72(float (&d)[36], uint32_t da, uint32_t db, int acc) {
    asm volatile("{.reg .pred p; .reg .b64 a, b; setp.ne.b32 p, %38, 0; mov.b64 a, {%36, %39}; mov.b64 b, {%37, %40};\n"
        "wgmma.mma_async.sync.aligned.m64n72k16.f32.bf16.bf16 {%0,%1,%2,%3,%4,%5,%6,%7,%8,%9,%10,%11,%12,%13,%14,%15,%16,%17,%18,%19,%20,%21,%22,%23,"
        "%24,%25,%26,%27,%28,%29,%30,%31,%32,%33,%34,%35}, a, b, p, 1, 1, 1, 1;}\n"
        : R36(0) : "r"(da), "r"(db), "r"(acc), "n"(DHI_A), "n"(DHI_H3));
}

__device__ __forceinline__ int g2_kb(int n, int kh) { return 36 * kh + (n < 32 ? 9 * ((n >> 2) & 3) + 2 * (n & 3) + (n >> 4) : 9 * (n - 32) + 8); }

template <uint32_t BHI, int I0, int I1, bool ZERO, bool FIRST, bool LAST, class Hook>
__device__ __forceinline__ void mainloop(float (&d)[72], uint32_t bars, uint32_t da0, uint32_t db0, bool lead, Hook hook) {
    uint32_t s = I0 % NST, ph = (I0 / NST) & 1, prev = (I0 + NST - 1) % NST;
    #pragma unroll 1
    for (int i = I0; i < I1; i++) {
        mbar_wait(bars + 8 * BAR_FULL + 8 * s, ph);
        const uint32_t da = da0 + s * (A_BYTES / 16), db = db0 + s * (B_BYTES / 16);
        WG_FENCE();
        wgmma144<BHI>(d, da, db, ZERO ? i - I0 : 1);
        wgmma144<BHI>(d, da + 128, db + 288, 1); wgmma144<BHI>(d, da + 256, db + 576, 1); wgmma144<BHI>(d, da + 384, db + 864, 1);
        WG_COMMIT();
        WG_WAIT(1);
        if (lead && (!FIRST || i > I0)) mbar_arrive(bars + 8 * BAR_EMPTY + 8 * prev);
        hook(i);
        prev = s; if (++s == NST) { s = 0; ph ^= 1; }
    }
    if (LAST) { WG_WAIT(0); if (lead) mbar_arrive(bars + 8 * BAR_EMPTY + 8 * prev); }
}

struct Params {
    const uint16_t *x, *wr, *wi, *w1, *b1, *w2, *b2, *c, *wmod;
    uint16_t* out;
    Scratch* scr;
    const Tab* tab;
};

__device__ __forceinline__ void mma_bf(float (&d)[4], const uint32_t (&a)[4], uint32_t b0, uint32_t b1) {
    asm("mma.sync.aligned.m16n8k16.row.col.f32.bf16.bf16.f32 {%0,%1,%2,%3}, {%4,%5,%6,%7}, {%8,%9}, {%0,%1,%2,%3};"
        : "+f"(d[0]), "+f"(d[1]), "+f"(d[2]), "+f"(d[3]) : "r"(a[0]), "r"(a[1]), "r"(a[2]), "r"(a[3]), "r"(b0), "r"(b1)); }
__device__ __forceinline__ void ldsm4t(uint32_t (&a)[4], uint32_t addr) {
    asm volatile("ldmatrix.sync.aligned.m8n8.x4.trans.shared.b16 {%0,%1,%2,%3}, [%4];" : "=r"(a[0]), "=r"(a[1]), "=r"(a[2]), "=r"(a[3]) : "r"(addr) : "memory"); }
__device__ __forceinline__ float silu(float v) { return __fdividef(v, 1.f + __expf(-v)); }
__device__ __forceinline__ uint32_t bfma2(uint32_t a, uint32_t b, uint32_t c) { uint32_t r; asm("fma.rn.bf16x2 %0, %1, %2, %3;" : "=r"(r) : "r"(a), "r"(b), "r"(c)); return r; }
__device__ __forceinline__ void radix16(const uint4 (&V)[4], const uint32_t (&B)[16], uint4 (&o)[4]) {
    #pragma unroll
    for (int nt = 0; nt < 4; nt++) {
        o[nt] = make_uint4(0, 0, 0, 0);
        #pragma unroll
        for (int ks = 0; ks < 2; ks++) {
            const uint32_t b0 = B[(ks * 4 + nt) * 2], b1 = B[(ks * 4 + nt) * 2 + 1];
            mma_h(o[nt].x, o[nt].y, V[2 * ks].x, V[2 * ks].y, V[2 * ks + 1].x, V[2 * ks + 1].y, b0, b1);
            mma_h(o[nt].z, o[nt].w, V[2 * ks].z, V[2 * ks].w, V[2 * ks + 1].z, V[2 * ks + 1].w, b0, b1);
        }
    }
}
template <int OFF, int N> __device__ __forceinline__ void gelu_store(const float (&d)[N], char* p, int q) {
    uint32_t w[9];
    #pragma unroll
    for (int blk = 0; blk < 9; blk++) w[blk] = pack_bf(gelu2(d[OFF + 4 * blk]), gelu2(d[OFF + 4 * blk + 1]));
    asm volatile("st.v4.u32 [%0], {%1,%2,%3,%4};" :: "l"(p + q * 128), "r"(w[0]), "r"(w[1]), "r"(w[2]), "r"(w[3]) : "memory");
    asm volatile("st.v4.u32 [%0+512], {%1,%2,%3,%4};" :: "l"(p + q * 128), "r"(w[4]), "r"(w[5]), "r"(w[6]), "r"(w[7]) : "memory");
    asm volatile("st.u32 [%0+1024], %1;" :: "l"(p + q * 4), "r"(w[8]) : "memory");
}

__global__ void __cluster_dims__(2, 1, 1) __launch_bounds__(NTHR, 1)
fused_kernel(const Params p,
             const __grid_constant__ CUtensorMap tm_w1a, const __grid_constant__ CUtensorMap tm_w1b, const __grid_constant__ CUtensorMap tm_w2,
             const __grid_constant__ CUtensorMap tm_h3a, const __grid_constant__ CUtensorMap tm_h3b,
             const __grid_constant__ CUtensorMap tm_wr, const __grid_constant__ CUtensorMap tm_wi, const __grid_constant__ CUtensorMap tm_wm,
             const __grid_constant__ CUtensorMap tm_t, const __grid_constant__ CUtensorMap tm_tx)
{
    extern __shared__ char smem_raw[];
    const uint32_t t0 = clk32();
    const uint32_t sm = __shfl_sync(~0u, ((uint32_t)__cvta_generic_to_shared(smem_raw) + 1023u) & ~1023u, 0);
    const int tid = threadIdx.x, warp = __shfl_sync(~0u, tid >> 5, 0), lane = tid & 31, g = lane >> 2, q = lane & 3;
    const int b = blockIdx.x;
    const uint32_t rank = b & 1;
    const uint32_t bars = sm + OFF_BAR;
    const bool rowcta = b < 128;

    auto nc_issue = [&](int st, uint32_t sl) {
        const int pass = st >= 18;
        mbar_expect(bars + 8 * (BAR_X + sl), 28672);
        tma3(sm + sl * 28672, &tm_wm, 0, 32 * (st - 18 * pass), 18 + 28 * pass + 7 * (b - 128), bars + 8 * (BAR_X + sl));
    };
    if (warp == 13) hb();
    uint32_t cw = 0, epoch;
    if (warp < 12) {
        if (lane < 24) cw = ldg_nc32(p.c + 48 * warp + 2 * lane);
        epoch = ld_relaxed(g_cnt + CNT_EPOCH * 32);
        if (b < 72) {
            const uint16_t* src = p.wmod + (48 * warp + (lane >> 1)) * 3456 + 16 * b + (lane & 1) * 8;
            const uint32_t dst = sm + OFF_STRIP + (48 * warp + (lane >> 1)) * 48 + (lane & 1) * 16;
            #pragma unroll
            for (int u = 0; u < 3; u++) asm volatile("cp.async.cg.shared.global" CPHINT " [%0], [%1], 16;" :: "r"(dst + u * 768), "l"(src + u * 16 * 3456) : "memory");
            asm volatile("cp.async.commit_group;" ::: "memory");
        }
    } else {
      if (elect()) {
        if (warp == 15) {
            mbar_init(bars + 8 * BAR_TAB, 1); fence_async_s();
            if (rowcta) { mbar_expect(bars + 8 * BAR_TAB, QA * 512); bulk_load(sm + OFF_TAB, p.tab, QA * 512, bars + 8 * BAR_TAB); }
            asm volatile("prefetch.tensormap [%0];" :: "l"(&tm_wr) : "memory"); asm volatile("prefetch.tensormap [%0];" :: "l"(&tm_wi) : "memory");
            asm volatile("prefetch.tensormap [%0];" :: "l"(&tm_t) : "memory"); asm volatile("prefetch.tensormap [%0];" :: "l"(&tm_tx) : "memory");
        } else if (warp == 14) {
            for (int i = BAR_W; i < BAR_X; i++) mbar_init(bars + 8 * i, i == BAR_CANSEND ? 2 : 1);
            mbar_expect(bars + 8 * BAR_W, 28672); mbar_expect(bars + 8 * BAR_TAB2, (QB + QC) * 512);
            mbar_expect(bars + 8 * BAR_ROLE, 4); mbar_expect(bars + 8 * BAR_P2R, 9216); mbar_expect(bars + 8 * BAR_RECV, 18432);
        } else if (warp == 13) {
            for (int i = 0; i < 2 * NST; i++) mbar_init(bars + 8 * i, 2);
            for (int i = 0; i < NST; i++) mbar_expect(bars + 8 * (BAR_FULL + i), A_BYTES);
        }
        else {
            for (int i = 0; i < 16; i++) mbar_init(bars + 8 * (BAR_X + i), rowcta || i < 6 ? 1 : 14);
            if (!rowcta) { fence_async_s(); for (int st = 0; st < 6; st++) nc_issue(st, st); }
        }
        asm volatile("fence.mbarrier_init.release.cluster;" ::: "memory");
      }
      __syncwarp();
      epoch = ld_relaxed(g_cnt + CNT_EPOCH * 32);
    }
    __syncthreads();
    PROF0(22);
    asm volatile("barrier.cluster.arrive.relaxed.aligned;" ::: "memory");
    if (warp < 4) sts16(sm + OFF_MODA + ((warp + 1) * 32 + lane) * 16 + warp * 4 + 2, 0);
    if (warp >= 8) {
        const int k1 = tid & 15, s1 = (tid >> 4) & 15;
        float s, c;
        __sincosf((float)(((k1 * (128 * s1 + b) + 1024) & 2047) - 1024) * (3.14159265358979f / 1024.f), &s, &c); s *= 0.25f; c *= 0.25f;
        const int rf = ((s1 >> 3) * 4 + (k1 >> 2)) * 2 + ((s1 >> 2) & 1), ri = ((k1 >> 3) * 4 + (s1 >> 2)) * 2 + ((k1 >> 2) & 1);
        const uint32_t af = sm + OFF_B3 + ((rf >> 2) * 32 + (k1 & 3) * 8 + (s1 & 3)) * 16 + (rf & 3) * 4;
        const uint32_t ai = sm + OFF_B3 + 2048 + ((ri >> 2) * 32 + (s1 & 3) * 8 + (k1 & 3)) * 16 + (ri & 3) * 4;
        sts32(af, pack_h(c, s)); sts32(af + 64, pack_h(-s, c)); sts32(ai, pack_h(c, -s)); sts32(ai + 64, pack_h(s, c));
    }
    if (rowcta) spin_until(t0 + XDELAY);
    if (rowcta && elect()) {
        mbar_expect(bars + 8 * (BAR_X + warp), 1152);
        bulk_load(sm + OFF_STAGE + warp * 1152, p.x + (size_t)(b + 128 * warp) * D_, 1152, bars + 8 * (BAR_X + warp));
    }
    const uint32_t tag = (epoch + 1) & 0xFFFFu;
    if (warp < 12 && lane < 24) sts32(sm + OFF_SILU + (24 * warp + lane) * 4, pack_bf(silu(bf_lo(cw)), silu(bf_hi(cw))));
    hb();
    PROF0(26);
    uint32_t ta[QA * 4];
    const bool ta_early = rowcta && __any_sync(~0u, mbar_test(bars + 8 * BAR_TAB, 0));
    if (ta_early) load_tab<QA>(ta, sm + OFF_TAB + lane * 16);
    if (warp < 12 && b < 72) {
        uint32_t sb[6];
        __syncwarp();
        #pragma unroll
        for (int u = 0; u < 6; u++) sb[u] = lds32(sm + OFF_SILU + (24 * warp + 4 * u + q) * 4);
        asm volatile("cp.async.wait_all;" ::: "memory");
        __syncwarp();
        float acc[4] = {0, 0, 0, 0};
        #pragma unroll
        for (int u = 0; u < 3; u++) {
            uint32_t a[4];
            ldsm4t(a, sm + OFF_STRIP + (48 * warp + 16 * u + (lane & 7) + 8 * (lane >> 4)) * 48 + ((lane >> 3) & 1) * 16);
            mma_bf(acc, a, sb[2 * u], sb[2 * u + 1]);
        }
        if (q == 0) { sts32(sm + OFF_RED + (g * 12 + warp) * 4, __float_as_uint(acc[0])); sts32(sm + OFF_RED + ((g + 8) * 12 + warp) * 4, __float_as_uint(acc[2])); }
        PROF0(0);
        bar_sync(3, 384);
        if (warp == 0) {
            if (lane < 16) {
                float sum = 0;
                #pragma unroll
                for (int u = 0; u < 3; u++) { const uint4 v = lds128(sm + OFF_RED + lane * 48 + u * 16);
                    sum += (__uint_as_float(v.x) + __uint_as_float(v.y)) + (__uint_as_float(v.z) + __uint_as_float(v.w)); }
                sum = bf_round(sum); if (b >= 36) sum = bf_round(1.f + sum);
                st_relaxed(g_mod + b * MODPAD + (lane & 1) * 8 + (lane >> 1), (pack_h(0.f, sum) & 0xFFFF0000u) | tag);
            }
            __syncwarp();
            PROF0(1);
        }
    }

    const int trow = 4 * (b & 7) + ((b >> 4) & 3) + 64 * ((b >> 3) & 1) + 32 * (b >> 6);
    uint32_t* const tptr = g_T + (size_t)trow * TP + (warp < 9 ? q * 288 + 32 * warp : 4608 + 8 * q) + 4 * g;
    const int tstr = warp < 9 ? 1152 : 32;
    const uint32_t scol = sm + OFF_SPEC + (q * SPEC_P + (warp < 8 ? 72 * (warp >> 1) + 40 * (warp & 1) + 4 * g : warp == 8 ? 72 * (g >> 1) + 32 + 4 * (g & 1) : 288 + 4 * g)) * 4;
    const int wc0 = (b >> 3) * 289 + 72 * ((b & 7) >> 1) + 40 * (b & 1);

    uint32_t xw[9], t_st = t0;
    if (!rowcta) {
        const int nst = b < 130 ? 36 : 18;
        __syncthreads();
        if (warp == 14) {
            uint32_t sl = 0, ph = 0;
            #pragma unroll 1
            for (int st = 6; st < nst; st++) {
                mbar_wait(bars + 8 * (BAR_X + 6 + sl), ph);
                if (elect()) nc_issue(st, sl);
                if (++sl == 6) { sl = 0; ph ^= 1; }
            }
        } else if (warp < 14) {
            uint32_t sl = 0, ph = 0;
            const uint32_t ad0 = sm + (warp >> 1) * 4096 + ((lane & 7) + 8 * (lane >> 4)) * 128, ch = (warp & 1) * 4 + ((lane >> 3) & 1);
            #pragma unroll 1
            for (int pass = 0; pass * 18 < nst; pass++) {
                float acc[2][4] = {};
                #pragma unroll 1
                for (int st = 0; st < 18; st++) {
                    const uint32_t sa = sm + OFF_SILU + (16 * st + q) * 4;
                    const uint32_t b0 = lds32(sa), b1 = lds32(sa + 16), b2 = lds32(sa + 32), b3 = lds32(sa + 48);
                    mbar_wait(bars + 8 * (BAR_X + sl), ph);
                    if (st == 0 && pass == 0) PROF0(9);
                    if (st == 17 && pass == 0) PROF0(24);
                    #pragma unroll
                    for (int m = 0; m < 2; m++) {
                        uint32_t a[4], a2[4];
                        const uint32_t ad = ad0 + sl * 28672 + ((ch + 2 * m) ^ (lane & 7)) * 16;
                        ldsm4t(a, ad); ldsm4t(a2, ad + 2048);
                        mma_bf(acc[m], a, b0, b1); mma_bf(acc[m], a2, b2, b3);
                    }
                    if (elect()) mbar_arrive(bars + 8 * (BAR_X + 6 + sl));
                    if (++sl == 6) { sl = 0; ph ^= 1; }
                }
                const int cb = 28 * pass + 7 * (b - 128) + (warp >> 1), gg = (g >> 1) + 4 * q;
                #pragma unroll
                for (int m = 0; m < 2; m++) {
                    const int qq = (warp & 1) * 2 + m;
                    float v = bf_round(q ? acc[m][2] : acc[m][0]); if (cb >= 27) v *= 0.5f; else if (cb >= 18) v += 1.f;
                    const uint32_t w = pack_bf(v, __shfl_xor_sync(~0u, v, 4));
                    if (q < 2 && !(g & 1) && cb < 36) p.scr->modc[cb < 27 ? ((cb >> 2) * 32 + 4 * gg + qq) * 4 + (cb & 3) : 896 + 32 * (cb - 27) + 8 * qq + gg] = w;
                }
                bar_sync(1, 448);
                if (tid == 0) { fence_async_g(); red_release(g_cnt + (CNT_NC + pass) * 32); if (pass == 0) PROFT(25); }
                __syncwarp();
            }
            fence_async_s();
        }
        __syncthreads();
    } else {
        if (!ta_early) { mbar_wait(bars + 8 * BAR_TAB, 0); load_tab<QA>(ta, sm + OFF_TAB + lane * 16); }
        uint32_t nb[2][5];
        uint4 mv = make_uint4(tag, tag, tag, tag);
        const int mc = tid - 224, mst = (mc >> 2) % 36, midx = (mc < 144 ? 10 : 0) + 5 * ((mc >> 1) & 1) + (mst >> 3);
        const uint32_t* mp = g_mod + (mc >> 2) * MODPAD + (mc & 3) * 4;
        const uint32_t ma = sm + OFF_MODA + ((midx >> 2) * 32 + (mc & 1) * 16 + (mst & 3)) * 16 + (midx & 3) * 4 + ((mst >> 2) & 1) * 2;
        #define MOD_MISSING ((((mv.x ^ tag) | (mv.y ^ tag) | (mv.z ^ tag) | (mv.w ^ tag)) & 0xFFFFu) != 0)
        hb();
        mbar_wait(bars + 8 * (BAR_X + warp), 0);
        if (warp >= 7) mv = ldx128(mp);
        PROF0(28);
        #pragma unroll
        for (int i = 0; i < 9; i++) xw[i] = lds32(sm + OFF_STAGE + warp * 1152 + (32 * i + 8 * q + g) * 4);
        {
            float s1 = 0, s2 = 0;
            #pragma unroll
            for (int i = 0; i < 9; i++) { float lo = bf_lo(xw[i]), hi = bf_hi(xw[i]); s1 += lo + hi; s2 = fmaf(lo, lo, fmaf(hi, hi, s2)); }
            warp_sum2(s1, s2);
            const float m = s1 * (1.f / D_), r = rsqrtf(fmaxf(s2 * (1.f / D_) - m * m, 0.f) + 1e-5f), mr = -m * r;
            #pragma unroll
            for (int pp = 0; pp < 5; pp++) {
                nb[0][pp] = pack_h(fmaf(bf_lo(xw[2 * pp]), r, mr), pp < 4 ? fmaf(bf_lo(xw[pp < 4 ? 2 * pp + 1 : 0]), r, mr) : 0.f);
                nb[1][pp] = pack_h(fmaf(bf_hi(xw[2 * pp]), r, mr), pp < 4 ? fmaf(bf_hi(xw[pp < 4 ? 2 * pp + 1 : 0]), r, mr) : 0.f);
            }
        }
        PROF0(2);
        if (warp >= 7) {
            for (int it = 0; __any_sync(~0u, MOD_MISSING); it++) { mv = ldx128(mp); hb(); if (it > SPIN_LIMIT) __trap(); }
            sts16(ma, mv.x >> 16); sts16(ma + 64, mv.y >> 16); sts16(ma + 128, mv.z >> 16); sts16(ma + 192, mv.w >> 16);
        }
        __syncthreads();
        PROF0(3);
        if (warp >= 13 && elect()) {
            if (warp == 15) bulk_load(sm + OFF_TAB + QA * 512, p.tab->w + QA * 128, (QB + QC) * 512, bars + 8 * BAR_TAB2);
            else tma3(sm + OFF_WRAW + (warp - 13) * 14336, warp == 13 ? &tm_wr : &tm_wi, wc0 & ~7, 0, 0, bars + 8 * BAR_W);
        }
        __syncwarp();
        {
            uint32_t md[20];
            load_tab<5>(md, sm + OFF_MODA + lane * 16);
            #pragma unroll
            for (int v = 0; v < 2; v++)
                #pragma unroll
                for (int pp = 0; pp < 5; pp++) nb[v][pp] = hfma2(nb[v][pp], md[v * 5 + pp], md[10 + v * 5 + pp]);
        }
        uint32_t re[3][2], im[3][2];
        #pragma unroll
        for (int mt = 0; mt < 3; mt++)
            #pragma unroll
            for (int v = 0; v < 2; v++) {
                re[mt][v] = 0; im[mt][v] = 0;
                mma_h8(re[mt][v], im[mt][v], ta[mt * 10 + 8], ta[mt * 10 + 9], nb[v][4]);
                mma_h(re[mt][v], im[mt][v], ta[mt * 10], ta[mt * 10 + 1], ta[mt * 10 + 2], ta[mt * 10 + 3], nb[v][0], nb[v][1]);
                mma_h(re[mt][v], im[mt][v], ta[mt * 10 + 4], ta[mt * 10 + 5], ta[mt * 10 + 6], ta[mt * 10 + 7], nb[v][2], nb[v][3]);
                cmul_neg(re[mt][v], im[mt][v], ta[30 + (mt * 2 + v) * 2], ta[31 + (mt * 2 + v) * 2]);
            }
        const uint32_t srow = sm + OFF_SPEC + warp * (SPEC_P * 4);
        #pragma unroll
        for (int nt = 0; nt < 2; nt++) {
            uint32_t o[2][4];
            #pragma unroll
            for (int v = 0; v < 2; v++) {
                const uint32_t b0 = ta[42 + (v * 2 + nt) * 2], b1 = ta[43 + (v * 2 + nt) * 2];
                o[v][0] = o[v][1] = o[v][2] = o[v][3] = 0;
                mma_h(o[v][0], o[v][1], re[0][v], re[1][v], im[0][v], im[1][v], b0, b1);
                mma_h(o[v][2], o[v][3], re[2][v], re[2][v], im[2][v], im[2][v], b0, b1);
            }
            const uint32_t a = srow + (g + 72 * q + 36 * nt) * 4, a2 = srow + (288 - g - 72 * q - 36 * nt) * 4;
            sts32(a, hadd2(o[0][0], o[1][0])); sts32(a + 32, hadd2(o[0][1], o[1][1])); if (g < 3) sts32(a + 64, hadd2(o[0][2], o[1][2]));
            if (g > 0 || (q == 0 && nt == 0)) sts32(a2, hsub2(o[0][0], o[1][0]) ^ 0x80000000u);
            sts32(a2 - 32, hsub2(o[0][1], o[1][1]) ^ 0x80000000u); if (g < 2) sts32(a2 - 64, hsub2(o[0][2], o[1][2]) ^ 0x80000000u);
        }
        uint32_t b3[16];
        if (warp < 10) load_tab<4>(b3, sm + OFF_B3 + lane * 16);
        __syncthreads();
        t_st = clk32();
        PROF0(4);
        if (warp < 10) {
            uint4 V[4], o[4];
            #pragma unroll
            for (int u = 0; u < 4; u++) V[u] = lds128(scol + u * (16 * SPEC_P));
            radix16(V, b3, o);
            #pragma unroll
            for (int nt = 0; nt < 4; nt++) { o[nt].x |= 1u; if (warp < 9 || g < 2) stx128(tptr + nt * tstr, o[nt]); }
        }
        PROF0(5);
    }

    int role = 0;
    asm volatile("barrier.cluster.wait.aligned;" ::: "memory");
    if (warp >= 12) {
        const int t = tid - 384;
        if (tid == 448 && rank == 0) {
            uint32_t smid; asm volatile("mov.u32 %0, %%smid;" : "=r"(smid));
            const uint32_t tp = smid >> 1;
            uint32_t pr = tp < 32 ? (tp & 7) * 8 + (tp >> 3) : tp < 60 ? (1 + (tp - 32) % 7) * 8 + 4 + (tp - 32) / 7 : tp < 62 ? 4 + tp : tp < 66 ? tp - 58 : 0;
            while (atomicExch(g_slot + pr, epoch + 1) == epoch + 1) pr = pr == 65 ? 0 : pr + 1;
            #pragma unroll
            for (int r = 0; r < 2; r++)
                asm volatile("st.async.weak.shared::cluster.mbarrier::complete_tx::bytes.u32 [%0], %1, [%2];" :: "r"(mapa(sm + OFF_MISC, r)), "r"(pr), "r"(mapa(bars + 8 * BAR_ROLE, r)) : "memory");
        }
        __syncwarp();
        if (t == 0) {
            asm volatile("prefetch.tensormap [%0];" :: "l"(&tm_w1a) : "memory");
            asm volatile("prefetch.tensormap [%0];" :: "l"(&tm_h3a) : "memory"); asm volatile("prefetch.tensormap [%0];" :: "l"(&tm_w1b) : "memory");
            asm volatile("prefetch.tensormap [%0];" :: "l"(&tm_h3b) : "memory"); asm volatile("prefetch.tensormap [%0];" :: "l"(&tm_w2) : "memory");
        }
        if (t == 32 && rowcta) {
            for (int it = 0; (int)(ld_acquire(g_cnt + CNT_NC * 32) - (epoch + 1) * 4) < 0; it++) { __nanosleep(100); if (it > SPIN_LIMIT) __trap(); }
            fence_async_g();
            mbar_expect(bars + 8 * BAR_NC, 3584);
            bulk_load(sm + OFF_MODC, p.scr->modc, 3584, bars + 8 * BAR_NC);
            PROFT(29);
        }
        __syncwarp();
    } else if (rowcta && warp < 11) {
        const int nw = !(b & 1) ? 10 : (b & 7) == 7 ? 9 : 8;
        const int cm = (b >> 3) * 288 + (b & 7) * 32, cx = (b & 1) ? 4608 + 8 * (b >> 3) : (b >> 3) * 288 + 256 + 4 * (b & 7);
        auto load_in = [&]() {
            if (elect()) {
                mbar_expect(bars + 8 * BAR_XB, nw > 8 ? 20480 : 16384);
                tma2(sm + OFF_STAGE, &tm_t, cm, 0, bars + 8 * BAR_XB);
                if (nw > 8) tma2(sm + OFF_STX, &tm_tx, cx, 0, bars + 8 * BAR_XB);
            }
            __syncwarp();
        };
        if (warp == 10) { fence_async_s(); spin_until(t_st + X1D); load_in(); }
        uint32_t tb[QB * 4], wre[4][2], wim[4][2];
        if (warp < nw) {
            mbar_wait(bars + 8 * BAR_TAB2, 0);
            load_tab<QB>(tb, sm + OFF_TAB + QA * 512 + lane * 16);
            mbar_wait(bars + 8 * BAR_W, 0);
            const int off = wc0 & 7;
            const uint32_t wa = sm + OFF_WRAW + lane * 112 + ((off >> 1) + 2 * warp) * 4, sh = (off & 1) * 16;
            #pragma unroll
            for (int c = 0; c < 2; c++)
                #pragma unroll
                for (int h = 0; h < 2; h++) {
                    uint32_t y[2][2];
                    #pragma unroll
                    for (int e = 0; e < 2; e++) {
                        const uint32_t a = wa + c * 14336 + (h + 2 * e) * 3584, x0 = lds32(a), x1 = lds32(a + 4), x2 = lds32(a + 8);
                        y[e][0] = __funnelshift_r(x0, x1, sh); y[e][1] = __funnelshift_r(x1, x2, sh);
                    }
                    #pragma unroll
                    for (int x = 0; x < 4; x++) {
                        const uint32_t v = (x & 1) ? pack_h(bf_hi(y[0][x >> 1]), bf_hi(y[1][x >> 1])) : pack_h(bf_lo(y[0][x >> 1]), bf_lo(y[1][x >> 1]));
                        if (c) wim[x][h] = v; else wre[x][h] = v;
                    }
                }
        }
        PROF0(6);
        const uint32_t ca = warp < 8 ? sm + OFF_STAGE + lane * 128 + (warp ^ (lane & 7)) * 16 : sm + OFF_STX + lane * 32 + ((warp ^ g) & 1) * 16, cs = warp < 8 ? 4096 : 1024;
        uint32_t V[4][4];
        for (int it = 0;; it++) {
            mbar_wait(bars + 8 * BAR_XB, it & 1);
            uint32_t ok = 1;
            if (warp < nw) {
                #pragma unroll
                for (int u = 0; u < 4; u++) { uint4 t4 = lds128(ca + u * cs); V[u][0] = t4.x; V[u][1] = t4.y; V[u][2] = t4.z; V[u][3] = t4.w; ok &= t4.x; }
            }
            asm volatile("{.reg .pred p; setp.ne.u32 p, %0, 0; bar.red.and.pred p, 1, 352, p; selp.u32 %0, 1, 0, p;}" : "+r"(ok) :: "memory");
            if (ok) break;
            if (warp == 10) { load_in(); hb(); }
            if (it > SPIN_LIMIT / 64) __trap();
        }
        PROF0(7);
        if (warp < nw) {
            uint32_t zr[4][2], zi[4][2];
            #pragma unroll
            for (int x = 0; x < 4; x++) {
                uint32_t er = 0, ei = 0, or_ = 0, oi = 0;
                mma_h(er, ei, tb[0], tb[1], tb[2], tb[3], V[0][x], V[1][x]);
                mma_h(or_, oi, tb[4], tb[5], tb[6], tb[7], V[2][x], V[3][x]);
                uint32_t r0 = hadd2(er, or_), r1 = hsub2(er, or_), i0 = hadd2(ei, oi), i1 = hsub2(ei, oi);
                cmul_neg(r0, i0, tb[8], tb[9]); cmul_neg(r1, i1, tb[10], tb[11]);
                uint32_t xr0 = 0, xr1 = 0, xi0 = 0, xi1 = 0;
                mma_h(xr0, xr1, r0, r1, i0, i1, tb[12], tb[13]);
                mma_h(xi0, xi1, r0, r1, i0, i1, tb[14], tb[12]);
                cmul_pos(xr0, xi0, wre[x][0], wim[x][0]); cmul_pos(xr1, xi1, wre[x][1], wim[x][1]);
                r0 = 0; i0 = 0; r1 = 0; i1 = 0;
                mma_h(r0, i0, tb[12], tb[13], tb[14], tb[12], xr0, xi0);
                mma_h(r1, i1, tb[12], tb[13], tb[14], tb[12], xr1, xi1);
                cmul_pos(r0, i0, tb[15], tb[16]); cmul_pos(r1, i1, tb[17], tb[18]);
                zr[x][0] = hadd2(r0, r1); zr[x][1] = hsub2(r0, r1); zi[x][0] = hadd2(i0, i1); zi[x][1] = hsub2(i0, i1);
            }
            #pragma unroll
            for (int nt = 0; nt < 4; nt++) {
                uint4 o = make_uint4(0, 0, 0, 0);
                const int h = nt >> 1;
                mma_h(o.x, o.y, zr[0][h], zr[1][h], zi[0][h], zi[1][h], tb[19 + 2 * nt], tb[20 + 2 * nt]);
                mma_h(o.z, o.w, zr[2][h], zr[3][h], zi[2][h], zi[3][h], tb[19 + 2 * nt], tb[20 + 2 * nt]);
                o.x &= ~1u;
                sts128(ca + nt * cs, o);
            }
        }
        fence_async_s();
        bar_sync(1, 352);
        t_st = clk32();
        PROF0(8);
        if (warp == 10 && elect()) {
            asm volatile("cp.async.bulk.tensor.2d.global.shared::cta.bulk_group [%0, {%2, %3}], [%1];" :: "l"(&tm_t), "r"(sm + OFF_STAGE), "r"(cm), "r"(0) : "memory");
            if (nw > 8) asm volatile("cp.async.bulk.tensor.2d.global.shared::cta.bulk_group [%0, {%2, %3}], [%1];" :: "l"(&tm_tx), "r"(sm + OFF_STX), "r"(cx), "r"(0) : "memory");
            asm volatile("cp.async.bulk.commit_group;" ::: "memory");
            asm volatile("cp.async.bulk.wait_group.read 0;" ::: "memory");
        }
        __syncwarp();
    }

    if (warp >= 10) { mbar_wait(bars + 8 * BAR_ROLE, 0); role = __shfl_sync(~0u, lds32(sm + OFF_MISC), 0); fence_async_s(); }
    auto first_a = [&]() {
        if (warp >= 10 && role < 64 && elect())
            tma4(sm + OFF_A + (warp - 10) * A_BYTES, &tm_w1a, 0, 0, 4 * (warp - 10), 9 * (role >> 3) + (role & 4) + 2 * rank, bars + 8 * (BAR_FULL + warp - 10));
        __syncwarp();
    };
    if (!rowcta) first_a();
    else {
        uint32_t tc[QC * 4];
        mbar_wait(bars + 8 * BAR_TAB2, 0);
        load_tab<QC>(tc, sm + OFF_TAB + (QA + QB) * 512 + lane * 16);
        if (warp < 10) {
            uint32_t b3[16];
            load_tab<4>(b3, sm + OFF_B3 + 2048 + lane * 16);
            uint4 V[4], o[4];
            const bool tact = warp < 9 || g == 0;
            spin_until(t_st + X2D);
            #pragma unroll
            for (int u = 0; u < 4; u++) V[u] = make_uint4(tact, 0, 0, 0);
            for (int it = 0; __any_sync(~0u, (V[0].x | V[1].x | V[2].x | V[3].x) & 1u); it++) {
                #pragma unroll
                for (int u = 0; u < 4; u++) if (V[u].x & 1u) V[u] = ldx128(tptr + u * tstr);
                hb();
                if (it > SPIN_LIMIT) __trap();
            }
            PROF0(10);
            radix16(V, b3, o);
            if (tact) {
                #pragma unroll
                for (int nt = 0; nt < 4; nt++) sts128(scol + nt * (16 * SPEC_P), o[nt]);
            }
        }
        __syncthreads();
        PROF0(11);
        first_a();
        const uint32_t srow = sm + OFF_SPEC + warp * (SPEC_P * 4);
        uint32_t re[2][3], im[2][3];
        #pragma unroll
        for (int mt = 0; mt < 3; mt++) {
            const uint32_t a = srow + (g + 72 * q + 8 * mt) * 4, a2 = srow + (288 - g - 72 * q - 8 * mt) * 4;
            const uint32_t z0 = lds32(a), z1 = lds32(a + 144), z2 = lds32(a2), z3 = lds32(a2 - 144);
            #pragma unroll
            for (int m2 = 0; m2 < 2; m2++) {
                re[m2][mt] = 0; im[m2][mt] = 0;
                const uint32_t sg = m2 ? 0x3C00BC00u : 0xBC003C00u;
                mma_h(re[m2][mt], im[m2][mt], tc[m2 * 4], tc[m2 * 4 + 1], tc[m2 * 4 + 2], tc[m2 * 4 + 3], hfma2(z2, sg, z0), hfma2(z3, sg, z1));
                cmul_pos(re[m2][mt], im[m2][mt], tc[8 + (m2 * 3 + mt) * 2], tc[9 + (m2 * 3 + mt) * 2]);
            }
        }
        uint32_t md[28];
        mbar_wait(bars + 8 * BAR_NC, 0);
        load_tab<7>(md, sm + OFF_MODC + lane * 16);
        float y[5][4];
        #pragma unroll
        for (int nt = 0; nt < 5; nt++) {
            y[nt][0] = y[nt][1] = y[nt][2] = y[nt][3] = 0.f;
            #pragma unroll
            for (int mt = 0; mt < 3; mt++)
                mma_f(y[nt], re[0][mt], re[1][mt], im[0][mt], im[1][mt], tc[20 + (mt * 5 + nt) * 2], tc[21 + (mt * 5 + nt) * 2]);
        }
        float v0[9], v1[9], s1 = 0, s2 = 0;
        #pragma unroll
        for (int i = 0; i < 9; i++) {
            xw[i] = bfma2(md[i], pack_bf(y[i >> 1][i & 1], y[i >> 1][2 + (i & 1)]), xw[i]);
            v0[i] = bf_lo(xw[i]); v1[i] = bf_hi(xw[i]);
            s1 += v0[i] + v1[i]; s2 = fmaf(v0[i], v0[i], fmaf(v1[i], v1[i], s2));
        }
        warp_sum2(s1, s2);
        float m = s1 * (1.f / D_), r = rsqrtf(fmaxf(s2 * (1.f / D_) - m * m, 0.f) + 1e-5f), mr = -m * r;
        s1 = 0; s2 = 0;
        #pragma unroll
        for (int i = 0; i < 9; i++) {
            v0[i] = fmaf(fmaf(v0[i], r, mr), bf_lo(md[18 + i]), bf_lo(md[9 + i]));
            v1[i] = fmaf(fmaf(v1[i], r, mr), bf_hi(md[18 + i]), bf_hi(md[9 + i]));
            s1 += v0[i] + v1[i]; s2 = fmaf(v0[i], v0[i], fmaf(v1[i], v1[i], s2));
        }
        if (warp == 15) hb();
        warp_sum2(s1, s2);
        m = s1 * (1.f / D_); r = rsqrtf(fmaxf(s2 * (1.f / D_) - m * m, 0.f) + 1e-5f); mr = -m * r;
        {
            const int n7 = 2 * q + (g >> 2);
            const uint32_t a = sm + OFF_STAGE + n7 * 256 + (warp >> 3) * 128 + ((warp & 7) ^ n7) * 16 + (g & 3) * 4;
            #pragma unroll
            for (int i = 0; i < 9; i++) sts32(a + i * 2048, pack_bf(fmaf(v0[i], r, mr), fmaf(v1[i], r, mr)));
        }
        __syncthreads();
        PROF0(12);
        #pragma unroll
        for (int u = 0; u < 3; u++) {
            const int e = tid + 512 * u;
            if (e < 1152) g_h3[b * 1152 + e] = lds128(sm + OFF_STAGE + ((e & ~7) | ((e ^ (e >> 4)) & 7)) * 16);
        }
        #pragma unroll
        for (int i = 0; i < 9; i++) sts32(sm + OFF_X1 + warp * 1152 + (32 * i + 8 * q + g) * 4, xw[i]);
    }
    __syncthreads();
    if (rowcta) {
        if (tid == 0) { fence_async_g(); red_release(g_cnt + CNT_H3 * 32); }
        PROF0(13);
        if (warp == 15) {
            __nanosleep(X1DELAY);
            #pragma unroll 1
            for (int r = 0; r < 16; r++) {
                uint4* dst = (uint4*)(p.out + (size_t)(b + 128 * r) * D_) + lane;
                const uint32_t src = sm + OFF_X1 + r * 1152 + lane * 16;
                dst[0] = lds128(src); dst[32] = lds128(src + 512); if (lane < 8) dst[64] = lds128(src + 1024);
            }
            __syncwarp();
            if (lane == 0) red_release(g_cnt + CNT_X1 * 32);
        }
    }
    role = __shfl_sync(~0u, lds32(sm + OFF_MISC), 0);
    if (role >= 64) { if (warp == 0) PROFDUMP(); return; }

    const int gi = role >> 3, dt = role & 3, c2 = (role >> 2) & 1;
    const int wg = warp >> 2, wi = warp & 3;
    if (wg == 3) {
        uint32_t so = 0, eph = 1;
        #define RING_STEP(BYTES, OFF, ISSUE) do { \
            mbar_wait(bars + 8 * BAR_EMPTY + so, eph); \
            if (elect()) { const uint32_t fb = bars + 8 * BAR_FULL + so, dst = sm + (OFF) + so * ((BYTES) / 8); mbar_expect(fb, BYTES); ISSUE; } \
            so += 8; if (so == 8 * NST) { so = 0; eph ^= 1; } } while (0)
        if (warp == 12) {
            eph = 0;
            const int fb1 = 9 * gi + 4 * c2 + 2 * rank, sb2 = 4 * gi + 2 * c2;
            #pragma unroll 1
            for (int j = 4 * NST; j < 128; j += 4) {
                RING_STEP(A_BYTES, OFF_A, tma4(dst, &tm_w1a, 0, 0, j, fb1, fb));
                if (PF2 && (j & 28) == 4 * (role & 7) && j >= 32 && elect()) {
                    if (j < 64) asm volatile("cp.async.bulk.prefetch.tensor.4d.L2.global [%0, {%1, %2, %3, %4}];" :: "l"(&tm_w1b), "r"(0), "r"(0), "r"(64 * (int)rank + 8 * (role & 7)), "r"(9 * gi + 8) : "memory");
                    else asm volatile("cp.async.bulk.prefetch.tensor.3d.L2.global [%0, {%1, %2, %3}];" :: "l"(&tm_w2), "r"(0), "r"(64 * g2_kb(dt + ((j >> 3) & 4), rank)), "r"(sb2) : "memory");
                }
            }
            #pragma unroll 1
            for (int j = 64 * rank; j < 64 * rank + 64; j += 8) {
                RING_STEP(A_BYTES, OFF_A, tma4(dst, &tm_w1b, 0, 0, j, 9 * gi + 8, fb));
            }
            #pragma unroll 1
            for (int n = 0; n < 36; n++) {
                if (n == A2E) { mbar_wait(bars + 8 * BAR_UOK, 0); if (A2D) spin_until(clk32() + A2D); }
                RING_STEP(A_BYTES, OFF_A, tma3(dst, &tm_w2, 0, 64 * g2_kb(n, rank), sb2, fb));
            }
        } else if (warp == 13) {
            const uint32_t e1 = __shfl_sync(~0u, epoch + 1, 0);
            fence_async_s();
            wait_count(g_cnt + CNT_H3 * 32, e1 * 128);
            fence_async_g();
            if (lane == 0) PROFT(14);
            #pragma unroll 1
            for (int j = 0; j < 128; j += 4) RING_STEP(B_BYTES, OFF_B, tma3(dst, &tm_h3a, 0, 18 * dt, j, fb));
            #pragma unroll 1
            for (int j = 64 * rank; j < 64 * rank + 64; j += 8) {
                RING_STEP(B_BYTES, OFF_B, tma3(dst, &tm_h3b, 0, 18 * dt + 9 * c2, j, fb));
            }
            #pragma unroll 1
            for (int cls = 0; cls < 3; cls++) {
                mbar_wait(bars + 8 * (BAR_UOK + cls), 0);
                fence_async_g();
                if (cls == 0 && lane == 0) PROFT(19);
                const int n1 = cls < 2 ? 16 * cls + 16 : 36;
                #pragma unroll 1
                for (int n = 16 * cls; n < n1; n++) RING_STEP(B_BYTES, OFF_B, bulk_load(dst, g_U + (g2_kb(n, rank) * 4 + dt) * 1152, B_BYTES, fb));
            }
            if (role == 0 && rank == 0 && lane == 0) st_relaxed(g_cnt + CNT_EPOCH * 32, e1);
        } else if (warp == 15) {
            asm volatile("bar.arrive 5, 160;" ::: "memory");
            bar_sync(6, 160);
            mbar_wait(bars + 8 * BAR_W1GO, 0);
            if (elect()) {
                char* dst = (char*)(g_U + ((9 * gi + 4 * c2 + 2 * rank + 1) * 4 + dt) * 1152);
                #pragma unroll 1
                for (int i = 0; i < W1N; i++) {
                    asm volatile("cp.async.bulk.global.shared::cta.bulk_group [%0], [%1], %2;" :: "l"(dst + i * (18432 / W1N)), "r"(sm + OFF_X1 + i * (18432 / W1N)), "n"(18432 / W1N) : "memory");
                    const uint32_t t1 = clk32(); while ((int)(clk32() - t1) < W1P) {}
                }
                asm volatile("cp.async.bulk.commit_group;" ::: "memory");
                asm volatile("cp.async.bulk.wait_group 0;" ::: "memory");
                mbar_arrive_remote(mapa(bars + 8 * BAR_HOLD, rank ^ 1));
                fence_async_g(); red_release(g_cnt + (CNT_U + 8 + UIDX(dt, gi >> 2)) * 32);
            }
        } else if (tid == 448) {
            __nanosleep(4000);
            for (int it = 0; (int)(ld_acquire(g_cnt + (CNT_NC + 1) * 32) - (epoch + 1) * 2) < 0 || (int)(ld_acquire(g_cnt + CNT_NC * 32) - (epoch + 1) * 4) < 0; it++) { __nanosleep(200); if (it > SPIN_LIMIT) __trap(); }
            fence_async_g();
            mbar_expect(bars + 8 * BAR_GB, 1152);
            bulk_load(sm + OFF_GB, p.scr->modc + 896, 1152, bars + 8 * BAR_GB);
            wait_count(g_cnt + CNT_X1 * 32, (epoch + 1) * 128);
            mbar_wait(bars + 8 * BAR_STGO, 0);
            #pragma unroll 1
            for (int cls = 0; cls < 3; cls++) {
                wait_count(g_cnt + (CNT_U + 8 * cls + UIDX(dt, rank)) * 32, (epoch + 1) * UCNT);
                mbar_arrive(bars + 8 * (BAR_UOK + cls));
                __nanosleep(1000);
            }
        }
    } else if (wg == 2) {
        float d0[36];
        const int fr = 576 * gi + 512 + 16 * wi + g;
        const float bias0 = bf_lo(ldg_nc16(p.b1 + fr)), bias1 = bf_lo(ldg_nc16(p.b1 + fr + 8));
        for (int it = 0; it < 200 && !__any_sync(~0u, mbar_test(bars + 8 * BAR_FULL, 0)); it++) { hb(); __nanosleep(100); }
        mbar_wait(bars + 8 * BAR_P2GO, 0);
        const bool lead = wi == 0 && elect();
        uint32_t s = IT_P2 % NST, ph = (IT_P2 / NST) & 1, prev = 0;
        #pragma unroll 1
        for (int i = 0; i < IT_G2 - IT_P2; i++) {
            if (i == P2A) {
                if (P2A) { WG_WAIT(0); if (lead) mbar_arrive_n(bars + 8 * BAR_EMPTY + 8 * prev, 2); }
                mbar_wait(bars + 8 * BAR_STGO, 0);
                spin_until(clk32() + P2D);
            }
            mbar_wait(bars + 8 * BAR_FULL + 8 * s, ph);
            const uint32_t da = desc_lo(sm + OFF_A, 8192) + s * (A_BYTES / 16), db = desc_lo(sm + OFF_B, 128) + s * (B_BYTES / 16);
            WG_FENCE();
            wgmma72(d0, da, db, i);
            #pragma unroll
            for (int k = 1; k < 8; k++) wgmma72(d0, da + k * 128, db + k * 144, 1);
            WG_COMMIT();
            if (lead && i == IT_G2 - IT_P2 - 1) mbar_arrive(bars + 8 * BAR_G2GO);
            WG_WAIT(1);
            if (lead && i && i != P2A) mbar_arrive_n(bars + 8 * BAR_EMPTY + 8 * prev, 2);
            prev = s; if (++s == NST) { s = 0; ph ^= 1; }
        }
        WG_WAIT(0);
        if (lead) { mbar_arrive_n(bars + 8 * BAR_EMPTY + 8 * prev, 2); PROFT(18); }
        const uint32_t slot = sm + OFF_P2R + ((wi & 1) * 32 + lane) * 16;
        if ((uint32_t)(wi >> 1) != rank) {
            const uint32_t ra = mapa(slot, rank ^ 1), rb = mapa(bars + 8 * BAR_P2R, rank ^ 1);
            mbar_wait(bars + 8 * BAR_HOLD, 0);
            #pragma unroll
            for (int i = 0; i < 9; i++)
                asm volatile("st.async.weak.shared::cluster.mbarrier::complete_tx::bytes.v4.f32 [%0], {%1,%2,%3,%4}, [%5];"
                    :: "r"(ra + i * 1024), "f"(d0[4 * i]), "f"(d0[4 * i + 1]), "f"(d0[4 * i + 2]), "f"(d0[4 * i + 3]), "r"(rb) : "memory");
        } else {
            mbar_wait(bars + 8 * BAR_P2R, 0);
            #pragma unroll
            for (int i = 0; i < 9; i++) {
                const uint4 v = lds128(slot + i * 1024);
                d0[4 * i] += __uint_as_float(v.x) + bias0; d0[4 * i + 1] += __uint_as_float(v.y) + bias0;
                d0[4 * i + 2] += __uint_as_float(v.z) + bias1; d0[4 * i + 3] += __uint_as_float(v.w) + bias1;
            }
            char* ub = (char*)(g_U + ((9 * gi + 8) * 4 + dt) * 1152) + wi * 4608 + c2 * 1152 + g * 16;
            gelu_store<0>(d0, ub, q); gelu_store<2>(d0, ub + 2304, q);
            bar_sync(8, 64);
            if ((wi & 1) == 0 && lane == 0) { fence_async_g(); red_release(g_cnt + (CNT_U + 16 + UIDX(dt, gi >> 2)) * 32); }
        }
    } else {
        float d[72];
        const bool lead = wi == 0 && elect();
        const uint32_t da0 = desc_lo(sm + OFF_A + wg * 8192, 8192);
        {
            const int fr = 576 * gi + 256 * c2 + 128 * rank + 64 * wg + 16 * wi + g;
            const float bias0 = bf_lo(ldg_nc16(p.b1 + fr)), bias1 = bf_lo(ldg_nc16(p.b1 + fr + 8));
            #pragma unroll
            for (int i = 0; i < 72; i++) d[i] = (i & 2) ? bias1 : bias0;
            mainloop<DHI_H3, 0, IT_P2, false, true, true>(d, bars, da0, desc_lo(sm + OFF_B, 128), lead,
                [&](int i) { if (i == IT_P2 - 1 && wg == 0 && lead) mbar_arrive(bars + 8 * BAR_P2GO); });
            PROF0(16);
            if (wg == 1) bar_sync(5, 160);
            char* const ub = (wg == 0 ? (char*)(g_U + ((9 * gi + 4 * c2 + 2 * rank) * 4 + dt) * 1152) : (char*)__cvta_shared_to_generic(sm + OFF_X1)) + wi * 4608 + g * 16;
            gelu_store<0>(d, ub, q); gelu_store<2>(d, ub + 2304, q); gelu_store<36>(d, ub + 1152, q); gelu_store<38>(d, ub + 3456, q);
            PROF0(27);
            if (wg == 0) {
                bar_sync(4, 128);
                if (lead) {
                    mbar_arrive(bars + 8 * BAR_STGO);
                    fence_async_g(); red_release(g_cnt + (CNT_U + UIDX(dt, gi >> 2)) * 32);
                }
                __syncwarp();
            } else { fence_async_s(); asm volatile("bar.arrive 6, 160;" ::: "memory"); }
            PROF0(17);
        }
        const int srow = 256 * gi + 128 * c2 + 64 * wg + 16 * wi + g + 8 * rank;
        uint16_t* const orow = p.out + (size_t)srow * D_ + 144 * dt;
        mbar_wait(bars + 8 * BAR_G2GO, 0);
        const uint32_t db0 = desc_lo(sm + OFF_B, 2304);
        mainloop<DHI_U, IT_G2, IT_G2 + 8, true, true, false>(d, bars, da0, db0, lead,
            [&](int i) { if (i == IT_G2 + W1S && wg == 0 && lead) mbar_arrive(bars + 8 * BAR_W1GO); });
        uint4 xq[4]; uint32_t xs[2];
        #pragma unroll
        for (int i = 0; i < 4; i++) xq[i] = *(const uint4*)(orow + 72 * (i >> 1) + 32 * (i & 1) + 8 * q);
        xs[0] = *(const uint32_t*)(orow + 64 + 2 * q); xs[1] = *(const uint32_t*)(orow + 136 + 2 * q);
        const uint32_t b2w = ldg_nc16(p.b2 + srow);
        const uint32_t cansend = mapa(bars + 8 * BAR_CANSEND, rank ^ 1);
        mainloop<DHI_U, IT_G2 + 8, IT_END, false, false, true>(d, bars, da0, db0, lead,
            [&](int i) { if (i == IT_END - 4 && lead) mbar_arrive_remote(cansend); });
        const float bias = 2.f * bf_lo(b2w);
        PROF0(21);
        static_assert((IT_END - 6) % NST == 4, "receive buffer = B slots 4 and 5");
        const uint32_t slot = sm + OFF_B + 4 * B_BYTES + tid * 16;
        mbar_wait(bars + 8 * BAR_CANSEND, 0);
        {
            const uint32_t ra = mapa(slot, rank ^ 1), rb = mapa(bars + 8 * BAR_RECV, rank ^ 1);
            uint32_t w[18];
            #pragma unroll
            for (int i = 0; i < 18; i++) w[i] = pack_bf(rank ? d[4 * i] : d[4 * i + 2], rank ? d[4 * i + 1] : d[4 * i + 3]);
            #pragma unroll
            for (int i = 0; i < 4; i++)
                asm volatile("st.async.weak.shared::cluster.mbarrier::complete_tx::bytes.v4.b32 [%0], {%1,%2,%3,%4}, [%5];"
                    :: "r"(ra + i * 4096), "r"(w[4 * i]), "r"(w[4 * i + 1]), "r"(w[4 * i + 2]), "r"(w[4 * i + 3]), "r"(rb) : "memory");
            asm volatile("st.async.weak.shared::cluster.mbarrier::complete_tx::bytes.v2.b32 [%0], {%1,%2}, [%3];" :: "r"(ra + 16384), "r"(w[16]), "r"(w[17]), "r"(rb) : "memory");
        }
        float v[36];
        #pragma unroll
        for (int i = 0; i < 18; i++) { v[2 * i] = (rank ? d[4 * i + 2] : d[4 * i]) + bias; v[2 * i + 1] = (rank ? d[4 * i + 3] : d[4 * i + 1]) + bias; }
        uint4 gq[4]; uint32_t gs[2];
        mbar_wait(bars + 8 * BAR_GB, 0);
        #pragma unroll
        for (int i = 0; i < 4; i++) gq[i] = lds128(sm + OFF_GB + (144 * dt + 72 * (i >> 1) + 32 * (i & 1) + 8 * q) * 2);
        gs[0] = lds32(sm + OFF_GB + (144 * dt + 64 + 2 * q) * 2); gs[1] = lds32(sm + OFF_GB + (144 * dt + 136 + 2 * q) * 2);
        mbar_wait(bars + 8 * BAR_RECV, 0);
        #pragma unroll
        for (int i = 0; i < 5; i++) {
            const uint4 t4 = lds128(slot + i * 4096);
            v[8 * i] += bf_lo(t4.x); v[8 * i + 1] += bf_hi(t4.x); v[8 * i + 2] += bf_lo(t4.y); v[8 * i + 3] += bf_hi(t4.y);
            if (i < 4) { v[8 * i + 4] += bf_lo(t4.z); v[8 * i + 5] += bf_hi(t4.z); v[8 * i + 6] += bf_lo(t4.w); v[8 * i + 7] += bf_hi(t4.w); }
        }
        #define FIN(x_, g_, k_) pack_bf(fmaf(bf_lo(g_), v[k_], bf_lo(x_)), fmaf(bf_hi(g_), v[(k_) + 1], bf_hi(x_)))
        #pragma unroll
        for (int i = 0; i < 4; i++) {
            const int k0 = 18 * (i >> 1) + 8 * (i & 1);
            *(uint4*)(orow + 72 * (i >> 1) + 32 * (i & 1) + 8 * q) =
                make_uint4(FIN(xq[i].x, gq[i].x, k0), FIN(xq[i].y, gq[i].y, k0 + 2), FIN(xq[i].z, gq[i].z, k0 + 4), FIN(xq[i].w, gq[i].w, k0 + 6));
        }
        *(uint32_t*)(orow + 64 + 2 * q) = FIN(xs[0], gs[0], 16);
        *(uint32_t*)(orow + 136 + 2 * q) = FIN(xs[1], gs[1], 34);
        PROF0(23);
        if (warp == 0) { __syncwarp(); PROFDUMP(); }
    }
}

typedef CUresult (*EncodeFn)(CUtensorMap*, CUtensorMapDataType, cuuint32_t, void*, const cuuint64_t*, const cuuint64_t*, const cuuint32_t*,
                             const cuuint32_t*, CUtensorMapInterleave, CUtensorMapSwizzle, CUtensorMapL2promotion, CUtensorMapFloatOOBfill);

void encode(EncodeFn fn, CUtensorMap* m, CUtensorMapDataType dt, int rank, const void* ptr, const cuuint64_t* dims, const cuuint64_t* strides,
            const cuuint32_t* box, CUtensorMapSwizzle sw, CUtensorMapL2promotion promo = CU_TENSOR_MAP_L2_PROMOTION_L2_128B) {
    const cuuint32_t es[5] = {1, 1, 1, 1, 1};
    fn(m, dt, rank, (void*)ptr, dims, strides, box, es, CU_TENSOR_MAP_INTERLEAVE_NONE, sw, promo, CU_TENSOR_MAP_FLOAT_OOB_FILL_NONE);
}

}

extern "C" void kernel_launch(void* const* d_in, const int* in_sizes, int n_in, void* d_out, int out_size) {
    (void)in_sizes; (void)n_in; (void)out_size;
    Params p;
    p.x = (const uint16_t*)d_in[0]; p.wr = (const uint16_t*)d_in[1]; p.wi = (const uint16_t*)d_in[2];
    p.w1 = (const uint16_t*)d_in[4]; p.b1 = (const uint16_t*)d_in[5]; p.w2 = (const uint16_t*)d_in[6]; p.b2 = (const uint16_t*)d_in[7];
    p.c = (const uint16_t*)d_in[8]; p.wmod = (const uint16_t*)d_in[9]; p.out = (uint16_t*)d_out;

    void* fnp = nullptr; cudaDriverEntryPointQueryResult qr;
    cudaGetDriverEntryPoint("cuTensorMapEncodeTiled", &fnp, cudaEnableDefault, &qr);
    EncodeFn fn = (EncodeFn)fnp;
    cudaGetSymbolAddress((void**)&p.scr, g_scr); cudaGetSymbolAddress((void**)&p.tab, g_tab);
    void* h3p = p.scr->h3;
    CUtensorMap tw1a, tw1b, tw2, th3a, th3b, twr, twi, twm, tt, ttx;
    {
        const cuuint64_t dims[4] = {64, 16, 128, 72}, st[3] = {128ull * F_ * 2, (cuuint64_t)F_ * 2, 128};
        const cuuint32_t ba[4] = {64, 16, 4, 2}, bb[4] = {64, 16, 8, 1};
        encode(fn, &tw1a, CU_TENSOR_MAP_DATA_TYPE_BFLOAT16, 4, p.w1, dims, st, ba, CU_TENSOR_MAP_SWIZZLE_128B);
        encode(fn, &tw1b, CU_TENSOR_MAP_DATA_TYPE_BFLOAT16, 4, p.w1, dims, st, bb, CU_TENSOR_MAP_SWIZZLE_128B);
    }
    {
        const cuuint64_t dims[3] = {64, F_, 32}, st[2] = {(cuuint64_t)S_ * 2, 128};
        const cuuint32_t bx[3] = {64, 64, 2};
        encode(fn, &tw2, CU_TENSOR_MAP_DATA_TYPE_BFLOAT16, 3, p.w2, dims, st, bx, CU_TENSOR_MAP_SWIZZLE_128B);
    }
    {
        const cuuint64_t dims[3] = {64, 72, 128}, st[2] = {256, 18432};
        const cuuint32_t ba[3] = {64, 18, 4}, bb[3] = {64, 9, 8};
        encode(fn, &th3a, CU_TENSOR_MAP_DATA_TYPE_UINT32, 3, h3p, dims, st, ba, CU_TENSOR_MAP_SWIZZLE_NONE);
        encode(fn, &th3b, CU_TENSOR_MAP_DATA_TYPE_UINT32, 3, h3p, dims, st, bb, CU_TENSOR_MAP_SWIZZLE_NONE);
    }
    {
        const cuuint64_t dims[3] = {4624, 4, 32}, st[2] = {9248 * 32, 9248};
        const cuuint32_t bx[3] = {56, 4, 32};
        encode(fn, &twr, CU_TENSOR_MAP_DATA_TYPE_BFLOAT16, 3, p.wr, dims, st, bx, CU_TENSOR_MAP_SWIZZLE_NONE);
        encode(fn, &twi, CU_TENSOR_MAP_DATA_TYPE_BFLOAT16, 3, p.wi, dims, st, bx, CU_TENSOR_MAP_SWIZZLE_NONE);
    }
    {
        const cuuint64_t dims[3] = {64, 576, 54}, st[2] = {6912, 128};
        const cuuint32_t bx[3] = {64, 32, 7};
        encode(fn, &twm, CU_TENSOR_MAP_DATA_TYPE_BFLOAT16, 3, p.wmod, dims, st, bx, CU_TENSOR_MAP_SWIZZLE_128B);
    }
    {
        const cuuint64_t dims[2] = {TP, 128}, st[1] = {TP * 4};
        const cuuint32_t ba[2] = {32, 128}, bb[2] = {8, 128};
        encode(fn, &tt, CU_TENSOR_MAP_DATA_TYPE_UINT32, 2, p.scr->T, dims, st, ba, CU_TENSOR_MAP_SWIZZLE_128B, CU_TENSOR_MAP_L2_PROMOTION_NONE);
        encode(fn, &ttx, CU_TENSOR_MAP_DATA_TYPE_UINT32, 2, p.scr->T, dims, st, bb, CU_TENSOR_MAP_SWIZZLE_32B, CU_TENSOR_MAP_L2_PROMOTION_NONE);
    }
    cudaFuncSetAttribute(fused_kernel, cudaFuncAttributeMaxDynamicSharedMemorySize, SMEM_BYTES);
    cudaLaunchConfig_t cfg = {};
    cfg.gridDim = dim3(NCTA); cfg.blockDim = dim3(NTHR); cfg.dynamicSmemBytes = SMEM_BYTES; cfg.stream = cudaStreamPerThread;
    cudaLaunchAttribute at[1];
    at[0].id = cudaLaunchAttributeCooperative; at[0].val.cooperative = 1;
    cfg.attrs = at; cfg.numAttrs = 1;
    cudaLaunchKernelEx(&cfg, fused_kernel, p, tw1a, tw1b, tw2, th3a, th3b, twr, twi, twm, tt, ttx);
}
```

```cpp
#include <cuda_runtime.h>
#include <cuda_bf16.h>
#include <cuda_fp16.h>
#include <cuda.h>
#include <stdint.h>

namespace {

constexpr int S_ = 2048, D_ = 576, F_ = 4608;
constexpr int NCTA = 132, NTHR = 512;
constexpr int TP = 4736;
constexpr int SPEC_P = 296;
constexpr int NST = 6;
constexpr int A_BYTES = 16384, B_BYTES = 18432;
constexpr int IT_P2 = 32, IT_G2 = 40, IT_TAIL = 72, IT_END = 80;
constexpr int SPIN_LIMIT = 1 << 22;
#define UIDX(dt_, kh_) 0
#define UCNT 128
#define MODPAD 16
#define MODSLEEP 0
#define X2D 1300
#define NCD 0
#define CPHINT ".L2::128B"
#define NCST 17
#define NCPF 1
#define NCPACE 0
#define P2A 2
#define P2D 400
#define P2CH 1
#define A2E 1
#define A2D 100
#define W1N 8
#define W1P 100
#define W1S 0
#define XDELAY 1600
#define X1D 2300
#define PF1 0
#define PF2 1
#define X1DELAY 2500

constexpr int OFF_A = 0;
constexpr int OFF_B = NST * A_BYTES;
constexpr int OFF_P = OFF_B + NST * B_BYTES;
constexpr int OFF_BAR = OFF_P;
constexpr int OFF_MISC = OFF_P + 368;
constexpr int OFF_GB = OFF_P + 384;
constexpr int OFF_P2R = OFF_P + 1536;
constexpr int OFF_X1 = OFF_P2R;
constexpr int OFF_PROF = OFF_X1 + 18432;
constexpr int SMEM_BYTES = OFF_PROF + 512 + 1024;
constexpr int QA = 13, QB = 7, QC = 13;
constexpr int TAB_BYTES = (QA + QB + QC) * 512;
constexpr int OFF_STAGE = OFF_B;
constexpr int OFF_STX = OFF_STAGE + 16384;
constexpr int OFF_TAB = OFF_STAGE + 20480;
constexpr int OFF_SPEC = OFF_TAB + TAB_BYTES;
constexpr int OFF_WRAW = OFF_SPEC + 19072;
constexpr int OFF_B3 = OFF_WRAW + 28672;
constexpr int OFF_MODA = OFF_B3 + 4096;
constexpr int OFF_MODC = OFF_MODA + 2560;
constexpr int OFF_RED = OFF_MODC + 3584;
constexpr int OFF_SILU = OFF_RED + 768;
static_assert(OFF_SILU + 1152 <= OFF_P && 6 * 28672 <= OFF_B3, "scratch overflow");
constexpr int OFF_STRIP = OFF_A;
static_assert(OFF_WRAW % 128 == 0 && OFF_STAGE % 128 == 0 && OFF_STX % 128 == 0, "align");
constexpr int BAR_FULL = 0, BAR_EMPTY = 6, BAR_TAB = 12, BAR_W = 13, BAR_P2GO = 14, BAR_G2GO = 15, BAR_P2R = 16,
              BAR_XT = 17, BAR_RECV = 18, BAR_ROLE = 19, BAR_NC = 20, BAR_TAB2 = 21, BAR_XB = 22, BAR_GB = 23, BAR_HOLD = 24, BAR_W1GO = 25, BAR_UOK = 26, BAR_STGO = 29, BAR_X = 30;

struct Cos1152 { double c[1152]; };
constexpr double cx_cos(double x) { double t = 1, s = 1; for (int i = 1; i < 14; i++) { t *= -x * x / ((2 * i - 1) * (2 * i)); s += t; } return s; }
constexpr Cos1152 make_cos() {
    Cos1152 r{};
    for (int i = 0; i <= 288; i++) {
        double v = (i == 288) ? 0.0 : cx_cos(3.14159265358979323846 * 2.0 * i / 1152.0);
        r.c[i] = v; r.c[576 - i] = -v; r.c[576 + i] = -v; r.c[(1152 - i) % 1152] = v;
    }
    return r;
}
constexpr uint32_t cx_f2h(double v) {
    uint32_t s = v < 0 ? 0x8000u : 0u; double a = v < 0 ? -v : v;
    if (a < 1e-9) return 0;
    int e = 0;
    while (a >= 2.0) { a *= 0.5; e++; }
    while (a < 1.0 && e > -14) { a *= 2.0; e--; }
    double m = a * 1024.0; uint32_t mi = (uint32_t)m; double fr = m - mi;
    if (fr > 0.5 || (fr == 0.5 && (mi & 1))) mi++;
    return s | (uint32_t)(((e + 14) << 10) + mi);
}
struct Tab { uint32_t w[(QA + QB + QC) * 128]; };
constexpr Tab make_tab() {
    Tab t{};
    Cos1152 ct = make_cos();
    auto C = [&](int num, int den) { return ct.c[(num % den) * (1152 / den)]; };
    auto Sn = [&](int num, int den) { return ct.c[((num % den) * (1152 / den) + 864) % 1152]; };
    auto put = [&](int q0, int idx, int lane, double lo, double hi) { t.w[((q0 + idx / 4) * 32 + lane) * 4 + idx % 4] = cx_f2h(lo) | (cx_f2h(hi) << 16); };
    for (int lane = 0; lane < 32; lane++) {
        const int g = lane >> 2, q = lane & 3;
        for (int mt = 0; mt < 3; mt++) {
            const int ka = 8 * mt + g;
            for (int r = 0; r < 10; r++) {
                const int im = r & 1, i0 = (r >> 1) * 2;
                double v[2] = {0, 0};
                for (int e = 0; e < 2; e++) { int i = i0 + e, d1 = 4 * i + q; if (i < 9 && ka <= 18) v[e] = (im ? -Sn(ka * d1, 36) : C(ka * d1, 36)) / 8; }
                put(0, mt * 10 + r, lane, v[0], v[1]);
            }
            for (int v = 0; v < 2; v++) {
                const int d2 = 4 * q + v;
                put(0, 30 + (mt * 2 + v) * 2, lane, C(ka * d2, 576) * 4 / 3, C(ka * (d2 + 2), 576) * 4 / 3);
                put(0, 31 + (mt * 2 + v) * 2, lane, Sn(ka * d2, 576) * 4 / 3, Sn(ka * (d2 + 2), 576) * 4 / 3);
            }
        }
        for (int v = 0; v < 2; v++) for (int nt = 0; nt < 2; nt++) {
            const int kb = 2 * (g >> 1) + nt, part = g & 1;
            double b0[2] = {0, 0}, b1[2] = {0, 0};
            for (int e = 0; e < 2; e++) { int d2 = 4 * q + 2 * e + v; double c = C(kb * d2, 16) / 4, s = Sn(kb * d2, 16) / 4;
                b0[e] = part ? -s : c; b1[e] = part ? c : s; }
            put(0, 42 + (v * 2 + nt) * 2, lane, b0[0], b0[1]); put(0, 43 + (v * 2 + nt) * 2, lane, b1[0], b1[1]);
        }
        for (int par = 0; par < 2; par++) for (int a = 0; a < 4; a++) {
            const int ja = 2 * (q + 4 * (a >> 1)) + par; const double c = C(g * ja, 16) / 4, s = Sn(g * ja, 16) / 4;
            put(QA, par * 4 + a, lane, (a & 1) ? -s : c, (a & 1) ? c : s);
        }
        for (int h = 0; h < 2; h++) {
            put(QA, 8 + 2 * h, lane, C((g + 8 * h) * (2 * q), 128) / 2, C((g + 8 * h) * (2 * q + 1), 128) / 2);
            put(QA, 9 + 2 * h, lane, Sn((g + 8 * h) * (2 * q), 128) / 2, Sn((g + 8 * h) * (2 * q + 1), 128) / 2);
            put(QA, 15 + 2 * h, lane, C(g * (8 * h + 2 * q), 128), C(g * (8 * h + 2 * q + 1), 128));
            put(QA, 16 + 2 * h, lane, Sn(g * (8 * h + 2 * q), 128), Sn(g * (8 * h + 2 * q + 1), 128));
        }
        put(QA, 12, lane, C(g * 2 * q, 8) / 2, C(g * (2 * q + 1), 8) / 2);
        put(QA, 13, lane, Sn(g * 2 * q, 8) / 2, Sn(g * (2 * q + 1), 8) / 2);
        put(QA, 14, lane, -Sn(g * 2 * q, 8) / 2, -Sn(g * (2 * q + 1), 8) / 2);
        for (int u = 0; u < 4; u++) {
            const int ja = 2 * ((g >> 1) + 4 * (u & 1)) + (u >> 1), part = g & 1; double b0[2] = {0, 0}, b1[2] = {0, 0};
            for (int e = 0; e < 2; e++) { int ka = 2 * q + e; double c = C(ja * ka, 16) / 4, s = Sn(ja * ka, 16) / 4;
                b0[e] = part ? s : c; b1[e] = part ? c : -s; }
            put(QA, 19 + u * 2, lane, b0[0], b0[1]); put(QA, 20 + u * 2, lane, b1[0], b1[1]);
        }
        for (int m2 = 0; m2 < 2; m2++) {
            const int d2 = 2 * g + m2;
            for (int a = 0; a < 4; a++) {
                const int kb = 2 * q + (a >> 1); const double c = C(d2 * kb, 16) / 4, s = Sn(d2 * kb, 16) / 4;
                put(QA + QB, m2 * 4 + a, lane, (a & 1) ? s : c, (a & 1) ? c : -s);
            }
            for (int mt = 0; mt < 3; mt++) {
                const int ka = 8 * mt + 2 * q;
                put(QA + QB, 8 + (m2 * 3 + mt) * 2, lane, C(ka * d2, 576) * 4 / 3, C((ka + 1) * d2, 576) * 4 / 3);
                put(QA + QB, 9 + (m2 * 3 + mt) * 2, lane, Sn(ka * d2, 576) * 4 / 3, Sn((ka + 1) * d2, 576) * 4 / 3);
            }
        }
        for (int mt = 0; mt < 3; mt++) for (int nt = 0; nt < 5; nt++) {
            const int i = 2 * nt + (g & 1), d1 = 4 * i + (g >> 1); double b0[2] = {0, 0}, b1[2] = {0, 0};
            for (int e = 0; e < 2; e++) { int ka = 8 * mt + 2 * q + e;
                if (ka <= 18 && i < 9) { double wt = (ka == 0 || ka == 18) ? 0.125 : 0.25; b0[e] = wt * C(ka * d1, 36); b1[e] = -wt * Sn(ka * d1, 36); } }
            put(QA + QB, 20 + (mt * 5 + nt) * 2, lane, b0[0], b0[1]); put(QA + QB, 21 + (mt * 5 + nt) * 2, lane, b1[0], b1[1]);
        }
    }
    return t;
}
__device__ __align__(128) const Tab g_tab = make_tab();

struct Scratch {
    uint32_t cnt[30 * 32];
    uint32_t slot[96];
    uint32_t mod[2304];
    uint32_t modc[896 + 288];
    uint32_t T[128 * TP];
    uint4 h3[128 * 1152];
    uint4 U[72 * 4 * 1152];
};
__device__ __align__(1024) Scratch g_scr;
#define g_cnt (p.scr->cnt)
#define g_slot (p.scr->slot)
#define g_mod (p.scr->mod)
#define g_T (p.scr->T)
#define g_h3 (p.scr->h3)
#define g_U (p.scr->U)
constexpr int CNT_EPOCH = 0, CNT_H3 = 1, CNT_X1 = 26, CNT_NC = 27, CNT_U = 2;
#define PROFT(i) do {} while (0)
#define PROFDUMP() do {} while (0)
#define PROF0(i) do {} while (0)

__device__ __forceinline__ void mbar_init(uint32_t bar, uint32_t cnt) { asm volatile("mbarrier.init.shared::cta.b64 [%0], %1;" :: "r"(bar), "r"(cnt) : "memory"); }
__device__ __forceinline__ void mbar_expect(uint32_t bar, uint32_t bytes) { asm volatile("mbarrier.arrive.expect_tx.shared::cta.b64 _, [%0], %1;" :: "r"(bar), "r"(bytes) : "memory"); }
__device__ __forceinline__ void mbar_arrive(uint32_t bar) { asm volatile("mbarrier.arrive.shared::cta.b64 _, [%0];" :: "r"(bar) : "memory"); }
__device__ __forceinline__ void mbar_arrive_n(uint32_t bar, uint32_t n) { asm volatile("mbarrier.arrive.shared::cta.b64 _, [%0], %1;" :: "r"(bar), "r"(n) : "memory"); }
__device__ __forceinline__ void mbar_arrive_remote(uint32_t rbar) { asm volatile("mbarrier.arrive.relaxed.cluster.shared::cluster.b64 _, [%0];" :: "r"(rbar) : "memory"); }
__device__ __forceinline__ void mbar_wait(uint32_t bar, uint32_t parity) {
    asm volatile("{.reg .pred p; .reg .u32 c;\n"
        "mbarrier.try_wait.parity.shared::cta.b64 p, [%0], %1;\n@p bra.uni DONE;\nmov.u32 c, 0;\n"
        "LOOP: mbarrier.try_wait.parity.shared::cta.b64 p, [%0], %1;\n@p bra.uni DONE;\n"
        "add.u32 c, c, 1;\nsetp.lt.u32 p, c, %2;\n@p bra.uni LOOP;\ntrap;\nDONE:}" :: "r"(bar), "r"(parity), "n"(SPIN_LIMIT) : "memory");
}
__device__ __forceinline__ bool mbar_test(uint32_t bar, uint32_t parity) {
    uint32_t ok; asm volatile("{.reg .pred p; mbarrier.test_wait.parity.shared::cta.b64 p, [%1], %2; selp.u32 %0, 1, 0, p;}" : "=r"(ok) : "r"(bar), "r"(parity) : "memory"); return ok; }
__device__ __forceinline__ uint32_t mapa(uint32_t a, uint32_t rank) { uint32_t r; asm("mapa.shared::cluster.u32 %0, %1, %2;" : "=r"(r) : "r"(a), "r"(rank)); return r; }
__device__ __forceinline__ uint32_t clk32() { uint32_t r; asm volatile("mov.u32 %0, %%clock;" : "=r"(r)); return r; }
__device__ __forceinline__ void hb() {
    asm volatile("{.reg .b32 a, b; .reg .pred p; mma.sync.aligned.m16n8k8.row.col.f16.f16.f16.f16 {a, b}, {%0,%0}, {%0}, {%0,%0};\n"
                 "setp.ne.u32 p, a, 0; @p trap;}" :: "r"(0));
}
__device__ __forceinline__ void spin_until(uint32_t t) { while (__any_sync(~0u, (int)(clk32() - t) < 0)) hb(); }
__device__ __forceinline__ bool elect() { uint32_t r; asm volatile("{.reg .pred p; elect.sync _|p, 0xffffffff; selp.u32 %0, 1, 0, p;}" : "=r"(r)); return r; }
__device__ __forceinline__ void bar_sync(int id, int n) { asm volatile("bar.sync %0, %1;" :: "r"(id), "r"(n) : "memory"); }
__device__ __forceinline__ void bulk_load(uint32_t dst, const void* src, uint32_t bytes, uint32_t bar) {
    asm volatile("cp.async.bulk.shared::cluster.global.mbarrier::complete_tx::bytes [%0], [%1], %2, [%3];" :: "r"(dst), "l"(src), "r"(bytes), "r"(bar) : "memory"); }
__device__ __forceinline__ void tma2(uint32_t dst, const CUtensorMap* m, int c0, int c1, uint32_t bar) {
    asm volatile("cp.async.bulk.tensor.2d.shared::cluster.global.mbarrier::complete_tx::bytes [%0], [%1, {%3, %4}], [%2];" :: "r"(dst), "l"(m), "r"(bar), "r"(c0), "r"(c1) : "memory"); }
__device__ __forceinline__ void tma3(uint32_t dst, const CUtensorMap* m, int c0, int c1, int c2, uint32_t bar) {
    asm volatile("cp.async.bulk.tensor.3d.shared::cluster.global.mbarrier::complete_tx::bytes [%0], [%1, {%3, %4, %5}], [%2];" :: "r"(dst), "l"(m), "r"(bar), "r"(c0), "r"(c1), "r"(c2) : "memory"); }
__device__ __forceinline__ void tma4(uint32_t dst, const CUtensorMap* m, int c0, int c1, int c2, int c3, uint32_t bar) {
    asm volatile("cp.async.bulk.tensor.4d.shared::cluster.global.mbarrier::complete_tx::bytes [%0], [%1, {%3, %4, %5, %6}], [%2];" :: "r"(dst), "l"(m), "r"(bar), "r"(c0), "r"(c1), "r"(c2), "r"(c3) : "memory"); }
__device__ __forceinline__ void fence_async_g() { asm volatile("fence.proxy.async.global;" ::: "memory"); }
__device__ __forceinline__ void fence_async_s() { asm volatile("fence.proxy.async.shared::cta;" ::: "memory"); }
__device__ __forceinline__ uint4 lds128(uint32_t a) { uint4 v; asm volatile("ld.shared.v4.u32 {%0,%1,%2,%3}, [%4];" : "=r"(v.x), "=r"(v.y), "=r"(v.z), "=r"(v.w) : "r"(a) : "memory"); return v; }
__device__ __forceinline__ uint32_t lds32(uint32_t a) { uint32_t v; asm volatile("ld.shared.u32 %0, [%1];" : "=r"(v) : "r"(a) : "memory"); return v; }
__device__ __forceinline__ void sts128(uint32_t a, uint4 v) { asm volatile("st.shared.v4.u32 [%0], {%1,%2,%3,%4};" :: "r"(a), "r"(v.x), "r"(v.y), "r"(v.z), "r"(v.w) : "memory"); }
__device__ __forceinline__ void sts32(uint32_t a, uint32_t v) { asm volatile("st.shared.u32 [%0], %1;" :: "r"(a), "r"(v) : "memory"); }
__device__ __forceinline__ void sts16(uint32_t a, uint32_t v) { asm volatile("st.shared.u16 [%0], %1;" :: "r"(a), "h"((uint16_t)v) : "memory"); }
__device__ __forceinline__ uint4 ldx128(const void* p) {
    uint4 v; asm volatile("{.reg .b128 t; .reg .b64 a, b; ld.relaxed.gpu.global.b128 t, [%4]; mov.b128 {a, b}, t; mov.b64 {%0,%1}, a; mov.b64 {%2,%3}, b;}"
        : "=r"(v.x), "=r"(v.y), "=r"(v.z), "=r"(v.w) : "l"(p) : "memory"); return v; }
__device__ __forceinline__ void stx128(void* p, uint4 v) {
    asm volatile("{.reg .b128 t; .reg .b64 a, b; mov.b64 a, {%1,%2}; mov.b64 b, {%3,%4}; mov.b128 t, {a, b}; st.relaxed.gpu.global.b128 [%0], t;}"
        :: "l"(p), "r"(v.x), "r"(v.y), "r"(v.z), "r"(v.w) : "memory"); }
__device__ __forceinline__ uint32_t ld_relaxed(const uint32_t* p) { uint32_t v; asm volatile("ld.relaxed.gpu.global.u32 %0, [%1];" : "=r"(v) : "l"(p) : "memory"); return v; }
__device__ __forceinline__ uint32_t ld_acquire(const uint32_t* p) { uint32_t v; asm volatile("ld.acquire.gpu.global.u32 %0, [%1];" : "=r"(v) : "l"(p) : "memory"); return v; }
__device__ __forceinline__ void st_relaxed(uint32_t* p, uint32_t v) { asm volatile("st.relaxed.gpu.global.u32 [%0], %1;" :: "l"(p), "r"(v) : "memory"); }
__device__ __forceinline__ void red_release(uint32_t* p) { asm volatile("red.release.gpu.global.add.u32 [%0], 1;" :: "l"(p) : "memory"); }
__device__ __forceinline__ void wait_count(const uint32_t* p, uint32_t target) {
    int it = 0; while ((int)(ld_acquire(p) - target) < 0) { if (++it > SPIN_LIMIT) __trap(); }
}
__device__ __forceinline__ uint32_t ldg_nc32(const void* p) { uint32_t v; asm volatile("ld.global.nc.L1::no_allocate.u32 %0, [%1];" : "=r"(v) : "l"(p)); return v; }
__device__ __forceinline__ uint32_t ldg_nc16(const void* p) { uint16_t v; asm volatile("ld.global.nc.u16 %0, [%1];" : "=h"(v) : "l"(p)); return v; }
__device__ __forceinline__ float bf_lo(uint32_t w) { return __uint_as_float(w << 16); }
__device__ __forceinline__ float bf_hi(uint32_t w) { return __uint_as_float(w & 0xFFFF0000u); }
__device__ __forceinline__ uint32_t pack_bf(float lo, float hi) { uint32_t r; asm("cvt.rn.bf16x2.f32 %0, %1, %2;" : "=r"(r) : "f"(hi), "f"(lo)); return r; }
__device__ __forceinline__ uint32_t pack_h(float lo, float hi) { uint32_t r; asm("cvt.rn.f16x2.f32 %0, %1, %2;" : "=r"(r) : "f"(hi), "f"(lo)); return r; }
__device__ __forceinline__ float bf_round(float v) { return bf_lo(pack_bf(v, 0.f)); }
__device__ __forceinline__ uint32_t hmul2(uint32_t a, uint32_t b) { uint32_t r; asm("mul.rn.f16x2 %0, %1, %2;" : "=r"(r) : "r"(a), "r"(b)); return r; }
__device__ __forceinline__ uint32_t hfma2(uint32_t a, uint32_t b, uint32_t c) { uint32_t r; asm("fma.rn.f16x2 %0, %1, %2, %3;" : "=r"(r) : "r"(a), "r"(b), "r"(c)); return r; }
__device__ __forceinline__ uint32_t hfms2(uint32_t a, uint32_t b, uint32_t c) { uint32_t r; asm("{.reg .b32 t; neg.f16x2 t, %3; fma.rn.f16x2 %0, %1, %2, t;}" : "=r"(r) : "r"(a), "r"(b), "r"(c)); return r; }
__device__ __forceinline__ uint32_t hadd2(uint32_t a, uint32_t b) { uint32_t r; asm("add.rn.f16x2 %0, %1, %2;" : "=r"(r) : "r"(a), "r"(b)); return r; }
__device__ __forceinline__ uint32_t hsub2(uint32_t a, uint32_t b) { uint32_t r; asm("sub.rn.f16x2 %0, %1, %2;" : "=r"(r) : "r"(a), "r"(b)); return r; }
__device__ __forceinline__ void cmul_neg(uint32_t& re, uint32_t& im, uint32_t c, uint32_t s) { uint32_t a = hfma2(re, c, hmul2(im, s)), b = hfms2(im, c, hmul2(re, s)); re = a; im = b; }
__device__ __forceinline__ void cmul_pos(uint32_t& re, uint32_t& im, uint32_t c, uint32_t s) { uint32_t a = hfms2(re, c, hmul2(im, s)), b = hfma2(im, c, hmul2(re, s)); re = a; im = b; }
__device__ __forceinline__ void mma_h(uint32_t& d0, uint32_t& d1, uint32_t a0, uint32_t a1, uint32_t a2, uint32_t a3, uint32_t b0, uint32_t b1) {
    asm("mma.sync.aligned.m16n8k16.row.col.f16.f16.f16.f16 {%0,%1}, {%2,%3,%4,%5}, {%6,%7}, {%0,%1};" : "+r"(d0), "+r"(d1) : "r"(a0), "r"(a1), "r"(a2), "r"(a3), "r"(b0), "r"(b1)); }
__device__ __forceinline__ void mma_h8(uint32_t& d0, uint32_t& d1, uint32_t a0, uint32_t a1, uint32_t b0) {
    asm("mma.sync.aligned.m16n8k8.row.col.f16.f16.f16.f16 {%0,%1}, {%2,%3}, {%4}, {%0,%1};" : "+r"(d0), "+r"(d1) : "r"(a0), "r"(a1), "r"(b0)); }
__device__ __forceinline__ void mma_f(float (&d)[4], uint32_t a0, uint32_t a1, uint32_t a2, uint32_t a3, uint32_t b0, uint32_t b1) {
    asm("mma.sync.aligned.m16n8k16.row.col.f32.f16.f16.f32 {%0,%1,%2,%3}, {%4,%5,%6,%7}, {%8,%9}, {%0,%1,%2,%3};"
        : "+f"(d[0]), "+f"(d[1]), "+f"(d[2]), "+f"(d[3]) : "r"(a0), "r"(a1), "r"(a2), "r"(a3), "r"(b0), "r"(b1)); }
template <int NQ> __device__ __forceinline__ void load_tab(uint32_t (&r)[NQ * 4], uint32_t addr) {
    #pragma unroll
    for (int i = 0; i < NQ; i++) { uint4 v = lds128(addr + i * 512); r[4 * i] = v.x; r[4 * i + 1] = v.y; r[4 * i + 2] = v.z; r[4 * i + 3] = v.w; }
}
__device__ __forceinline__ void warp_sum2(float& a, float& b) {
    #pragma unroll
    for (int o = 16; o; o >>= 1) { a += __shfl_xor_sync(~0u, a, o); b += __shfl_xor_sync(~0u, b, o); }
}
__device__ __forceinline__ float gelu2(float x) {
    float t = x * fmaf(x * x, 0.044715f * 0.7978845608028654f, 0.7978845608028654f), th;
    asm volatile("tanh.approx.f32 %0, %1;" : "=f"(th) : "f"(t));
    return fmaf(x, th, x);
}
__device__ __forceinline__ uint32_t desc_lo(uint32_t addr, uint32_t lbo) { return ((addr & 0x3FFFF) >> 4) | ((lbo >> 4) << 16); }
constexpr uint32_t DHI_A = (1024 >> 4) | (1u << 30), DHI_H3 = 256 >> 4, DHI_U = 128 >> 4;
#define WG_FENCE() asm volatile("wgmma.fence.sync.aligned;" ::: "memory")
#define WG_COMMIT() asm volatile("wgmma.commit_group.sync.aligned;" ::: "memory")
#define WG_WAIT(n) asm volatile("wgmma.wait_group.sync.aligned %0;" :: "n"(n) : "memory")
#define R4(b) "+f"(d[b]), "+f"(d[b + 1]), "+f"(d[b + 2]), "+f"(d[b + 3])
#define R12(b) R4(b), R4(b + 4), R4(b + 8)
#define R36(b) R12(b), R12(b + 12), R12(b + 24)
template <uint32_t BHI> __device__ __forceinline__ void wgmma144(float (&d)[72], uint32_t da, uint32_t db, int acc) {
    asm volatile("{.reg .pred p; .reg .b64 a, b; setp.ne.b32 p, %74, 0; mov.b64 a, {%72, %75}; mov.b64 b, {%73, %76};\n"
        "wgmma.mma_async.sync.aligned.m64n144k16.f32.bf16.bf16 {%0,%1,%2,%3,%4,%5,%6,%7,%8,%9,%10,%11,%12,%13,%14,%15,%16,%17,%18,%19,%20,%21,%22,%23,"
        "%24,%25,%26,%27,%28,%29,%30,%31,%32,%33,%34,%35,%36,%37,%38,%39,%40,%41,%42,%43,%44,%45,%46,%47,"
        "%48,%49,%50,%51,%52,%53,%54,%55,%56,%57,%58,%59,%60,%61,%62,%63,%64,%65,%66,%67,%68,%69,%70,%71}, a, b, p, 1, 1, 1, 1;}\n"
        : R36(0), R36(36) : "r"(da), "r"(db), "r"(acc), "n"(DHI_A), "n"(BHI));
}
__device__ __forceinline__ void wgmma72(float (&d)[36], uint32_t da, uint32_t db, int acc) {
    asm volatile("{.reg .pred p; .reg .b64 a, b; setp.ne.b32 p, %38, 0; mov.b64 a, {%36, %39}; mov.b64 b, {%37, %40};\n"
        "wgmma.mma_async.sync.aligned.m64n72k16.f32.bf16.bf16 {%0,%1,%2,%3,%4,%5,%6,%7,%8,%9,%10,%11,%12,%13,%14,%15,%16,%17,%18,%19,%20,%21,%22,%23,"
        "%24,%25,%26,%27,%28,%29,%30,%31,%32,%33,%34,%35}, a, b, p, 1, 1, 1, 1;}\n"
        : R36(0) : "r"(da), "r"(db), "r"(acc), "n"(DHI_A), "n"(DHI_H3));
}

__device__ __forceinline__ int g2_kb(int n, int kh) { return n < 32 ? 36 * kh + 9 * ((n >> 2) & 3) + 2 * (n & 3) + (n >> 4) : 9 * (n - 32) + 8; }

template <uint32_t BHI, int I0, int I1, bool ZERO, bool FIRST, bool LAST, int NARR = 1, class Hook>
__device__ __forceinline__ void mainloop(float (&d)[72], uint32_t bars, uint32_t da0, uint32_t db0, bool lead, Hook hook) {
    uint32_t s = I0 % NST, ph = (I0 / NST) & 1, prev = (I0 + NST - 1) % NST;
    #pragma unroll 1
    for (int i = I0; i < I1; i++) {
        mbar_wait(bars + 8 * BAR_FULL + 8 * s, ph);
        const uint32_t da = da0 + s * (A_BYTES / 16), db = db0 + s * (B_BYTES / 16);
        WG_FENCE();
        wgmma144<BHI>(d, da, db, ZERO ? i - I0 : 1);
        wgmma144<BHI>(d, da + 128, db + 288, 1); wgmma144<BHI>(d, da + 256, db + 576, 1); wgmma144<BHI>(d, da + 384, db + 864, 1);
        WG_COMMIT();
        WG_WAIT(1);
        if (lead && (!FIRST || i > I0)) mbar_arrive_n(bars + 8 * BAR_EMPTY + 8 * prev, i > I0 ? NARR : 1);
        hook(i);
        prev = s; if (++s == NST) { s = 0; ph ^= 1; }
    }
    if (LAST) { WG_WAIT(0); if (lead) mbar_arrive(bars + 8 * BAR_EMPTY + 8 * prev); }
}

struct Params {
    const uint16_t *x, *wr, *wi, *w1, *b1, *w2, *b2, *c, *wmod;
    uint16_t* out;
    Scratch* scr;
    const Tab* tab;
};

__device__ __forceinline__ void mma_bf(float (&d)[4], const uint32_t (&a)[4], uint32_t b0, uint32_t b1) {
    asm("mma.sync.aligned.m16n8k16.row.col.f32.bf16.bf16.f32 {%0,%1,%2,%3}, {%4,%5,%6,%7}, {%8,%9}, {%0,%1,%2,%3};"
        : "+f"(d[0]), "+f"(d[1]), "+f"(d[2]), "+f"(d[3]) : "r"(a[0]), "r"(a[1]), "r"(a[2]), "r"(a[3]), "r"(b0), "r"(b1)); }
__device__ __forceinline__ void ldsm4t(uint32_t (&a)[4], uint32_t addr) {
    asm volatile("ldmatrix.sync.aligned.m8n8.x4.trans.shared.b16 {%0,%1,%2,%3}, [%4];" : "=r"(a[0]), "=r"(a[1]), "=r"(a[2]), "=r"(a[3]) : "r"(addr) : "memory"); }
__device__ __forceinline__ float silu(float v) { return __fdividef(v, 1.f + __expf(-v)); }
__device__ __forceinline__ uint32_t bfma2(uint32_t a, uint32_t b, uint32_t c) { uint32_t r; asm("fma.rn.bf16x2 %0, %1, %2, %3;" : "=r"(r) : "r"(a), "r"(b), "r"(c)); return r; }
__device__ __forceinline__ void radix16(const uint4 (&V)[4], const uint32_t (&B)[16], uint4 (&o)[4]) {
    #pragma unroll
    for (int nt = 0; nt < 4; nt++) {
        o[nt] = make_uint4(0, 0, 0, 0);
        #pragma unroll
        for (int ks = 0; ks < 2; ks++) {
            const uint32_t b0 = B[(ks * 4 + nt) * 2], b1 = B[(ks * 4 + nt) * 2 + 1];
            mma_h(o[nt].x, o[nt].y, V[2 * ks].x, V[2 * ks].y, V[2 * ks + 1].x, V[2 * ks + 1].y, b0, b1);
            mma_h(o[nt].z, o[nt].w, V[2 * ks].z, V[2 * ks].w, V[2 * ks + 1].z, V[2 * ks + 1].w, b0, b1);
        }
    }
}
template <int OFF, int N> __device__ __forceinline__ void gelu_store(const float (&d)[N], char* p, int q) {
    uint32_t w[9];
    #pragma unroll
    for (int blk = 0; blk < 9; blk++) w[blk] = pack_bf(gelu2(d[OFF + 4 * blk]), gelu2(d[OFF + 4 * blk + 1]));
    asm volatile("st.v4.u32 [%0], {%1,%2,%3,%4};" :: "l"(p + q * 128), "r"(w[0]), "r"(w[1]), "r"(w[2]), "r"(w[3]) : "memory");
    asm volatile("st.v4.u32 [%0+512], {%1,%2,%3,%4};" :: "l"(p + q * 128), "r"(w[4]), "r"(w[5]), "r"(w[6]), "r"(w[7]) : "memory");
    asm volatile("st.u32 [%0+1024], %1;" :: "l"(p + q * 4), "r"(w[8]) : "memory");
}

__global__ void __cluster_dims__(2, 1, 1) __launch_bounds__(NTHR, 1)
fused_kernel(const Params p,
             const __grid_constant__ CUtensorMap tm_w1a, const __grid_constant__ CUtensorMap tm_w1b, const __grid_constant__ CUtensorMap tm_w2, const __grid_constant__ CUtensorMap tm_w2b,
             const __grid_constant__ CUtensorMap tm_h3a, const __grid_constant__ CUtensorMap tm_h3b,
             const __grid_constant__ CUtensorMap tm_wr, const __grid_constant__ CUtensorMap tm_wi, const __grid_constant__ CUtensorMap tm_wm,
             const __grid_constant__ CUtensorMap tm_t, const __grid_constant__ CUtensorMap tm_tx, const __grid_constant__ CUtensorMap tm_o)
{
    extern __shared__ char smem_raw[];
    const uint32_t t0 = clk32();
    const uint32_t sm = __shfl_sync(~0u, ((uint32_t)__cvta_generic_to_shared(smem_raw) + 1023u) & ~1023u, 0);
    const int tid = threadIdx.x, warp = __shfl_sync(~0u, tid >> 5, 0), lane = tid & 31, g = lane >> 2, q = lane & 3;
    const int b = blockIdx.x;
    const uint32_t rank = b & 1;
    const uint32_t bars = sm + OFF_BAR;
    const bool rowcta = b < 128;

    auto nc_issue = [&](int st, uint32_t sl) {
        const int pass = st >= 18;
        mbar_expect(bars + 8 * (BAR_X + sl), 28672);
        tma3(sm + sl * 28672, &tm_wm, 0, 32 * (st - 18 * pass), 18 + 28 * pass + 7 * (b - 128), bars + 8 * (BAR_X + sl));
    };
    if (warp == 13) hb();
    uint32_t cw = 0, epoch;
    if (warp < 12) {
        if (lane < 24) cw = ldg_nc32(p.c + 48 * warp + 2 * lane);
        epoch = ld_relaxed(g_cnt + CNT_EPOCH * 32);
        if (b < 72) {
            const uint16_t* src = p.wmod + (48 * warp + (lane >> 1)) * 3456 + 16 * b + (lane & 1) * 8;
            const uint32_t dst = sm + OFF_STRIP + (48 * warp + (lane >> 1)) * 48 + (lane & 1) * 16;
            #pragma unroll
            for (int u = 0; u < 3; u++) asm volatile("cp.async.cg.shared.global" CPHINT " [%0], [%1], 16;" :: "r"(dst + u * 768), "l"(src + u * 16 * 3456) : "memory");
            asm volatile("cp.async.commit_group;" ::: "memory");
        }
    } else {
      if (elect()) {
        if (warp == 15) {
            mbar_init(bars + 8 * BAR_TAB, 1); fence_async_s();
            if (rowcta) { mbar_expect(bars + 8 * BAR_TAB, QA * 512); bulk_load(sm + OFF_TAB, p.tab, QA * 512, bars + 8 * BAR_TAB); }
            asm volatile("prefetch.tensormap [%0];" :: "l"(&tm_wr) : "memory"); asm volatile("prefetch.tensormap [%0];" :: "l"(&tm_wi) : "memory");
            asm volatile("prefetch.tensormap [%0];" :: "l"(&tm_t) : "memory"); asm volatile("prefetch.tensormap [%0];" :: "l"(&tm_tx) : "memory");
        } else if (warp == 14) {
            for (int i = BAR_W; i < BAR_X; i++) mbar_init(bars + 8 * i, 1);
            mbar_expect(bars + 8 * BAR_W, 28672); mbar_expect(bars + 8 * BAR_TAB2, (QB + QC) * 512);
            mbar_expect(bars + 8 * BAR_ROLE, 4); mbar_expect(bars + 8 * BAR_P2R, 9216); mbar_expect(bars + 8 * BAR_RECV, 18432); mbar_expect(bars + 8 * BAR_XT, 18432);
        } else if (warp == 13) {
            for (int i = 0; i < 2 * NST; i++) mbar_init(bars + 8 * i, 2);
            for (int i = 0; i < NST; i++) mbar_expect(bars + 8 * (BAR_FULL + i), A_BYTES);
        }
        else {
            for (int i = 0; i < 16; i++) mbar_init(bars + 8 * (BAR_X + i), rowcta || i < 6 ? 1 : 14);
            if (!rowcta) { fence_async_s(); for (int st = 0; st < 6; st++) nc_issue(st, st); }
        }
        asm volatile("fence.mbarrier_init.release.cluster;" ::: "memory");
      }
      __syncwarp();
      epoch = ld_relaxed(g_cnt + CNT_EPOCH * 32);
    }
    __syncthreads();
    PROF0(22);
    asm volatile("barrier.cluster.arrive.relaxed.aligned;" ::: "memory");
    if (warp < 4) sts16(sm + OFF_MODA + ((warp + 1) * 32 + lane) * 16 + warp * 4 + 2, 0);
    if (warp >= 8) {
        const int k1 = tid & 15, s1 = (tid >> 4) & 15;
        float s, c;
        __sincosf((float)(((k1 * (128 * s1 + b) + 1024) & 2047) - 1024) * (3.14159265358979f / 1024.f), &s, &c); s *= 0.25f; c *= 0.25f;
        const int rf = ((s1 >> 3) * 4 + (k1 >> 2)) * 2 + ((s1 >> 2) & 1), ri = ((k1 >> 3) * 4 + (s1 >> 2)) * 2 + ((k1 >> 2) & 1);
        const uint32_t af = sm + OFF_B3 + ((rf >> 2) * 32 + (k1 & 3) * 8 + (s1 & 3)) * 16 + (rf & 3) * 4;
        const uint32_t ai = sm + OFF_B3 + 2048 + ((ri >> 2) * 32 + (s1 & 3) * 8 + (k1 & 3)) * 16 + (ri & 3) * 4;
        sts32(af, pack_h(c, s)); sts32(af + 64, pack_h(-s, c)); sts32(ai, pack_h(c, -s)); sts32(ai + 64, pack_h(s, c));
    }
    if (rowcta) spin_until(t0 + XDELAY);
    if (rowcta && elect()) {
        mbar_expect(bars + 8 * (BAR_X + warp), 1152);
        bulk_load(sm + OFF_STAGE + warp * 1152, p.x + (size_t)(b + 128 * warp) * D_, 1152, bars + 8 * (BAR_X + warp));
    }
    const uint32_t tag = (epoch + 1) & 0xFFFFu;
    if (warp < 12 && lane < 24) sts32(sm + OFF_SILU + (24 * warp + lane) * 4, pack_bf(silu(bf_lo(cw)), silu(bf_hi(cw))));
    hb();
    PROF0(26);
    uint32_t ta[QA * 4];
    const bool ta_early = rowcta && __any_sync(~0u, mbar_test(bars + 8 * BAR_TAB, 0));
    if (ta_early) load_tab<QA>(ta, sm + OFF_TAB + lane * 16);
    if (warp < 12 && b < 72) {
        uint32_t sb[6];
        __syncwarp();
        #pragma unroll
        for (int u = 0; u < 6; u++) sb[u] = lds32(sm + OFF_SILU + (24 * warp + 4 * u + q) * 4);
        asm volatile("cp.async.wait_all;" ::: "memory");
        __syncwarp();
        float acc[4] = {0, 0, 0, 0};
        #pragma unroll
        for (int u = 0; u < 3; u++) {
            uint32_t a[4];
            ldsm4t(a, sm + OFF_STRIP + (48 * warp + 16 * u + (lane & 7) + 8 * (lane >> 4)) * 48 + ((lane >> 3) & 1) * 16);
            mma_bf(acc, a, sb[2 * u], sb[2 * u + 1]);
        }
        if (q == 0) { sts32(sm + OFF_RED + (g * 12 + warp) * 4, __float_as_uint(acc[0])); sts32(sm + OFF_RED + ((g + 8) * 12 + warp) * 4, __float_as_uint(acc[2])); }
        PROF0(0);
        bar_sync(3, 384);
        if (warp == 0) {
            if (lane < 16) {
                float sum = 0;
                #pragma unroll
                for (int u = 0; u < 3; u++) { const uint4 v = lds128(sm + OFF_RED + lane * 48 + u * 16);
                    sum += (__uint_as_float(v.x) + __uint_as_float(v.y)) + (__uint_as_float(v.z) + __uint_as_float(v.w)); }
                sum = bf_round(sum); if (b >= 36) sum = bf_round(1.f + sum);
                st_relaxed(g_mod + b * MODPAD + (lane & 1) * 8 + (lane >> 1), (pack_h(0.f, sum) & 0xFFFF0000u) | tag);
            }
            __syncwarp();
            PROF0(1);
        }
    }

    const int trow = 4 * (b & 7) + ((b >> 4) & 3) + 64 * ((b >> 3) & 1) + 32 * (b >> 6);
    uint32_t* const tptr = g_T + (size_t)trow * TP + (warp < 9 ? q * 288 + 32 * warp : 4608 + 8 * q) + 4 * g;
    const int tstr = warp < 9 ? 1152 : 32;
    const uint32_t scol = sm + OFF_SPEC + (q * SPEC_P + (warp < 8 ? 72 * (warp >> 1) + 40 * (warp & 1) + 4 * g : warp == 8 ? 72 * (g >> 1) + 32 + 4 * (g & 1) : 288 + 4 * g)) * 4;
    const int wc0 = (b >> 3) * 289 + 72 * ((b & 7) >> 1) + 40 * (b & 1);

    uint32_t xw[9], t_st = t0;
    if (!rowcta) {
        const int nst = b < 130 ? 36 : 18;
        __syncthreads();
        if (warp == 14) {
            uint32_t sl = 0, ph = 0;
            #pragma unroll 1
            for (int st = 6; st < nst; st++) {
                mbar_wait(bars + 8 * (BAR_X + 6 + sl), ph);
                if (elect()) nc_issue(st, sl);
                if (++sl == 6) { sl = 0; ph ^= 1; }
            }
        } else if (warp < 14) {
            uint32_t sl = 0, ph = 0;
            const uint32_t ad0 = sm + (warp >> 1) * 4096 + ((lane & 7) + 8 * (lane >> 4)) * 128, ch = (warp & 1) * 4 + ((lane >> 3) & 1);
            #pragma unroll 1
            for (int pass = 0; pass * 18 < nst; pass++) {
                float acc[2][4] = {};
                #pragma unroll 1
                for (int st = 0; st < 18; st++) {
                    const uint32_t sa = sm + OFF_SILU + (16 * st + q) * 4;
                    const uint32_t b0 = lds32(sa), b1 = lds32(sa + 16), b2 = lds32(sa + 32), b3 = lds32(sa + 48);
                    mbar_wait(bars + 8 * (BAR_X + sl), ph);
                    #pragma unroll
                    for (int m = 0; m < 2; m++) {
                        uint32_t a[4], a2[4];
                        const uint32_t ad = ad0 + sl * 28672 + ((ch + 2 * m) ^ (lane & 7)) * 16;
                        ldsm4t(a, ad); ldsm4t(a2, ad + 2048);
                        mma_bf(acc[m], a, b0, b1); mma_bf(acc[m], a2, b2, b3);
                    }
                    if (elect()) mbar_arrive(bars + 8 * (BAR_X + 6 + sl));
                    if (++sl == 6) { sl = 0; ph ^= 1; }
                }
                const int cb = 28 * pass + 7 * (b - 128) + (warp >> 1), gg = (g >> 1) + 4 * q;
                #pragma unroll
                for (int m = 0; m < 2; m++) {
                    const int qq = (warp & 1) * 2 + m;
                    float v = bf_round(q ? acc[m][2] : acc[m][0]); if (cb >= 27) v *= 0.5f; else if (cb >= 18) v += 1.f;
                    const uint32_t w = pack_bf(v, __shfl_xor_sync(~0u, v, 4));
                    if (q < 2 && !(g & 1) && cb < 36) p.scr->modc[cb < 27 ? ((cb >> 2) * 32 + 4 * gg + qq) * 4 + (cb & 3) : 896 + 32 * (cb - 27) + 8 * qq + gg] = w;
                }
                bar_sync(1, 448);
                if (tid == 0) { fence_async_g(); red_release(g_cnt + (CNT_NC + pass) * 32); if (pass == 0) PROFT(25); }
                __syncwarp();
            }
            fence_async_s();
        }
        __syncthreads();
    } else {
        if (!ta_early) { mbar_wait(bars + 8 * BAR_TAB, 0); load_tab<QA>(ta, sm + OFF_TAB + lane * 16); }
        uint32_t nb[2][5];
        uint4 mv = make_uint4(tag, tag, tag, tag);
        const int mc = tid - 224, mst = (mc >> 2) % 36, midx = (mc < 144 ? 10 : 0) + 5 * ((mc >> 1) & 1) + (mst >> 3);
        const uint32_t* mp = g_mod + (mc >> 2) * MODPAD + (mc & 3) * 4;
        const uint32_t ma = sm + OFF_MODA + ((midx >> 2) * 32 + (mc & 1) * 16 + (mst & 3)) * 16 + (midx & 3) * 4 + ((mst >> 2) & 1) * 2;
        #define MOD_MISSING ((((mv.x ^ tag) | (mv.y ^ tag) | (mv.z ^ tag) | (mv.w ^ tag)) & 0xFFFFu) != 0)
        hb();
        mbar_wait(bars + 8 * (BAR_X + warp), 0);
        if (warp >= 7) mv = ldx128(mp);
        PROF0(28);
        #pragma unroll
        for (int i = 0; i < 9; i++) xw[i] = lds32(sm + OFF_STAGE + warp * 1152 + (32 * i + 8 * q + g) * 4);
        {
            float s1 = 0, s2 = 0;
            #pragma unroll
            for (int i = 0; i < 9; i++) { float lo = bf_lo(xw[i]), hi = bf_hi(xw[i]); s1 += lo + hi; s2 = fmaf(lo, lo, fmaf(hi, hi, s2)); }
            warp_sum2(s1, s2);
            const float m = s1 * (1.f / D_), r = rsqrtf(fmaxf(s2 * (1.f / D_) - m * m, 0.f) + 1e-5f), mr = -m * r;
            #pragma unroll
            for (int pp = 0; pp < 5; pp++) {
                nb[0][pp] = pack_h(fmaf(bf_lo(xw[2 * pp]), r, mr), pp < 4 ? fmaf(bf_lo(xw[pp < 4 ? 2 * pp + 1 : 0]), r, mr) : 0.f);
                nb[1][pp] = pack_h(fmaf(bf_hi(xw[2 * pp]), r, mr), pp < 4 ? fmaf(bf_hi(xw[pp < 4 ? 2 * pp + 1 : 0]), r, mr) : 0.f);
            }
        }
        PROF0(2);
        if (warp >= 7) {
            for (int it = 0; __any_sync(~0u, MOD_MISSING); it++) { mv = ldx128(mp); hb(); if (it > SPIN_LIMIT) __trap(); }
            sts16(ma, mv.x >> 16); sts16(ma + 64, mv.y >> 16); sts16(ma + 128, mv.z >> 16); sts16(ma + 192, mv.w >> 16);
        }
        __syncthreads();
        PROF0(3);
        if (warp >= 13 && elect()) {
            if (warp == 15) bulk_load(sm + OFF_TAB + QA * 512, p.tab->w + QA * 128, (QB + QC) * 512, bars + 8 * BAR_TAB2);
            else tma3(sm + OFF_WRAW + (warp - 13) * 14336, warp == 13 ? &tm_wr : &tm_wi, wc0 & ~7, 0, 0, bars + 8 * BAR_W);
        }
        __syncwarp();
        {
            uint32_t md[20];
            load_tab<5>(md, sm + OFF_MODA + lane * 16);
            #pragma unroll
            for (int v = 0; v < 2; v++)
                #pragma unroll
                for (int pp = 0; pp < 5; pp++) nb[v][pp] = hfma2(nb[v][pp], md[v * 5 + pp], md[10 + v * 5 + pp]);
        }
        uint32_t re[3][2], im[3][2];
        #pragma unroll
        for (int mt = 0; mt < 3; mt++)
            #pragma unroll
            for (int v = 0; v < 2; v++) {
                re[mt][v] = 0; im[mt][v] = 0;
                mma_h8(re[mt][v], im[mt][v], ta[mt * 10 + 8], ta[mt * 10 + 9], nb[v][4]);
                mma_h(re[mt][v], im[mt][v], ta[mt * 10], ta[mt * 10 + 1], ta[mt * 10 + 2], ta[mt * 10 + 3], nb[v][0], nb[v][1]);
                mma_h(re[mt][v], im[mt][v], ta[mt * 10 + 4], ta[mt * 10 + 5], ta[mt * 10 + 6], ta[mt * 10 + 7], nb[v][2], nb[v][3]);
                cmul_neg(re[mt][v], im[mt][v], ta[30 + (mt * 2 + v) * 2], ta[31 + (mt * 2 + v) * 2]);
            }
        const uint32_t srow = sm + OFF_SPEC + warp * (SPEC_P * 4);
        #pragma unroll
        for (int nt = 0; nt < 2; nt++) {
            uint32_t o[2][4];
            #pragma unroll
            for (int v = 0; v < 2; v++) {
                const uint32_t b0 = ta[42 + (v * 2 + nt) * 2], b1 = ta[43 + (v * 2 + nt) * 2];
                o[v][0] = o[v][1] = o[v][2] = o[v][3] = 0;
                mma_h(o[v][0], o[v][1], re[0][v], re[1][v], im[0][v], im[1][v], b0, b1);
                mma_h(o[v][2], o[v][3], re[2][v], re[2][v], im[2][v], im[2][v], b0, b1);
            }
            const uint32_t a = srow + (g + 72 * q + 36 * nt) * 4, a2 = srow + (288 - g - 72 * q - 36 * nt) * 4;
            sts32(a, hadd2(o[0][0], o[1][0])); sts32(a + 32, hadd2(o[0][1], o[1][1])); if (g < 3) sts32(a + 64, hadd2(o[0][2], o[1][2]));
            if (g > 0 || (q == 0 && nt == 0)) sts32(a2, hsub2(o[0][0], o[1][0]) ^ 0x80000000u);
            sts32(a2 - 32, hsub2(o[0][1], o[1][1]) ^ 0x80000000u); if (g < 2) sts32(a2 - 64, hsub2(o[0][2], o[1][2]) ^ 0x80000000u);
        }
        uint32_t b3[16];
        if (warp < 10) load_tab<4>(b3, sm + OFF_B3 + lane * 16);
        __syncthreads();
        t_st = clk32();
        PROF0(4);
        if (warp < 10) {
            uint4 V[4], o[4];
            #pragma unroll
            for (int u = 0; u < 4; u++) V[u] = lds128(scol + u * (16 * SPEC_P));
            radix16(V, b3, o);
            #pragma unroll
            for (int nt = 0; nt < 4; nt++) { o[nt].x |= 1u; if (warp < 9 || g < 2) stx128(tptr + nt * tstr, o[nt]); }
        }
        PROF0(5);
    }

    int role = 0;
    asm volatile("barrier.cluster.wait.aligned;" ::: "memory");
    if (warp >= 12) {
        const int t = tid - 384;
        if (tid == 448 && rank == 0) {
            uint32_t smid; asm volatile("mov.u32 %0, %%smid;" : "=r"(smid));
            const uint32_t tp = smid >> 1;
            uint32_t pr = tp < 32 ? (tp & 7) * 8 + (tp >> 3) : tp < 60 ? (1 + (tp - 32) % 7) * 8 + 4 + (tp - 32) / 7 : tp < 62 ? 4 + tp : tp < 66 ? tp - 58 : 0;
            while (atomicExch(g_slot + pr, epoch + 1) == epoch + 1) pr = pr == 65 ? 0 : pr + 1;
            #pragma unroll
            for (int r = 0; r < 2; r++)
                asm volatile("st.async.weak.shared::cluster.mbarrier::complete_tx::bytes.u32 [%0], %1, [%2];" :: "r"(mapa(sm + OFF_MISC, r)), "r"(pr), "r"(mapa(bars + 8 * BAR_ROLE, r)) : "memory");
        }
        __syncwarp();
        if (t == 0) {
            asm volatile("prefetch.tensormap [%0];" :: "l"(&tm_w1a) : "memory");
            asm volatile("prefetch.tensormap [%0];" :: "l"(&tm_h3a) : "memory"); asm volatile("prefetch.tensormap [%0];" :: "l"(&tm_w1b) : "memory");
            asm volatile("prefetch.tensormap [%0];" :: "l"(&tm_h3b) : "memory"); asm volatile("prefetch.tensormap [%0];" :: "l"(&tm_w2) : "memory");
            asm volatile("prefetch.tensormap [%0];" :: "l"(&tm_w2b) : "memory"); asm volatile("prefetch.tensormap [%0];" :: "l"(&tm_o) : "memory");
        }
        if (t == 32 && rowcta) {
            for (int it = 0; (int)(ld_acquire(g_cnt + CNT_NC * 32) - (epoch + 1) * 4) < 0; it++) { __nanosleep(100); if (it > SPIN_LIMIT) __trap(); }
            fence_async_g();
            mbar_expect(bars + 8 * BAR_NC, 3584);
            bulk_load(sm + OFF_MODC, p.scr->modc, 3584, bars + 8 * BAR_NC);
            PROFT(29);
        }
        __syncwarp();
    } else if (rowcta && warp < 11) {
        const int nw = !(b & 1) ? 10 : (b & 7) == 7 ? 9 : 8;
        const int cm = (b >> 3) * 288 + (b & 7) * 32, cx = (b & 1) ? 4608 + 8 * (b >> 3) : (b >> 3) * 288 + 256 + 4 * (b & 7);
        auto load_in = [&]() {
            if (elect()) {
                mbar_expect(bars + 8 * BAR_XB, nw > 8 ? 20480 : 16384);
                tma2(sm + OFF_STAGE, &tm_t, cm, 0, bars + 8 * BAR_XB);
                if (nw > 8) tma2(sm + OFF_STX, &tm_tx, cx, 0, bars + 8 * BAR_XB);
            }
            __syncwarp();
        };
        if (warp == 10) { fence_async_s(); spin_until(t_st + X1D); load_in(); }
        uint32_t tb[QB * 4], wre[4][2], wim[4][2];
        if (warp < nw) {
            mbar_wait(bars + 8 * BAR_TAB2, 0);
            load_tab<QB>(tb, sm + OFF_TAB + QA * 512 + lane * 16);
            mbar_wait(bars + 8 * BAR_W, 0);
            const int off = wc0 & 7;
            const uint32_t wa = sm + OFF_WRAW + lane * 112 + ((off >> 1) + 2 * warp) * 4, sh = (off & 1) * 16;
            #pragma unroll
            for (int c = 0; c < 2; c++)
                #pragma unroll
                for (int h = 0; h < 2; h++) {
                    uint32_t y[2][2];
                    #pragma unroll
                    for (int e = 0; e < 2; e++) {
                        const uint32_t a = wa + c * 14336 + (h + 2 * e) * 3584, x0 = lds32(a), x1 = lds32(a + 4), x2 = lds32(a + 8);
                        y[e][0] = __funnelshift_r(x0, x1, sh); y[e][1] = __funnelshift_r(x1, x2, sh);
                    }
                    #pragma unroll
                    for (int x = 0; x < 4; x++) {
                        const uint32_t v = (x & 1) ? pack_h(bf_hi(y[0][x >> 1]), bf_hi(y[1][x >> 1])) : pack_h(bf_lo(y[0][x >> 1]), bf_lo(y[1][x >> 1]));
                        if (c) wim[x][h] = v; else wre[x][h] = v;
                    }
                }
        }
        const uint32_t ca = warp < 8 ? sm + OFF_STAGE + lane * 128 + (warp ^ (lane & 7)) * 16 : sm + OFF_STX + lane * 32 + ((warp ^ g) & 1) * 16, cs = warp < 8 ? 4096 : 1024;
        uint32_t V[4][4];
        for (int it = 0;; it++) {
            mbar_wait(bars + 8 * BAR_XB, it & 1);
            uint32_t ok = 1;
            if (warp < nw) {
                #pragma unroll
                for (int u = 0; u < 4; u++) { uint4 t4 = lds128(ca + u * cs); V[u][0] = t4.x; V[u][1] = t4.y; V[u][2] = t4.z; V[u][3] = t4.w; ok &= t4.x; }
            }
            asm volatile("{.reg .pred p; setp.ne.u32 p, %0, 0; bar.red.and.pred p, 1, 352, p; selp.u32 %0, 1, 0, p;}" : "+r"(ok) :: "memory");
            if (ok) break;
            if (warp == 10) { load_in(); hb(); }
            if (it > SPIN_LIMIT / 64) __trap();
        }
        PROF0(7);
        if (warp < nw) {
            uint32_t zr[4][2], zi[4][2];
            #pragma unroll
            for (int x = 0; x < 4; x++) {
                uint32_t er = 0, ei = 0, or_ = 0, oi = 0;
                mma_h(er, ei, tb[0], tb[1], tb[2], tb[3], V[0][x], V[1][x]);
                mma_h(or_, oi, tb[4], tb[5], tb[6], tb[7], V[2][x], V[3][x]);
                uint32_t r0 = hadd2(er, or_), r1 = hsub2(er, or_), i0 = hadd2(ei, oi), i1 = hsub2(ei, oi);
                cmul_neg(r0, i0, tb[8], tb[9]); cmul_neg(r1, i1, tb[10], tb[11]);
                uint32_t xr0 = 0, xr1 = 0, xi0 = 0, xi1 = 0;
                mma_h(xr0, xr1, r0, r1, i0, i1, tb[12], tb[13]);
                mma_h(xi0, xi1, r0, r1, i0, i1, tb[14], tb[12]);
                cmul_pos(xr0, xi0, wre[x][0], wim[x][0]); cmul_pos(xr1, xi1, wre[x][1], wim[x][1]);
                r0 = 0; i0 = 0; r1 = 0; i1 = 0;
                mma_h(r0, i0, tb[12], tb[13], tb[14], tb[12], xr0, xi0);
                mma_h(r1, i1, tb[12], tb[13], tb[14], tb[12], xr1, xi1);
                cmul_pos(r0, i0, tb[15], tb[16]); cmul_pos(r1, i1, tb[17], tb[18]);
                zr[x][0] = hadd2(r0, r1); zr[x][1] = hsub2(r0, r1); zi[x][0] = hadd2(i0, i1); zi[x][1] = hsub2(i0, i1);
            }
            #pragma unroll
            for (int nt = 0; nt < 4; nt++) {
                uint4 o = make_uint4(0, 0, 0, 0);
                const int h = nt >> 1;
                mma_h(o.x, o.y, zr[0][h], zr[1][h], zi[0][h], zi[1][h], tb[19 + 2 * nt], tb[20 + 2 * nt]);
                mma_h(o.z, o.w, zr[2][h], zr[3][h], zi[2][h], zi[3][h], tb[19 + 2 * nt], tb[20 + 2 * nt]);
                o.x &= ~1u;
                sts128(ca + nt * cs, o);
            }
        }
        fence_async_s();
        bar_sync(1, 352);
        t_st = clk32();
        PROF0(8);
        if (warp == 10 && elect()) {
            asm volatile("cp.async.bulk.tensor.2d.global.shared::cta.bulk_group [%0, {%2, %3}], [%1];" :: "l"(&tm_t), "r"(sm + OFF_STAGE), "r"(cm), "r"(0) : "memory");
            if (nw > 8) asm volatile("cp.async.bulk.tensor.2d.global.shared::cta.bulk_group [%0, {%2, %3}], [%1];" :: "l"(&tm_tx), "r"(sm + OFF_STX), "r"(cx), "r"(0) : "memory");
            asm volatile("cp.async.bulk.commit_group;" ::: "memory");
            asm volatile("cp.async.bulk.wait_group.read 0;" ::: "memory");
        }
        __syncwarp();
    }

    if (warp >= 10) { mbar_wait(bars + 8 * BAR_ROLE, 0); role = __shfl_sync(~0u, lds32(sm + OFF_MISC), 0); fence_async_s(); }
    auto first_a = [&]() {
        if (warp >= 10 && role < 64 && elect())
            tma4(sm + OFF_A + (warp - 10) * A_BYTES, &tm_w1a, 0, 0, 4 * (warp - 10), 9 * (role >> 3) + (role & 4) + 2 * rank, bars + 8 * (BAR_FULL + warp - 10));
        __syncwarp();
    };
    if (!rowcta) first_a();
    else {
        uint32_t tc[QC * 4];
        mbar_wait(bars + 8 * BAR_TAB2, 0);
        load_tab<QC>(tc, sm + OFF_TAB + (QA + QB) * 512 + lane * 16);
        if (warp < 10) {
            uint32_t b3[16];
            load_tab<4>(b3, sm + OFF_B3 + 2048 + lane * 16);
            uint4 V[4], o[4];
            const bool tact = warp < 9 || g == 0;
            spin_until(t_st + X2D);
            #pragma unroll
            for (int u = 0; u < 4; u++) V[u] = make_uint4(tact, 0, 0, 0);
            for (int it = 0; __any_sync(~0u, (V[0].x | V[1].x | V[2].x | V[3].x) & 1u); it++) {
                #pragma unroll
                for (int u = 0; u < 4; u++) if (V[u].x & 1u) V[u] = ldx128(tptr + u * tstr);
                hb();
                if (it > SPIN_LIMIT) __trap();
            }
            PROF0(10);
            radix16(V, b3, o);
            if (tact) {
                #pragma unroll
                for (int nt = 0; nt < 4; nt++) sts128(scol + nt * (16 * SPEC_P), o[nt]);
            }
        }
        __syncthreads();
        PROF0(11);
        first_a();
        const uint32_t srow = sm + OFF_SPEC + warp * (SPEC_P * 4);
        uint32_t re[2][3], im[2][3];
        #pragma unroll
        for (int mt = 0; mt < 3; mt++) {
            const uint32_t a = srow + (g + 72 * q + 8 * mt) * 4, a2 = srow + (288 - g - 72 * q - 8 * mt) * 4;
            const uint32_t z0 = lds32(a), z1 = lds32(a + 144), z2 = lds32(a2), z3 = lds32(a2 - 144);
            #pragma unroll
            for (int m2 = 0; m2 < 2; m2++) {
                re[m2][mt] = 0; im[m2][mt] = 0;
                const uint32_t sg = m2 ? 0x3C00BC00u : 0xBC003C00u;
                mma_h(re[m2][mt], im[m2][mt], tc[m2 * 4], tc[m2 * 4 + 1], tc[m2 * 4 + 2], tc[m2 * 4 + 3], hfma2(z2, sg, z0), hfma2(z3, sg, z1));
                cmul_pos(re[m2][mt], im[m2][mt], tc[8 + (m2 * 3 + mt) * 2], tc[9 + (m2 * 3 + mt) * 2]);
            }
        }
        uint32_t md[28];
        mbar_wait(bars + 8 * BAR_NC, 0);
        load_tab<7>(md, sm + OFF_MODC + lane * 16);
        float y[5][4];
        #pragma unroll
        for (int nt = 0; nt < 5; nt++) {
            y[nt][0] = y[nt][1] = y[nt][2] = y[nt][3] = 0.f;
            #pragma unroll
            for (int mt = 0; mt < 3; mt++)
                mma_f(y[nt], re[0][mt], re[1][mt], im[0][mt], im[1][mt], tc[20 + (mt * 5 + nt) * 2], tc[21 + (mt * 5 + nt) * 2]);
        }
        float v0[9], v1[9], s1 = 0, s2 = 0;
        #pragma unroll
        for (int i = 0; i < 9; i++) {
            xw[i] = bfma2(md[i], pack_bf(y[i >> 1][i & 1], y[i >> 1][2 + (i & 1)]), xw[i]);
            v0[i] = bf_lo(xw[i]); v1[i] = bf_hi(xw[i]);
            s1 += v0[i] + v1[i]; s2 = fmaf(v0[i], v0[i], fmaf(v1[i], v1[i], s2));
        }
        warp_sum2(s1, s2);
        float m = s1 * (1.f / D_), r = rsqrtf(fmaxf(s2 * (1.f / D_) - m * m, 0.f) + 1e-5f), mr = -m * r;
        s1 = 0; s2 = 0;
        #pragma unroll
        for (int i = 0; i < 9; i++) {
            v0[i] = fmaf(fmaf(v0[i], r, mr), bf_lo(md[18 + i]), bf_lo(md[9 + i]));
            v1[i] = fmaf(fmaf(v1[i], r, mr), bf_hi(md[18 + i]), bf_hi(md[9 + i]));
            s1 += v0[i] + v1[i]; s2 = fmaf(v0[i], v0[i], fmaf(v1[i], v1[i], s2));
        }
        if (warp == 15) hb();
        warp_sum2(s1, s2);
        m = s1 * (1.f / D_); r = rsqrtf(fmaxf(s2 * (1.f / D_) - m * m, 0.f) + 1e-5f); mr = -m * r;
        {
            const int n7 = 2 * q + (g >> 2);
            const uint32_t a = sm + OFF_STAGE + n7 * 256 + (warp >> 3) * 128 + ((warp & 7) ^ n7) * 16 + (g & 3) * 4;
            #pragma unroll
            for (int i = 0; i < 9; i++) sts32(a + i * 2048, pack_bf(fmaf(v0[i], r, mr), fmaf(v1[i], r, mr)));
        }
        __syncthreads();
        PROF0(12);
        #pragma unroll
        for (int u = 0; u < 3; u++) {
            const int e = tid + 512 * u;
            if (e < 1152) g_h3[b * 1152 + e] = lds128(sm + OFF_STAGE + ((e & ~7) | ((e ^ (e >> 4)) & 7)) * 16);
        }
        #pragma unroll
        for (int i = 0; i < 9; i++) sts32(sm + OFF_X1 + warp * 1152 + (32 * i + 8 * q + g) * 4, xw[i]);
    }
    __syncthreads();
    if (rowcta) {
        if (tid == 0) { fence_async_g(); red_release(g_cnt + CNT_H3 * 32); }
        PROF0(13);
        if (warp == 15) {
            __nanosleep(X1DELAY);
            #pragma unroll 1
            for (int r = 0; r < 16; r++) {
                uint4* dst = (uint4*)(p.out + (size_t)(b + 128 * r) * D_) + lane;
                const uint32_t src = sm + OFF_X1 + r * 1152 + lane * 16;
                dst[0] = lds128(src); dst[32] = lds128(src + 512); if (lane < 8) dst[64] = lds128(src + 1024);
            }
            __syncwarp();
            if (lane == 0) { fence_async_g(); red_release(g_cnt + CNT_X1 * 32); }
        }
    }
    role = __shfl_sync(~0u, lds32(sm + OFF_MISC), 0);
    if (role >= 64) { if (warp == 0) PROFDUMP(); return; }

    const int gi = role >> 3, dt = role & 3, c2 = (role >> 2) & 1;
    const int wg = warp >> 2, wi = warp & 3;
    if (wg == 3) {
        uint32_t so = 0, eph = 1;
        #define RING_STEP(BYTES, OFF, ISSUE) do { \
            mbar_wait(bars + 8 * BAR_EMPTY + so, eph); \
            if (elect()) { const uint32_t fb = bars + 8 * BAR_FULL + so, dst = sm + (OFF) + so * ((BYTES) / 8); mbar_expect(fb, BYTES); ISSUE; } \
            so += 8; if (so == 8 * NST) { so = 0; eph ^= 1; } } while (0)
        if (warp == 12) {
            eph = 0;
            const int fb1 = 9 * gi + 4 * c2 + 2 * rank, sb2 = 4 * gi + 2 * c2;
            #pragma unroll 1
            for (int j = 4 * NST; j < 128; j += 4) {
                RING_STEP(A_BYTES, OFF_A, tma4(dst, &tm_w1a, 0, 0, j, fb1, fb));
                if (PF2 && (j & 28) == 4 * (role & 7) && j >= 32 && elect()) {
                    if (j < 64) asm volatile("cp.async.bulk.prefetch.tensor.4d.L2.global [%0, {%1, %2, %3, %4}];" :: "l"(&tm_w1b), "r"(0), "r"(0), "r"(64 * (int)rank + 8 * (role & 7)), "r"(9 * gi + 8) : "memory");
                    else asm volatile("cp.async.bulk.prefetch.tensor.3d.L2.global [%0, {%1, %2, %3}];" :: "l"(&tm_w2), "r"(0), "r"(64 * g2_kb(dt + ((j >> 3) & 4), rank)), "r"(sb2) : "memory");
                }
            }
            #pragma unroll 1
            for (int j = 64 * rank; j < 64 * rank + 64; j += 8) {
                RING_STEP(A_BYTES, OFF_A, tma4(dst, &tm_w1b, 0, 0, j, 9 * gi + 8, fb));
            }
            #pragma unroll 1
            for (int n = 0; n < 32; n++) {
                if (n == A2E) { mbar_wait(bars + 8 * BAR_UOK, 0); fence_async_g(); if (A2D) spin_until(clk32() + A2D); }
                RING_STEP(A_BYTES, OFF_A, tma3(dst, &tm_w2, 0, 64 * g2_kb(n, rank), sb2, fb));
            }
            #pragma unroll 1
            for (int n = 0; n < 8; n++)
                RING_STEP(A_BYTES / 2, OFF_A + so * (A_BYTES / 16) + rank * 8192, { tma3(dst, &tm_w2b, 0, 512 + 576 * n, sb2 + rank, fb);
                    if (n < 4) tma2(dst + 8192 - 16384 * rank, &tm_o, 144 * dt, 64 * (sb2 + (rank ^ 1)) + 16 * n, bars + 8 * BAR_XT); });
        } else if (warp == 13) {
            const uint32_t e1 = __shfl_sync(~0u, epoch + 1, 0);
            fence_async_s();
            wait_count(g_cnt + CNT_H3 * 32, e1 * 128);
            fence_async_g();
            if (lane == 0) PROFT(14);
            #pragma unroll 1
            for (int j = 0; j < 128; j += 4) RING_STEP(B_BYTES, OFF_B, tma3(dst, &tm_h3a, 0, 18 * dt, j, fb));
            #pragma unroll 1
            for (int j = 64 * rank; j < 64 * rank + 64; j += 8) {
                RING_STEP(B_BYTES, OFF_B, tma3(dst, &tm_h3b, 0, 18 * dt + 9 * c2, j, fb));
            }
            #pragma unroll 1
            for (int cls = 0; cls < 3; cls++) {
                mbar_wait(bars + 8 * (BAR_UOK + cls), 0);
                fence_async_g();
                if (cls == 0 && lane == 0) PROFT(19);
                const int n1 = cls < 2 ? 16 * cls + 16 : 40;
                #pragma unroll 1
                for (int n = 16 * cls; n < n1; n++) RING_STEP(B_BYTES, OFF_B, bulk_load(dst, g_U + (g2_kb(n, rank) * 4 + dt) * 1152, B_BYTES, fb));
            }
            if (role == 0 && rank == 0 && lane == 0) st_relaxed(g_cnt + CNT_EPOCH * 32, e1);
        } else if (warp == 15) {
            asm volatile("bar.arrive 5, 160;" ::: "memory");
            bar_sync(6, 160);
            mbar_wait(bars + 8 * BAR_W1GO, 0);
            if (elect()) {
                char* dst = (char*)(g_U + ((9 * gi + 4 * c2 + 2 * rank + 1) * 4 + dt) * 1152);
                #pragma unroll 1
                for (int i = 0; i < W1N; i++) {
                    asm volatile("cp.async.bulk.global.shared::cta.bulk_group [%0], [%1], %2;" :: "l"(dst + i * (18432 / W1N)), "r"(sm + OFF_X1 + i * (18432 / W1N)), "n"(18432 / W1N) : "memory");
                    const uint32_t t1 = clk32(); while ((int)(clk32() - t1) < W1P) {}
                }
                asm volatile("cp.async.bulk.commit_group;" ::: "memory");
                asm volatile("cp.async.bulk.wait_group 0;" ::: "memory");
                mbar_arrive_remote(mapa(bars + 8 * BAR_HOLD, rank ^ 1));
                fence_async_g(); red_release(g_cnt + (CNT_U + 8 + UIDX(dt, gi >> 2)) * 32);
            }
        } else if (tid == 448) {
            __nanosleep(4000);
            for (int it = 0; (int)(ld_acquire(g_cnt + (CNT_NC + 1) * 32) - (epoch + 1) * 2) < 0 || (int)(ld_acquire(g_cnt + CNT_NC * 32) - (epoch + 1) * 4) < 0; it++) { __nanosleep(200); if (it > SPIN_LIMIT) __trap(); }
            fence_async_g();
            mbar_expect(bars + 8 * BAR_GB, 1152);
            bulk_load(sm + OFF_GB, p.scr->modc + 896, 1152, bars + 8 * BAR_GB);
            wait_count(g_cnt + CNT_X1 * 32, (epoch + 1) * 128);
            mbar_wait(bars + 8 * BAR_STGO, 0);
            #pragma unroll 1
            for (int cls = 0; cls < 3; cls++) {
                wait_count(g_cnt + (CNT_U + 8 * cls + (cls < 2 ? UIDX(dt, rank) : 0)) * 32, (epoch + 1) * (cls < 2 ? UCNT : 128));
                mbar_arrive(bars + 8 * (BAR_UOK + cls));
                __nanosleep(1000);
            }
        }
    } else if (wg == 2) {
        float d0[36];
        const int fr = 576 * gi + 512 + 16 * wi + g;
        const float bias0 = bf_lo(ldg_nc16(p.b1 + fr)), bias1 = bf_lo(ldg_nc16(p.b1 + fr + 8));
        for (int it = 0; it < 200 && !__any_sync(~0u, mbar_test(bars + 8 * BAR_FULL, 0)); it++) { hb(); __nanosleep(100); }
        mbar_wait(bars + 8 * BAR_P2GO, 0);
        const bool lead = wi == 0 && elect();
        uint32_t s = IT_P2 % NST, ph = (IT_P2 / NST) & 1, prev = 0;
        #pragma unroll 1
        for (int i = 0; i < IT_G2 - IT_P2; i++) {
            if (i == P2A) {
                if (P2A) { WG_WAIT(0); if (lead) mbar_arrive_n(bars + 8 * BAR_EMPTY + 8 * prev, 2); }
                mbar_wait(bars + 8 * BAR_STGO, 0);
                spin_until(clk32() + P2D);
            }
            mbar_wait(bars + 8 * BAR_FULL + 8 * s, ph);
            const uint32_t da = desc_lo(sm + OFF_A, 8192) + s * (A_BYTES / 16), db = desc_lo(sm + OFF_B, 128) + s * (B_BYTES / 16);
            WG_FENCE();
            wgmma72(d0, da, db, i);
            #pragma unroll
            for (int k = 1; k < 8; k++) wgmma72(d0, da + k * 128, db + k * 144, 1);
            WG_COMMIT();
            if (lead && i == IT_G2 - IT_P2 - 1) mbar_arrive(bars + 8 * BAR_G2GO);
            WG_WAIT(1);
            if (lead && i && i != P2A) mbar_arrive_n(bars + 8 * BAR_EMPTY + 8 * prev, 2);
            prev = s; if (++s == NST) { s = 0; ph ^= 1; }
        }
        WG_WAIT(0);
        if (lead) { mbar_arrive_n(bars + 8 * BAR_EMPTY + 8 * prev, 2); PROFT(18); }
        const uint32_t slot = sm + OFF_P2R + ((wi & 1) * 32 + lane) * 16;
        if ((uint32_t)(wi >> 1) != rank) {
            const uint32_t ra = mapa(slot, rank ^ 1), rb = mapa(bars + 8 * BAR_P2R, rank ^ 1);
            mbar_wait(bars + 8 * BAR_HOLD, 0);
            #pragma unroll
            for (int i = 0; i < 9; i++)
                asm volatile("st.async.weak.shared::cluster.mbarrier::complete_tx::bytes.v4.f32 [%0], {%1,%2,%3,%4}, [%5];"
                    :: "r"(ra + i * 1024), "f"(d0[4 * i]), "f"(d0[4 * i + 1]), "f"(d0[4 * i + 2]), "f"(d0[4 * i + 3]), "r"(rb) : "memory");
        } else {
            mbar_wait(bars + 8 * BAR_P2R, 0);
            #pragma unroll
            for (int i = 0; i < 9; i++) {
                const uint4 v = lds128(slot + i * 1024);
                d0[4 * i] += __uint_as_float(v.x) + bias0; d0[4 * i + 1] += __uint_as_float(v.y) + bias0;
                d0[4 * i + 2] += __uint_as_float(v.z) + bias1; d0[4 * i + 3] += __uint_as_float(v.w) + bias1;
            }
            char* ub = (char*)(g_U + ((9 * gi + 8) * 4 + dt) * 1152) + wi * 4608 + c2 * 1152 + g * 16;
            gelu_store<0>(d0, ub, q); gelu_store<2>(d0, ub + 2304, q);
            bar_sync(8, 64);
            if ((wi & 1) == 0 && lane == 0) { fence_async_g(); red_release(g_cnt + (CNT_U + 16) * 32); }
        }
    } else {
        float d[72];
        const bool lead = wi == 0 && elect();
        const uint32_t da0 = desc_lo(sm + OFF_A + wg * 8192, 8192);
        {
            const int fr = 576 * gi + 256 * c2 + 128 * rank + 64 * wg + 16 * wi + g;
            const float bias0 = bf_lo(ldg_nc16(p.b1 + fr)), bias1 = bf_lo(ldg_nc16(p.b1 + fr + 8));
            #pragma unroll
            for (int i = 0; i < 72; i++) d[i] = (i & 2) ? bias1 : bias0;
            mainloop<DHI_H3, 0, IT_P2, false, true, true>(d, bars, da0, desc_lo(sm + OFF_B, 128), lead,
                [&](int i) { if (i == IT_P2 - 1 && wg == 0 && lead) mbar_arrive(bars + 8 * BAR_P2GO); });
            PROF0(16);
            if (wg == 1) bar_sync(5, 160);
            char* const ub = (wg == 0 ? (char*)(g_U + ((9 * gi + 4 * c2 + 2 * rank) * 4 + dt) * 1152) : (char*)__cvta_shared_to_generic(sm + OFF_X1)) + wi * 4608 + g * 16;
            gelu_store<0>(d, ub, q); gelu_store<2>(d, ub + 2304, q); gelu_store<36>(d, ub + 1152, q); gelu_store<38>(d, ub + 3456, q);
            PROF0(27);
            if (wg == 0) {
                bar_sync(4, 128);
                if (lead) {
                    mbar_arrive(bars + 8 * BAR_STGO);
                    fence_async_g(); red_release(g_cnt + (CNT_U + UIDX(dt, gi >> 2)) * 32);
                }
                __syncwarp();
            } else { fence_async_s(); asm volatile("bar.arrive 6, 160;" ::: "memory"); }
            PROF0(17);
        }
        const bool owner = (uint32_t)wg == rank;
        const int srow = 256 * gi + 128 * c2 + 64 * wg + 16 * wi;
        const uint32_t b2w0 = ldg_nc16(p.b2 + srow + g), b2w1 = ldg_nc16(p.b2 + srow + g + 8);
        mbar_wait(bars + 8 * BAR_G2GO, 0);
        const uint32_t db0 = desc_lo(sm + OFF_B, 2304);
        mainloop<DHI_U, IT_G2, IT_TAIL, true, true, false>(d, bars, da0, db0, lead,
            [&](int i) { if (i == IT_G2 + W1S && wg == 0 && lead) mbar_arrive(bars + 8 * BAR_W1GO); });
        PROF0(9);
        static_assert(IT_TAIL % NST == 0, "x1 pieces sit in slots 0..3");
        const uint32_t ga0 = sm + OFF_GB + (144 * dt + 8 * q) * 2, tile = sm + OFF_X1 + wi * 4608, to = g * 288 + q * 16;
        #define QOFF(i_) (((i_) >> 2) * 2304 + 144 * (((i_) >> 1) & 1) + 64 * ((i_) & 1))
        #define SOFF(k_) (((k_) >> 1) * 2304 + 144 * ((k_) & 1) + 128 - 12 * q)
        #define DIDX(i_, k_) ((i_) < 8 ? 36 * (((i_) >> 1) & 1) + 16 * ((i_) & 1) + 4 * (k_) + 2 * ((i_) >> 2) : 36 * ((k_) & 1) + 32 + 2 * ((k_) >> 1))
        uint4 gq[5];
        auto load_gb = [&]() {
            mbar_wait(bars + 8 * BAR_GB, 0);
            #pragma unroll
            for (int i = 0; i < 4; i++) gq[i] = lds128(ga0 + QOFF(i));
            gq[4].x = gq[4].z = lds32(ga0 + SOFF(0)); gq[4].y = gq[4].w = lds32(ga0 + SOFF(1));
        };
        auto load_q = [&](uint32_t a, int i) { return i < 8 ? lds128(a + QOFF(i)) : make_uint4(lds32(a + SOFF(0)), lds32(a + SOFF(1)), lds32(a + SOFF(2)), lds32(a + SOFF(3))); };
        if (!owner) {
            load_gb();
            mbar_wait(bars + 8 * (BAR_UOK + 2), 0);
            mbar_wait(bars + 8 * BAR_XT, 0);
            const uint32_t ra = mapa(tile + to, rank ^ 1), rb = mapa(bars + 8 * BAR_RECV, rank ^ 1), xa = sm + OFF_A + wi * A_BYTES + wg * 8192 + to;
            const float bias[2] = {2.f * bf_lo(b2w0), 2.f * bf_lo(b2w1)};
            WG_WAIT(0);
            if (lead) mbar_arrive(bars + 8 * (BAR_EMPTY + (IT_TAIL - 1) % NST));
            #pragma unroll
            for (int i = 0; i < 9; i++) {
                const uint4 x4 = load_q(xa, i), g4 = gq[i < 8 ? i & 3 : 4];
                const uint32_t gw[4] = {g4.x, g4.y, g4.z, g4.w}, xw4[4] = {x4.x, x4.y, x4.z, x4.w};
                uint32_t w[4];
                #pragma unroll
                for (int k = 0; k < 4; k++) { const float bb = bias[i < 8 ? i >> 2 : k >> 1];
                    w[k] = pack_bf(fmaf(bf_lo(gw[k]), d[DIDX(i, k)] + bb, bf_lo(xw4[k])), fmaf(bf_hi(gw[k]), d[DIDX(i, k) + 1] + bb, bf_hi(xw4[k]))); }
                if (i < 8) asm volatile("st.async.weak.shared::cluster.mbarrier::complete_tx::bytes.v4.b32 [%0], {%1,%2,%3,%4}, [%5];"
                        :: "r"(ra + QOFF(i)), "r"(w[0]), "r"(w[1]), "r"(w[2]), "r"(w[3]), "r"(rb) : "memory");
                else {
                    #pragma unroll
                    for (int k = 0; k < 4; k++)
                        asm volatile("st.async.weak.shared::cluster.mbarrier::complete_tx::bytes.b32 [%0], %1, [%2];" :: "r"(ra + SOFF(k)), "r"(w[k]), "r"(rb) : "memory");
                }
            }
            PROF0(6);
            if (warp == 0) PROFDUMP();
            return;
        }
        mainloop<DHI_U, IT_TAIL, IT_END, false, false, false, 2>(d, bars, da0, db0, lead, [&](int) {});
        PROF0(24);
        load_gb();
        mbar_wait(bars + 8 * BAR_RECV, 0);
        uint4 xq[9];
        #pragma unroll
        for (int i = 0; i < 5; i++) xq[i] = load_q(tile + to, i);
        WG_WAIT(0);
        PROF0(21);
        #pragma unroll
        for (int i = 0; i < 9; i++) {
            if (i < 4) xq[i + 5] = load_q(tile + to, i + 5);
            const uint4 g4 = gq[i < 8 ? i & 3 : 4];
            #define FIN(k_, f_) bfma2(g4.f_, pack_bf(d[DIDX(i, k_)], d[DIDX(i, k_) + 1]), xq[i].f_)
            const uint4 o = make_uint4(FIN(0, x), FIN(1, y), FIN(2, z), FIN(3, w));
            if (i < 8) sts128(tile + to + QOFF(i), o);
            else { sts32(tile + to + SOFF(0), o.x); sts32(tile + to + SOFF(1), o.y); sts32(tile + to + SOFF(2), o.z); sts32(tile + to + SOFF(3), o.w); }
        }
        fence_async_s();
        __syncwarp();
        if (elect()) {
            asm volatile("cp.async.bulk.tensor.2d.global.shared::cta.bulk_group [%0, {%2, %3}], [%1];" :: "l"(&tm_o), "r"(tile), "r"(144 * dt), "r"(srow) : "memory");
            asm volatile("cp.async.bulk.commit_group;" ::: "memory");
            asm volatile("cp.async.bulk.wait_group.read 0;" ::: "memory");
        }
        PROF0(23);
        if (warp == 0) { __syncwarp(); PROFDUMP(); }
    }
}

typedef CUresult (*EncodeFn)(CUtensorMap*, CUtensorMapDataType, cuuint32_t, void*, const cuuint64_t*, const cuuint64_t*, const cuuint32_t*,
                             const cuuint32_t*, CUtensorMapInterleave, CUtensorMapSwizzle, CUtensorMapL2promotion, CUtensorMapFloatOOBfill);

void encode(EncodeFn fn, CUtensorMap* m, CUtensorMapDataType dt, int rank, const void* ptr, const cuuint64_t* dims, const cuuint64_t* strides,
            const cuuint32_t* box, CUtensorMapSwizzle sw, CUtensorMapL2promotion promo = CU_TENSOR_MAP_L2_PROMOTION_L2_128B) {
    const cuuint32_t es[5] = {1, 1, 1, 1, 1};
    fn(m, dt, rank, (void*)ptr, dims, strides, box, es, CU_TENSOR_MAP_INTERLEAVE_NONE, sw, promo, CU_TENSOR_MAP_FLOAT_OOB_FILL_NONE);
}

}

extern "C" void kernel_launch(void* const* d_in, const int* in_sizes, int n_in, void* d_out, int out_size) {
    (void)in_sizes; (void)n_in; (void)out_size;
    Params p;
    p.x = (const uint16_t*)d_in[0]; p.wr = (const uint16_t*)d_in[1]; p.wi = (const uint16_t*)d_in[2];
    p.w1 = (const uint16_t*)d_in[4]; p.b1 = (const uint16_t*)d_in[5]; p.w2 = (const uint16_t*)d_in[6]; p.b2 = (const uint16_t*)d_in[7];
    p.c = (const uint16_t*)d_in[8]; p.wmod = (const uint16_t*)d_in[9]; p.out = (uint16_t*)d_out;

    void* fnp = nullptr; cudaDriverEntryPointQueryResult qr;
    cudaGetDriverEntryPoint("cuTensorMapEncodeTiled", &fnp, cudaEnableDefault, &qr);
    EncodeFn fn = (EncodeFn)fnp;
    cudaGetSymbolAddress((void**)&p.scr, g_scr); cudaGetSymbolAddress((void**)&p.tab, g_tab);
    void* h3p = p.scr->h3;
    CUtensorMap tw1a, tw1b, tw2, tw2b, th3a, th3b, twr, twi, twm, tt, ttx, to;
    {
        const cuuint64_t dims[4] = {64, 16, 128, 72}, st[3] = {128ull * F_ * 2, (cuuint64_t)F_ * 2, 128};
        const cuuint32_t ba[4] = {64, 16, 4, 2}, bb[4] = {64, 16, 8, 1};
        encode(fn, &tw1a, CU_TENSOR_MAP_DATA_TYPE_BFLOAT16, 4, p.w1, dims, st, ba, CU_TENSOR_MAP_SWIZZLE_128B);
        encode(fn, &tw1b, CU_TENSOR_MAP_DATA_TYPE_BFLOAT16, 4, p.w1, dims, st, bb, CU_TENSOR_MAP_SWIZZLE_128B);
    }
    {
        const cuuint64_t dims[3] = {64, F_, 32}, st[2] = {(cuuint64_t)S_ * 2, 128};
        const cuuint32_t bx[3] = {64, 64, 2}, bb[3] = {64, 64, 1};
        encode(fn, &tw2, CU_TENSOR_MAP_DATA_TYPE_BFLOAT16, 3, p.w2, dims, st, bx, CU_TENSOR_MAP_SWIZZLE_128B);
        encode(fn, &tw2b, CU_TENSOR_MAP_DATA_TYPE_BFLOAT16, 3, p.w2, dims, st, bb, CU_TENSOR_MAP_SWIZZLE_128B);
    }
    {
        const cuuint64_t dims[3] = {64, 72, 128}, st[2] = {256, 18432};
        const cuuint32_t ba[3] = {64, 18, 4}, bb[3] = {64, 9, 8};
        encode(fn, &th3a, CU_TENSOR_MAP_DATA_TYPE_UINT32, 3, h3p, dims, st, ba, CU_TENSOR_MAP_SWIZZLE_NONE);
        encode(fn, &th3b, CU_TENSOR_MAP_DATA_TYPE_UINT32, 3, h3p, dims, st, bb, CU_TENSOR_MAP_SWIZZLE_NONE);
    }
    {
        const cuuint64_t dims[3] = {4624, 4, 32}, st[2] = {9248 * 32, 9248};
        const cuuint32_t bx[3] = {56, 4, 32};
        encode(fn, &twr, CU_TENSOR_MAP_DATA_TYPE_BFLOAT16, 3, p.wr, dims, st, bx, CU_TENSOR_MAP_SWIZZLE_NONE);
        encode(fn, &twi, CU_TENSOR_MAP_DATA_TYPE_BFLOAT16, 3, p.wi, dims, st, bx, CU_TENSOR_MAP_SWIZZLE_NONE);
    }
    {
        const cuuint64_t dims[3] = {64, 576, 54}, st[2] = {6912, 128};
        const cuuint32_t bx[3] = {64, 32, 7};
        encode(fn, &twm, CU_TENSOR_MAP_DATA_TYPE_BFLOAT16, 3, p.wmod, dims, st, bx, CU_TENSOR_MAP_SWIZZLE_128B);
    }
    {
        const cuuint64_t dims[2] = {TP, 128}, st[1] = {TP * 4};
        const cuuint32_t ba[2] = {32, 128}, bb[2] = {8, 128};
        encode(fn, &tt, CU_TENSOR_MAP_DATA_TYPE_UINT32, 2, p.scr->T, dims, st, ba, CU_TENSOR_MAP_SWIZZLE_128B, CU_TENSOR_MAP_L2_PROMOTION_NONE);
        encode(fn, &ttx, CU_TENSOR_MAP_DATA_TYPE_UINT32, 2, p.scr->T, dims, st, bb, CU_TENSOR_MAP_SWIZZLE_32B, CU_TENSOR_MAP_L2_PROMOTION_NONE);
    }
    {
        const cuuint64_t dims[2] = {D_, S_}, st[1] = {D_ * 2};
        const cuuint32_t bx[2] = {144, 16};
        encode(fn, &to, CU_TENSOR_MAP_DATA_TYPE_BFLOAT16, 2, p.out, dims, st, bx, CU_TENSOR_MAP_SWIZZLE_NONE, CU_TENSOR_MAP_L2_PROMOTION_NONE);
    }
    cudaFuncSetAttribute(fused_kernel, cudaFuncAttributeMaxDynamicSharedMemorySize, SMEM_BYTES);
    cudaLaunchConfig_t cfg = {};
    cfg.gridDim = dim3(NCTA); cfg.blockDim = dim3(NTHR); cfg.dynamicSmemBytes = SMEM_BYTES; cfg.stream = cudaStreamPerThread;
    cudaLaunchAttribute at[1];
    at[0].id = cudaLaunchAttributeCooperative; at[0].val.cooperative = 1;
    cfg.attrs = at; cfg.numAttrs = 1;
    cudaLaunchKernelEx(&cfg, fused_kernel, p, tw1a, tw1b, tw2, tw2b, th3a, th3b, twr, twi, twm, tt, ttx, to);
}
```

```cpp
#include <cuda_runtime.h>
#include <cuda_bf16.h>
#include <cuda_fp16.h>
#include <cuda.h>
#include <stdint.h>

namespace {

constexpr int S_ = 2048, D_ = 576, F_ = 4608;
constexpr int NCTA = 132, NTHR = 512;
constexpr int TP = 4736;
constexpr int SPEC_P = 296;
constexpr int NST = 6;
constexpr int A_BYTES = 16384, B_BYTES = 18432;
constexpr int IT_P2 = 32, IT_G2 = 40, IT_END = 76;
constexpr int SPIN_LIMIT = 1 << 22;
#define UIDX(dt_, kh_) 0
#define UCNT 128
#define MODPAD 16
#define X2D 1300
#define CPHINT ".L2::128B"
#define P2A 2
#define P2D 400
#define A2E 1
#define A2D 100
#define W1N 8
#define W1P 100
#define W1S 0
#define XDELAY 1600
#define X1D 2300
#define PF2 1
#define X1DELAY 2500

constexpr int OFF_A = 0;
constexpr int OFF_B = NST * A_BYTES;
constexpr int OFF_P = OFF_B + NST * B_BYTES;
constexpr int OFF_BAR = OFF_P;
constexpr int OFF_MISC = OFF_P + 376;
constexpr int OFF_GB = OFF_P + 384;
constexpr int OFF_P2R = OFF_P + 1536;
constexpr int OFF_X1 = OFF_P2R;
constexpr int OFF_PROF = OFF_X1 + 18432;
constexpr int SMEM_BYTES = OFF_PROF + 512 + 1024;
constexpr int QA = 13, QB = 7, QC = 13;
constexpr int TAB_BYTES = (QA + QB + QC) * 512;
constexpr int OFF_STAGE = OFF_B;
constexpr int OFF_STX = OFF_STAGE + 16384;
constexpr int OFF_TAB = OFF_STAGE + 20480;
constexpr int OFF_SPEC = OFF_TAB + TAB_BYTES;
constexpr int OFF_WRAW = OFF_SPEC + 19072;
constexpr int OFF_B3 = OFF_WRAW + 28672;
constexpr int OFF_MODA = OFF_B3 + 4096;
constexpr int OFF_MODC = OFF_MODA + 2560;
constexpr int OFF_RED = OFF_MODC + 3584;
constexpr int OFF_SILU = OFF_RED + 768;
static_assert(OFF_SILU + 1152 <= OFF_P && 6 * 28672 <= OFF_B3, "scratch overflow");
constexpr int OFF_STRIP = OFF_A;
static_assert(OFF_WRAW % 128 == 0 && OFF_STAGE % 128 == 0 && OFF_STX % 128 == 0, "align");
constexpr int BAR_FULL = 0, BAR_EMPTY = 6, BAR_TAB = 12, BAR_W = 13, BAR_P2GO = 14, BAR_G2GO = 15, BAR_P2R = 16,
              BAR_XT = 17, BAR_RECV = 18, BAR_ROLE = 19, BAR_NC = 20, BAR_TAB2 = 21, BAR_XB = 22, BAR_GB = 23, BAR_HOLD = 24, BAR_W1GO = 25, BAR_UOK = 26, BAR_STGO = 29, BAR_DONE = 30, BAR_X = 31;

struct Cos1152 { double c[1152]; };
constexpr double cx_cos(double x) { double t = 1, s = 1; for (int i = 1; i < 14; i++) { t *= -x * x / ((2 * i - 1) * (2 * i)); s += t; } return s; }
constexpr Cos1152 make_cos() {
    Cos1152 r{};
    for (int i = 0; i <= 288; i++) {
        double v = (i == 288) ? 0.0 : cx_cos(3.14159265358979323846 * 2.0 * i / 1152.0);
        r.c[i] = v; r.c[576 - i] = -v; r.c[576 + i] = -v; r.c[(1152 - i) % 1152] = v;
    }
    return r;
}
constexpr uint32_t cx_f2h(double v) {
    uint32_t s = v < 0 ? 0x8000u : 0u; double a = v < 0 ? -v : v;
    if (a < 1e-9) return 0;
    int e = 0;
    while (a >= 2.0) { a *= 0.5; e++; }
    while (a < 1.0 && e > -14) { a *= 2.0; e--; }
    double m = a * 1024.0; uint32_t mi = (uint32_t)m; double fr = m - mi;
    if (fr > 0.5 || (fr == 0.5 && (mi & 1))) mi++;
    return s | (uint32_t)(((e + 14) << 10) + mi);
}
struct Tab { uint32_t w[(QA + QB + QC) * 128]; };
constexpr Tab make_tab() {
    Tab t{};
    Cos1152 ct = make_cos();
    auto C = [&](int num, int den) { return ct.c[(num % den) * (1152 / den)]; };
    auto Sn = [&](int num, int den) { return ct.c[((num % den) * (1152 / den) + 864) % 1152]; };
    auto put = [&](int q0, int idx, int lane, double lo, double hi) { t.w[((q0 + idx / 4) * 32 + lane) * 4 + idx % 4] = cx_f2h(lo) | (cx_f2h(hi) << 16); };
    for (int lane = 0; lane < 32; lane++) {
        const int g = lane >> 2, q = lane & 3;
        for (int mt = 0; mt < 3; mt++) {
            const int ka = 8 * mt + g;
            for (int r = 0; r < 10; r++) {
                const int im = r & 1, i0 = (r >> 1) * 2;
                double v[2] = {0, 0};
                for (int e = 0; e < 2; e++) { int i = i0 + e, d1 = 4 * i + q; if (i < 9 && ka <= 18) v[e] = (im ? -Sn(ka * d1, 36) : C(ka * d1, 36)) / 8; }
                put(0, mt * 10 + r, lane, v[0], v[1]);
            }
            for (int v = 0; v < 2; v++) {
                const int d2 = 4 * q + v;
                put(0, 30 + (mt * 2 + v) * 2, lane, C(ka * d2, 576) * 4 / 3, C(ka * (d2 + 2), 576) * 4 / 3);
                put(0, 31 + (mt * 2 + v) * 2, lane, Sn(ka * d2, 576) * 4 / 3, Sn(ka * (d2 + 2), 576) * 4 / 3);
            }
        }
        for (int v = 0; v < 2; v++) for (int nt = 0; nt < 2; nt++) {
            const int kb = 2 * (g >> 1) + nt, part = g & 1;
            double b0[2] = {0, 0}, b1[2] = {0, 0};
            for (int e = 0; e < 2; e++) { int d2 = 4 * q + 2 * e + v; double c = C(kb * d2, 16) / 4, s = Sn(kb * d2, 16) / 4;
                b0[e] = part ? -s : c; b1[e] = part ? c : s; }
            put(0, 42 + (v * 2 + nt) * 2, lane, b0[0], b0[1]); put(0, 43 + (v * 2 + nt) * 2, lane, b1[0], b1[1]);
        }
        for (int par = 0; par < 2; par++) for (int a = 0; a < 4; a++) {
            const int ja = 2 * (q + 4 * (a >> 1)) + par; const double c = C(g * ja, 16) / 4, s = Sn(g * ja, 16) / 4;
            put(QA, par * 4 + a, lane, (a & 1) ? -s : c, (a & 1) ? c : s);
        }
        for (int h = 0; h < 2; h++) {
            put(QA, 8 + 2 * h, lane, C((g + 8 * h) * (2 * q), 128) / 2, C((g + 8 * h) * (2 * q + 1), 128) / 2);
            put(QA, 9 + 2 * h, lane, Sn((g + 8 * h) * (2 * q), 128) / 2, Sn((g + 8 * h) * (2 * q + 1), 128) / 2);
            put(QA, 15 + 2 * h, lane, C(g * (8 * h + 2 * q), 128), C(g * (8 * h + 2 * q + 1), 128));
            put(QA, 16 + 2 * h, lane, Sn(g * (8 * h + 2 * q), 128), Sn(g * (8 * h + 2 * q + 1), 128));
        }
        put(QA, 12, lane, C(g * 2 * q, 8) / 2, C(g * (2 * q + 1), 8) / 2);
        put(QA, 13, lane, Sn(g * 2 * q, 8) / 2, Sn(g * (2 * q + 1), 8) / 2);
        put(QA, 14, lane, -Sn(g * 2 * q, 8) / 2, -Sn(g * (2 * q + 1), 8) / 2);
        for (int u = 0; u < 4; u++) {
            const int ja = 2 * ((g >> 1) + 4 * (u & 1)) + (u >> 1), part = g & 1; double b0[2] = {0, 0}, b1[2] = {0, 0};
            for (int e = 0; e < 2; e++) { int ka = 2 * q + e; double c = C(ja * ka, 16) / 4, s = Sn(ja * ka, 16) / 4;
                b0[e] = part ? s : c; b1[e] = part ? c : -s; }
            put(QA, 19 + u * 2, lane, b0[0], b0[1]); put(QA, 20 + u * 2, lane, b1[0], b1[1]);
        }
        for (int m2 = 0; m2 < 2; m2++) {
            const int d2 = 2 * g + m2;
            for (int a = 0; a < 4; a++) {
                const int kb = 2 * q + (a >> 1); const double c = C(d2 * kb, 16) / 4, s = Sn(d2 * kb, 16) / 4;
                put(QA + QB, m2 * 4 + a, lane, (a & 1) ? s : c, (a & 1) ? c : -s);
            }
            for (int mt = 0; mt < 3; mt++) {
                const int ka = 8 * mt + 2 * q;
                put(QA + QB, 8 + (m2 * 3 + mt) * 2, lane, C(ka * d2, 576) * 4 / 3, C((ka + 1) * d2, 576) * 4 / 3);
                put(QA + QB, 9 + (m2 * 3 + mt) * 2, lane, Sn(ka * d2, 576) * 4 / 3, Sn((ka + 1) * d2, 576) * 4 / 3);
            }
        }
        for (int mt = 0; mt < 3; mt++) for (int nt = 0; nt < 5; nt++) {
            const int i = 2 * nt + (g & 1), d1 = 4 * i + (g >> 1); double b0[2] = {0, 0}, b1[2] = {0, 0};
            for (int e = 0; e < 2; e++) { int ka = 8 * mt + 2 * q + e;
                if (ka <= 18 && i < 9) { double wt = (ka == 0 || ka == 18) ? 0.125 : 0.25; b0[e] = wt * C(ka * d1, 36); b1[e] = -wt * Sn(ka * d1, 36); } }
            put(QA + QB, 20 + (mt * 5 + nt) * 2, lane, b0[0], b0[1]); put(QA + QB, 21 + (mt * 5 + nt) * 2, lane, b1[0], b1[1]);
        }
    }
    return t;
}
__device__ __align__(128) const Tab g_tab = make_tab();

struct Scratch {
    uint32_t cnt[30 * 32];
    uint32_t slot[96];
    uint32_t mod[2304];
    uint32_t modc[896 + 288];
    uint32_t T[128 * TP];
    uint4 h3[128 * 1152];
    uint4 U[72 * 4 * 1152];
};
__device__ __align__(1024) Scratch g_scr;
#define g_cnt (p.scr->cnt)
#define g_slot (p.scr->slot)
#define g_mod (p.scr->mod)
#define g_T (p.scr->T)
#define g_h3 (p.scr->h3)
#define g_U (p.scr->U)
constexpr int CNT_EPOCH = 0, CNT_H3 = 1, CNT_X1 = 26, CNT_NC = 27, CNT_U = 2;
#define PROFT(i) do {} while (0)
#define PROFDUMP() do {} while (0)
#define PROF0(i) do {} while (0)

__device__ __forceinline__ void mbar_init(uint32_t bar, uint32_t cnt) { asm volatile("mbarrier.init.shared::cta.b64 [%0], %1;" :: "r"(bar), "r"(cnt) : "memory"); }
__device__ __forceinline__ void mbar_expect(uint32_t bar, uint32_t bytes) { asm volatile("mbarrier.arrive.expect_tx.shared::cta.b64 _, [%0], %1;" :: "r"(bar), "r"(bytes) : "memory"); }
__device__ __forceinline__ void mbar_arrive(uint32_t bar) { asm volatile("mbarrier.arrive.shared::cta.b64 _, [%0];" :: "r"(bar) : "memory"); }
__device__ __forceinline__ void mbar_arrive_n(uint32_t bar, uint32_t n) { asm volatile("mbarrier.arrive.shared::cta.b64 _, [%0], %1;" :: "r"(bar), "r"(n) : "memory"); }
__device__ __forceinline__ void mbar_arrive_remote(uint32_t rbar) { asm volatile("mbarrier.arrive.relaxed.cluster.shared::cluster.b64 _, [%0];" :: "r"(rbar) : "memory"); }
__device__ __forceinline__ void mbar_wait(uint32_t bar, uint32_t parity) {
    asm volatile("{.reg .pred p; .reg .u32 c;\n"
        "mbarrier.try_wait.parity.shared::cta.b64 p, [%0], %1;\n@p bra.uni DONE;\nmov.u32 c, 0;\n"
        "LOOP: mbarrier.try_wait.parity.shared::cta.b64 p, [%0], %1;\n@p bra.uni DONE;\n"
        "add.u32 c, c, 1;\nsetp.lt.u32 p, c, %2;\n@p bra.uni LOOP;\ntrap;\nDONE:}" :: "r"(bar), "r"(parity), "n"(SPIN_LIMIT) : "memory");
}
__device__ __forceinline__ bool mbar_test(uint32_t bar, uint32_t parity) {
    uint32_t ok; asm volatile("{.reg .pred p; mbarrier.test_wait.parity.shared::cta.b64 p, [%1], %2; selp.u32 %0, 1, 0, p;}" : "=r"(ok) : "r"(bar), "r"(parity) : "memory"); return ok; }
__device__ __forceinline__ uint32_t mapa(uint32_t a, uint32_t rank) { uint32_t r; asm("mapa.shared::cluster.u32 %0, %1, %2;" : "=r"(r) : "r"(a), "r"(rank)); return r; }
__device__ __forceinline__ uint32_t clk32() { uint32_t r; asm volatile("mov.u32 %0, %%clock;" : "=r"(r)); return r; }
__device__ __forceinline__ void hb() {
    asm volatile("{.reg .b32 a, b; .reg .pred p; mma.sync.aligned.m16n8k8.row.col.f16.f16.f16.f16 {a, b}, {%0,%0}, {%0}, {%0,%0};\n"
                 "setp.ne.u32 p, a, 0; @p trap;}" :: "r"(0));
}
__device__ __forceinline__ void spin_until(uint32_t t) { while (__any_sync(~0u, (int)(clk32() - t) < 0)) hb(); }
__device__ __forceinline__ bool elect() { uint32_t r; asm volatile("{.reg .pred p; elect.sync _|p, 0xffffffff; selp.u32 %0, 1, 0, p;}" : "=r"(r)); return r; }
__device__ __forceinline__ void bar_sync(int id, int n) { asm volatile("bar.sync %0, %1;" :: "r"(id), "r"(n) : "memory"); }
__device__ __forceinline__ void bulk_load(uint32_t dst, const void* src, uint32_t bytes, uint32_t bar) {
    asm volatile("cp.async.bulk.shared::cluster.global.mbarrier::complete_tx::bytes [%0], [%1], %2, [%3];" :: "r"(dst), "l"(src), "r"(bytes), "r"(bar) : "memory"); }
__device__ __forceinline__ void tma2(uint32_t dst, const CUtensorMap* m, int c0, int c1, uint32_t bar) {
    asm volatile("cp.async.bulk.tensor.2d.shared::cluster.global.mbarrier::complete_tx::bytes [%0], [%1, {%3, %4}], [%2];" :: "r"(dst), "l"(m), "r"(bar), "r"(c0), "r"(c1) : "memory"); }
__device__ __forceinline__ void tma3(uint32_t dst, const CUtensorMap* m, int c0, int c1, int c2, uint32_t bar) {
    asm volatile("cp.async.bulk.tensor.3d.shared::cluster.global.mbarrier::complete_tx::bytes [%0], [%1, {%3, %4, %5}], [%2];" :: "r"(dst), "l"(m), "r"(bar), "r"(c0), "r"(c1), "r"(c2) : "memory"); }
__device__ __forceinline__ void tma4(uint32_t dst, const CUtensorMap* m, int c0, int c1, int c2, int c3, uint32_t bar) {
    asm volatile("cp.async.bulk.tensor.4d.shared::cluster.global.mbarrier::complete_tx::bytes [%0], [%1, {%3, %4, %5, %6}], [%2];" :: "r"(dst), "l"(m), "r"(bar), "r"(c0), "r"(c1), "r"(c2), "r"(c3) : "memory"); }
__device__ __forceinline__ void fence_async_g() { asm volatile("fence.proxy.async.global;" ::: "memory"); }
__device__ __forceinline__ void fence_async_s() { asm volatile("fence.proxy.async.shared::cta;" ::: "memory"); }
__device__ __forceinline__ uint4 lds128(uint32_t a) { uint4 v; asm volatile("ld.shared.v4.u32 {%0,%1,%2,%3}, [%4];" : "=r"(v.x), "=r"(v.y), "=r"(v.z), "=r"(v.w) : "r"(a) : "memory"); return v; }
__device__ __forceinline__ uint32_t lds32(uint32_t a) { uint32_t v; asm volatile("ld.shared.u32 %0, [%1];" : "=r"(v) : "r"(a) : "memory"); return v; }
__device__ __forceinline__ void sts128(uint32_t a, uint4 v) { asm volatile("st.shared.v4.u32 [%0], {%1,%2,%3,%4};" :: "r"(a), "r"(v.x), "r"(v.y), "r"(v.z), "r"(v.w) : "memory"); }
__device__ __forceinline__ void sts32(uint32_t a, uint32_t v) { asm volatile("st.shared.u32 [%0], %1;" :: "r"(a), "r"(v) : "memory"); }
__device__ __forceinline__ void sts16(uint32_t a, uint32_t v) { asm volatile("st.shared.u16 [%0], %1;" :: "r"(a), "h"((uint16_t)v) : "memory"); }
__device__ __forceinline__ uint4 ldx128(const void* p) {
    uint4 v; asm volatile("{.reg .b128 t; .reg .b64 a, b; ld.relaxed.gpu.global.b128 t, [%4]; mov.b128 {a, b}, t; mov.b64 {%0,%1}, a; mov.b64 {%2,%3}, b;}"
        : "=r"(v.x), "=r"(v.y), "=r"(v.z), "=r"(v.w) : "l"(p) : "memory"); return v; }
__device__ __forceinline__ void stx128(void* p, uint4 v) {
    asm volatile("{.reg .b128 t; .reg .b64 a, b; mov.b64 a, {%1,%2}; mov.b64 b, {%3,%4}; mov.b128 t, {a, b}; st.relaxed.gpu.global.b128 [%0], t;}"
        :: "l"(p), "r"(v.x), "r"(v.y), "r"(v.z), "r"(v.w) : "memory"); }
__device__ __forceinline__ uint32_t ld_relaxed(const uint32_t* p) { uint32_t v; asm volatile("ld.relaxed.gpu.global.u32 %0, [%1];" : "=r"(v) : "l"(p) : "memory"); return v; }
__device__ __forceinline__ uint32_t ld_acquire(const uint32_t* p) { uint32_t v; asm volatile("ld.acquire.gpu.global.u32 %0, [%1];" : "=r"(v) : "l"(p) : "memory"); return v; }
__device__ __forceinline__ void st_relaxed(uint32_t* p, uint32_t v) { asm volatile("st.relaxed.gpu.global.u32 [%0], %1;" :: "l"(p), "r"(v) : "memory"); }
__device__ __forceinline__ void red_release(uint32_t* p) { asm volatile("red.release.gpu.global.add.u32 [%0], 1;" :: "l"(p) : "memory"); }
__device__ __forceinline__ void wait_count(const uint32_t* p, uint32_t target) {
    int it = 0; while ((int)(ld_acquire(p) - target) < 0) { if (++it > SPIN_LIMIT) __trap(); }
}
__device__ __forceinline__ uint32_t ldg_nc32(const void* p) { uint32_t v; asm volatile("ld.global.nc.L1::no_allocate.u32 %0, [%1];" : "=r"(v) : "l"(p)); return v; }
__device__ __forceinline__ uint32_t ldg_nc16(const void* p) { uint16_t v; asm volatile("ld.global.nc.u16 %0, [%1];" : "=h"(v) : "l"(p)); return v; }
__device__ __forceinline__ float bf_lo(uint32_t w) { return __uint_as_float(w << 16); }
__device__ __forceinline__ float bf_hi(uint32_t w) { return __uint_as_float(w & 0xFFFF0000u); }
__device__ __forceinline__ uint32_t pack_bf(float lo, float hi) { uint32_t r; asm("cvt.rn.bf16x2.f32 %0, %1, %2;" : "=r"(r) : "f"(hi), "f"(lo)); return r; }
__device__ __forceinline__ uint32_t pack_h(float lo, float hi) { uint32_t r; asm("cvt.rn.f16x2.f32 %0, %1, %2;" : "=r"(r) : "f"(hi), "f"(lo)); return r; }
__device__ __forceinline__ float bf_round(float v) { return bf_lo(pack_bf(v, 0.f)); }
__device__ __forceinline__ uint32_t hmul2(uint32_t a, uint32_t b) { uint32_t r; asm("mul.rn.f16x2 %0, %1, %2;" : "=r"(r) : "r"(a), "r"(b)); return r; }
__device__ __forceinline__ uint32_t hfma2(uint32_t a, uint32_t b, uint32_t c) { uint32_t r; asm("fma.rn.f16x2 %0, %1, %2, %3;" : "=r"(r) : "r"(a), "r"(b), "r"(c)); return r; }
__device__ __forceinline__ uint32_t hfms2(uint32_t a, uint32_t b, uint32_t c) { uint32_t r; asm("{.reg .b32 t; neg.f16x2 t, %3; fma.rn.f16x2 %0, %1, %2, t;}" : "=r"(r) : "r"(a), "r"(b), "r"(c)); return r; }
__device__ __forceinline__ uint32_t hadd2(uint32_t a, uint32_t b) { uint32_t r; asm("add.rn.f16x2 %0, %1, %2;" : "=r"(r) : "r"(a), "r"(b)); return r; }
__device__ __forceinline__ uint32_t hsub2(uint32_t a, uint32_t b) { uint32_t r; asm("sub.rn.f16x2 %0, %1, %2;" : "=r"(r) : "r"(a), "r"(b)); return r; }
__device__ __forceinline__ void cmul_neg(uint32_t& re, uint32_t& im, uint32_t c, uint32_t s) { uint32_t a = hfma2(re, c, hmul2(im, s)), b = hfms2(im, c, hmul2(re, s)); re = a; im = b; }
__device__ __forceinline__ void cmul_pos(uint32_t& re, uint32_t& im, uint32_t c, uint32_t s) { uint32_t a = hfms2(re, c, hmul2(im, s)), b = hfma2(im, c, hmul2(re, s)); re = a; im = b; }
__device__ __forceinline__ void mma_h(uint32_t& d0, uint32_t& d1, uint32_t a0, uint32_t a1, uint32_t a2, uint32_t a3, uint32_t b0, uint32_t b1) {
    asm("mma.sync.aligned.m16n8k16.row.col.f16.f16.f16.f16 {%0,%1}, {%2,%3,%4,%5}, {%6,%7}, {%0,%1};" : "+r"(d0), "+r"(d1) : "r"(a0), "r"(a1), "r"(a2), "r"(a3), "r"(b0), "r"(b1)); }
__device__ __forceinline__ void mma_h8(uint32_t& d0, uint32_t& d1, uint32_t a0, uint32_t a1, uint32_t b0) {
    asm("mma.sync.aligned.m16n8k8.row.col.f16.f16.f16.f16 {%0,%1}, {%2,%3}, {%4}, {%0,%1};" : "+r"(d0), "+r"(d1) : "r"(a0), "r"(a1), "r"(b0)); }
__device__ __forceinline__ void mma_f(float (&d)[4], uint32_t a0, uint32_t a1, uint32_t a2, uint32_t a3, uint32_t b0, uint32_t b1) {
    asm("mma.sync.aligned.m16n8k16.row.col.f32.f16.f16.f32 {%0,%1,%2,%3}, {%4,%5,%6,%7}, {%8,%9}, {%0,%1,%2,%3};"
        : "+f"(d[0]), "+f"(d[1]), "+f"(d[2]), "+f"(d[3]) : "r"(a0), "r"(a1), "r"(a2), "r"(a3), "r"(b0), "r"(b1)); }
template <int NQ> __device__ __forceinline__ void load_tab(uint32_t (&r)[NQ * 4], uint32_t addr) {
    #pragma unroll
    for (int i = 0; i < NQ; i++) { uint4 v = lds128(addr + i * 512); r[4 * i] = v.x; r[4 * i + 1] = v.y; r[4 * i + 2] = v.z; r[4 * i + 3] = v.w; }
}
__device__ __forceinline__ void warp_sum2(float& a, float& b) {
    #pragma unroll
    for (int o = 16; o; o >>= 1) { a += __shfl_xor_sync(~0u, a, o); b += __shfl_xor_sync(~0u, b, o); }
}
__device__ __forceinline__ float gelu2(float x) {
    float t = x * fmaf(x * x, 0.044715f * 0.7978845608028654f, 0.7978845608028654f), th;
    asm volatile("tanh.approx.f32 %0, %1;" : "=f"(th) : "f"(t));
    return fmaf(x, th, x);
}
__device__ __forceinline__ uint32_t desc_lo(uint32_t addr, uint32_t lbo) { return ((addr & 0x3FFFF) >> 4) | ((lbo >> 4) << 16); }
constexpr uint32_t DHI_A = (1024 >> 4) | (1u << 30), DHI_H3 = 256 >> 4, DHI_U = 128 >> 4;
#define WG_FENCE() asm volatile("wgmma.fence.sync.aligned;" ::: "memory")
#define WG_COMMIT() asm volatile("wgmma.commit_group.sync.aligned;" ::: "memory")
#define WG_WAIT(n) asm volatile("wgmma.wait_group.sync.aligned %0;" :: "n"(n) : "memory")
#define R4(b) "+f"(d[b]), "+f"(d[b + 1]), "+f"(d[b + 2]), "+f"(d[b + 3])
#define R12(b) R4(b), R4(b + 4), R4(b + 8)
#define R36(b) R12(b), R12(b + 12), R12(b + 24)
template <uint32_t BHI> __device__ __forceinline__ void wgmma144(float (&d)[72], uint32_t da, uint32_t db, int acc) {
    asm volatile("{.reg .pred p; .reg .b64 a, b; setp.ne.b32 p, %74, 0; mov.b64 a, {%72, %75}; mov.b64 b, {%73, %76};\n"
        "wgmma.mma_async.sync.aligned.m64n144k16.f32.bf16.bf16 {%0,%1,%2,%3,%4,%5,%6,%7,%8,%9,%10,%11,%12,%13,%14,%15,%16,%17,%18,%19,%20,%21,%22,%23,"
        "%24,%25,%26,%27,%28,%29,%30,%31,%32,%33,%34,%35,%36,%37,%38,%39,%40,%41,%42,%43,%44,%45,%46,%47,"
        "%48,%49,%50,%51,%52,%53,%54,%55,%56,%57,%58,%59,%60,%61,%62,%63,%64,%65,%66,%67,%68,%69,%70,%71}, a, b, p, 1, 1, 1, 1;}\n"
        : R36(0), R36(36) : "r"(da), "r"(db), "r"(acc), "n"(DHI_A), "n"(BHI));
}
__device__ __forceinline__ void wgmma72(float (&d)[36], uint32_t da, uint32_t db, int acc) {
    asm volatile("{.reg .pred p; .reg .b64 a, b; setp.ne.b32 p, %38, 0; mov.b64 a, {%36, %39}; mov.b64 b, {%37, %40};\n"
        "wgmma.mma_async.sync.aligned.m64n72k16.f32.bf16.bf16 {%0,%1,%2,%3,%4,%5,%6,%7,%8,%9,%10,%11,%12,%13,%14,%15,%16,%17,%18,%19,%20,%21,%22,%23,"
        "%24,%25,%26,%27,%28,%29,%30,%31,%32,%33,%34,%35}, a, b, p, 1, 1, 1, 1;}\n"
        : R36(0) : "r"(da), "r"(db), "r"(acc), "n"(DHI_A), "n"(DHI_H3));
}

__device__ __forceinline__ int g2_kb(int n, int kh) { return 36 * kh + (n < 32 ? 9 * ((n >> 2) & 3) + 2 * (n & 3) + (n >> 4) : 9 * (n - 32) + 8); }

template <uint32_t BHI, int I0, int I1, bool ZERO, bool FIRST, bool LAST, class Hook>
__device__ __forceinline__ void mainloop(float (&d)[72], uint32_t bars, uint32_t da0, uint32_t db0, bool lead, Hook hook) {
    uint32_t s = I0 % NST, ph = (I0 / NST) & 1, prev = (I0 + NST - 1) % NST;
    #pragma unroll 1
    for (int i = I0; i < I1; i++) {
        mbar_wait(bars + 8 * BAR_FULL + 8 * s, ph);
        const uint32_t da = da0 + s * (A_BYTES / 16), db = db0 + s * (B_BYTES / 16);
        WG_FENCE();
        wgmma144<BHI>(d, da, db, ZERO ? i - I0 : 1);
        wgmma144<BHI>(d, da + 128, db + 288, 1); wgmma144<BHI>(d, da + 256, db + 576, 1); wgmma144<BHI>(d, da + 384, db + 864, 1);
        WG_COMMIT();
        WG_WAIT(1);
        if (lead && (!FIRST || i > I0)) mbar_arrive(bars + 8 * BAR_EMPTY + 8 * prev);
        hook(i);
        prev = s; if (++s == NST) { s = 0; ph ^= 1; }
    }
    if (LAST) { WG_WAIT(0); if (lead) mbar_arrive(bars + 8 * BAR_EMPTY + 8 * prev); }
}

struct Params {
    const uint16_t *x, *wr, *wi, *w1, *b1, *w2, *b2, *c, *wmod;
    uint16_t* out;
    Scratch* scr;
    const Tab* tab;
};

__device__ __forceinline__ void mma_bf(float (&d)[4], const uint32_t (&a)[4], uint32_t b0, uint32_t b1) {
    asm("mma.sync.aligned.m16n8k16.row.col.f32.bf16.bf16.f32 {%0,%1,%2,%3}, {%4,%5,%6,%7}, {%8,%9}, {%0,%1,%2,%3};"
        : "+f"(d[0]), "+f"(d[1]), "+f"(d[2]), "+f"(d[3]) : "r"(a[0]), "r"(a[1]), "r"(a[2]), "r"(a[3]), "r"(b0), "r"(b1)); }
__device__ __forceinline__ void ldsm4t(uint32_t (&a)[4], uint32_t addr) {
    asm volatile("ldmatrix.sync.aligned.m8n8.x4.trans.shared.b16 {%0,%1,%2,%3}, [%4];" : "=r"(a[0]), "=r"(a[1]), "=r"(a[2]), "=r"(a[3]) : "r"(addr) : "memory"); }
__device__ __forceinline__ float silu(float v) { return __fdividef(v, 1.f + __expf(-v)); }
__device__ __forceinline__ uint32_t bfma2(uint32_t a, uint32_t b, uint32_t c) { uint32_t r; asm("fma.rn.bf16x2 %0, %1, %2, %3;" : "=r"(r) : "r"(a), "r"(b), "r"(c)); return r; }
__device__ __forceinline__ void radix16(const uint4 (&V)[4], const uint32_t (&B)[16], uint4 (&o)[4]) {
    #pragma unroll
    for (int nt = 0; nt < 4; nt++) {
        o[nt] = make_uint4(0, 0, 0, 0);
        #pragma unroll
        for (int ks = 0; ks < 2; ks++) {
            const uint32_t b0 = B[(ks * 4 + nt) * 2], b1 = B[(ks * 4 + nt) * 2 + 1];
            mma_h(o[nt].x, o[nt].y, V[2 * ks].x, V[2 * ks].y, V[2 * ks + 1].x, V[2 * ks + 1].y, b0, b1);
            mma_h(o[nt].z, o[nt].w, V[2 * ks].z, V[2 * ks].w, V[2 * ks + 1].z, V[2 * ks + 1].w, b0, b1);
        }
    }
}
template <int OFF, int N> __device__ __forceinline__ void gelu_store(const float (&d)[N], char* p, int q) {
    uint32_t w[9];
    #pragma unroll
    for (int blk = 0; blk < 9; blk++) w[blk] = pack_bf(gelu2(d[OFF + 4 * blk]), gelu2(d[OFF + 4 * blk + 1]));
    asm volatile("st.v4.u32 [%0], {%1,%2,%3,%4};" :: "l"(p + q * 128), "r"(w[0]), "r"(w[1]), "r"(w[2]), "r"(w[3]) : "memory");
    asm volatile("st.v4.u32 [%0+512], {%1,%2,%3,%4};" :: "l"(p + q * 128), "r"(w[4]), "r"(w[5]), "r"(w[6]), "r"(w[7]) : "memory");
    asm volatile("st.u32 [%0+1024], %1;" :: "l"(p + q * 4), "r"(w[8]) : "memory");
}

__global__ void __cluster_dims__(2, 1, 1) __launch_bounds__(NTHR, 1)
fused_kernel(const Params p,
             const __grid_constant__ CUtensorMap tm_w1a, const __grid_constant__ CUtensorMap tm_w1b, const __grid_constant__ CUtensorMap tm_w2,
             const __grid_constant__ CUtensorMap tm_h3a, const __grid_constant__ CUtensorMap tm_h3b,
             const __grid_constant__ CUtensorMap tm_wr, const __grid_constant__ CUtensorMap tm_wi, const __grid_constant__ CUtensorMap tm_wm,
             const __grid_constant__ CUtensorMap tm_t, const __grid_constant__ CUtensorMap tm_tx, const __grid_constant__ CUtensorMap tm_o)
{
    extern __shared__ char smem_raw[];
    const uint32_t t0 = clk32();
    const uint32_t sm = __shfl_sync(~0u, ((uint32_t)__cvta_generic_to_shared(smem_raw) + 1023u) & ~1023u, 0);
    const int tid = threadIdx.x, warp = __shfl_sync(~0u, tid >> 5, 0), lane = tid & 31, g = lane >> 2, q = lane & 3;
    const int b = blockIdx.x;
    const uint32_t rank = b & 1;
    const uint32_t bars = sm + OFF_BAR;
    const bool rowcta = b < 128;

    auto nc_issue = [&](int st, uint32_t sl) {
        const int pass = st >= 18;
        mbar_expect(bars + 8 * (BAR_X + sl), 28672);
        tma3(sm + sl * 28672, &tm_wm, 0, 32 * (st - 18 * pass), 18 + 28 * pass + 7 * (b - 128), bars + 8 * (BAR_X + sl));
    };
    if (warp == 13) hb();
    uint32_t cw = 0, epoch;
    if (warp < 12) {
        if (lane < 24) cw = ldg_nc32(p.c + 48 * warp + 2 * lane);
        epoch = ld_relaxed(g_cnt + CNT_EPOCH * 32);
        if (b < 72) {
            const uint16_t* src = p.wmod + (48 * warp + (lane >> 1)) * 3456 + 16 * b + (lane & 1) * 8;
            const uint32_t dst = sm + OFF_STRIP + (48 * warp + (lane >> 1)) * 48 + (lane & 1) * 16;
            #pragma unroll
            for (int u = 0; u < 3; u++) asm volatile("cp.async.cg.shared.global" CPHINT " [%0], [%1], 16;" :: "r"(dst + u * 768), "l"(src + u * 16 * 3456) : "memory");
            asm volatile("cp.async.commit_group;" ::: "memory");
        }
    } else {
      if (elect()) {
        if (warp == 15) {
            mbar_init(bars + 8 * BAR_TAB, 1); fence_async_s();
            if (rowcta) { mbar_expect(bars + 8 * BAR_TAB, QA * 512); bulk_load(sm + OFF_TAB, p.tab, QA * 512, bars + 8 * BAR_TAB); }
            asm volatile("prefetch.tensormap [%0];" :: "l"(&tm_wr) : "memory"); asm volatile("prefetch.tensormap [%0];" :: "l"(&tm_wi) : "memory");
            asm volatile("prefetch.tensormap [%0];" :: "l"(&tm_t) : "memory"); asm volatile("prefetch.tensormap [%0];" :: "l"(&tm_tx) : "memory");
        } else if (warp == 14) {
            for (int i = BAR_W; i < BAR_X; i++) mbar_init(bars + 8 * i, i == BAR_DONE ? 4 : 1);
            mbar_expect(bars + 8 * BAR_W, 28672); mbar_expect(bars + 8 * BAR_TAB2, (QB + QC) * 512);
            mbar_expect(bars + 8 * BAR_ROLE, 4); mbar_expect(bars + 8 * BAR_P2R, 9216); mbar_expect(bars + 8 * BAR_RECV, 18432); mbar_expect(bars + 8 * BAR_XT, 18432);
        } else if (warp == 13) {
            for (int i = 0; i < 2 * NST; i++) mbar_init(bars + 8 * i, 2);
            for (int i = 0; i < NST; i++) mbar_expect(bars + 8 * (BAR_FULL + i), A_BYTES);
        }
        else {
            for (int i = 0; i < 16; i++) mbar_init(bars + 8 * (BAR_X + i), rowcta || i < 6 ? 1 : 14);
            if (!rowcta) { fence_async_s(); for (int st = 0; st < 6; st++) nc_issue(st, st); }
        }
        asm volatile("fence.mbarrier_init.release.cluster;" ::: "memory");
      }
      __syncwarp();
      epoch = ld_relaxed(g_cnt + CNT_EPOCH * 32);
    }
    __syncthreads();
    PROF0(22);
    asm volatile("barrier.cluster.arrive.relaxed.aligned;" ::: "memory");
    if (warp < 4) sts16(sm + OFF_MODA + ((warp + 1) * 32 + lane) * 16 + warp * 4 + 2, 0);
    if (warp >= 8) {
        const int k1 = tid & 15, s1 = (tid >> 4) & 15;
        float s, c;
        __sincosf((float)(((k1 * (128 * s1 + b) + 1024) & 2047) - 1024) * (3.14159265358979f / 1024.f), &s, &c); s *= 0.25f; c *= 0.25f;
        const int rf = ((s1 >> 3) * 4 + (k1 >> 2)) * 2 + ((s1 >> 2) & 1), ri = ((k1 >> 3) * 4 + (s1 >> 2)) * 2 + ((k1 >> 2) & 1);
        const uint32_t af = sm + OFF_B3 + ((rf >> 2) * 32 + (k1 & 3) * 8 + (s1 & 3)) * 16 + (rf & 3) * 4;
        const uint32_t ai = sm + OFF_B3 + 2048 + ((ri >> 2) * 32 + (s1 & 3) * 8 + (k1 & 3)) * 16 + (ri & 3) * 4;
        sts32(af, pack_h(c, s)); sts32(af + 64, pack_h(-s, c)); sts32(ai, pack_h(c, -s)); sts32(ai + 64, pack_h(s, c));
    }
    if (rowcta) spin_until(t0 + XDELAY);
    if (rowcta && elect()) {
        mbar_expect(bars + 8 * (BAR_X + warp), 1152);
        bulk_load(sm + OFF_STAGE + warp * 1152, p.x + (size_t)(b + 128 * warp) * D_, 1152, bars + 8 * (BAR_X + warp));
    }
    const uint32_t tag = (epoch + 1) & 0xFFFFu;
    if (warp < 12 && lane < 24) sts32(sm + OFF_SILU + (24 * warp + lane) * 4, pack_bf(silu(bf_lo(cw)), silu(bf_hi(cw))));
    hb();
    PROF0(26);
    uint32_t ta[QA * 4];
    const bool ta_early = rowcta && __any_sync(~0u, mbar_test(bars + 8 * BAR_TAB, 0));
    if (ta_early) load_tab<QA>(ta, sm + OFF_TAB + lane * 16);
    if (warp < 12 && b < 72) {
        uint32_t sb[6];
        __syncwarp();
        #pragma unroll
        for (int u = 0; u < 6; u++) sb[u] = lds32(sm + OFF_SILU + (24 * warp + 4 * u + q) * 4);
        asm volatile("cp.async.wait_all;" ::: "memory");
        __syncwarp();
        float acc[4] = {0, 0, 0, 0};
        #pragma unroll
        for (int u = 0; u < 3; u++) {
            uint32_t a[4];
            ldsm4t(a, sm + OFF_STRIP + (48 * warp + 16 * u + (lane & 7) + 8 * (lane >> 4)) * 48 + ((lane >> 3) & 1) * 16);
            mma_bf(acc, a, sb[2 * u], sb[2 * u + 1]);
        }
        if (q == 0) { sts32(sm + OFF_RED + (g * 12 + warp) * 4, __float_as_uint(acc[0])); sts32(sm + OFF_RED + ((g + 8) * 12 + warp) * 4, __float_as_uint(acc[2])); }
        PROF0(0);
        bar_sync(3, 384);
        if (warp == 0) {
            if (lane < 16) {
                float sum = 0;
                #pragma unroll
                for (int u = 0; u < 3; u++) { const uint4 v = lds128(sm + OFF_RED + lane * 48 + u * 16);
                    sum += (__uint_as_float(v.x) + __uint_as_float(v.y)) + (__uint_as_float(v.z) + __uint_as_float(v.w)); }
                sum = bf_round(sum); if (b >= 36) sum = bf_round(1.f + sum);
                st_relaxed(g_mod + b * MODPAD + (lane & 1) * 8 + (lane >> 1), (pack_h(0.f, sum) & 0xFFFF0000u) | tag);
            }
            __syncwarp();
            PROF0(1);
        }
    }

    const int trow = 4 * (b & 7) + ((b >> 4) & 3) + 64 * ((b >> 3) & 1) + 32 * (b >> 6);
    uint32_t* const tptr = g_T + (size_t)trow * TP + (warp < 9 ? q * 288 + 32 * warp : 4608 + 8 * q) + 4 * g;
    const int tstr = warp < 9 ? 1152 : 32;
    const uint32_t scol = sm + OFF_SPEC + (q * SPEC_P + (warp < 8 ? 72 * (warp >> 1) + 40 * (warp & 1) + 4 * g : warp == 8 ? 72 * (g >> 1) + 32 + 4 * (g & 1) : 288 + 4 * g)) * 4;
    const int wc0 = (b >> 3) * 289 + 72 * ((b & 7) >> 1) + 40 * (b & 1);

    uint32_t xw[9], t_st = t0;
    if (!rowcta) {
        const int nst = b < 130 ? 36 : 18;
        __syncthreads();
        if (warp == 14) {
            uint32_t sl = 0, ph = 0;
            #pragma unroll 1
            for (int st = 6; st < nst; st++) {
                mbar_wait(bars + 8 * (BAR_X + 6 + sl), ph);
                if (elect()) nc_issue(st, sl);
                if (++sl == 6) { sl = 0; ph ^= 1; }
            }
        } else if (warp < 14) {
            uint32_t sl = 0, ph = 0;
            const uint32_t ad0 = sm + (warp >> 1) * 4096 + ((lane & 7) + 8 * (lane >> 4)) * 128, ch = (warp & 1) * 4 + ((lane >> 3) & 1);
            #pragma unroll 1
            for (int pass = 0; pass * 18 < nst; pass++) {
                float acc[2][4] = {};
                #pragma unroll 1
                for (int st = 0; st < 18; st++) {
                    const uint32_t sa = sm + OFF_SILU + (16 * st + q) * 4;
                    const uint32_t b0 = lds32(sa), b1 = lds32(sa + 16), b2 = lds32(sa + 32), b3 = lds32(sa + 48);
                    mbar_wait(bars + 8 * (BAR_X + sl), ph);
                    #pragma unroll
                    for (int m = 0; m < 2; m++) {
                        uint32_t a[4], a2[4];
                        const uint32_t ad = ad0 + sl * 28672 + ((ch + 2 * m) ^ (lane & 7)) * 16;
                        ldsm4t(a, ad); ldsm4t(a2, ad + 2048);
                        mma_bf(acc[m], a, b0, b1); mma_bf(acc[m], a2, b2, b3);
                    }
                    if (elect()) mbar_arrive(bars + 8 * (BAR_X + 6 + sl));
                    if (++sl == 6) { sl = 0; ph ^= 1; }
                }
                const int cb = 28 * pass + 7 * (b - 128) + (warp >> 1), gg = (g >> 1) + 4 * q;
                #pragma unroll
                for (int m = 0; m < 2; m++) {
                    const int qq = (warp & 1) * 2 + m;
                    float v = bf_round(q ? acc[m][2] : acc[m][0]); if (cb >= 27) v *= 0.5f; else if (cb >= 18) v += 1.f;
                    const uint32_t w = pack_bf(v, __shfl_xor_sync(~0u, v, 4));
                    if (q < 2 && !(g & 1) && cb < 36) p.scr->modc[cb < 27 ? ((cb >> 2) * 32 + 4 * gg + qq) * 4 + (cb & 3) : 896 + 32 * (cb - 27) + 8 * qq + gg] = w;
                }
                bar_sync(1, 448);
                if (tid == 0) { fence_async_g(); red_release(g_cnt + (CNT_NC + pass) * 32); if (pass == 0) PROFT(25); }
                __syncwarp();
            }
            fence_async_s();
        }
        __syncthreads();
    } else {
        if (!ta_early) { mbar_wait(bars + 8 * BAR_TAB, 0); load_tab<QA>(ta, sm + OFF_TAB + lane * 16); }
        uint32_t nb[2][5];
        uint4 mv = make_uint4(tag, tag, tag, tag);
        const int mc = tid - 224, mst = (mc >> 2) % 36, midx = (mc < 144 ? 10 : 0) + 5 * ((mc >> 1) & 1) + (mst >> 3);
        const uint32_t* mp = g_mod + (mc >> 2) * MODPAD + (mc & 3) * 4;
        const uint32_t ma = sm + OFF_MODA + ((midx >> 2) * 32 + (mc & 1) * 16 + (mst & 3)) * 16 + (midx & 3) * 4 + ((mst >> 2) & 1) * 2;
        #define MOD_MISSING ((((mv.x ^ tag) | (mv.y ^ tag) | (mv.z ^ tag) | (mv.w ^ tag)) & 0xFFFFu) != 0)
        hb();
        mbar_wait(bars + 8 * (BAR_X + warp), 0);
        if (warp >= 7) mv = ldx128(mp);
        PROF0(28);
        #pragma unroll
        for (int i = 0; i < 9; i++) xw[i] = lds32(sm + OFF_STAGE + warp * 1152 + (32 * i + 8 * q + g) * 4);
        {
            float s1 = 0, s2 = 0;
            #pragma unroll
            for (int i = 0; i < 9; i++) { float lo = bf_lo(xw[i]), hi = bf_hi(xw[i]); s1 += lo + hi; s2 = fmaf(lo, lo, fmaf(hi, hi, s2)); }
            warp_sum2(s1, s2);
            const float m = s1 * (1.f / D_), r = rsqrtf(fmaxf(s2 * (1.f / D_) - m * m, 0.f) + 1e-5f), mr = -m * r;
            #pragma unroll
            for (int pp = 0; pp < 5; pp++) {
                nb[0][pp] = pack_h(fmaf(bf_lo(xw[2 * pp]), r, mr), pp < 4 ? fmaf(bf_lo(xw[pp < 4 ? 2 * pp + 1 : 0]), r, mr) : 0.f);
                nb[1][pp] = pack_h(fmaf(bf_hi(xw[2 * pp]), r, mr), pp < 4 ? fmaf(bf_hi(xw[pp < 4 ? 2 * pp + 1 : 0]), r, mr) : 0.f);
            }
        }
        PROF0(2);
        if (warp >= 7) {
            for (int it = 0; __any_sync(~0u, MOD_MISSING); it++) { mv = ldx128(mp); hb(); if (it > SPIN_LIMIT) __trap(); }
            sts16(ma, mv.x >> 16); sts16(ma + 64, mv.y >> 16); sts16(ma + 128, mv.z >> 16); sts16(ma + 192, mv.w >> 16);
        }
        __syncthreads();
        PROF0(3);
        if (warp >= 13 && elect()) {
            if (warp == 15) bulk_load(sm + OFF_TAB + QA * 512, p.tab->w + QA * 128, (QB + QC) * 512, bars + 8 * BAR_TAB2);
            else tma3(sm + OFF_WRAW + (warp - 13) * 14336, warp == 13 ? &tm_wr : &tm_wi, wc0 & ~7, 0, 0, bars + 8 * BAR_W);
        }
        __syncwarp();
        {
            uint32_t md[20];
            load_tab<5>(md, sm + OFF_MODA + lane * 16);
            #pragma unroll
            for (int v = 0; v < 2; v++)
                #pragma unroll
                for (int pp = 0; pp < 5; pp++) nb[v][pp] = hfma2(nb[v][pp], md[v * 5 + pp], md[10 + v * 5 + pp]);
        }
        uint32_t re[3][2], im[3][2];
        #pragma unroll
        for (int mt = 0; mt < 3; mt++)
            #pragma unroll
            for (int v = 0; v < 2; v++) {
                re[mt][v] = 0; im[mt][v] = 0;
                mma_h8(re[mt][v], im[mt][v], ta[mt * 10 + 8], ta[mt * 10 + 9], nb[v][4]);
                mma_h(re[mt][v], im[mt][v], ta[mt * 10], ta[mt * 10 + 1], ta[mt * 10 + 2], ta[mt * 10 + 3], nb[v][0], nb[v][1]);
                mma_h(re[mt][v], im[mt][v], ta[mt * 10 + 4], ta[mt * 10 + 5], ta[mt * 10 + 6], ta[mt * 10 + 7], nb[v][2], nb[v][3]);
                cmul_neg(re[mt][v], im[mt][v], ta[30 + (mt * 2 + v) * 2], ta[31 + (mt * 2 + v) * 2]);
            }
        const uint32_t srow = sm + OFF_SPEC + warp * (SPEC_P * 4);
        #pragma unroll
        for (int nt = 0; nt < 2; nt++) {
            uint32_t o[2][4];
            #pragma unroll
            for (int v = 0; v < 2; v++) {
                const uint32_t b0 = ta[42 + (v * 2 + nt) * 2], b1 = ta[43 + (v * 2 + nt) * 2];
                o[v][0] = o[v][1] = o[v][2] = o[v][3] = 0;
                mma_h(o[v][0], o[v][1], re[0][v], re[1][v], im[0][v], im[1][v], b0, b1);
                mma_h(o[v][2], o[v][3], re[2][v], re[2][v], im[2][v], im[2][v], b0, b1);
            }
            const uint32_t a = srow + (g + 72 * q + 36 * nt) * 4, a2 = srow + (288 - g - 72 * q - 36 * nt) * 4;
            sts32(a, hadd2(o[0][0], o[1][0])); sts32(a + 32, hadd2(o[0][1], o[1][1])); if (g < 3) sts32(a + 64, hadd2(o[0][2], o[1][2]));
            if (g > 0 || (q == 0 && nt == 0)) sts32(a2, hsub2(o[0][0], o[1][0]) ^ 0x80000000u);
            sts32(a2 - 32, hsub2(o[0][1], o[1][1]) ^ 0x80000000u); if (g < 2) sts32(a2 - 64, hsub2(o[0][2], o[1][2]) ^ 0x80000000u);
        }
        uint32_t b3[16];
        if (warp < 10) load_tab<4>(b3, sm + OFF_B3 + lane * 16);
        __syncthreads();
        t_st = clk32();
        PROF0(4);
        if (warp < 10) {
            uint4 V[4], o[4];
            #pragma unroll
            for (int u = 0; u < 4; u++) V[u] = lds128(scol + u * (16 * SPEC_P));
            radix16(V, b3, o);
            #pragma unroll
            for (int nt = 0; nt < 4; nt++) { o[nt].x |= 1u; if (warp < 9 || g < 2) stx128(tptr + nt * tstr, o[nt]); }
        }
        PROF0(5);
    }

    int role = 0;
    asm volatile("barrier.cluster.wait.aligned;" ::: "memory");
    if (warp >= 12) {
        const int t = tid - 384;
        if (tid == 448 && rank == 0) {
            uint32_t smid; asm volatile("mov.u32 %0, %%smid;" : "=r"(smid));
            const uint32_t tp = smid >> 1;
            uint32_t pr = tp < 32 ? (tp & 7) * 8 + (tp >> 3) : tp < 60 ? (1 + (tp - 32) % 7) * 8 + 4 + (tp - 32) / 7 : tp < 62 ? 4 + tp : tp < 66 ? tp - 58 : 0;
            while (atomicExch(g_slot + pr, epoch + 1) == epoch + 1) pr = pr == 65 ? 0 : pr + 1;
            #pragma unroll
            for (int r = 0; r < 2; r++)
                asm volatile("st.async.weak.shared::cluster.mbarrier::complete_tx::bytes.u32 [%0], %1, [%2];" :: "r"(mapa(sm + OFF_MISC, r)), "r"(pr), "r"(mapa(bars + 8 * BAR_ROLE, r)) : "memory");
        }
        __syncwarp();
        if (t == 0) {
            asm volatile("prefetch.tensormap [%0];" :: "l"(&tm_w1a) : "memory");
            asm volatile("prefetch.tensormap [%0];" :: "l"(&tm_h3a) : "memory"); asm volatile("prefetch.tensormap [%0];" :: "l"(&tm_w1b) : "memory");
            asm volatile("prefetch.tensormap [%0];" :: "l"(&tm_h3b) : "memory"); asm volatile("prefetch.tensormap [%0];" :: "l"(&tm_w2) : "memory");
            asm volatile("prefetch.tensormap [%0];" :: "l"(&tm_o) : "memory");
        }
        if (t == 32 && rowcta) {
            for (int it = 0; (int)(ld_acquire(g_cnt + CNT_NC * 32) - (epoch + 1) * 4) < 0; it++) { __nanosleep(100); if (it > SPIN_LIMIT) __trap(); }
            fence_async_g();
            mbar_expect(bars + 8 * BAR_NC, 3584);
            bulk_load(sm + OFF_MODC, p.scr->modc, 3584, bars + 8 * BAR_NC);
            PROFT(29);
        }
        __syncwarp();
    } else if (rowcta && warp < 11) {
        const int nw = !(b & 1) ? 10 : (b & 7) == 7 ? 9 : 8;
        const int cm = (b >> 3) * 288 + (b & 7) * 32, cx = (b & 1) ? 4608 + 8 * (b >> 3) : (b >> 3) * 288 + 256 + 4 * (b & 7);
        auto load_in = [&]() {
            if (elect()) {
                mbar_expect(bars + 8 * BAR_XB, nw > 8 ? 20480 : 16384);
                tma2(sm + OFF_STAGE, &tm_t, cm, 0, bars + 8 * BAR_XB);
                if (nw > 8) tma2(sm + OFF_STX, &tm_tx, cx, 0, bars + 8 * BAR_XB);
            }
            __syncwarp();
        };
        if (warp == 10) { fence_async_s(); spin_until(t_st + X1D); load_in(); }
        uint32_t tb[QB * 4], wre[4][2], wim[4][2];
        if (warp < nw) {
            mbar_wait(bars + 8 * BAR_TAB2, 0);
            load_tab<QB>(tb, sm + OFF_TAB + QA * 512 + lane * 16);
            mbar_wait(bars + 8 * BAR_W, 0);
            const int off = wc0 & 7;
            const uint32_t wa = sm + OFF_WRAW + lane * 112 + ((off >> 1) + 2 * warp) * 4, sh = (off & 1) * 16;
            #pragma unroll
            for (int c = 0; c < 2; c++)
                #pragma unroll
                for (int h = 0; h < 2; h++) {
                    uint32_t y[2][2];
                    #pragma unroll
                    for (int e = 0; e < 2; e++) {
                        const uint32_t a = wa + c * 14336 + (h + 2 * e) * 3584, x0 = lds32(a), x1 = lds32(a + 4), x2 = lds32(a + 8);
                        y[e][0] = __funnelshift_r(x0, x1, sh); y[e][1] = __funnelshift_r(x1, x2, sh);
                    }
                    #pragma unroll
                    for (int x = 0; x < 4; x++) {
                        const uint32_t v = (x & 1) ? pack_h(bf_hi(y[0][x >> 1]), bf_hi(y[1][x >> 1])) : pack_h(bf_lo(y[0][x >> 1]), bf_lo(y[1][x >> 1]));
                        if (c) wim[x][h] = v; else wre[x][h] = v;
                    }
                }
        }
        const uint32_t ca = warp < 8 ? sm + OFF_STAGE + lane * 128 + (warp ^ (lane & 7)) * 16 : sm + OFF_STX + lane * 32 + ((warp ^ g) & 1) * 16, cs = warp < 8 ? 4096 : 1024;
        uint32_t V[4][4];
        for (int it = 0;; it++) {
            mbar_wait(bars + 8 * BAR_XB, it & 1);
            uint32_t ok = 1;
            if (warp < nw) {
                #pragma unroll
                for (int u = 0; u < 4; u++) { uint4 t4 = lds128(ca + u * cs); V[u][0] = t4.x; V[u][1] = t4.y; V[u][2] = t4.z; V[u][3] = t4.w; ok &= t4.x; }
            }
            asm volatile("{.reg .pred p; setp.ne.u32 p, %0, 0; bar.red.and.pred p, 1, 352, p; selp.u32 %0, 1, 0, p;}" : "+r"(ok) :: "memory");
            if (ok) break;
            if (warp == 10) { load_in(); hb(); }
            if (it > SPIN_LIMIT / 64) __trap();
        }
        PROF0(7);
        if (warp < nw) {
            uint32_t zr[4][2], zi[4][2];
            #pragma unroll
            for (int x = 0; x < 4; x++) {
                uint32_t er = 0, ei = 0, or_ = 0, oi = 0;
                mma_h(er, ei, tb[0], tb[1], tb[2], tb[3], V[0][x], V[1][x]);
                mma_h(or_, oi, tb[4], tb[5], tb[6], tb[7], V[2][x], V[3][x]);
                uint32_t r0 = hadd2(er, or_), r1 = hsub2(er, or_), i0 = hadd2(ei, oi), i1 = hsub2(ei, oi);
                cmul_neg(r0, i0, tb[8], tb[9]); cmul_neg(r1, i1, tb[10], tb[11]);
                uint32_t xr0 = 0, xr1 = 0, xi0 = 0, xi1 = 0;
                mma_h(xr0, xr1, r0, r1, i0, i1, tb[12], tb[13]);
                mma_h(xi0, xi1, r0, r1, i0, i1, tb[14], tb[12]);
                cmul_pos(xr0, xi0, wre[x][0], wim[x][0]); cmul_pos(xr1, xi1, wre[x][1], wim[x][1]);
                r0 = 0; i0 = 0; r1 = 0; i1 = 0;
                mma_h(r0, i0, tb[12], tb[13], tb[14], tb[12], xr0, xi0);
                mma_h(r1, i1, tb[12], tb[13], tb[14], tb[12], xr1, xi1);
                cmul_pos(r0, i0, tb[15], tb[16]); cmul_pos(r1, i1, tb[17], tb[18]);
                zr[x][0] = hadd2(r0, r1); zr[x][1] = hsub2(r0, r1); zi[x][0] = hadd2(i0, i1); zi[x][1] = hsub2(i0, i1);
            }
            #pragma unroll
            for (int nt = 0; nt < 4; nt++) {
                uint4 o = make_uint4(0, 0, 0, 0);
                const int h = nt >> 1;
                mma_h(o.x, o.y, zr[0][h], zr[1][h], zi[0][h], zi[1][h], tb[19 + 2 * nt], tb[20 + 2 * nt]);
                mma_h(o.z, o.w, zr[2][h], zr[3][h], zi[2][h], zi[3][h], tb[19 + 2 * nt], tb[20 + 2 * nt]);
                o.x &= ~1u;
                sts128(ca + nt * cs, o);
            }
        }
        fence_async_s();
        bar_sync(1, 352);
        t_st = clk32();
        PROF0(8);
        if (warp == 10 && elect()) {
            asm volatile("cp.async.bulk.tensor.2d.global.shared::cta.bulk_group [%0, {%2, %3}], [%1];" :: "l"(&tm_t), "r"(sm + OFF_STAGE), "r"(cm), "r"(0) : "memory");
            if (nw > 8) asm volatile("cp.async.bulk.tensor.2d.global.shared::cta.bulk_group [%0, {%2, %3}], [%1];" :: "l"(&tm_tx), "r"(sm + OFF_STX), "r"(cx), "r"(0) : "memory");
            asm volatile("cp.async.bulk.commit_group;" ::: "memory");
            asm volatile("cp.async.bulk.wait_group.read 0;" ::: "memory");
        }
        __syncwarp();
    }

    if (warp >= 10) { mbar_wait(bars + 8 * BAR_ROLE, 0); role = __shfl_sync(~0u, lds32(sm + OFF_MISC), 0); fence_async_s(); }
    auto first_a = [&]() {
        if (warp >= 10 && role < 64 && elect())
            tma4(sm + OFF_A + (warp - 10) * A_BYTES, &tm_w1a, 0, 0, 4 * (warp - 10), 9 * (role >> 3) + (role & 4) + 2 * rank, bars + 8 * (BAR_FULL + warp - 10));
        __syncwarp();
    };
    if (!rowcta) first_a();
    else {
        uint32_t tc[QC * 4];
        mbar_wait(bars + 8 * BAR_TAB2, 0);
        load_tab<QC>(tc, sm + OFF_TAB + (QA + QB) * 512 + lane * 16);
        if (warp < 10) {
            uint32_t b3[16];
            load_tab<4>(b3, sm + OFF_B3 + 2048 + lane * 16);
            uint4 V[4], o[4];
            const bool tact = warp < 9 || g == 0;
            spin_until(t_st + X2D);
            #pragma unroll
            for (int u = 0; u < 4; u++) V[u] = make_uint4(tact, 0, 0, 0);
            for (int it = 0; __any_sync(~0u, (V[0].x | V[1].x | V[2].x | V[3].x) & 1u); it++) {
                #pragma unroll
                for (int u = 0; u < 4; u++) if (V[u].x & 1u) V[u] = ldx128(tptr + u * tstr);
                hb();
                if (it > SPIN_LIMIT) __trap();
            }
            PROF0(10);
            radix16(V, b3, o);
            if (tact) {
                #pragma unroll
                for (int nt = 0; nt < 4; nt++) sts128(scol + nt * (16 * SPEC_P), o[nt]);
            }
        }
        __syncthreads();
        PROF0(11);
        first_a();
        const uint32_t srow = sm + OFF_SPEC + warp * (SPEC_P * 4);
        uint32_t re[2][3], im[2][3];
        #pragma unroll
        for (int mt = 0; mt < 3; mt++) {
            const uint32_t a = srow + (g + 72 * q + 8 * mt) * 4, a2 = srow + (288 - g - 72 * q - 8 * mt) * 4;
            const uint32_t z0 = lds32(a), z1 = lds32(a + 144), z2 = lds32(a2), z3 = lds32(a2 - 144);
            #pragma unroll
            for (int m2 = 0; m2 < 2; m2++) {
                re[m2][mt] = 0; im[m2][mt] = 0;
                const uint32_t sg = m2 ? 0x3C00BC00u : 0xBC003C00u;
                mma_h(re[m2][mt], im[m2][mt], tc[m2 * 4], tc[m2 * 4 + 1], tc[m2 * 4 + 2], tc[m2 * 4 + 3], hfma2(z2, sg, z0), hfma2(z3, sg, z1));
                cmul_pos(re[m2][mt], im[m2][mt], tc[8 + (m2 * 3 + mt) * 2], tc[9 + (m2 * 3 + mt) * 2]);
            }
        }
        uint32_t md[28];
        mbar_wait(bars + 8 * BAR_NC, 0);
        load_tab<7>(md, sm + OFF_MODC + lane * 16);
        float y[5][4];
        #pragma unroll
        for (int nt = 0; nt < 5; nt++) {
            y[nt][0] = y[nt][1] = y[nt][2] = y[nt][3] = 0.f;
            #pragma unroll
            for (int mt = 0; mt < 3; mt++)
                mma_f(y[nt], re[0][mt], re[1][mt], im[0][mt], im[1][mt], tc[20 + (mt * 5 + nt) * 2], tc[21 + (mt * 5 + nt) * 2]);
        }
        float v0[9], v1[9], s1 = 0, s2 = 0;
        #pragma unroll
        for (int i = 0; i < 9; i++) {
            xw[i] = bfma2(md[i], pack_bf(y[i >> 1][i & 1], y[i >> 1][2 + (i & 1)]), xw[i]);
            v0[i] = bf_lo(xw[i]); v1[i] = bf_hi(xw[i]);
            s1 += v0[i] + v1[i]; s2 = fmaf(v0[i], v0[i], fmaf(v1[i], v1[i], s2));
        }
        warp_sum2(s1, s2);
        float m = s1 * (1.f / D_), r = rsqrtf(fmaxf(s2 * (1.f / D_) - m * m, 0.f) + 1e-5f), mr = -m * r;
        s1 = 0; s2 = 0;
        #pragma unroll
        for (int i = 0; i < 9; i++) {
            v0[i] = fmaf(fmaf(v0[i], r, mr), bf_lo(md[18 + i]), bf_lo(md[9 + i]));
            v1[i] = fmaf(fmaf(v1[i], r, mr), bf_hi(md[18 + i]), bf_hi(md[9 + i]));
            s1 += v0[i] + v1[i]; s2 = fmaf(v0[i], v0[i], fmaf(v1[i], v1[i], s2));
        }
        if (warp == 15) hb();
        warp_sum2(s1, s2);
        m = s1 * (1.f / D_); r = rsqrtf(fmaxf(s2 * (1.f / D_) - m * m, 0.f) + 1e-5f); mr = -m * r;
        {
            const int n7 = 2 * q + (g >> 2);
            const uint32_t a = sm + OFF_STAGE + n7 * 256 + (warp >> 3) * 128 + ((warp & 7) ^ n7) * 16 + (g & 3) * 4;
            #pragma unroll
            for (int i = 0; i < 9; i++) sts32(a + i * 2048, pack_bf(fmaf(v0[i], r, mr), fmaf(v1[i], r, mr)));
        }
        __syncthreads();
        PROF0(12);
        #pragma unroll
        for (int u = 0; u < 3; u++) {
            const int e = tid + 512 * u;
            if (e < 1152) g_h3[b * 1152 + e] = lds128(sm + OFF_STAGE + ((e & ~7) | ((e ^ (e >> 4)) & 7)) * 16);
        }
        #pragma unroll
        for (int i = 0; i < 9; i++) sts32(sm + OFF_X1 + warp * 1152 + (32 * i + 8 * q + g) * 4, xw[i]);
    }
    __syncthreads();
    if (rowcta) {
        if (tid == 0) { fence_async_g(); red_release(g_cnt + CNT_H3 * 32); }
        PROF0(13);
        if (warp == 15) {
            __nanosleep(X1DELAY);
            #pragma unroll 1
            for (int r = 0; r < 16; r++) {
                uint4* dst = (uint4*)(p.out + (size_t)(b + 128 * r) * D_) + lane;
                const uint32_t src = sm + OFF_X1 + r * 1152 + lane * 16;
                dst[0] = lds128(src); dst[32] = lds128(src + 512); if (lane < 8) dst[64] = lds128(src + 1024);
            }
            __syncwarp();
            if (lane == 0) { fence_async_g(); red_release(g_cnt + CNT_X1 * 32); }
        }
    }
    role = __shfl_sync(~0u, lds32(sm + OFF_MISC), 0);
    if (role >= 64) { if (warp == 0) PROFDUMP(); return; }

    const int gi = role >> 3, dt = role & 3, c2 = (role >> 2) & 1;
    const int wg = warp >> 2, wi = warp & 3;
    if (wg == 3) {
        uint32_t so = 0, eph = 1;
        #define RING_STEP(BYTES, OFF, ISSUE) do { \
            mbar_wait(bars + 8 * BAR_EMPTY + so, eph); \
            if (elect()) { const uint32_t fb = bars + 8 * BAR_FULL + so, dst = sm + (OFF) + so * ((BYTES) / 8); mbar_expect(fb, BYTES); ISSUE; } \
            so += 8; if (so == 8 * NST) { so = 0; eph ^= 1; } } while (0)
        if (warp == 12) {
            eph = 0;
            const int fb1 = 9 * gi + 4 * c2 + 2 * rank, sb2 = 4 * gi + 2 * c2;
            #pragma unroll 1
            for (int j = 4 * NST; j < 128; j += 4) {
                RING_STEP(A_BYTES, OFF_A, tma4(dst, &tm_w1a, 0, 0, j, fb1, fb));
                if (PF2 && (j & 28) == 4 * (role & 7) && j >= 32 && elect()) {
                    if (j < 64) asm volatile("cp.async.bulk.prefetch.tensor.4d.L2.global [%0, {%1, %2, %3, %4}];" :: "l"(&tm_w1b), "r"(0), "r"(0), "r"(64 * (int)rank + 8 * (role & 7)), "r"(9 * gi + 8) : "memory");
                    else asm volatile("cp.async.bulk.prefetch.tensor.3d.L2.global [%0, {%1, %2, %3}];" :: "l"(&tm_w2), "r"(0), "r"(64 * g2_kb(dt + ((j >> 3) & 4), rank)), "r"(sb2) : "memory");
                }
            }
            #pragma unroll 1
            for (int j = 64 * rank; j < 64 * rank + 64; j += 8) {
                RING_STEP(A_BYTES, OFF_A, tma4(dst, &tm_w1b, 0, 0, j, 9 * gi + 8, fb));
            }
            #pragma unroll 1
            for (int n = 0; n < 36; n++) {
                if (n == A2E) { mbar_wait(bars + 8 * BAR_UOK, 0); if (A2D) spin_until(clk32() + A2D); }
                RING_STEP(A_BYTES, OFF_A, tma3(dst, &tm_w2, 0, 64 * g2_kb(n, rank), sb2, fb));
            }
        } else if (warp == 13) {
            const uint32_t e1 = __shfl_sync(~0u, epoch + 1, 0);
            fence_async_s();
            wait_count(g_cnt + CNT_H3 * 32, e1 * 128);
            fence_async_g();
            if (lane == 0) PROFT(14);
            #pragma unroll 1
            for (int j = 0; j < 128; j += 4) RING_STEP(B_BYTES, OFF_B, tma3(dst, &tm_h3a, 0, 18 * dt, j, fb));
            #pragma unroll 1
            for (int j = 64 * rank; j < 64 * rank + 64; j += 8) {
                RING_STEP(B_BYTES, OFF_B, tma3(dst, &tm_h3b, 0, 18 * dt + 9 * c2, j, fb));
            }
            #pragma unroll 1
            for (int cls = 0; cls < 3; cls++) {
                mbar_wait(bars + 8 * (BAR_UOK + cls), 0);
                fence_async_g();
                if (cls == 0 && lane == 0) PROFT(19);
                const int n1 = cls < 2 ? 16 * cls + 16 : 36;
                #pragma unroll 1
                for (int n = 16 * cls; n < n1; n++) RING_STEP(B_BYTES, OFF_B, bulk_load(dst, g_U + (g2_kb(n, rank) * 4 + dt) * 1152, B_BYTES, fb));
            }
            if (role == 0 && rank == 0 && lane == 0) st_relaxed(g_cnt + CNT_EPOCH * 32, e1);
        } else if (warp == 15) {
            asm volatile("bar.arrive 5, 160;" ::: "memory");
            bar_sync(6, 160);
            mbar_wait(bars + 8 * BAR_W1GO, 0);
            if (elect()) {
                char* dst = (char*)(g_U + ((9 * gi + 4 * c2 + 2 * rank + 1) * 4 + dt) * 1152);
                #pragma unroll 1
                for (int i = 0; i < W1N; i++) {
                    asm volatile("cp.async.bulk.global.shared::cta.bulk_group [%0], [%1], %2;" :: "l"(dst + i * (18432 / W1N)), "r"(sm + OFF_X1 + i * (18432 / W1N)), "n"(18432 / W1N) : "memory");
                    const uint32_t t1 = clk32(); while ((int)(clk32() - t1) < W1P) {}
                }
                asm volatile("cp.async.bulk.commit_group;" ::: "memory");
                asm volatile("cp.async.bulk.wait_group 0;" ::: "memory");
                mbar_arrive_remote(mapa(bars + 8 * BAR_HOLD, rank ^ 1));
                fence_async_g(); red_release(g_cnt + (CNT_U + 8 + UIDX(dt, gi >> 2)) * 32);
            }
        } else if (tid == 448) {
            __nanosleep(4000);
            for (int it = 0; (int)(ld_acquire(g_cnt + (CNT_NC + 1) * 32) - (epoch + 1) * 2) < 0 || (int)(ld_acquire(g_cnt + CNT_NC * 32) - (epoch + 1) * 4) < 0; it++) { __nanosleep(200); if (it > SPIN_LIMIT) __trap(); }
            fence_async_g();
            mbar_expect(bars + 8 * BAR_GB, 1152);
            bulk_load(sm + OFF_GB, p.scr->modc + 896, 1152, bars + 8 * BAR_GB);
            wait_count(g_cnt + CNT_X1 * 32, (epoch + 1) * 128);
            mbar_wait(bars + 8 * BAR_STGO, 0);
            #pragma unroll 1
            for (int cls = 0; cls < 3; cls++) {
                wait_count(g_cnt + (CNT_U + 8 * cls + (cls < 2 ? UIDX(dt, rank) : 0)) * 32, (epoch + 1) * (cls < 2 ? UCNT : 128));
                mbar_arrive(bars + 8 * (BAR_UOK + cls));
                __nanosleep(1000);
            }
            fence_async_s(); fence_async_g();
            #pragma unroll 1
            for (int n = 0; n < 4; n++) { tma2(sm + OFF_X1 + n * 4608, &tm_o, 144 * dt, 256 * gi + 128 * c2 + 64 * (rank ^ 1) + 16 * n, bars + 8 * BAR_XT); __nanosleep(200); }
        }
    } else if (wg == 2) {
        float d0[36];
        const int fr = 576 * gi + 512 + 16 * wi + g;
        const float bias0 = bf_lo(ldg_nc16(p.b1 + fr)), bias1 = bf_lo(ldg_nc16(p.b1 + fr + 8));
        for (int it = 0; it < 200 && !__any_sync(~0u, mbar_test(bars + 8 * BAR_FULL, 0)); it++) { hb(); __nanosleep(100); }
        mbar_wait(bars + 8 * BAR_P2GO, 0);
        const bool lead = wi == 0 && elect();
        uint32_t s = IT_P2 % NST, ph = (IT_P2 / NST) & 1, prev = 0;
        #pragma unroll 1
        for (int i = 0; i < IT_G2 - IT_P2; i++) {
            if (i == P2A) {
                if (P2A) { WG_WAIT(0); if (lead) mbar_arrive_n(bars + 8 * BAR_EMPTY + 8 * prev, 2); }
                mbar_wait(bars + 8 * BAR_STGO, 0);
                spin_until(clk32() + P2D);
            }
            mbar_wait(bars + 8 * BAR_FULL + 8 * s, ph);
            const uint32_t da = desc_lo(sm + OFF_A, 8192) + s * (A_BYTES / 16), db = desc_lo(sm + OFF_B, 128) + s * (B_BYTES / 16);
            WG_FENCE();
            wgmma72(d0, da, db, i);
            #pragma unroll
            for (int k = 1; k < 8; k++) wgmma72(d0, da + k * 128, db + k * 144, 1);
            WG_COMMIT();
            if (lead && i == IT_G2 - IT_P2 - 1) mbar_arrive(bars + 8 * BAR_G2GO);
            WG_WAIT(1);
            if (lead && i && i != P2A) mbar_arrive_n(bars + 8 * BAR_EMPTY + 8 * prev, 2);
            prev = s; if (++s == NST) { s = 0; ph ^= 1; }
        }
        WG_WAIT(0);
        if (lead) { mbar_arrive_n(bars + 8 * BAR_EMPTY + 8 * prev, 2); PROFT(18); }
        const uint32_t slot = sm + OFF_P2R + ((wi & 1) * 32 + lane) * 16;
        if ((uint32_t)(wi >> 1) != rank) {
            const uint32_t ra = mapa(slot, rank ^ 1), rb = mapa(bars + 8 * BAR_P2R, rank ^ 1);
            mbar_wait(bars + 8 * BAR_HOLD, 0);
            #pragma unroll
            for (int i = 0; i < 9; i++)
                asm volatile("st.async.weak.shared::cluster.mbarrier::complete_tx::bytes.v4.f32 [%0], {%1,%2,%3,%4}, [%5];"
                    :: "r"(ra + i * 1024), "f"(d0[4 * i]), "f"(d0[4 * i + 1]), "f"(d0[4 * i + 2]), "f"(d0[4 * i + 3]), "r"(rb) : "memory");
        } else {
            mbar_wait(bars + 8 * BAR_P2R, 0);
            #pragma unroll
            for (int i = 0; i < 9; i++) {
                const uint4 v = lds128(slot + i * 1024);
                d0[4 * i] += __uint_as_float(v.x) + bias0; d0[4 * i + 1] += __uint_as_float(v.y) + bias0;
                d0[4 * i + 2] += __uint_as_float(v.z) + bias1; d0[4 * i + 3] += __uint_as_float(v.w) + bias1;
            }
            char* ub = (char*)(g_U + ((9 * gi + 8) * 4 + dt) * 1152) + wi * 4608 + c2 * 1152 + g * 16;
            gelu_store<0>(d0, ub, q); gelu_store<2>(d0, ub + 2304, q);
            bar_sync(8, 64);
            if ((wi & 1) == 0 && lane == 0) { fence_async_g(); red_release(g_cnt + (CNT_U + 16) * 32); }
        }
    } else {
        float d[72];
        const bool lead = wi == 0 && elect();
        const uint32_t da0 = desc_lo(sm + OFF_A + wg * 8192, 8192);
        const bool owner = (uint32_t)wg == rank;
        const int srow = 256 * gi + 128 * c2 + 64 * wg + 16 * wi;
        const uint32_t b2w0 = ldg_nc16(p.b2 + srow + g), b2w1 = ldg_nc16(p.b2 + srow + g + 8);
        {
            const int fr = 576 * gi + 256 * c2 + 128 * rank + 64 * wg + 16 * wi + g;
            const float bias0 = bf_lo(ldg_nc16(p.b1 + fr)), bias1 = bf_lo(ldg_nc16(p.b1 + fr + 8));
            #pragma unroll
            for (int i = 0; i < 72; i++) d[i] = (i & 2) ? bias1 : bias0;
            mainloop<DHI_H3, 0, IT_P2, false, true, true>(d, bars, da0, desc_lo(sm + OFF_B, 128), lead,
                [&](int i) { if (i == IT_P2 - 1 && wg == 0 && lead) mbar_arrive(bars + 8 * BAR_P2GO); });
            PROF0(16);
            if (wg == 1) bar_sync(5, 160);
            char* const ub = (wg == 0 ? (char*)(g_U + ((9 * gi + 4 * c2 + 2 * rank) * 4 + dt) * 1152) : (char*)__cvta_shared_to_generic(sm + OFF_X1)) + wi * 4608 + g * 16;
            gelu_store<0>(d, ub, q); gelu_store<2>(d, ub + 2304, q); gelu_store<36>(d, ub + 1152, q); gelu_store<38>(d, ub + 3456, q);
            PROF0(27);
            if (wg == 0) {
                bar_sync(4, 128);
                if (lead) {
                    mbar_arrive(bars + 8 * BAR_STGO);
                    fence_async_g(); red_release(g_cnt + (CNT_U + UIDX(dt, gi >> 2)) * 32);
                }
                __syncwarp();
            } else { fence_async_s(); asm volatile("bar.arrive 6, 160;" ::: "memory"); }
            PROF0(17);
        }
        mbar_wait(bars + 8 * BAR_G2GO, 0);
        const uint32_t db0 = desc_lo(sm + OFF_B, 2304);
        constexpr int IT_L = IT_END - NST, IT_X = IT_L - 4;
        mainloop<DHI_U, IT_G2, IT_X, true, true, false>(d, bars, da0, db0, lead,
            [&](int i) { if (i == IT_G2 + W1S && wg == 0 && lead) mbar_arrive(bars + 8 * BAR_W1GO); });
        const uint32_t ga0 = sm + OFF_GB + (144 * dt + 8 * q) * 2, tile = sm + OFF_X1 + wi * 4608, to = g * 288 + q * 16;
        #define QOFF(i_) (((i_) >> 2) * 2304 + 144 * (((i_) >> 1) & 1) + 64 * ((i_) & 1))
        #define SOFF(k_) (((k_) >> 1) * 2304 + 144 * ((k_) & 1) + 128 - 12 * q)
        #define DIDX(i_, k_) ((i_) < 8 ? 36 * (((i_) >> 1) & 1) + 16 * ((i_) & 1) + 4 * (k_) + 2 * ((i_) >> 2) : 36 * ((k_) & 1) + 32 + 2 * ((k_) >> 1))
        #define FIN(k_, f_) bfma2(g4.f_, pack_bf(d[DIDX(i, k_)], d[DIDX(i, k_) + 1]), xq[i].f_)
        uint4 xq[9];
        auto load_g = [&](int i) { uint4 r; if (i < 4) r = lds128(ga0 + QOFF(i)); else { r.x = r.z = lds32(ga0 + SOFF(0)); r.y = r.w = lds32(ga0 + SOFF(1)); } return r; };
        mainloop<DHI_U, IT_X, IT_L, false, false, false>(d, bars, da0, db0, lead, [&](int i) {
            if (!owner) {
                const uint32_t xa = tile + to;
                if (i == IT_X) { mbar_wait(bars + 8 * BAR_XT, 0); xq[0] = lds128(xa + QOFF(0)); xq[4] = lds128(xa + QOFF(4)); xq[1] = lds128(xa + QOFF(1)); }
                else if (i == IT_X + 1) { xq[5] = lds128(xa + QOFF(5)); xq[2] = lds128(xa + QOFF(2)); xq[6] = lds128(xa + QOFF(6)); }
                else if (i == IT_X + 2) { xq[3] = lds128(xa + QOFF(3)); xq[7] = lds128(xa + QOFF(7));
                    xq[8] = make_uint4(lds32(xa + SOFF(0)), lds32(xa + SOFF(1)), lds32(xa + SOFF(2)), lds32(xa + SOFF(3))); }
                else if (i == IT_X + 3) { if (elect()) mbar_arrive_remote(mapa(bars + 8 * BAR_DONE, rank ^ 1)); }
            } });
        if (owner) { WG_WAIT(0); if (lead) mbar_arrive(bars + 8 * (BAR_EMPTY + (IT_L - 1) % NST)); bar_sync(7, 256); }
        #pragma unroll
        for (int i = IT_L; i < IT_END; i++) {
            mbar_wait(bars + 8 * (BAR_FULL + i % NST), (i / NST) & 1);
            WG_FENCE();
            #pragma unroll
            for (int k = 0; k < 4; k++) wgmma144<DHI_U>(d, da0 + (i % NST) * (A_BYTES / 16) + k * 128, db0 + (i % NST) * (B_BYTES / 16) + k * 288, 1);
            WG_COMMIT();
            if (i == IT_L) { WG_WAIT(1); if (lead && !owner) mbar_arrive(bars + 8 * (BAR_EMPTY + (IT_L - 1) % NST)); }
        }
        PROF0(9);
        mbar_wait(bars + 8 * BAR_GB, 0);
        if (!owner) {
            const uint32_t ra = mapa(tile + lane * 16, rank ^ 1), rb = mapa(bars + 8 * BAR_RECV, rank ^ 1);
            mbar_wait(bars + 8 * BAR_DONE, 0);
            uint4 gn = load_g(0);
            WG_WAIT(1);
            asm volatile("bar.arrive 7, 256;" ::: "memory");
            WG_WAIT(0);
            #pragma unroll
            for (int i = 0; i < 72; i++) d[i] = fmaf(bf_lo((i & 2) ? b2w1 : b2w0), 2.f, d[i]);
            #pragma unroll
            for (int j = 0; j < 5; j++) {
                const uint4 g4 = gn;
                if (j < 4) gn = load_g(j + 1);
                #pragma unroll
                for (int i = j < 4 ? j : 8; i < 9; i += 4) if (i < 8 || j == 4)
                    asm volatile("st.async.weak.shared::cluster.mbarrier::complete_tx::bytes.v4.b32 [%0], {%1,%2,%3,%4}, [%5];"
                        :: "r"(ra + i * 512), "r"(FIN(0, x)), "r"(FIN(1, y)), "r"(FIN(2, z)), "r"(FIN(3, w)), "r"(rb) : "memory");
            }
            PROF0(6);
            if (warp == 0) PROFDUMP();
            return;
        }
        PROF0(24);
        mbar_wait(bars + 8 * BAR_RECV, 0);
        #pragma unroll
        for (int i = 0; i < 9; i++) xq[i] = lds128(tile + lane * 16 + i * 512);
        uint4 gn = load_g(0);
        WG_WAIT(0);
        __syncwarp();
        PROF0(21);
        #pragma unroll
        for (int j = 0; j < 5; j++) {
            const uint4 g4 = gn;
            if (j < 4) gn = load_g(j + 1);
            #pragma unroll
            for (int i = j < 4 ? j : 8; i < 9; i += 4) if (i < 8 || j == 4) {
                const uint4 o = make_uint4(FIN(0, x), FIN(1, y), FIN(2, z), FIN(3, w));
                if (i < 8) sts128(tile + to + QOFF(i), o);
                else { sts32(tile + to + SOFF(0), o.x); sts32(tile + to + SOFF(1), o.y); sts32(tile + to + SOFF(2), o.z); sts32(tile + to + SOFF(3), o.w); }
            }
        }
        fence_async_s();
        __syncwarp();
        if (elect()) {
            asm volatile("cp.async.bulk.tensor.2d.global.shared::cta.bulk_group [%0, {%2, %3}], [%1];" :: "l"(&tm_o), "r"(tile), "r"(144 * dt), "r"(srow) : "memory");
            asm volatile("cp.async.bulk.commit_group;" ::: "memory");
            asm volatile("cp.async.bulk.wait_group.read 0;" ::: "memory");
        }
        PROF0(23);
        if (warp == 0) { __syncwarp(); PROFDUMP(); }
    }
}

typedef CUresult (*EncodeFn)(CUtensorMap*, CUtensorMapDataType, cuuint32_t, void*, const cuuint64_t*, const cuuint64_t*, const cuuint32_t*,
                             const cuuint32_t*, CUtensorMapInterleave, CUtensorMapSwizzle, CUtensorMapL2promotion, CUtensorMapFloatOOBfill);

void encode(EncodeFn fn, CUtensorMap* m, CUtensorMapDataType dt, int rank, const void* ptr, const cuuint64_t* dims, const cuuint64_t* strides,
            const cuuint32_t* box, CUtensorMapSwizzle sw, CUtensorMapL2promotion promo = CU_TENSOR_MAP_L2_PROMOTION_L2_128B) {
    const cuuint32_t es[5] = {1, 1, 1, 1, 1};
    fn(m, dt, rank, (void*)ptr, dims, strides, box, es, CU_TENSOR_MAP_INTERLEAVE_NONE, sw, promo, CU_TENSOR_MAP_FLOAT_OOB_FILL_NONE);
}

}

extern "C" void kernel_launch(void* const* d_in, const int* in_sizes, int n_in, void* d_out, int out_size) {
    (void)in_sizes; (void)n_in; (void)out_size;
    Params p;
    p.x = (const uint16_t*)d_in[0]; p.wr = (const uint16_t*)d_in[1]; p.wi = (const uint16_t*)d_in[2];
    p.w1 = (const uint16_t*)d_in[4]; p.b1 = (const uint16_t*)d_in[5]; p.w2 = (const uint16_t*)d_in[6]; p.b2 = (const uint16_t*)d_in[7];
    p.c = (const uint16_t*)d_in[8]; p.wmod = (const uint16_t*)d_in[9]; p.out = (uint16_t*)d_out;

    void* fnp = nullptr; cudaDriverEntryPointQueryResult qr;
    cudaGetDriverEntryPoint("cuTensorMapEncodeTiled", &fnp, cudaEnableDefault, &qr);
    EncodeFn fn = (EncodeFn)fnp;
    cudaGetSymbolAddress((void**)&p.scr, g_scr); cudaGetSymbolAddress((void**)&p.tab, g_tab);
    void* h3p = p.scr->h3;
    CUtensorMap tw1a, tw1b, tw2, th3a, th3b, twr, twi, twm, tt, ttx, to;
    {
        const cuuint64_t dims[4] = {64, 16, 128, 72}, st[3] = {128ull * F_ * 2, (cuuint64_t)F_ * 2, 128};
        const cuuint32_t ba[4] = {64, 16, 4, 2}, bb[4] = {64, 16, 8, 1};
        encode(fn, &tw1a, CU_TENSOR_MAP_DATA_TYPE_BFLOAT16, 4, p.w1, dims, st, ba, CU_TENSOR_MAP_SWIZZLE_128B);
        encode(fn, &tw1b, CU_TENSOR_MAP_DATA_TYPE_BFLOAT16, 4, p.w1, dims, st, bb, CU_TENSOR_MAP_SWIZZLE_128B);
    }
    {
        const cuuint64_t dims[3] = {64, F_, 32}, st[2] = {(cuuint64_t)S_ * 2, 128};
        const cuuint32_t bx[3] = {64, 64, 2};
        encode(fn, &tw2, CU_TENSOR_MAP_DATA_TYPE_BFLOAT16, 3, p.w2, dims, st, bx, CU_TENSOR_MAP_SWIZZLE_128B);
    }
    {
        const cuuint64_t dims[3] = {64, 72, 128}, st[2] = {256, 18432};
        const cuuint32_t ba[3] = {64, 18, 4}, bb[3] = {64, 9, 8};
        encode(fn, &th3a, CU_TENSOR_MAP_DATA_TYPE_UINT32, 3, h3p, dims, st, ba, CU_TENSOR_MAP_SWIZZLE_NONE);
        encode(fn, &th3b, CU_TENSOR_MAP_DATA_TYPE_UINT32, 3, h3p, dims, st, bb, CU_TENSOR_MAP_SWIZZLE_NONE);
    }
    {
        const cuuint64_t dims[3] = {4624, 4, 32}, st[2] = {9248 * 32, 9248};
        const cuuint32_t bx[3] = {56, 4, 32};
        encode(fn, &twr, CU_TENSOR_MAP_DATA_TYPE_BFLOAT16, 3, p.wr, dims, st, bx, CU_TENSOR_MAP_SWIZZLE_NONE);
        encode(fn, &twi, CU_TENSOR_MAP_DATA_TYPE_BFLOAT16, 3, p.wi, dims, st, bx, CU_TENSOR_MAP_SWIZZLE_NONE);
    }
    {
        const cuuint64_t dims[3] = {64, 576, 54}, st[2] = {6912, 128};
        const cuuint32_t bx[3] = {64, 32, 7};
        encode(fn, &twm, CU_TENSOR_MAP_DATA_TYPE_BFLOAT16, 3, p.wmod, dims, st, bx, CU_TENSOR_MAP_SWIZZLE_128B);
    }
    {
        const cuuint64_t dims[2] = {TP, 128}, st[1] = {TP * 4};
        const cuuint32_t ba[2] = {32, 128}, bb[2] = {8, 128};
        encode(fn, &tt, CU_TENSOR_MAP_DATA_TYPE_UINT32, 2, p.scr->T, dims, st, ba, CU_TENSOR_MAP_SWIZZLE_128B, CU_TENSOR_MAP_L2_PROMOTION_NONE);
        encode(fn, &ttx, CU_TENSOR_MAP_DATA_TYPE_UINT32, 2, p.scr->T, dims, st, bb, CU_TENSOR_MAP_SWIZZLE_32B, CU_TENSOR_MAP_L2_PROMOTION_NONE);
    }
    {
        const cuuint64_t dims[2] = {D_, S_}, st[1] = {D_ * 2};
        const cuuint32_t bx[2] = {144, 16};
        encode(fn, &to, CU_TENSOR_MAP_DATA_TYPE_BFLOAT16, 2, p.out, dims, st, bx, CU_TENSOR_MAP_SWIZZLE_NONE, CU_TENSOR_MAP_L2_PROMOTION_NONE);
    }
    cudaFuncSetAttribute(fused_kernel, cudaFuncAttributeMaxDynamicSharedMemorySize, SMEM_BYTES);
    cudaLaunchConfig_t cfg = {};
    cfg.gridDim = dim3(NCTA); cfg.blockDim = dim3(NTHR); cfg.dynamicSmemBytes = SMEM_BYTES; cfg.stream = cudaStreamPerThread;
    cudaLaunchAttribute at[1];
    at[0].id = cudaLaunchAttributeCooperative; at[0].val.cooperative = 1;
    cfg.attrs = at; cfg.numAttrs = 1;
    cudaLaunchKernelEx(&cfg, fused_kernel, p, tw1a, tw1b, tw2, th3a, th3b, twr, twi, twm, tt, ttx, to);
}
```

```cpp
#include <cuda_runtime.h>
#include <cuda_bf16.h>
#include <cuda_fp16.h>
#include <cuda.h>
#include <stdint.h>

namespace {

constexpr int S_ = 2048, D_ = 576, F_ = 4608;
constexpr int NCTA = 132, NTHR = 512;
constexpr int TP = 4736;
constexpr int SPEC_P = 296;
constexpr int NST = 6;
constexpr int A_BYTES = 16384, B_BYTES = 18432;
constexpr int IT_P1 = 24, IT_G2 = 40, IT_END = 76;
constexpr int SPIN_LIMIT = 1 << 22;
#define UIDX(dt_, kh_) 0
#define UCNT 128
#define MODPAD 16
#define X2D 1300
#define CPHINT ".L2::128B"
constexpr int P2S = 2;
#define G2E 4
#define LEAD1 4
#define A2E 6
#define A2D 100
#define W1N 8
#define W1P 100
#define W1S 4
#define XDELAY 1600
#define X1D 2300
#define PF2 1
#define X1DELAY 2000
#define X1PACE 400

constexpr int OFF_A = 0;
constexpr int OFF_B = NST * A_BYTES;
constexpr int OFF_P = OFF_B + NST * B_BYTES;
constexpr int OFF_BAR = OFF_P;
constexpr int OFF_MISC = OFF_P + 376;
constexpr int OFF_GB = OFF_P + 384;
constexpr int OFF_P2R = OFF_P + 1536;
constexpr int OFF_X1 = OFF_P2R;
constexpr int OFF_PROF = OFF_X1 + 18432;
constexpr int SMEM_BYTES = OFF_PROF + 512 + 1024;
constexpr int QA = 13, QB = 7, QC = 13;
constexpr int TAB_BYTES = (QA + QB + QC) * 512;
constexpr int OFF_STAGE = OFF_B;
constexpr int OFF_STX = OFF_STAGE + 16384;
constexpr int OFF_TAB = OFF_STAGE + 20480;
constexpr int OFF_SPEC = OFF_TAB + TAB_BYTES;
constexpr int OFF_WRAW = OFF_SPEC + 19072;
constexpr int OFF_B3 = OFF_WRAW + 28672;
constexpr int OFF_MODA = OFF_B3 + 4096;
constexpr int OFF_MODC = OFF_MODA + 2560;
constexpr int OFF_RED = OFF_MODC + 3584;
constexpr int OFF_SILU = OFF_RED + 768;
static_assert(OFF_SILU + 1152 <= OFF_P && 6 * 28672 <= OFF_B3, "scratch overflow");
constexpr int OFF_STRIP = OFF_A;
static_assert(OFF_WRAW % 128 == 0 && OFF_STAGE % 128 == 0 && OFF_STX % 128 == 0, "align");
constexpr int BAR_FULL = 0, BAR_EMPTY = 6, BAR_TAB = 12, BAR_W = 13, BAR_REL = 14, BAR_P2R = 16,
              BAR_XT = 17, BAR_RECV = 18, BAR_ROLE = 19, BAR_NC = 20, BAR_TAB2 = 21, BAR_XB = 22, BAR_GB = 23, BAR_HOLD = 24, BAR_W1GO = 25, BAR_UOK = 26, BAR_DONE = 30, BAR_X = 31;

struct Cos1152 { double c[1152]; };
constexpr double cx_cos(double x) { double t = 1, s = 1; for (int i = 1; i < 14; i++) { t *= -x * x / ((2 * i - 1) * (2 * i)); s += t; } return s; }
constexpr Cos1152 make_cos() {
    Cos1152 r{};
    for (int i = 0; i <= 288; i++) {
        double v = (i == 288) ? 0.0 : cx_cos(3.14159265358979323846 * 2.0 * i / 1152.0);
        r.c[i] = v; r.c[576 - i] = -v; r.c[576 + i] = -v; r.c[(1152 - i) % 1152] = v;
    }
    return r;
}
constexpr uint32_t cx_f2h(double v) {
    uint32_t s = v < 0 ? 0x8000u : 0u; double a = v < 0 ? -v : v;
    if (a < 1e-9) return 0;
    int e = 0;
    while (a >= 2.0) { a *= 0.5; e++; }
    while (a < 1.0 && e > -14) { a *= 2.0; e--; }
    double m = a * 1024.0; uint32_t mi = (uint32_t)m; double fr = m - mi;
    if (fr > 0.5 || (fr == 0.5 && (mi & 1))) mi++;
    return s | (uint32_t)(((e + 14) << 10) + mi);
}
struct Tab { uint32_t w[(QA + QB + QC) * 128]; };
constexpr Tab make_tab() {
    Tab t{};
    Cos1152 ct = make_cos();
    auto C = [&](int num, int den) { return ct.c[(num % den) * (1152 / den)]; };
    auto Sn = [&](int num, int den) { return ct.c[((num % den) * (1152 / den) + 864) % 1152]; };
    auto put = [&](int q0, int idx, int lane, double lo, double hi) { t.w[((q0 + idx / 4) * 32 + lane) * 4 + idx % 4] = cx_f2h(lo) | (cx_f2h(hi) << 16); };
    for (int lane = 0; lane < 32; lane++) {
        const int g = lane >> 2, q = lane & 3;
        for (int mt = 0; mt < 3; mt++) {
            const int ka = 8 * mt + g;
            for (int r = 0; r < 10; r++) {
                const int im = r & 1, i0 = (r >> 1) * 2;
                double v[2] = {0, 0};
                for (int e = 0; e < 2; e++) { int i = i0 + e, d1 = 4 * i + q; if (i < 9 && ka <= 18) v[e] = (im ? -Sn(ka * d1, 36) : C(ka * d1, 36)) / 8; }
                put(0, mt * 10 + r, lane, v[0], v[1]);
            }
            for (int v = 0; v < 2; v++) {
                const int d2 = 4 * q + v;
                put(0, 30 + (mt * 2 + v) * 2, lane, C(ka * d2, 576) * 4 / 3, C(ka * (d2 + 2), 576) * 4 / 3);
                put(0, 31 + (mt * 2 + v) * 2, lane, Sn(ka * d2, 576) * 4 / 3, Sn(ka * (d2 + 2), 576) * 4 / 3);
            }
        }
        for (int v = 0; v < 2; v++) for (int nt = 0; nt < 2; nt++) {
            const int kb = 2 * (g >> 1) + nt, part = g & 1;
            double b0[2] = {0, 0}, b1[2] = {0, 0};
            for (int e = 0; e < 2; e++) { int d2 = 4 * q + 2 * e + v; double c = C(kb * d2, 16) / 4, s = Sn(kb * d2, 16) / 4;
                b0[e] = part ? -s : c; b1[e] = part ? c : s; }
            put(0, 42 + (v * 2 + nt) * 2, lane, b0[0], b0[1]); put(0, 43 + (v * 2 + nt) * 2, lane, b1[0], b1[1]);
        }
        for (int par = 0; par < 2; par++) for (int a = 0; a < 4; a++) {
            const int ja = 2 * (q + 4 * (a >> 1)) + par; const double c = C(g * ja, 16) / 4, s = Sn(g * ja, 16) / 4;
            put(QA, par * 4 + a, lane, (a & 1) ? -s : c, (a & 1) ? c : s);
        }
        for (int h = 0; h < 2; h++) {
            put(QA, 8 + 2 * h, lane, C((g + 8 * h) * (2 * q), 128) / 2, C((g + 8 * h) * (2 * q + 1), 128) / 2);
            put(QA, 9 + 2 * h, lane, Sn((g + 8 * h) * (2 * q), 128) / 2, Sn((g + 8 * h) * (2 * q + 1), 128) / 2);
            put(QA, 15 + 2 * h, lane, C(g * (8 * h + 2 * q), 128), C(g * (8 * h + 2 * q + 1), 128));
            put(QA, 16 + 2 * h, lane, Sn(g * (8 * h + 2 * q), 128), Sn(g * (8 * h + 2 * q + 1), 128));
        }
        put(QA, 12, lane, C(g * 2 * q, 8) / 2, C(g * (2 * q + 1), 8) / 2);
        put(QA, 13, lane, Sn(g * 2 * q, 8) / 2, Sn(g * (2 * q + 1), 8) / 2);
        put(QA, 14, lane, -Sn(g * 2 * q, 8) / 2, -Sn(g * (2 * q + 1), 8) / 2);
        for (int u = 0; u < 4; u++) {
            const int ja = 2 * ((g >> 1) + 4 * (u & 1)) + (u >> 1), part = g & 1; double b0[2] = {0, 0}, b1[2] = {0, 0};
            for (int e = 0; e < 2; e++) { int ka = 2 * q + e; double c = C(ja * ka, 16) / 4, s = Sn(ja * ka, 16) / 4;
                b0[e] = part ? s : c; b1[e] = part ? c : -s; }
            put(QA, 19 + u * 2, lane, b0[0], b0[1]); put(QA, 20 + u * 2, lane, b1[0], b1[1]);
        }
        for (int m2 = 0; m2 < 2; m2++) {
            const int d2 = 2 * g + m2;
            for (int a = 0; a < 4; a++) {
                const int kb = 2 * q + (a >> 1); const double c = C(d2 * kb, 16) / 4, s = Sn(d2 * kb, 16) / 4;
                put(QA + QB, m2 * 4 + a, lane, (a & 1) ? s : c, (a & 1) ? c : -s);
            }
            for (int mt = 0; mt < 3; mt++) {
                const int ka = 8 * mt + 2 * q;
                put(QA + QB, 8 + (m2 * 3 + mt) * 2, lane, C(ka * d2, 576) * 4 / 3, C((ka + 1) * d2, 576) * 4 / 3);
                put(QA + QB, 9 + (m2 * 3 + mt) * 2, lane, Sn(ka * d2, 576) * 4 / 3, Sn((ka + 1) * d2, 576) * 4 / 3);
            }
        }
        for (int mt = 0; mt < 3; mt++) for (int nt = 0; nt < 5; nt++) {
            const int i = 2 * nt + (g & 1), d1 = 4 * i + (g >> 1); double b0[2] = {0, 0}, b1[2] = {0, 0};
            for (int e = 0; e < 2; e++) { int ka = 8 * mt + 2 * q + e;
                if (ka <= 18 && i < 9) { double wt = (ka == 0 || ka == 18) ? 0.125 : 0.25; b0[e] = wt * C(ka * d1, 36); b1[e] = -wt * Sn(ka * d1, 36); } }
            put(QA + QB, 20 + (mt * 5 + nt) * 2, lane, b0[0], b0[1]); put(QA + QB, 21 + (mt * 5 + nt) * 2, lane, b1[0], b1[1]);
        }
    }
    return t;
}
__device__ __align__(128) const Tab g_tab = make_tab();

struct Scratch {
    uint32_t cnt[30 * 32];
    uint32_t slot[96];
    uint32_t mod[2304];
    uint32_t modc[896 + 288];
    uint32_t T[128 * TP];
    uint4 h3[128 * 1152];
    uint4 U[72 * 4 * 1152];
};
__device__ __align__(1024) Scratch g_scr;
#define g_cnt (p.scr->cnt)
#define g_slot (p.scr->slot)
#define g_mod (p.scr->mod)
#define g_T (p.scr->T)
#define g_h3 (p.scr->h3)
#define g_U (p.scr->U)
constexpr int CNT_EPOCH = 0, CNT_H3 = 1, CNT_X1 = 26, CNT_NC = 27, CNT_U = 2;
#define PROFT(i) do {} while (0)
#define PROFDUMP() do {} while (0)
#define PROF0(i) do {} while (0)

__device__ __forceinline__ void mbar_init(uint32_t bar, uint32_t cnt) { asm volatile("mbarrier.init.shared::cta.b64 [%0], %1;" :: "r"(bar), "r"(cnt) : "memory"); }
__device__ __forceinline__ void mbar_expect(uint32_t bar, uint32_t bytes) { asm volatile("mbarrier.arrive.expect_tx.shared::cta.b64 _, [%0], %1;" :: "r"(bar), "r"(bytes) : "memory"); }
__device__ __forceinline__ void mbar_arrive(uint32_t bar) { asm volatile("mbarrier.arrive.shared::cta.b64 _, [%0];" :: "r"(bar) : "memory"); }
__device__ __forceinline__ void mbar_arrive_n(uint32_t bar, uint32_t n) { asm volatile("mbarrier.arrive.shared::cta.b64 _, [%0], %1;" :: "r"(bar), "r"(n) : "memory"); }
__device__ __forceinline__ void mbar_arrive_remote(uint32_t rbar) { asm volatile("mbarrier.arrive.relaxed.cluster.shared::cluster.b64 _, [%0];" :: "r"(rbar) : "memory"); }
__device__ __forceinline__ void mbar_wait(uint32_t bar, uint32_t parity) {
    asm volatile("{.reg .pred p; .reg .u32 c;\n"
        "mbarrier.try_wait.parity.shared::cta.b64 p, [%0], %1;\n@p bra.uni DONE;\nmov.u32 c, 0;\n"
        "LOOP: mbarrier.try_wait.parity.shared::cta.b64 p, [%0], %1;\n@p bra.uni DONE;\n"
        "add.u32 c, c, 1;\nsetp.lt.u32 p, c, %2;\n@p bra.uni LOOP;\ntrap;\nDONE:}" :: "r"(bar), "r"(parity), "n"(SPIN_LIMIT) : "memory");
}
__device__ __forceinline__ bool mbar_test(uint32_t bar, uint32_t parity) {
    uint32_t ok; asm volatile("{.reg .pred p; mbarrier.test_wait.parity.shared::cta.b64 p, [%1], %2; selp.u32 %0, 1, 0, p;}" : "=r"(ok) : "r"(bar), "r"(parity) : "memory"); return ok; }
__device__ __forceinline__ uint32_t mapa(uint32_t a, uint32_t rank) { uint32_t r; asm("mapa.shared::cluster.u32 %0, %1, %2;" : "=r"(r) : "r"(a), "r"(rank)); return r; }
__device__ __forceinline__ uint32_t clk32() { uint32_t r; asm volatile("mov.u32 %0, %%clock;" : "=r"(r)); return r; }
__device__ __forceinline__ void hb() {
    asm volatile("{.reg .b32 a, b; .reg .pred p; mma.sync.aligned.m16n8k8.row.col.f16.f16.f16.f16 {a, b}, {%0,%0}, {%0}, {%0,%0};\n"
                 "setp.ne.u32 p, a, 0; @p trap;}" :: "r"(0));
}
__device__ __forceinline__ void spin_until(uint32_t t) { while (__any_sync(~0u, (int)(clk32() - t) < 0)) hb(); }
__device__ __forceinline__ bool elect() { uint32_t r; asm volatile("{.reg .pred p; elect.sync _|p, 0xffffffff; selp.u32 %0, 1, 0, p;}" : "=r"(r)); return r; }
__device__ __forceinline__ void bar_sync(int id, int n) { asm volatile("bar.sync %0, %1;" :: "r"(id), "r"(n) : "memory"); }
__device__ __forceinline__ void bulk_load(uint32_t dst, const void* src, uint32_t bytes, uint32_t bar) {
    asm volatile("cp.async.bulk.shared::cluster.global.mbarrier::complete_tx::bytes [%0], [%1], %2, [%3];" :: "r"(dst), "l"(src), "r"(bytes), "r"(bar) : "memory"); }
__device__ __forceinline__ void tma2(uint32_t dst, const CUtensorMap* m, int c0, int c1, uint32_t bar) {
    asm volatile("cp.async.bulk.tensor.2d.shared::cluster.global.mbarrier::complete_tx::bytes [%0], [%1, {%3, %4}], [%2];" :: "r"(dst), "l"(m), "r"(bar), "r"(c0), "r"(c1) : "memory"); }
__device__ __forceinline__ void tma3(uint32_t dst, const CUtensorMap* m, int c0, int c1, int c2, uint32_t bar) {
    asm volatile("cp.async.bulk.tensor.3d.shared::cluster.global.mbarrier::complete_tx::bytes [%0], [%1, {%3, %4, %5}], [%2];" :: "r"(dst), "l"(m), "r"(bar), "r"(c0), "r"(c1), "r"(c2) : "memory"); }
__device__ __forceinline__ void tma4(uint32_t dst, const CUtensorMap* m, int c0, int c1, int c2, int c3, uint32_t bar) {
    asm volatile("cp.async.bulk.tensor.4d.shared::cluster.global.mbarrier::complete_tx::bytes [%0], [%1, {%3, %4, %5, %6}], [%2];" :: "r"(dst), "l"(m), "r"(bar), "r"(c0), "r"(c1), "r"(c2), "r"(c3) : "memory"); }
__device__ __forceinline__ void fence_async_g() { asm volatile("fence.proxy.async.global;" ::: "memory"); }
__device__ __forceinline__ void fence_async_s() { asm volatile("fence.proxy.async.shared::cta;" ::: "memory"); }
__device__ __forceinline__ uint4 lds128(uint32_t a) { uint4 v; asm volatile("ld.shared.v4.u32 {%0,%1,%2,%3}, [%4];" : "=r"(v.x), "=r"(v.y), "=r"(v.z), "=r"(v.w) : "r"(a) : "memory"); return v; }
__device__ __forceinline__ uint32_t lds32(uint32_t a) { uint32_t v; asm volatile("ld.shared.u32 %0, [%1];" : "=r"(v) : "r"(a) : "memory"); return v; }
__device__ __forceinline__ void sts128(uint32_t a, uint4 v) { asm volatile("st.shared.v4.u32 [%0], {%1,%2,%3,%4};" :: "r"(a), "r"(v.x), "r"(v.y), "r"(v.z), "r"(v.w) : "memory"); }
__device__ __forceinline__ void sts32(uint32_t a, uint32_t v) { asm volatile("st.shared.u32 [%0], %1;" :: "r"(a), "r"(v) : "memory"); }
__device__ __forceinline__ void sts16(uint32_t a, uint32_t v) { asm volatile("st.shared.u16 [%0], %1;" :: "r"(a), "h"((uint16_t)v) : "memory"); }
__device__ __forceinline__ uint4 ldx128(const void* p) {
    uint4 v; asm volatile("{.reg .b128 t; .reg .b64 a, b; ld.relaxed.gpu.global.b128 t, [%4]; mov.b128 {a, b}, t; mov.b64 {%0,%1}, a; mov.b64 {%2,%3}, b;}"
        : "=r"(v.x), "=r"(v.y), "=r"(v.z), "=r"(v.w) : "l"(p) : "memory"); return v; }
__device__ __forceinline__ void stx128(void* p, uint4 v) {
    asm volatile("{.reg .b128 t; .reg .b64 a, b; mov.b64 a, {%1,%2}; mov.b64 b, {%3,%4}; mov.b128 t, {a, b}; st.relaxed.gpu.global.b128 [%0], t;}"
        :: "l"(p), "r"(v.x), "r"(v.y), "r"(v.z), "r"(v.w) : "memory"); }
__device__ __forceinline__ uint32_t ld_relaxed(const uint32_t* p) { uint32_t v; asm volatile("ld.relaxed.gpu.global.u32 %0, [%1];" : "=r"(v) : "l"(p) : "memory"); return v; }
__device__ __forceinline__ uint32_t ld_acquire(const uint32_t* p) { uint32_t v; asm volatile("ld.acquire.gpu.global.u32 %0, [%1];" : "=r"(v) : "l"(p) : "memory"); return v; }
__device__ __forceinline__ void st_relaxed(uint32_t* p, uint32_t v) { asm volatile("st.relaxed.gpu.global.u32 [%0], %1;" :: "l"(p), "r"(v) : "memory"); }
__device__ __forceinline__ void red_release(uint32_t* p) { asm volatile("red.release.gpu.global.add.u32 [%0], 1;" :: "l"(p) : "memory"); }
template <int SLEEP> __device__ __forceinline__ void wait_count(const uint32_t* p, uint32_t target) {
    int it = 0; while ((int)(ld_acquire(p) - target) < 0) { if (SLEEP) __nanosleep(SLEEP); if (++it > SPIN_LIMIT) __trap(); }
}
__device__ __forceinline__ uint32_t ldg_nc32(const void* p) { uint32_t v; asm volatile("ld.global.nc.L1::no_allocate.u32 %0, [%1];" : "=r"(v) : "l"(p)); return v; }
__device__ __forceinline__ uint32_t ldg_nc16(const void* p) { uint16_t v; asm volatile("ld.global.nc.u16 %0, [%1];" : "=h"(v) : "l"(p)); return v; }
__device__ __forceinline__ float bf_lo(uint32_t w) { return __uint_as_float(w << 16); }
__device__ __forceinline__ float bf_hi(uint32_t w) { return __uint_as_float(w & 0xFFFF0000u); }
__device__ __forceinline__ uint32_t pack_bf(float lo, float hi) { uint32_t r; asm("cvt.rn.bf16x2.f32 %0, %1, %2;" : "=r"(r) : "f"(hi), "f"(lo)); return r; }
__device__ __forceinline__ uint32_t pack_h(float lo, float hi) { uint32_t r; asm("cvt.rn.f16x2.f32 %0, %1, %2;" : "=r"(r) : "f"(hi), "f"(lo)); return r; }
__device__ __forceinline__ float bf_round(float v) { return bf_lo(pack_bf(v, 0.f)); }
__device__ __forceinline__ uint32_t hmul2(uint32_t a, uint32_t b) { uint32_t r; asm("mul.rn.f16x2 %0, %1, %2;" : "=r"(r) : "r"(a), "r"(b)); return r; }
__device__ __forceinline__ uint32_t hfma2(uint32_t a, uint32_t b, uint32_t c) { uint32_t r; asm("fma.rn.f16x2 %0, %1, %2, %3;" : "=r"(r) : "r"(a), "r"(b), "r"(c)); return r; }
__device__ __forceinline__ uint32_t hfms2(uint32_t a, uint32_t b, uint32_t c) { uint32_t r; asm("{.reg .b32 t; neg.f16x2 t, %3; fma.rn.f16x2 %0, %1, %2, t;}" : "=r"(r) : "r"(a), "r"(b), "r"(c)); return r; }
__device__ __forceinline__ uint32_t hadd2(uint32_t a, uint32_t b) { uint32_t r; asm("add.rn.f16x2 %0, %1, %2;" : "=r"(r) : "r"(a), "r"(b)); return r; }
__device__ __forceinline__ uint32_t hsub2(uint32_t a, uint32_t b) { uint32_t r; asm("sub.rn.f16x2 %0, %1, %2;" : "=r"(r) : "r"(a), "r"(b)); return r; }
__device__ __forceinline__ void cmul_neg(uint32_t& re, uint32_t& im, uint32_t c, uint32_t s) { uint32_t a = hfma2(re, c, hmul2(im, s)), b = hfms2(im, c, hmul2(re, s)); re = a; im = b; }
__device__ __forceinline__ void cmul_pos(uint32_t& re, uint32_t& im, uint32_t c, uint32_t s) { uint32_t a = hfms2(re, c, hmul2(im, s)), b = hfma2(im, c, hmul2(re, s)); re = a; im = b; }
__device__ __forceinline__ void mma_h(uint32_t& d0, uint32_t& d1, uint32_t a0, uint32_t a1, uint32_t a2, uint32_t a3, uint32_t b0, uint32_t b1) {
    asm("mma.sync.aligned.m16n8k16.row.col.f16.f16.f16.f16 {%0,%1}, {%2,%3,%4,%5}, {%6,%7}, {%0,%1};" : "+r"(d0), "+r"(d1) : "r"(a0), "r"(a1), "r"(a2), "r"(a3), "r"(b0), "r"(b1)); }
__device__ __forceinline__ void mma_h8(uint32_t& d0, uint32_t& d1, uint32_t a0, uint32_t a1, uint32_t b0) {
    asm("mma.sync.aligned.m16n8k8.row.col.f16.f16.f16.f16 {%0,%1}, {%2,%3}, {%4}, {%0,%1};" : "+r"(d0), "+r"(d1) : "r"(a0), "r"(a1), "r"(b0)); }
__device__ __forceinline__ void mma_f(float (&d)[4], uint32_t a0, uint32_t a1, uint32_t a2, uint32_t a3, uint32_t b0, uint32_t b1) {
    asm("mma.sync.aligned.m16n8k16.row.col.f32.f16.f16.f32 {%0,%1,%2,%3}, {%4,%5,%6,%7}, {%8,%9}, {%0,%1,%2,%3};"
        : "+f"(d[0]), "+f"(d[1]), "+f"(d[2]), "+f"(d[3]) : "r"(a0), "r"(a1), "r"(a2), "r"(a3), "r"(b0), "r"(b1)); }
template <int NQ> __device__ __forceinline__ void load_tab(uint32_t (&r)[NQ * 4], uint32_t addr) {
    #pragma unroll
    for (int i = 0; i < NQ; i++) { uint4 v = lds128(addr + i * 512); r[4 * i] = v.x; r[4 * i + 1] = v.y; r[4 * i + 2] = v.z; r[4 * i + 3] = v.w; }
}
__device__ __forceinline__ void warp_sum2(float& a, float& b) {
    #pragma unroll
    for (int o = 16; o; o >>= 1) { a += __shfl_xor_sync(~0u, a, o); b += __shfl_xor_sync(~0u, b, o); }
}
__device__ __forceinline__ float gelu2(float x) {
    float t = x * fmaf(x * x, 0.044715f * 0.7978845608028654f, 0.7978845608028654f), th;
    asm volatile("tanh.approx.f32 %0, %1;" : "=f"(th) : "f"(t));
    return fmaf(x, th, x);
}
__device__ __forceinline__ uint32_t desc_lo(uint32_t addr, uint32_t lbo) { return ((addr & 0x3FFFF) >> 4) | ((lbo >> 4) << 16); }
constexpr uint32_t DHI_A = (1024 >> 4) | (1u << 30), DHI_H3 = 256 >> 4, DHI_U = 128 >> 4;
#define WG_FENCE() asm volatile("wgmma.fence.sync.aligned;" ::: "memory")
#define WG_COMMIT() asm volatile("wgmma.commit_group.sync.aligned;" ::: "memory")
#define WG_WAIT(n) asm volatile("wgmma.wait_group.sync.aligned %0;" :: "n"(n) : "memory")
#define R4(b) "+f"(d[b]), "+f"(d[b + 1]), "+f"(d[b + 2]), "+f"(d[b + 3])
#define R12(b) R4(b), R4(b + 4), R4(b + 8)
#define R36(b) R12(b), R12(b + 12), R12(b + 24)
template <uint32_t BHI> __device__ __forceinline__ void wgmma144(float (&d)[72], uint32_t da, uint32_t db, int acc) {
    asm volatile("{.reg .pred p; .reg .b64 a, b; setp.ne.b32 p, %74, 0; mov.b64 a, {%72, %75}; mov.b64 b, {%73, %76};\n"
        "wgmma.mma_async.sync.aligned.m64n144k16.f32.bf16.bf16 {%0,%1,%2,%3,%4,%5,%6,%7,%8,%9,%10,%11,%12,%13,%14,%15,%16,%17,%18,%19,%20,%21,%22,%23,"
        "%24,%25,%26,%27,%28,%29,%30,%31,%32,%33,%34,%35,%36,%37,%38,%39,%40,%41,%42,%43,%44,%45,%46,%47,"
        "%48,%49,%50,%51,%52,%53,%54,%55,%56,%57,%58,%59,%60,%61,%62,%63,%64,%65,%66,%67,%68,%69,%70,%71}, a, b, p, 1, 1, 1, 1;}\n"
        : R36(0), R36(36) : "r"(da), "r"(db), "r"(acc), "n"(DHI_A), "n"(BHI));
}
__device__ __forceinline__ void wgmma144x4(float (&d)[72], const uint64_t (&a)[4], const uint64_t (&b)[4], int acc) {
    #define WG144 "wgmma.mma_async.sync.aligned.m64n144k16.f32.bf16.bf16 {%0,%1,%2,%3,%4,%5,%6,%7,%8,%9,%10,%11,%12,%13,%14,%15,%16,%17,%18,%19,%20,%21,%22,%23,%24,%25,%26,%27,%28,%29,%30,%31,%32,%33,%34,%35,%36,%37,%38,%39,%40,%41,%42,%43,%44,%45,%46,%47,%48,%49,%50,%51,%52,%53,%54,%55,%56,%57,%58,%59,%60,%61,%62,%63,%64,%65,%66,%67,%68,%69,%70,%71}, "
    asm volatile("{.reg .pred p; setp.ne.b32 p, %80, 0;\n"
        WG144 "%72, %76, p, 1, 1, 1, 1;\n" WG144 "%73, %77, 1, 1, 1, 1, 1;\n" WG144 "%74, %78, 1, 1, 1, 1, 1;\n" WG144 "%75, %79, 1, 1, 1, 1, 1;}\n"
        : R36(0), R36(36) : "l"(a[0]), "l"(a[1]), "l"(a[2]), "l"(a[3]), "l"(b[0]), "l"(b[1]), "l"(b[2]), "l"(b[3]), "r"(acc));
}
__device__ __forceinline__ void wgmma72(float (&d)[36], uint32_t da, uint32_t db, int acc) {
    asm volatile("{.reg .pred p; .reg .b64 a, b; setp.ne.b32 p, %38, 0; mov.b64 a, {%36, %39}; mov.b64 b, {%37, %40};\n"
        "wgmma.mma_async.sync.aligned.m64n72k16.f32.bf16.bf16 {%0,%1,%2,%3,%4,%5,%6,%7,%8,%9,%10,%11,%12,%13,%14,%15,%16,%17,%18,%19,%20,%21,%22,%23,"
        "%24,%25,%26,%27,%28,%29,%30,%31,%32,%33,%34,%35}, a, b, p, 1, 1, 1, 1;}\n"
        : R36(0) : "r"(da), "r"(db), "r"(acc), "n"(DHI_A), "n"(DHI_H3));
}

__device__ __forceinline__ int g2_kb(int n, int kh) { const int m = n - 4; return 36 * kh + (n < 4 ? 9 * n + 8 : 9 * ((m >> 2) & 3) + 2 * (m & 3) + (m >> 4)); }

template <uint32_t BHI, int I0, int I1, bool ZERO, bool FIRST, bool LAST, class Hook>
__device__ __forceinline__ void mainloop(float (&d)[72], uint32_t bars, uint32_t da0, uint32_t db0, bool lead, Hook hook) {
    uint32_t s = I0 % NST, ph = (I0 / NST) & 1, prev = (I0 + NST - (I0 == IT_P1 ? 2 : 1)) % NST;
    uint32_t ready = 0;
    uint64_t da[4], db[4];
    #pragma unroll
    for (int k = 0; k < 4; k++) { da[k] = ((uint64_t)DHI_A << 32) + da0 + s * (A_BYTES / 16) + k * 128; db[k] = ((uint64_t)BHI << 32) + db0 + s * (B_BYTES / 16) + k * 288; }
    #pragma unroll 1
    for (int i = I0; i < I1; i++) {
        if (!ready) mbar_wait(bars + 8 * BAR_FULL + 8 * s, ph);
        WG_FENCE();
        wgmma144x4(d, da, db, ZERO ? i - I0 : 1);
        WG_COMMIT();
        const uint32_t rel = bars + 8 * BAR_EMPTY + 8 * prev; const int i0 = i;
        prev = s; if (++s == NST) { s = 0; ph ^= 1; }
        if (I1 == IT_P1 && (s == P2S || s == P2S + 3)) {
            mbar_wait(bars + 8 * BAR_FULL + 8 * s, ph);
            i++; if (++s == NST) { s = 0; ph ^= 1; }
        }
        const int64_t adv = (int)s - (int)prev;
        #pragma unroll
        for (int k = 0; k < 4; k++) { da[k] += adv * (A_BYTES / 16); db[k] += adv * (B_BYTES / 16); }
        ready = __shfl_sync(~0u, (uint32_t)mbar_test(bars + 8 * BAR_FULL + 8 * s, ph), 0);
        WG_WAIT(1);
        if (lead && (!FIRST || i0 > I0)) mbar_arrive(rel);
        hook(i0);
    }
    if (LAST) { WG_WAIT(0); if (lead) mbar_arrive(bars + 8 * BAR_EMPTY + 8 * prev); }
}

struct Params {
    const uint16_t *x, *wr, *wi, *w1, *b1, *w2, *b2, *c, *wmod;
    uint16_t* out;
    Scratch* scr;
    const Tab* tab;
};

__device__ __forceinline__ void mma_bf(float (&d)[4], const uint32_t (&a)[4], uint32_t b0, uint32_t b1) {
    asm("mma.sync.aligned.m16n8k16.row.col.f32.bf16.bf16.f32 {%0,%1,%2,%3}, {%4,%5,%6,%7}, {%8,%9}, {%0,%1,%2,%3};"
        : "+f"(d[0]), "+f"(d[1]), "+f"(d[2]), "+f"(d[3]) : "r"(a[0]), "r"(a[1]), "r"(a[2]), "r"(a[3]), "r"(b0), "r"(b1)); }
__device__ __forceinline__ void ldsm4t(uint32_t (&a)[4], uint32_t addr) {
    asm volatile("ldmatrix.sync.aligned.m8n8.x4.trans.shared.b16 {%0,%1,%2,%3}, [%4];" : "=r"(a[0]), "=r"(a[1]), "=r"(a[2]), "=r"(a[3]) : "r"(addr) : "memory"); }
__device__ __forceinline__ float silu(float v) { return __fdividef(v, 1.f + __expf(-v)); }
__device__ __forceinline__ uint32_t bfma2(uint32_t a, uint32_t b, uint32_t c) { uint32_t r; asm("fma.rn.bf16x2 %0, %1, %2, %3;" : "=r"(r) : "r"(a), "r"(b), "r"(c)); return r; }
__device__ __forceinline__ void radix16(const uint4 (&V)[4], const uint32_t (&B)[16], uint4 (&o)[4]) {
    #pragma unroll
    for (int nt = 0; nt < 4; nt++) {
        o[nt] = make_uint4(0, 0, 0, 0);
        #pragma unroll
        for (int ks = 0; ks < 2; ks++) {
            const uint32_t b0 = B[(ks * 4 + nt) * 2], b1 = B[(ks * 4 + nt) * 2 + 1];
            mma_h(o[nt].x, o[nt].y, V[2 * ks].x, V[2 * ks].y, V[2 * ks + 1].x, V[2 * ks + 1].y, b0, b1);
            mma_h(o[nt].z, o[nt].w, V[2 * ks].z, V[2 * ks].w, V[2 * ks + 1].z, V[2 * ks + 1].w, b0, b1);
        }
    }
}
template <int OFF, int N> __device__ __forceinline__ void gelu_store(const float (&d)[N], char* p, int q) {
    uint32_t w[9];
    #pragma unroll
    for (int blk = 0; blk < 9; blk++) w[blk] = pack_bf(gelu2(d[OFF + 4 * blk]), gelu2(d[OFF + 4 * blk + 1]));
    asm volatile("st.v4.u32 [%0], {%1,%2,%3,%4};" :: "l"(p + q * 128), "r"(w[0]), "r"(w[1]), "r"(w[2]), "r"(w[3]) : "memory");
    asm volatile("st.v4.u32 [%0+512], {%1,%2,%3,%4};" :: "l"(p + q * 128), "r"(w[4]), "r"(w[5]), "r"(w[6]), "r"(w[7]) : "memory");
    asm volatile("st.u32 [%0+1024], %1;" :: "l"(p + q * 4), "r"(w[8]) : "memory");
}

__global__ void __cluster_dims__(2, 1, 1) __launch_bounds__(NTHR, 1)
fused_kernel(const Params p,
             const __grid_constant__ CUtensorMap tm_w1a, const __grid_constant__ CUtensorMap tm_w1b, const __grid_constant__ CUtensorMap tm_w2,
             const __grid_constant__ CUtensorMap tm_h3a, const __grid_constant__ CUtensorMap tm_h3b,
             const __grid_constant__ CUtensorMap tm_wr, const __grid_constant__ CUtensorMap tm_wi, const __grid_constant__ CUtensorMap tm_wm,
             const __grid_constant__ CUtensorMap tm_t, const __grid_constant__ CUtensorMap tm_tx, const __grid_constant__ CUtensorMap tm_o)
{
    extern __shared__ char smem_raw[];
    const uint32_t t0 = clk32();
    const uint32_t sm = __shfl_sync(~0u, ((uint32_t)__cvta_generic_to_shared(smem_raw) + 1023u) & ~1023u, 0);
    const int tid = threadIdx.x, warp = __shfl_sync(~0u, tid >> 5, 0), lane = tid & 31, g = lane >> 2, q = lane & 3;
    const int b = blockIdx.x;
    const uint32_t rank = b & 1;
    const uint32_t bars = sm + OFF_BAR;
    const bool rowcta = b < 128;

    auto nc_issue = [&](int st, uint32_t sl) {
        const int pass = st >= 18;
        mbar_expect(bars + 8 * (BAR_X + sl), 28672);
        tma3(sm + sl * 28672, &tm_wm, 0, 32 * (st - 18 * pass), 18 + 28 * pass + 7 * (b - 128), bars + 8 * (BAR_X + sl));
    };
    if (warp == 13) hb();
    uint32_t cw = 0, epoch;
    if (warp < 12) {
        if (lane < 24) cw = ldg_nc32(p.c + 48 * warp + 2 * lane);
        epoch = ld_relaxed(g_cnt + CNT_EPOCH * 32);
        if (b < 72) {
            const uint16_t* src = p.wmod + (48 * warp + (lane >> 1)) * 3456 + 16 * b + (lane & 1) * 8;
            const uint32_t dst = sm + OFF_STRIP + (48 * warp + (lane >> 1)) * 48 + (lane & 1) * 16;
            #pragma unroll
            for (int u = 0; u < 3; u++) asm volatile("cp.async.cg.shared.global" CPHINT " [%0], [%1], 16;" :: "r"(dst + u * 768), "l"(src + u * 16 * 3456) : "memory");
            asm volatile("cp.async.commit_group;" ::: "memory");
        }
    } else {
      if (elect()) {
        if (warp == 15) {
            mbar_init(bars + 8 * BAR_TAB, 1); fence_async_s();
            if (rowcta) { mbar_expect(bars + 8 * BAR_TAB, QA * 512); bulk_load(sm + OFF_TAB, p.tab, QA * 512, bars + 8 * BAR_TAB); }
            asm volatile("prefetch.tensormap [%0];" :: "l"(&tm_wr) : "memory"); asm volatile("prefetch.tensormap [%0];" :: "l"(&tm_wi) : "memory");
            asm volatile("prefetch.tensormap [%0];" :: "l"(&tm_t) : "memory"); asm volatile("prefetch.tensormap [%0];" :: "l"(&tm_tx) : "memory");
        } else if (warp == 14) {
            for (int i = BAR_W; i < BAR_X; i++) mbar_init(bars + 8 * i, i == BAR_DONE ? 4 : 1);
            mbar_expect(bars + 8 * BAR_W, 28672); mbar_expect(bars + 8 * BAR_TAB2, (QB + QC) * 512);
            mbar_expect(bars + 8 * BAR_ROLE, 4); mbar_expect(bars + 8 * BAR_P2R, 9216); mbar_expect(bars + 8 * BAR_RECV, 18432); mbar_expect(bars + 8 * BAR_XT, 18432);
        } else if (warp == 13) {
            for (int i = 0; i < 2 * NST; i++) mbar_init(bars + 8 * i, 2);
            for (int i = 0; i < NST; i++) mbar_expect(bars + 8 * (BAR_FULL + i), A_BYTES);
        }
        else {
            for (int i = 0; i < 16; i++) mbar_init(bars + 8 * (BAR_X + i), rowcta || i < 6 ? 1 : 14);
            if (!rowcta) { fence_async_s(); for (int st = 0; st < 6; st++) nc_issue(st, st); }
        }
        asm volatile("fence.mbarrier_init.release.cluster;" ::: "memory");
      }
      __syncwarp();
      epoch = ld_relaxed(g_cnt + CNT_EPOCH * 32);
    }
    __syncthreads();
    asm volatile("barrier.cluster.arrive.relaxed.aligned;" ::: "memory");
    if (warp < 4) sts16(sm + OFF_MODA + ((warp + 1) * 32 + lane) * 16 + warp * 4 + 2, 0);
    if (warp >= 8) {
        const int k1 = tid & 15, s1 = (tid >> 4) & 15;
        float s, c;
        __sincosf((float)(((k1 * (128 * s1 + b) + 1024) & 2047) - 1024) * (3.14159265358979f / 1024.f), &s, &c); s *= 0.25f; c *= 0.25f;
        const int rf = ((s1 >> 3) * 4 + (k1 >> 2)) * 2 + ((s1 >> 2) & 1), ri = ((k1 >> 3) * 4 + (s1 >> 2)) * 2 + ((k1 >> 2) & 1);
        const uint32_t af = sm + OFF_B3 + ((rf >> 2) * 32 + (k1 & 3) * 8 + (s1 & 3)) * 16 + (rf & 3) * 4;
        const uint32_t ai = sm + OFF_B3 + 2048 + ((ri >> 2) * 32 + (s1 & 3) * 8 + (k1 & 3)) * 16 + (ri & 3) * 4;
        sts32(af, pack_h(c, s)); sts32(af + 64, pack_h(-s, c)); sts32(ai, pack_h(c, -s)); sts32(ai + 64, pack_h(s, c));
    }
    if (rowcta) spin_until(t0 + XDELAY);
    if (rowcta && elect()) {
        mbar_expect(bars + 8 * (BAR_X + warp), 1152);
        bulk_load(sm + OFF_STAGE + warp * 1152, p.x + (size_t)(b + 128 * warp) * D_, 1152, bars + 8 * (BAR_X + warp));
    }
    const uint32_t tag = (epoch + 1) & 0xFFFFu;
    if (warp < 12 && lane < 24) sts32(sm + OFF_SILU + (24 * warp + lane) * 4, pack_bf(silu(bf_lo(cw)), silu(bf_hi(cw))));
    hb();
    uint32_t ta[QA * 4];
    const bool ta_early = rowcta && __any_sync(~0u, mbar_test(bars + 8 * BAR_TAB, 0));
    if (ta_early) load_tab<QA>(ta, sm + OFF_TAB + lane * 16);
    if (warp < 12 && b < 72) {
        uint32_t sb[6];
        __syncwarp();
        #pragma unroll
        for (int u = 0; u < 6; u++) sb[u] = lds32(sm + OFF_SILU + (24 * warp + 4 * u + q) * 4);
        asm volatile("cp.async.wait_all;" ::: "memory");
        __syncwarp();
        float acc[4] = {0, 0, 0, 0};
        #pragma unroll
        for (int u = 0; u < 3; u++) {
            uint32_t a[4];
            ldsm4t(a, sm + OFF_STRIP + (48 * warp + 16 * u + (lane & 7) + 8 * (lane >> 4)) * 48 + ((lane >> 3) & 1) * 16);
            mma_bf(acc, a, sb[2 * u], sb[2 * u + 1]);
        }
        if (q == 0) { sts32(sm + OFF_RED + (g * 12 + warp) * 4, __float_as_uint(acc[0])); sts32(sm + OFF_RED + ((g + 8) * 12 + warp) * 4, __float_as_uint(acc[2])); }
        PROF0(0);
        bar_sync(3, 384);
        if (warp == 0) {
            if (lane < 16) {
                float sum = 0;
                #pragma unroll
                for (int u = 0; u < 3; u++) { const uint4 v = lds128(sm + OFF_RED + lane * 48 + u * 16);
                    sum += (__uint_as_float(v.x) + __uint_as_float(v.y)) + (__uint_as_float(v.z) + __uint_as_float(v.w)); }
                sum = bf_round(sum); if (b >= 36) sum = bf_round(1.f + sum);
                st_relaxed(g_mod + b * MODPAD + (lane & 1) * 8 + (lane >> 1), (pack_h(0.f, sum) & 0xFFFF0000u) | tag);
            }
            __syncwarp();
            PROF0(1);
        }
    }

    const int trow = 4 * (b & 7) + ((b >> 4) & 3) + 64 * ((b >> 3) & 1) + 32 * (b >> 6);
    uint32_t* const tptr = g_T + (size_t)trow * TP + (warp < 9 ? q * 288 + 32 * warp : 4608 + 8 * q) + 4 * g;
    const int tstr = warp < 9 ? 1152 : 32;
    const uint32_t scol = sm + OFF_SPEC + (q * SPEC_P + (warp < 8 ? 72 * (warp >> 1) + 40 * (warp & 1) + 4 * g : warp == 8 ? 72 * (g >> 1) + 32 + 4 * (g & 1) : 288 + 4 * g)) * 4;
    const int wc0 = (b >> 3) * 289 + 72 * ((b & 7) >> 1) + 40 * (b & 1);

    uint32_t xw[9], t_st = t0;
    if (!rowcta) {
        const int nst = b < 130 ? 36 : 18;
        __syncthreads();
        if (warp == 14) {
            uint32_t sl = 0, ph = 0;
            #pragma unroll 1
            for (int st = 6; st < nst; st++) {
                mbar_wait(bars + 8 * (BAR_X + 6 + sl), ph);
                if (elect()) nc_issue(st, sl);
                if (++sl == 6) { sl = 0; ph ^= 1; }
            }
        } else if (warp < 14) {
            uint32_t sl = 0, ph = 0;
            const uint32_t ad0 = sm + (warp >> 1) * 4096 + ((lane & 7) + 8 * (lane >> 4)) * 128, ch = (warp & 1) * 4 + ((lane >> 3) & 1);
            #pragma unroll 1
            for (int pass = 0; pass * 18 < nst; pass++) {
                float acc[2][4] = {};
                #pragma unroll 1
                for (int st = 0; st < 18; st++) {
                    const uint32_t sa = sm + OFF_SILU + (16 * st + q) * 4;
                    const uint32_t b0 = lds32(sa), b1 = lds32(sa + 16), b2 = lds32(sa + 32), b3 = lds32(sa + 48);
                    mbar_wait(bars + 8 * (BAR_X + sl), ph);
                    #pragma unroll
                    for (int m = 0; m < 2; m++) {
                        uint32_t a[4], a2[4];
                        const uint32_t ad = ad0 + sl * 28672 + ((ch + 2 * m) ^ (lane & 7)) * 16;
                        ldsm4t(a, ad); ldsm4t(a2, ad + 2048);
                        mma_bf(acc[m], a, b0, b1); mma_bf(acc[m], a2, b2, b3);
                    }
                    if (elect()) mbar_arrive(bars + 8 * (BAR_X + 6 + sl));
                    if (++sl == 6) { sl = 0; ph ^= 1; }
                }
                const int cb = 28 * pass + 7 * (b - 128) + (warp >> 1), gg = (g >> 1) + 4 * q;
                #pragma unroll
                for (int m = 0; m < 2; m++) {
                    const int qq = (warp & 1) * 2 + m;
                    float v = bf_round(q ? acc[m][2] : acc[m][0]); if (cb >= 27) v *= 0.5f; else if (cb >= 18) v += 1.f;
                    const uint32_t w = pack_bf(v, __shfl_xor_sync(~0u, v, 4));
                    if (q < 2 && !(g & 1) && cb < 36) p.scr->modc[cb < 27 ? ((cb >> 2) * 32 + 4 * gg + qq) * 4 + (cb & 3) : 896 + 32 * (cb - 27) + 8 * qq + gg] = w;
                }
                bar_sync(1, 448);
                if (tid == 0) { fence_async_g(); red_release(g_cnt + (CNT_NC + pass) * 32); if (pass == 0) PROFT(25); }
                __syncwarp();
            }
            fence_async_s();
        }
        __syncthreads();
    } else {
        if (!ta_early) { mbar_wait(bars + 8 * BAR_TAB, 0); load_tab<QA>(ta, sm + OFF_TAB + lane * 16); }
        uint32_t nb[2][5];
        uint4 mv = make_uint4(tag, tag, tag, tag);
        const int mc = tid - 224, mst = (mc >> 2) % 36, midx = (mc < 144 ? 10 : 0) + 5 * ((mc >> 1) & 1) + (mst >> 3);
        const uint32_t* mp = g_mod + (mc >> 2) * MODPAD + (mc & 3) * 4;
        const uint32_t ma = sm + OFF_MODA + ((midx >> 2) * 32 + (mc & 1) * 16 + (mst & 3)) * 16 + (midx & 3) * 4 + ((mst >> 2) & 1) * 2;
        #define MOD_MISSING ((((mv.x ^ tag) | (mv.y ^ tag) | (mv.z ^ tag) | (mv.w ^ tag)) & 0xFFFFu) != 0)
        hb();
        mbar_wait(bars + 8 * (BAR_X + warp), 0);
        if (warp >= 7) mv = ldx128(mp);
        PROF0(28);
        #pragma unroll
        for (int i = 0; i < 9; i++) xw[i] = lds32(sm + OFF_STAGE + warp * 1152 + (32 * i + 8 * q + g) * 4);
        {
            float s1 = 0, s2 = 0;
            #pragma unroll
            for (int i = 0; i < 9; i++) { float lo = bf_lo(xw[i]), hi = bf_hi(xw[i]); s1 += lo + hi; s2 = fmaf(lo, lo, fmaf(hi, hi, s2)); }
            warp_sum2(s1, s2);
            const float m = s1 * (1.f / D_), r = rsqrtf(fmaxf(s2 * (1.f / D_) - m * m, 0.f) + 1e-5f), mr = -m * r;
            #pragma unroll
            for (int pp = 0; pp < 5; pp++) {
                nb[0][pp] = pack_h(fmaf(bf_lo(xw[2 * pp]), r, mr), pp < 4 ? fmaf(bf_lo(xw[pp < 4 ? 2 * pp + 1 : 0]), r, mr) : 0.f);
                nb[1][pp] = pack_h(fmaf(bf_hi(xw[2 * pp]), r, mr), pp < 4 ? fmaf(bf_hi(xw[pp < 4 ? 2 * pp + 1 : 0]), r, mr) : 0.f);
            }
        }
        PROF0(2);
        if (warp >= 7) {
            for (int it = 0; __any_sync(~0u, MOD_MISSING); it++) { mv = ldx128(mp); hb(); if (it > SPIN_LIMIT) __trap(); }
            sts16(ma, mv.x >> 16); sts16(ma + 64, mv.y >> 16); sts16(ma + 128, mv.z >> 16); sts16(ma + 192, mv.w >> 16);
        }
        __syncthreads();
        PROF0(3);
        if (warp >= 13 && elect()) {
            if (warp == 15) bulk_load(sm + OFF_TAB + QA * 512, p.tab->w + QA * 128, (QB + QC) * 512, bars + 8 * BAR_TAB2);
            else tma3(sm + OFF_WRAW + (warp - 13) * 14336, warp == 13 ? &tm_wr : &tm_wi, wc0 & ~7, 0, 0, bars + 8 * BAR_W);
        }
        __syncwarp();
        {
            uint32_t md[20];
            load_tab<5>(md, sm + OFF_MODA + lane * 16);
            #pragma unroll
            for (int v = 0; v < 2; v++)
                #pragma unroll
                for (int pp = 0; pp < 5; pp++) nb[v][pp] = hfma2(nb[v][pp], md[v * 5 + pp], md[10 + v * 5 + pp]);
        }
        uint32_t re[3][2], im[3][2];
        #pragma unroll
        for (int mt = 0; mt < 3; mt++)
            #pragma unroll
            for (int v = 0; v < 2; v++) {
                re[mt][v] = 0; im[mt][v] = 0;
                mma_h8(re[mt][v], im[mt][v], ta[mt * 10 + 8], ta[mt * 10 + 9], nb[v][4]);
                mma_h(re[mt][v], im[mt][v], ta[mt * 10], ta[mt * 10 + 1], ta[mt * 10 + 2], ta[mt * 10 + 3], nb[v][0], nb[v][1]);
                mma_h(re[mt][v], im[mt][v], ta[mt * 10 + 4], ta[mt * 10 + 5], ta[mt * 10 + 6], ta[mt * 10 + 7], nb[v][2], nb[v][3]);
                cmul_neg(re[mt][v], im[mt][v], ta[30 + (mt * 2 + v) * 2], ta[31 + (mt * 2 + v) * 2]);
            }
        const uint32_t srow = sm + OFF_SPEC + warp * (SPEC_P * 4);
        #pragma unroll
        for (int nt = 0; nt < 2; nt++) {
            uint32_t o[2][4];
            #pragma unroll
            for (int v = 0; v < 2; v++) {
                const uint32_t b0 = ta[42 + (v * 2 + nt) * 2], b1 = ta[43 + (v * 2 + nt) * 2];
                o[v][0] = o[v][1] = o[v][2] = o[v][3] = 0;
                mma_h(o[v][0], o[v][1], re[0][v], re[1][v], im[0][v], im[1][v], b0, b1);
                mma_h(o[v][2], o[v][3], re[2][v], re[2][v], im[2][v], im[2][v], b0, b1);
            }
            const uint32_t a = srow + (g + 72 * q + 36 * nt) * 4, a2 = srow + (288 - g - 72 * q - 36 * nt) * 4;
            sts32(a, hadd2(o[0][0], o[1][0])); sts32(a + 32, hadd2(o[0][1], o[1][1])); if (g < 3) sts32(a + 64, hadd2(o[0][2], o[1][2]));
            if (g > 0 || (q == 0 && nt == 0)) sts32(a2, hsub2(o[0][0], o[1][0]) ^ 0x80000000u);
            sts32(a2 - 32, hsub2(o[0][1], o[1][1]) ^ 0x80000000u); if (g < 2) sts32(a2 - 64, hsub2(o[0][2], o[1][2]) ^ 0x80000000u);
        }
        uint32_t b3[16];
        if (warp < 10) load_tab<4>(b3, sm + OFF_B3 + lane * 16);
        __syncthreads();
        t_st = clk32();
        PROF0(4);
        if (warp < 10) {
            uint4 V[4], o[4];
            #pragma unroll
            for (int u = 0; u < 4; u++) V[u] = lds128(scol + u * (16 * SPEC_P));
            radix16(V, b3, o);
            #pragma unroll
            for (int nt = 0; nt < 4; nt++) { o[nt].x |= 1u; if (warp < 9 || g < 2) stx128(tptr + nt * tstr, o[nt]); }
        }
        PROF0(5);
    }

    int role = 0;
    asm volatile("barrier.cluster.wait.aligned;" ::: "memory");
    if (warp >= 12) {
        const int t = tid - 384;
        if (tid == 448 && rank == 0) {
            uint32_t smid; asm volatile("mov.u32 %0, %%smid;" : "=r"(smid));
            const uint32_t tp = smid >> 1;
            uint32_t pr = tp < 32 ? (tp & 7) * 8 + (tp >> 3) : tp < 60 ? (1 + (tp - 32) % 7) * 8 + 4 + (tp - 32) / 7 : tp < 62 ? 4 + tp : tp < 66 ? tp - 58 : 0;
            while (atomicExch(g_slot + pr, epoch + 1) == epoch + 1) pr = pr == 65 ? 0 : pr + 1;
            #pragma unroll
            for (int r = 0; r < 2; r++)
                asm volatile("st.async.weak.shared::cluster.mbarrier::complete_tx::bytes.u32 [%0], %1, [%2];" :: "r"(mapa(sm + OFF_MISC, r)), "r"(pr), "r"(mapa(bars + 8 * BAR_ROLE, r)) : "memory");
        }
        __syncwarp();
        if (t == 0) {
            asm volatile("prefetch.tensormap [%0];" :: "l"(&tm_w1a) : "memory");
            asm volatile("prefetch.tensormap [%0];" :: "l"(&tm_h3a) : "memory"); asm volatile("prefetch.tensormap [%0];" :: "l"(&tm_w1b) : "memory");
            asm volatile("prefetch.tensormap [%0];" :: "l"(&tm_h3b) : "memory"); asm volatile("prefetch.tensormap [%0];" :: "l"(&tm_w2) : "memory");
            asm volatile("prefetch.tensormap [%0];" :: "l"(&tm_o) : "memory");
        }
        if (t == 32 && rowcta) {
            for (int it = 0; (int)(ld_acquire(g_cnt + CNT_NC * 32) - (epoch + 1) * 4) < 0; it++) { __nanosleep(100); if (it > SPIN_LIMIT) __trap(); }
            fence_async_g();
            mbar_expect(bars + 8 * BAR_NC, 3584);
            bulk_load(sm + OFF_MODC, p.scr->modc, 3584, bars + 8 * BAR_NC);
            PROFT(29);
        }
        __syncwarp();
    } else if (rowcta && warp < 11) {
        const int nw = !(b & 1) ? 10 : (b & 7) == 7 ? 9 : 8;
        const int cm = (b >> 3) * 288 + (b & 7) * 32, cx = (b & 1) ? 4608 + 8 * (b >> 3) : (b >> 3) * 288 + 256 + 4 * (b & 7);
        auto load_in = [&]() {
            if (elect()) {
                mbar_expect(bars + 8 * BAR_XB, nw > 8 ? 20480 : 16384);
                tma2(sm + OFF_STAGE, &tm_t, cm, 0, bars + 8 * BAR_XB);
                if (nw > 8) tma2(sm + OFF_STX, &tm_tx, cx, 0, bars + 8 * BAR_XB);
            }
            __syncwarp();
        };
        if (warp == 10) { fence_async_s(); spin_until(t_st + X1D); load_in(); }
        uint32_t tb[QB * 4], wre[4][2], wim[4][2];
        if (warp < nw) {
            mbar_wait(bars + 8 * BAR_TAB2, 0);
            load_tab<QB>(tb, sm + OFF_TAB + QA * 512 + lane * 16);
            mbar_wait(bars + 8 * BAR_W, 0);
            const int off = wc0 & 7;
            const uint32_t wa = sm + OFF_WRAW + lane * 112 + ((off >> 1) + 2 * warp) * 4, sh = (off & 1) * 16;
            #pragma unroll
            for (int c = 0; c < 2; c++)
                #pragma unroll
                for (int h = 0; h < 2; h++) {
                    uint32_t y[2][2];
                    #pragma unroll
                    for (int e = 0; e < 2; e++) {
                        const uint32_t a = wa + c * 14336 + (h + 2 * e) * 3584, x0 = lds32(a), x1 = lds32(a + 4), x2 = lds32(a + 8);
                        y[e][0] = __funnelshift_r(x0, x1, sh); y[e][1] = __funnelshift_r(x1, x2, sh);
                    }
                    #pragma unroll
                    for (int x = 0; x < 4; x++) {
                        const uint32_t v = (x & 1) ? pack_h(bf_hi(y[0][x >> 1]), bf_hi(y[1][x >> 1])) : pack_h(bf_lo(y[0][x >> 1]), bf_lo(y[1][x >> 1]));
                        if (c) wim[x][h] = v; else wre[x][h] = v;
                    }
                }
        }
        const uint32_t ca = warp < 8 ? sm + OFF_STAGE + lane * 128 + (warp ^ (lane & 7)) * 16 : sm + OFF_STX + lane * 32 + ((warp ^ g) & 1) * 16, cs = warp < 8 ? 4096 : 1024;
        uint32_t V[4][4];
        for (int it = 0;; it++) {
            mbar_wait(bars + 8 * BAR_XB, it & 1);
            uint32_t ok = 1;
            if (warp < nw) {
                #pragma unroll
                for (int u = 0; u < 4; u++) { uint4 t4 = lds128(ca + u * cs); V[u][0] = t4.x; V[u][1] = t4.y; V[u][2] = t4.z; V[u][3] = t4.w; ok &= t4.x; }
            }
            asm volatile("{.reg .pred p; setp.ne.u32 p, %0, 0; bar.red.and.pred p, 1, 352, p; selp.u32 %0, 1, 0, p;}" : "+r"(ok) :: "memory");
            if (ok) break;
            if (warp == 10) { load_in(); hb(); }
            if (it > SPIN_LIMIT / 64) __trap();
        }
        PROF0(7);
        if (warp < nw) {
            uint32_t zr[4][2], zi[4][2];
            #pragma unroll
            for (int x = 0; x < 4; x++) {
                uint32_t er = 0, ei = 0, or_ = 0, oi = 0;
                mma_h(er, ei, tb[0], tb[1], tb[2], tb[3], V[0][x], V[1][x]);
                mma_h(or_, oi, tb[4], tb[5], tb[6], tb[7], V[2][x], V[3][x]);
                uint32_t r0 = hadd2(er, or_), r1 = hsub2(er, or_), i0 = hadd2(ei, oi), i1 = hsub2(ei, oi);
                cmul_neg(r0, i0, tb[8], tb[9]); cmul_neg(r1, i1, tb[10], tb[11]);
                uint32_t xr0 = 0, xr1 = 0, xi0 = 0, xi1 = 0;
                mma_h(xr0, xr1, r0, r1, i0, i1, tb[12], tb[13]);
                mma_h(xi0, xi1, r0, r1, i0, i1, tb[14], tb[12]);
                cmul_pos(xr0, xi0, wre[x][0], wim[x][0]); cmul_pos(xr1, xi1, wre[x][1], wim[x][1]);
                r0 = 0; i0 = 0; r1 = 0; i1 = 0;
                mma_h(r0, i0, tb[12], tb[13], tb[14], tb[12], xr0, xi0);
                mma_h(r1, i1, tb[12], tb[13], tb[14], tb[12], xr1, xi1);
                cmul_pos(r0, i0, tb[15], tb[16]); cmul_pos(r1, i1, tb[17], tb[18]);
                zr[x][0] = hadd2(r0, r1); zr[x][1] = hsub2(r0, r1); zi[x][0] = hadd2(i0, i1); zi[x][1] = hsub2(i0, i1);
            }
            #pragma unroll
            for (int nt = 0; nt < 4; nt++) {
                uint4 o = make_uint4(0, 0, 0, 0);
                const int h = nt >> 1;
                mma_h(o.x, o.y, zr[0][h], zr[1][h], zi[0][h], zi[1][h], tb[19 + 2 * nt], tb[20 + 2 * nt]);
                mma_h(o.z, o.w, zr[2][h], zr[3][h], zi[2][h], zi[3][h], tb[19 + 2 * nt], tb[20 + 2 * nt]);
                o.x &= ~1u;
                sts128(ca + nt * cs, o);
            }
        }
        fence_async_s();
        bar_sync(1, 352);
        t_st = clk32();
        PROF0(8);
        if (warp == 10 && elect()) {
            asm volatile("cp.async.bulk.tensor.2d.global.shared::cta.bulk_group [%0, {%2, %3}], [%1];" :: "l"(&tm_t), "r"(sm + OFF_STAGE), "r"(cm), "r"(0) : "memory");
            if (nw > 8) asm volatile("cp.async.bulk.tensor.2d.global.shared::cta.bulk_group [%0, {%2, %3}], [%1];" :: "l"(&tm_tx), "r"(sm + OFF_STX), "r"(cx), "r"(0) : "memory");
            asm volatile("cp.async.bulk.commit_group;" ::: "memory");
            asm volatile("cp.async.bulk.wait_group.read 0;" ::: "memory");
        }
        __syncwarp();
    }

    if (warp >= 10) { mbar_wait(bars + 8 * BAR_ROLE, 0); role = __shfl_sync(~0u, lds32(sm + OFF_MISC), 0); fence_async_s(); }
    auto first_a = [&]() {
        if (warp >= 10 && role < 64 && elect()) {
            const int it = warp - 10, hi = it >= 3; const bool p2 = it - 3 * hi == 2;
            tma4(sm + OFF_A + it * A_BYTES, p2 ? &tm_w1b : &tm_w1a, 0, 0, p2 ? 64 * rank + 8 * hi : 4 * (it - hi),
                 9 * (role >> 3) + (p2 ? 8 : (role & 4) + 2 * rank), bars + 8 * (BAR_FULL + it));
        }
        __syncwarp();
    };
    if (!rowcta) first_a();
    else {
        uint32_t tc[QC * 4];
        mbar_wait(bars + 8 * BAR_TAB2, 0);
        load_tab<QC>(tc, sm + OFF_TAB + (QA + QB) * 512 + lane * 16);
        if (warp < 10) {
            uint32_t b3[16];
            load_tab<4>(b3, sm + OFF_B3 + 2048 + lane * 16);
            uint4 V[4], o[4];
            const bool tact = warp < 9 || g == 0;
            spin_until(t_st + X2D);
            #pragma unroll
            for (int u = 0; u < 4; u++) V[u] = make_uint4(tact, 0, 0, 0);
            for (int it = 0; __any_sync(~0u, (V[0].x | V[1].x | V[2].x | V[3].x) & 1u); it++) {
                #pragma unroll
                for (int u = 0; u < 4; u++) if (V[u].x & 1u) V[u] = ldx128(tptr + u * tstr);
                hb();
                if (it > SPIN_LIMIT) __trap();
            }
            PROF0(10);
            radix16(V, b3, o);
            if (tact) {
                #pragma unroll
                for (int nt = 0; nt < 4; nt++) sts128(scol + nt * (16 * SPEC_P), o[nt]);
            }
        }
        __syncthreads();
        PROF0(11);
        first_a();
        const uint32_t srow = sm + OFF_SPEC + warp * (SPEC_P * 4);
        uint32_t re[2][3], im[2][3];
        #pragma unroll
        for (int mt = 0; mt < 3; mt++) {
            const uint32_t a = srow + (g + 72 * q + 8 * mt) * 4, a2 = srow + (288 - g - 72 * q - 8 * mt) * 4;
            const uint32_t z0 = lds32(a), z1 = lds32(a + 144), z2 = lds32(a2), z3 = lds32(a2 - 144);
            #pragma unroll
            for (int m2 = 0; m2 < 2; m2++) {
                re[m2][mt] = 0; im[m2][mt] = 0;
                const uint32_t sg = m2 ? 0x3C00BC00u : 0xBC003C00u;
                mma_h(re[m2][mt], im[m2][mt], tc[m2 * 4], tc[m2 * 4 + 1], tc[m2 * 4 + 2], tc[m2 * 4 + 3], hfma2(z2, sg, z0), hfma2(z3, sg, z1));
                cmul_pos(re[m2][mt], im[m2][mt], tc[8 + (m2 * 3 + mt) * 2], tc[9 + (m2 * 3 + mt) * 2]);
            }
        }
        uint32_t md[28];
        mbar_wait(bars + 8 * BAR_NC, 0);
        load_tab<7>(md, sm + OFF_MODC + lane * 16);
        float y[5][4];
        #pragma unroll
        for (int nt = 0; nt < 5; nt++) {
            y[nt][0] = y[nt][1] = y[nt][2] = y[nt][3] = 0.f;
            #pragma unroll
            for (int mt = 0; mt < 3; mt++)
                mma_f(y[nt], re[0][mt], re[1][mt], im[0][mt], im[1][mt], tc[20 + (mt * 5 + nt) * 2], tc[21 + (mt * 5 + nt) * 2]);
        }
        float v0[9], v1[9], s1 = 0, s2 = 0;
        #pragma unroll
        for (int i = 0; i < 9; i++) {
            xw[i] = bfma2(md[i], pack_bf(y[i >> 1][i & 1], y[i >> 1][2 + (i & 1)]), xw[i]);
            v0[i] = bf_lo(xw[i]); v1[i] = bf_hi(xw[i]);
            s1 += v0[i] + v1[i]; s2 = fmaf(v0[i], v0[i], fmaf(v1[i], v1[i], s2));
        }
        warp_sum2(s1, s2);
        float m = s1 * (1.f / D_), r = rsqrtf(fmaxf(s2 * (1.f / D_) - m * m, 0.f) + 1e-5f), mr = -m * r;
        s1 = 0; s2 = 0;
        #pragma unroll
        for (int i = 0; i < 9; i++) {
            v0[i] = fmaf(fmaf(v0[i], r, mr), bf_lo(md[18 + i]), bf_lo(md[9 + i]));
            v1[i] = fmaf(fmaf(v1[i], r, mr), bf_hi(md[18 + i]), bf_hi(md[9 + i]));
            s1 += v0[i] + v1[i]; s2 = fmaf(v0[i], v0[i], fmaf(v1[i], v1[i], s2));
        }
        if (warp == 15) hb();
        warp_sum2(s1, s2);
        m = s1 * (1.f / D_); r = rsqrtf(fmaxf(s2 * (1.f / D_) - m * m, 0.f) + 1e-5f); mr = -m * r;
        {
            const int n7 = 2 * q + (g >> 2);
            const uint32_t a = sm + OFF_STAGE + n7 * 256 + (warp >> 3) * 128 + ((warp & 7) ^ n7) * 16 + (g & 3) * 4;
            #pragma unroll
            for (int i = 0; i < 9; i++) sts32(a + i * 2048, pack_bf(fmaf(v0[i], r, mr), fmaf(v1[i], r, mr)));
        }
        __syncthreads();
        PROF0(12);
        #pragma unroll
        for (int u = 0; u < 3; u++) {
            const int e = tid + 512 * u;
            if (e < 1152) g_h3[b * 1152 + e] = lds128(sm + OFF_STAGE + ((e & ~7) | ((e ^ (e >> 4)) & 7)) * 16);
        }
        #pragma unroll
        for (int i = 0; i < 9; i++) sts32(sm + OFF_X1 + warp * 1152 + (32 * i + 8 * q + g) * 4, xw[i]);
    }
    __syncthreads();
    if (rowcta) {
        if (tid == 0) { fence_async_g(); red_release(g_cnt + CNT_H3 * 32); }
        PROF0(13);
        if (warp == 15) {
            __nanosleep(X1DELAY);
            #pragma unroll 1
            for (int r = 0; r < 16; r++) {
                uint4* dst = (uint4*)(p.out + (size_t)(b + 128 * r) * D_) + lane;
                const uint32_t src = sm + OFF_X1 + r * 1152 + lane * 16;
                dst[0] = lds128(src); dst[32] = lds128(src + 512); if (lane < 8) dst[64] = lds128(src + 1024);
                const uint32_t t1 = clk32(); while ((int)(clk32() - t1) < X1PACE) __nanosleep(50);
            }
            __syncwarp();
            if (lane == 0) { fence_async_g(); red_release(g_cnt + CNT_X1 * 32); }
        }
    }
    role = __shfl_sync(~0u, lds32(sm + OFF_MISC), 0);
    if (role >= 64) { if (warp == 0) PROFDUMP(); return; }

    const int gi = role >> 3, dt = role & 3, c2 = (role >> 2) & 1;
    const int wg = warp >> 2, wi = warp & 3;
    if (wg == 3) {
        uint32_t so = 0, eph = 1;
        #define RING_STEP(BYTES, OFF, ISSUE) do { \
            mbar_wait(bars + 8 * BAR_EMPTY + so, eph); \
            if (elect()) { const uint32_t fb = bars + 8 * BAR_FULL + so, dst = sm + (OFF) + so * ((BYTES) / 8); mbar_expect(fb, BYTES); ISSUE; } \
            so += 8; if (so == 8 * NST) { so = 0; eph ^= 1; } } while (0)
        if (warp == 12) {
            eph = 0;
            const int fb1 = 9 * gi + 4 * c2 + 2 * rank, sb2 = 4 * gi + 2 * c2;
            #pragma unroll 1
            for (int j = 16; j < 128; j += 4) {
                RING_STEP(A_BYTES, OFF_A, tma4(dst, &tm_w1a, 0, 0, j, fb1, fb));
                if (j < 64) { if (j & 4) RING_STEP(A_BYTES, OFF_A, tma4(dst, &tm_w1b, 0, 0, 64 * rank + j - 4, 9 * gi + 8, fb)); }
                else if (PF2 && (j & 28) == 4 * (role & 7) && elect())
                    asm volatile("cp.async.bulk.prefetch.tensor.3d.L2.global [%0, {%1, %2, %3}];" :: "l"(&tm_w2), "r"(0), "r"(64 * g2_kb(dt + ((j >> 3) & 4), rank)), "r"(sb2) : "memory");
            }
            #pragma unroll 1
            for (int n = 0; n < 36; n++) {
                if (n == G2E) mbar_wait(bars + 8 * BAR_REL, 0);
                if (n == A2E) { mbar_wait(bars + 8 * (BAR_UOK + 1), 0); if (A2D) spin_until(clk32() + A2D); }
                RING_STEP(A_BYTES, OFF_A, tma3(dst, &tm_w2, 0, 64 * g2_kb(n, rank), sb2, fb));
            }
        } else if (warp == 13) {
            const uint32_t e1 = __shfl_sync(~0u, epoch + 1, 0);
            fence_async_s();
            wait_count<0>(g_cnt + CNT_H3 * 32, e1 * 128);
            fence_async_g();
            if (lane == 0) PROFT(14);
            #pragma unroll 1
            for (int j = 0; j < 128; j += 4) {
                RING_STEP(B_BYTES, OFF_B, tma3(dst, &tm_h3a, 0, 18 * dt, j, fb));
                if (j < 64 && (j & 4)) RING_STEP(B_BYTES, OFF_B, tma3(dst, &tm_h3b, 0, 18 * dt + 9 * c2, 64 * rank + j - 4, fb));
            }
            int n = 0;
            #pragma unroll 1
            for (int cls = 0; cls < 3; cls++) {
                mbar_wait(bars + 8 * (BAR_UOK + cls), 0);
                fence_async_g();
                if (cls == 1 && lane == 0) PROFT(19);
                if (cls == 0 && lane == 0) PROFT(22);
                #pragma unroll 1
                for (; n < 16 * cls + 4; n++) {
                    if (n == G2E) mbar_wait(bars + 8 * BAR_REL, 0);
                    RING_STEP(B_BYTES, OFF_B, bulk_load(dst, g_U + (g2_kb(n, rank) * 4 + dt) * 1152, B_BYTES, fb));
                }
            }
            if (role == 0 && rank == 0 && lane == 0) st_relaxed(g_cnt + CNT_EPOCH * 32, e1);
        } else if (warp == 15) {
            if (elect()) mbar_arrive_remote(mapa(bars + 8 * BAR_HOLD, rank ^ 1));
            __syncwarp();
            bar_sync(6, 160);
            mbar_wait(bars + 8 * BAR_W1GO, 0);
            if (elect()) {
                char* dst = (char*)(g_U + ((9 * gi + 4 * c2 + 2 * rank + 1) * 4 + dt) * 1152);
                #pragma unroll 1
                for (int i = 0; i < W1N; i++) {
                    asm volatile("cp.async.bulk.global.shared::cta.bulk_group [%0], [%1], %2;" :: "l"(dst + i * (18432 / W1N)), "r"(sm + OFF_X1 + i * (18432 / W1N)), "n"(18432 / W1N) : "memory");
                    const uint32_t t1 = clk32(); while ((int)(clk32() - t1) < W1P) {}
                }
                asm volatile("cp.async.bulk.commit_group;" ::: "memory");
                asm volatile("cp.async.bulk.wait_group 0;" ::: "memory");
                fence_async_g(); red_release(g_cnt + (CNT_U + 16 + UIDX(dt, gi >> 2)) * 32);
                #pragma unroll 1
                for (int n = 0; n < 4; n++) { __nanosleep(300); tma2(sm + OFF_X1 + n * 4608, &tm_o, 144 * dt, 256 * gi + 128 * c2 + 64 * (rank ^ 1) + 16 * n, bars + 8 * BAR_XT); }
            }
        } else {
            const uint32_t e1 = epoch + 1;
            if (lane == 0) {
                __nanosleep(4000);
                wait_count<200>(g_cnt + CNT_NC * 32, e1 * 4); wait_count<200>(g_cnt + (CNT_NC + 1) * 32, e1 * 2);
                fence_async_g();
                mbar_expect(bars + 8 * BAR_GB, 1152);
                bulk_load(sm + OFF_GB, p.scr->modc + 896, 1152, bars + 8 * BAR_GB);
                wait_count<200>(g_cnt + CNT_X1 * 32, e1 * 128);
                wait_count<50>(g_cnt + (CNT_U + dt * 2 + rank) * 32, e1 * 16);
                mbar_arrive(bars + 8 * BAR_UOK);
            }
            __syncwarp();
            bar_sync(4, 160);
            if (lane == 0) {
                fence_async_g(); red_release(g_cnt + (CNT_U + 8 + UIDX(dt, gi >> 2)) * 32);
                mbar_arrive(bars + 8 * BAR_REL);
                PROFT(17);
                wait_count<0>(g_cnt + (CNT_U + 8 + UIDX(dt, rank)) * 32, e1 * UCNT);
                mbar_arrive(bars + 8 * (BAR_UOK + 1));
                __nanosleep(1000);
                wait_count<100>(g_cnt + (CNT_U + 16 + UIDX(dt, rank)) * 32, e1 * UCNT);
                mbar_arrive(bars + 8 * (BAR_UOK + 2));
            }
        }
    } else if (wg == 2) {
        float d0[36];
        const float bias = bf_lo(ldg_nc16(p.b1 + 576 * gi + 512 + 16 * wi + g + 8 * rank));
        for (int it = 0; it < 200 && !__any_sync(~0u, mbar_test(bars + 8 * BAR_FULL, 0)); it++) { hb(); __nanosleep(100); }
        const bool lead = wi == 0 && elect();
        #pragma unroll 1
        for (int i = 0; i < 8; i++) {
            const uint32_t s = P2S + 3 * (i & 1);
            mbar_wait(bars + 8 * BAR_FULL + 8 * s, (i >> 1) & 1);
            const uint32_t da = desc_lo(sm + OFF_A, 8192) + s * (A_BYTES / 16), db = desc_lo(sm + OFF_B, 128) + s * (B_BYTES / 16);
            WG_FENCE();
            wgmma72(d0, da, db, i);
            #pragma unroll
            for (int k = 1; k < 8; k++) wgmma72(d0, da + k * 128, db + k * 144, 1);
            WG_COMMIT();
            WG_WAIT(0);
            if (lead) mbar_arrive_n(bars + 8 * BAR_EMPTY + 8 * s, 2);
        }
        if (lead) PROFT(18);
        const uint32_t slot = sm + OFF_P2R + (tid & 127) * 16, ra = mapa(slot, rank ^ 1), rb = mapa(bars + 8 * BAR_P2R, rank ^ 1);
        float sv[18];
        #pragma unroll
        for (int i = 0; i < 18; i++) { const float lo = d0[4 * (i >> 1) + (i & 1)], hi = d0[4 * (i >> 1) + 2 + (i & 1)];
            sv[i] = rank ? lo : hi; d0[4 * (i >> 1) + (i & 1)] = (rank ? hi : lo) + bias; }
        mbar_wait(bars + 8 * BAR_HOLD, 0);
        #pragma unroll
        for (int i = 0; i < 4; i++)
            asm volatile("st.async.weak.shared::cluster.mbarrier::complete_tx::bytes.v4.f32 [%0], {%1,%2,%3,%4}, [%5];"
                :: "r"(ra + i * 2048), "f"(sv[4 * i]), "f"(sv[4 * i + 1]), "f"(sv[4 * i + 2]), "f"(sv[4 * i + 3]), "r"(rb) : "memory");
        asm volatile("st.async.weak.shared::cluster.mbarrier::complete_tx::bytes.v2.f32 [%0], {%1,%2}, [%3];" :: "r"(ra + 8192), "f"(sv[16]), "f"(sv[17]), "r"(rb) : "memory");
        mbar_wait(bars + 8 * BAR_P2R, 0);
        #pragma unroll
        for (int i = 0; i < 5; i++) {
            const uint4 v = lds128(slot + i * 2048);
            d0[8 * i] += __uint_as_float(v.x); d0[8 * i + 1] += __uint_as_float(v.y);
            if (i < 4) { d0[8 * i + 4] += __uint_as_float(v.z); d0[8 * i + 5] += __uint_as_float(v.w); }
        }
        asm volatile("bar.arrive 5, 256;" ::: "memory");
        gelu_store<0>(d0, (char*)(g_U + ((9 * gi + 8) * 4 + dt) * 1152) + wi * 4608 + rank * 2304 + c2 * 1152 + g * 16, q);
        bar_sync(8, 128);
        if (lead) { fence_async_g(); red_release(g_cnt + (CNT_U + dt * 2 + (gi >> 2)) * 32); PROFT(26); }
    } else {
        float d[72];
        const bool lead = wi == 0 && elect();
        const uint32_t da0 = desc_lo(sm + OFF_A + wg * 8192, 8192);
        const bool owner = (uint32_t)wg == rank;
        const int srow = 256 * gi + 128 * c2 + 64 * wg + 16 * wi;
        const uint32_t b2w0 = ldg_nc16(p.b2 + srow + g), b2w1 = ldg_nc16(p.b2 + srow + g + 8);
        {
            const int fr = 576 * gi + 256 * c2 + 128 * rank + 64 * wg + 16 * wi + g;
            const float bias0 = bf_lo(ldg_nc16(p.b1 + fr)), bias1 = bf_lo(ldg_nc16(p.b1 + fr + 8));
            #pragma unroll
            for (int i = 0; i < 72; i++) d[i] = (i & 2) ? bias1 : bias0;
            const uint32_t db1 = desc_lo(sm + OFF_B, 128);
            mainloop<DHI_H3, 0, IT_P1, false, true, false>(d, bars, da0, db1, lead, [&](int) {});
            mainloop<DHI_H3, IT_P1, IT_G2 - LEAD1, false, false, false>(d, bars, da0, db1, lead, [&](int) {});
            constexpr uint32_t EB = 8 * (BAR_EMPTY + (IT_G2 - LEAD1 - 1) % NST);
            if (wg == 1) { WG_WAIT(0); if (lead) mbar_arrive(bars + EB); bar_sync(9, 256); }
            mainloop<DHI_H3, IT_G2 - LEAD1, IT_G2, false, true, true>(d, bars, da0, db1, lead, [&](int i) {
                if (wg == 0) { if (i == IT_G2 - LEAD1 && lead) mbar_arrive(bars + EB); if (i == IT_G2 - 1) asm volatile("bar.arrive 9, 256;" ::: "memory"); } });
            PROF0(16);
            if (wg == 1) bar_sync(5, 256);
            char* const ub = (wg == 0 ? (char*)(g_U + ((9 * gi + 4 * c2 + 2 * rank) * 4 + dt) * 1152) : (char*)__cvta_shared_to_generic(sm + OFF_X1)) + wi * 4608 + g * 16;
            gelu_store<0>(d, ub, q); gelu_store<2>(d, ub + 2304, q); gelu_store<36>(d, ub + 1152, q); gelu_store<38>(d, ub + 3456, q);
            PROF0(27);
            if (wg == 0) asm volatile("bar.arrive 4, 160;" ::: "memory");
            else { fence_async_s(); asm volatile("bar.arrive 6, 160;" ::: "memory"); }
        }
        const uint32_t db0 = desc_lo(sm + OFF_B, 2304);
        constexpr int IT_L = IT_END - NST, IT_X = IT_L - 4;
        mainloop<DHI_U, IT_G2, IT_X, true, true, false>(d, bars, da0, db0, lead,
            [&](int i) { if (i == IT_G2 + W1S && wg == 0 && lead) mbar_arrive(bars + 8 * BAR_W1GO); });
        const uint32_t ga0 = sm + OFF_GB + (144 * dt + 8 * q) * 2, tile = sm + OFF_X1 + wi * 4608, to = g * 288 + q * 16;
        #define QOFF(i_) (((i_) >> 2) * 2304 + 144 * (((i_) >> 1) & 1) + 64 * ((i_) & 1))
        #define SOFF(k_) (((k_) >> 1) * 2304 + 144 * ((k_) & 1) + 128 - 12 * q)
        #define DIDX(i_, k_) ((i_) < 8 ? 36 * (((i_) >> 1) & 1) + 16 * ((i_) & 1) + 4 * (k_) + 2 * ((i_) >> 2) : 36 * ((k_) & 1) + 32 + 2 * ((k_) >> 1))
        #define FIN(k_, f_) bfma2(g4.f_, pack_bf(d[DIDX(i, k_)], d[DIDX(i, k_) + 1]), xq[i].f_)
        uint4 xq[9];
        auto load_g = [&](int i) { uint4 r; if (i < 4) r = lds128(ga0 + QOFF(i)); else { r.x = r.z = lds32(ga0 + SOFF(0)); r.y = r.w = lds32(ga0 + SOFF(1)); } return r; };
        mainloop<DHI_U, IT_X, IT_L, false, false, false>(d, bars, da0, db0, lead, [&](int i) {
            if (!owner) {
                const uint32_t xa = tile + to;
                if (i == IT_X) { mbar_wait(bars + 8 * BAR_XT, 0); xq[0] = lds128(xa + QOFF(0)); xq[4] = lds128(xa + QOFF(4)); xq[1] = lds128(xa + QOFF(1)); }
                else if (i == IT_X + 1) { xq[5] = lds128(xa + QOFF(5)); xq[2] = lds128(xa + QOFF(2)); xq[6] = lds128(xa + QOFF(6)); }
                else if (i == IT_X + 2) { xq[3] = lds128(xa + QOFF(3)); xq[7] = lds128(xa + QOFF(7));
                    xq[8] = make_uint4(lds32(xa + SOFF(0)), lds32(xa + SOFF(1)), lds32(xa + SOFF(2)), lds32(xa + SOFF(3))); }
                else if (i == IT_X + 3) { if (elect()) mbar_arrive_remote(mapa(bars + 8 * BAR_DONE, rank ^ 1)); }
            } });
        if (owner) { WG_WAIT(0); if (lead) mbar_arrive(bars + 8 * (BAR_EMPTY + (IT_L - 1) % NST)); bar_sync(7, 256); }
        #pragma unroll
        for (int i = IT_L; i < IT_END; i++) {
            mbar_wait(bars + 8 * (BAR_FULL + i % NST), (i / NST) & 1);
            WG_FENCE();
            #pragma unroll
            for (int k = 0; k < 4; k++) wgmma144<DHI_U>(d, da0 + (i % NST) * (A_BYTES / 16) + k * 128, db0 + (i % NST) * (B_BYTES / 16) + k * 288, 1);
            WG_COMMIT();
            if (i == IT_L) { WG_WAIT(1); if (lead && !owner) mbar_arrive(bars + 8 * (BAR_EMPTY + (IT_L - 1) % NST)); }
        }
        PROF0(9);
        mbar_wait(bars + 8 * BAR_GB, 0);
        if (!owner) {
            const uint32_t ra = mapa(tile + lane * 16, rank ^ 1), rb = mapa(bars + 8 * BAR_RECV, rank ^ 1);
            mbar_wait(bars + 8 * BAR_DONE, 0);
            uint4 gn = load_g(0);
            WG_WAIT(1);
            asm volatile("bar.arrive 7, 256;" ::: "memory");
            WG_WAIT(0);
            #pragma unroll
            for (int i = 0; i < 72; i++) d[i] = fmaf(bf_lo((i & 2) ? b2w1 : b2w0), 2.f, d[i]);
            #pragma unroll
            for (int j = 0; j < 5; j++) {
                const uint4 g4 = gn;
                if (j < 4) gn = load_g(j + 1);
                #pragma unroll
                for (int i = j < 4 ? j : 8; i < 9; i += 4) if (i < 8 || j == 4)
                    asm volatile("st.async.weak.shared::cluster.mbarrier::complete_tx::bytes.v4.b32 [%0], {%1,%2,%3,%4}, [%5];"
                        :: "r"(ra + i * 512), "r"(FIN(0, x)), "r"(FIN(1, y)), "r"(FIN(2, z)), "r"(FIN(3, w)), "r"(rb) : "memory");
            }
            PROF0(6);
            if (warp == 0) PROFDUMP();
            return;
        }
        PROF0(24);
        mbar_wait(bars + 8 * BAR_RECV, 0);
        #pragma unroll
        for (int i = 0; i < 9; i++) xq[i] = lds128(tile + lane * 16 + i * 512);
        uint4 gn = load_g(0);
        WG_WAIT(0);
        __syncwarp();
        PROF0(21);
        #pragma unroll
        for (int j = 0; j < 5; j++) {
            const uint4 g4 = gn;
            if (j < 4) gn = load_g(j + 1);
            #pragma unroll
            for (int i = j < 4 ? j : 8; i < 9; i += 4) if (i < 8 || j == 4) {
                const uint4 o = make_uint4(FIN(0, x), FIN(1, y), FIN(2, z), FIN(3, w));
                if (i < 8) sts128(tile + to + QOFF(i), o);
                else { sts32(tile + to + SOFF(0), o.x); sts32(tile + to + SOFF(1), o.y); sts32(tile + to + SOFF(2), o.z); sts32(tile + to + SOFF(3), o.w); }
            }
        }
        fence_async_s();
        __syncwarp();
        if (elect()) {
            asm volatile("cp.async.bulk.tensor.2d.global.shared::cta.bulk_group [%0, {%2, %3}], [%1];" :: "l"(&tm_o), "r"(tile), "r"(144 * dt), "r"(srow) : "memory");
            asm volatile("cp.async.bulk.commit_group;" ::: "memory");
            asm volatile("cp.async.bulk.wait_group.read 0;" ::: "memory");
        }
        PROF0(23);
        if (warp == 0) { __syncwarp(); PROFDUMP(); }
    }
}

typedef CUresult (*EncodeFn)(CUtensorMap*, CUtensorMapDataType, cuuint32_t, void*, const cuuint64_t*, const cuuint64_t*, const cuuint32_t*,
                             const cuuint32_t*, CUtensorMapInterleave, CUtensorMapSwizzle, CUtensorMapL2promotion, CUtensorMapFloatOOBfill);

void encode(EncodeFn fn, CUtensorMap* m, CUtensorMapDataType dt, int rank, const void* ptr, const cuuint64_t* dims, const cuuint64_t* strides,
            const cuuint32_t* box, CUtensorMapSwizzle sw, CUtensorMapL2promotion promo = CU_TENSOR_MAP_L2_PROMOTION_L2_128B) {
    const cuuint32_t es[5] = {1, 1, 1, 1, 1};
    fn(m, dt, rank, (void*)ptr, dims, strides, box, es, CU_TENSOR_MAP_INTERLEAVE_NONE, sw, promo, CU_TENSOR_MAP_FLOAT_OOB_FILL_NONE);
}

}

extern "C" void kernel_launch(void* const* d_in, const int* in_sizes, int n_in, void* d_out, int out_size) {
    (void)in_sizes; (void)n_in; (void)out_size;
    Params p;
    p.x = (const uint16_t*)d_in[0]; p.wr = (const uint16_t*)d_in[1]; p.wi = (const uint16_t*)d_in[2];
    p.w1 = (const uint16_t*)d_in[4]; p.b1 = (const uint16_t*)d_in[5]; p.w2 = (const uint16_t*)d_in[6]; p.b2 = (const uint16_t*)d_in[7];
    p.c = (const uint16_t*)d_in[8]; p.wmod = (const uint16_t*)d_in[9]; p.out = (uint16_t*)d_out;

    void* fnp = nullptr; cudaDriverEntryPointQueryResult qr;
    cudaGetDriverEntryPoint("cuTensorMapEncodeTiled", &fnp, cudaEnableDefault, &qr);
    EncodeFn fn = (EncodeFn)fnp;
    cudaGetSymbolAddress((void**)&p.scr, g_scr); cudaGetSymbolAddress((void**)&p.tab, g_tab);
    void* h3p = p.scr->h3;
    CUtensorMap tw1a, tw1b, tw2, th3a, th3b, twr, twi, twm, tt, ttx, to;
    {
        const cuuint64_t dims[4] = {64, 16, 128, 72}, st[3] = {128ull * F_ * 2, (cuuint64_t)F_ * 2, 128};
        const cuuint32_t ba[4] = {64, 16, 4, 2}, bb[4] = {64, 16, 8, 1};
        encode(fn, &tw1a, CU_TENSOR_MAP_DATA_TYPE_BFLOAT16, 4, p.w1, dims, st, ba, CU_TENSOR_MAP_SWIZZLE_128B);
        encode(fn, &tw1b, CU_TENSOR_MAP_DATA_TYPE_BFLOAT16, 4, p.w1, dims, st, bb, CU_TENSOR_MAP_SWIZZLE_128B);
    }
    {
        const cuuint64_t dims[3] = {64, F_, 32}, st[2] = {(cuuint64_t)S_ * 2, 128};
        const cuuint32_t bx[3] = {64, 64, 2};
        encode(fn, &tw2, CU_TENSOR_MAP_DATA_TYPE_BFLOAT16, 3, p.w2, dims, st, bx, CU_TENSOR_MAP_SWIZZLE_128B);
    }
    {
        const cuuint64_t dims[3] = {64, 72, 128}, st[2] = {256, 18432};
        const cuuint32_t ba[3] = {64, 18, 4}, bb[3] = {64, 9, 8};
        encode(fn, &th3a, CU_TENSOR_MAP_DATA_TYPE_UINT32, 3, h3p, dims, st, ba, CU_TENSOR_MAP_SWIZZLE_NONE);
        encode(fn, &th3b, CU_TENSOR_MAP_DATA_TYPE_UINT32, 3, h3p, dims, st, bb, CU_TENSOR_MAP_SWIZZLE_NONE);
    }
    {
        const cuuint64_t dims[3] = {4624, 4, 32}, st[2] = {9248 * 32, 9248};
        const cuuint32_t bx[3] = {56, 4, 32};
        encode(fn, &twr, CU_TENSOR_MAP_DATA_TYPE_BFLOAT16, 3, p.wr, dims, st, bx, CU_TENSOR_MAP_SWIZZLE_NONE);
        encode(fn, &twi, CU_TENSOR_MAP_DATA_TYPE_BFLOAT16, 3, p.wi, dims, st, bx, CU_TENSOR_MAP_SWIZZLE_NONE);
    }
    {
        const cuuint64_t dims[3] = {64, 576, 54}, st[2] = {6912, 128};
        const cuuint32_t bx[3] = {64, 32, 7};
        encode(fn, &twm, CU_TENSOR_MAP_DATA_TYPE_BFLOAT16, 3, p.wmod, dims, st, bx, CU_TENSOR_MAP_SWIZZLE_128B);
    }
    {
        const cuuint64_t dims[2] = {TP, 128}, st[1] = {TP * 4};
        const cuuint32_t ba[2] = {32, 128}, bb[2] = {8, 128};
        encode(fn, &tt, CU_TENSOR_MAP_DATA_TYPE_UINT32, 2, p.scr->T, dims, st, ba, CU_TENSOR_MAP_SWIZZLE_128B, CU_TENSOR_MAP_L2_PROMOTION_NONE);
        encode(fn, &ttx, CU_TENSOR_MAP_DATA_TYPE_UINT32, 2, p.scr->T, dims, st, bb, CU_TENSOR_MAP_SWIZZLE_32B, CU_TENSOR_MAP_L2_PROMOTION_NONE);
    }
    {
        const cuuint64_t dims[2] = {D_, S_}, st[1] = {D_ * 2};
        const cuuint32_t bx[2] = {144, 16};
        encode(fn, &to, CU_TENSOR_MAP_DATA_TYPE_BFLOAT16, 2, p.out, dims, st, bx, CU_TENSOR_MAP_SWIZZLE_NONE, CU_TENSOR_MAP_L2_PROMOTION_NONE);
    }
    cudaFuncSetAttribute(fused_kernel, cudaFuncAttributeMaxDynamicSharedMemorySize, SMEM_BYTES);
    cudaLaunchConfig_t cfg = {};
    cfg.gridDim = dim3(NCTA); cfg.blockDim = dim3(NTHR); cfg.dynamicSmemBytes = SMEM_BYTES; cfg.stream = cudaStreamPerThread;
    cudaLaunchAttribute at[1];
    at[0].id = cudaLaunchAttributeCooperative; at[0].val.cooperative = 1;
    cfg.attrs = at; cfg.numAttrs = 1;
    cudaLaunchKernelEx(&cfg, fused_kernel, p, tw1a, tw1b, tw2, th3a, th3b, twr, twi, twm, tt, ttx, to);
}
```

```cpp
#include <cuda_runtime.h>
#include <cuda_bf16.h>
#include <cuda_fp16.h>
#include <cuda.h>
#include <stdint.h>

namespace {

constexpr int S_ = 2048, D_ = 576, F_ = 4608;
constexpr int NCTA = 132, NTHR = 512;
constexpr int TP = 4736;
constexpr int SPEC_P = 296;
constexpr int NST = 6;
constexpr int A_BYTES = 16384, B_BYTES = 18432;
constexpr int IT_P1 = 24, IT_G2 = 40, IT_END = 76;
constexpr int SPIN_LIMIT = 1 << 22;
#define UIDX(dt_, kh_) 0
#define UCNT 128
#define MODPAD 16
#define X2D 1300
#define CPHINT ".L2::128B"
constexpr int P2S = 2;
#define G2E 4
#define LEAD1 4
#define A2E 6
#define A2D 100
#define W1N 8
#define W1P 100
#define W1S 4
#define XDELAY 1600
#define X1D 2300
#define PF2 1
#define X1DELAY 2000
#define X1PACE 400

constexpr int OFF_A = 0;
constexpr int OFF_B = NST * A_BYTES;
constexpr int OFF_P = OFF_B + NST * B_BYTES;
constexpr int OFF_BAR = OFF_P;
constexpr int OFF_MISC = OFF_P + 376;
constexpr int OFF_GB = OFF_P + 384;
constexpr int OFF_P2R = OFF_P + 1536;
constexpr int OFF_X1 = OFF_P2R;
constexpr int OFF_PROF = OFF_X1 + 18432;
constexpr int SMEM_BYTES = OFF_PROF + 512 + 1024;
constexpr int QA = 13, QB = 7, QC = 13;
constexpr int TAB_BYTES = (QA + QB + QC) * 512;
constexpr int OFF_STAGE = OFF_B;
constexpr int OFF_STX = OFF_STAGE + 16384;
constexpr int OFF_TAB = OFF_STAGE + 20480;
constexpr int OFF_SPEC = OFF_TAB + TAB_BYTES;
constexpr int OFF_WRAW = OFF_SPEC + 19072;
constexpr int OFF_B3 = OFF_WRAW + 28672;
constexpr int OFF_MODA = OFF_B3 + 4096;
constexpr int OFF_MODC = OFF_MODA + 2560;
constexpr int OFF_RED = OFF_MODC + 3584;
constexpr int OFF_SILU = OFF_RED + 768;
static_assert(OFF_SILU + 1152 <= OFF_P && 6 * 28672 <= OFF_B3, "scratch overflow");
constexpr int OFF_STRIP = OFF_A;
static_assert(OFF_WRAW % 128 == 0 && OFF_STAGE % 128 == 0 && OFF_STX % 128 == 0, "align");
constexpr int BAR_FULL = 0, BAR_EMPTY = 6, BAR_TAB = 12, BAR_W = 13, BAR_REL = 14, BAR_P2R = 16,
              BAR_XT = 17, BAR_RECV = 18, BAR_ROLE = 19, BAR_NC = 20, BAR_TAB2 = 21, BAR_XB = 22, BAR_GB = 23, BAR_HOLD = 24, BAR_W1GO = 25, BAR_UOK = 26, BAR_DONE = 30, BAR_X = 31;

struct Cos1152 { double c[1152]; };
constexpr double cx_cos(double x) { double t = 1, s = 1; for (int i = 1; i < 14; i++) { t *= -x * x / ((2 * i - 1) * (2 * i)); s += t; } return s; }
constexpr Cos1152 make_cos() {
    Cos1152 r{};
    for (int i = 0; i <= 288; i++) {
        double v = (i == 288) ? 0.0 : cx_cos(3.14159265358979323846 * 2.0 * i / 1152.0);
        r.c[i] = v; r.c[576 - i] = -v; r.c[576 + i] = -v; r.c[(1152 - i) % 1152] = v;
    }
    return r;
}
constexpr uint32_t cx_f2h(double v) {
    uint32_t s = v < 0 ? 0x8000u : 0u; double a = v < 0 ? -v : v;
    if (a < 1e-9) return 0;
    int e = 0;
    while (a >= 2.0) { a *= 0.5; e++; }
    while (a < 1.0 && e > -14) { a *= 2.0; e--; }
    double m = a * 1024.0; uint32_t mi = (uint32_t)m; double fr = m - mi;
    if (fr > 0.5 || (fr == 0.5 && (mi & 1))) mi++;
    return s | (uint32_t)(((e + 14) << 10) + mi);
}
struct Tab { uint32_t w[(QA + QB + QC) * 128]; };
constexpr Tab make_tab() {
    Tab t{};
    Cos1152 ct = make_cos();
    auto C = [&](int num, int den) { return ct.c[(num % den) * (1152 / den)]; };
    auto Sn = [&](int num, int den) { return ct.c[((num % den) * (1152 / den) + 864) % 1152]; };
    auto put = [&](int q0, int idx, int lane, double lo, double hi) { t.w[((q0 + idx / 4) * 32 + lane) * 4 + idx % 4] = cx_f2h(lo) | (cx_f2h(hi) << 16); };
    for (int lane = 0; lane < 32; lane++) {
        const int g = lane >> 2, q = lane & 3;
        for (int mt = 0; mt < 3; mt++) {
            const int ka = 8 * mt + g;
            for (int r = 0; r < 10; r++) {
                const int im = r & 1, i0 = (r >> 1) * 2;
                double v[2] = {0, 0};
                for (int e = 0; e < 2; e++) { int i = i0 + e, d1 = 4 * i + q; if (i < 9 && ka <= 18) v[e] = (im ? -Sn(ka * d1, 36) : C(ka * d1, 36)) / 8; }
                put(0, mt * 10 + r, lane, v[0], v[1]);
            }
            for (int v = 0; v < 2; v++) {
                const int d2 = 4 * q + v;
                put(0, 30 + (mt * 2 + v) * 2, lane, C(ka * d2, 576) * 4 / 3, C(ka * (d2 + 2), 576) * 4 / 3);
                put(0, 31 + (mt * 2 + v) * 2, lane, Sn(ka * d2, 576) * 4 / 3, Sn(ka * (d2 + 2), 576) * 4 / 3);
            }
        }
        for (int v = 0; v < 2; v++) for (int nt = 0; nt < 2; nt++) {
            const int kb = 2 * (g >> 1) + nt, part = g & 1;
            double b0[2] = {0, 0}, b1[2] = {0, 0};
            for (int e = 0; e < 2; e++) { int d2 = 4 * q + 2 * e + v; double c = C(kb * d2, 16) / 4, s = Sn(kb * d2, 16) / 4;
                b0[e] = part ? -s : c; b1[e] = part ? c : s; }
            put(0, 42 + (v * 2 + nt) * 2, lane, b0[0], b0[1]); put(0, 43 + (v * 2 + nt) * 2, lane, b1[0], b1[1]);
        }
        for (int par = 0; par < 2; par++) for (int a = 0; a < 4; a++) {
            const int ja = 2 * (q + 4 * (a >> 1)) + par; const double c = C(g * ja, 16) / 4, s = Sn(g * ja, 16) / 4;
            put(QA, par * 4 + a, lane, (a & 1) ? -s : c, (a & 1) ? c : s);
        }
        for (int h = 0; h < 2; h++) {
            put(QA, 8 + 2 * h, lane, C((g + 8 * h) * (2 * q), 128) / 2, C((g + 8 * h) * (2 * q + 1), 128) / 2);
            put(QA, 9 + 2 * h, lane, Sn((g + 8 * h) * (2 * q), 128) / 2, Sn((g + 8 * h) * (2 * q + 1), 128) / 2);
            put(QA, 15 + 2 * h, lane, C(g * (8 * h + 2 * q), 128), C(g * (8 * h + 2 * q + 1), 128));
            put(QA, 16 + 2 * h, lane, Sn(g * (8 * h + 2 * q), 128), Sn(g * (8 * h + 2 * q + 1), 128));
        }
        put(QA, 12, lane, C(g * 2 * q, 8) / 2, C(g * (2 * q + 1), 8) / 2);
        put(QA, 13, lane, Sn(g * 2 * q, 8) / 2, Sn(g * (2 * q + 1), 8) / 2);
        put(QA, 14, lane, -Sn(g * 2 * q, 8) / 2, -Sn(g * (2 * q + 1), 8) / 2);
        for (int u = 0; u < 4; u++) {
            const int ja = 2 * ((g >> 1) + 4 * (u & 1)) + (u >> 1), part = g & 1; double b0[2] = {0, 0}, b1[2] = {0, 0};
            for (int e = 0; e < 2; e++) { int ka = 2 * q + e; double c = C(ja * ka, 16) / 4, s = Sn(ja * ka, 16) / 4;
                b0[e] = part ? s : c; b1[e] = part ? c : -s; }
            put(QA, 19 + u * 2, lane, b0[0], b0[1]); put(QA, 20 + u * 2, lane, b1[0], b1[1]);
        }
        for (int m2 = 0; m2 < 2; m2++) {
            const int d2 = 2 * g + m2;
            for (int a = 0; a < 4; a++) {
                const int kb = 2 * q + (a >> 1); const double c = C(d2 * kb, 16) / 4, s = Sn(d2 * kb, 16) / 4;
                put(QA + QB, m2 * 4 + a, lane, (a & 1) ? s : c, (a & 1) ? c : -s);
            }
            for (int mt = 0; mt < 3; mt++) {
                const int ka = 8 * mt + 2 * q;
                put(QA + QB, 8 + (m2 * 3 + mt) * 2, lane, C(ka * d2, 576) * 4 / 3, C((ka + 1) * d2, 576) * 4 / 3);
                put(QA + QB, 9 + (m2 * 3 + mt) * 2, lane, Sn(ka * d2, 576) * 4 / 3, Sn((ka + 1) * d2, 576) * 4 / 3);
            }
        }
        for (int mt = 0; mt < 3; mt++) for (int nt = 0; nt < 5; nt++) {
            const int i = 2 * nt + (g & 1), d1 = 4 * i + (g >> 1); double b0[2] = {0, 0}, b1[2] = {0, 0};
            for (int e = 0; e < 2; e++) { int ka = 8 * mt + 2 * q + e;
                if (ka <= 18 && i < 9) { double wt = (ka == 0 || ka == 18) ? 0.125 : 0.25; b0[e] = wt * C(ka * d1, 36); b1[e] = -wt * Sn(ka * d1, 36); } }
            put(QA + QB, 20 + (mt * 5 + nt) * 2, lane, b0[0], b0[1]); put(QA + QB, 21 + (mt * 5 + nt) * 2, lane, b1[0], b1[1]);
        }
    }
    return t;
}
__device__ __align__(128) const Tab g_tab = make_tab();

struct Scratch {
    uint32_t cnt[30 * 32];
    uint32_t slot[96];
    uint32_t mod[2304];
    uint32_t modc[896 + 288];
    uint32_t T[128 * TP];
    uint4 h3[128 * 1152];
    uint4 U[72 * 4 * 1152];
};
__device__ __align__(1024) Scratch g_scr;
#define g_cnt (p.scr->cnt)
#define g_slot (p.scr->slot)
#define g_mod (p.scr->mod)
#define g_T (p.scr->T)
#define g_h3 (p.scr->h3)
#define g_U (p.scr->U)
constexpr int CNT_EPOCH = 0, CNT_H3 = 1, CNT_X1 = 26, CNT_NC = 27, CNT_U = 2;
#define PROFT(i) do {} while (0)
#define PROFDUMP() do {} while (0)
#define PROF0(i) do {} while (0)

__device__ __forceinline__ void mbar_init(uint32_t bar, uint32_t cnt) { asm volatile("mbarrier.init.shared::cta.b64 [%0], %1;" :: "r"(bar), "r"(cnt) : "memory"); }
__device__ __forceinline__ void mbar_expect(uint32_t bar, uint32_t bytes) { asm volatile("mbarrier.arrive.expect_tx.shared::cta.b64 _, [%0], %1;" :: "r"(bar), "r"(bytes) : "memory"); }
__device__ __forceinline__ void mbar_arrive(uint32_t bar) { asm volatile("mbarrier.arrive.shared::cta.b64 _, [%0];" :: "r"(bar) : "memory"); }
__device__ __forceinline__ void mbar_arrive_n(uint32_t bar, uint32_t n) { asm volatile("mbarrier.arrive.shared::cta.b64 _, [%0], %1;" :: "r"(bar), "r"(n) : "memory"); }
__device__ __forceinline__ void mbar_arrive_remote(uint32_t rbar) { asm volatile("mbarrier.arrive.relaxed.cluster.shared::cluster.b64 _, [%0];" :: "r"(rbar) : "memory"); }
__device__ __forceinline__ void mbar_wait(uint32_t bar, uint32_t parity) {
    asm volatile("{.reg .pred p; .reg .u32 c;\n"
        "mbarrier.try_wait.parity.shared::cta.b64 p, [%0], %1;\n@p bra.uni DONE;\nmov.u32 c, 0;\n"
        "LOOP: mbarrier.try_wait.parity.shared::cta.b64 p, [%0], %1;\n@p bra.uni DONE;\n"
        "add.u32 c, c, 1;\nsetp.lt.u32 p, c, %2;\n@p bra.uni LOOP;\ntrap;\nDONE:}" :: "r"(bar), "r"(parity), "n"(SPIN_LIMIT) : "memory");
}
__device__ __forceinline__ bool mbar_test(uint32_t bar, uint32_t parity) {
    uint32_t ok; asm volatile("{.reg .pred p; mbarrier.test_wait.parity.shared::cta.b64 p, [%1], %2; selp.u32 %0, 1, 0, p;}" : "=r"(ok) : "r"(bar), "r"(parity) : "memory"); return ok; }
__device__ __forceinline__ uint32_t mapa(uint32_t a, uint32_t rank) { uint32_t r; asm("mapa.shared::cluster.u32 %0, %1, %2;" : "=r"(r) : "r"(a), "r"(rank)); return r; }
__device__ __forceinline__ uint32_t clk32() { uint32_t r; asm volatile("mov.u32 %0, %%clock;" : "=r"(r)); return r; }
__device__ __forceinline__ void hb() {
    asm volatile("{.reg .b32 a, b; .reg .pred p; mma.sync.aligned.m16n8k8.row.col.f16.f16.f16.f16 {a, b}, {%0,%0}, {%0}, {%0,%0};\n"
                 "setp.ne.u32 p, a, 0; @p trap;}" :: "r"(0));
}
__device__ __forceinline__ void spin_until(uint32_t t) { while (__any_sync(~0u, (int)(clk32() - t) < 0)) hb(); }
__device__ __forceinline__ bool elect() { uint32_t r; asm volatile("{.reg .pred p; elect.sync _|p, 0xffffffff; selp.u32 %0, 1, 0, p;}" : "=r"(r)); return r; }
__device__ __forceinline__ void bar_sync(int id, int n) { asm volatile("bar.sync %0, %1;" :: "r"(id), "r"(n) : "memory"); }
__device__ __forceinline__ void bulk_load(uint32_t dst, const void* src, uint32_t bytes, uint32_t bar) {
    asm volatile("cp.async.bulk.shared::cluster.global.mbarrier::complete_tx::bytes [%0], [%1], %2, [%3];" :: "r"(dst), "l"(src), "r"(bytes), "r"(bar) : "memory"); }
__device__ __forceinline__ void tma2(uint32_t dst, const CUtensorMap* m, int c0, int c1, uint32_t bar) {
    asm volatile("cp.async.bulk.tensor.2d.shared::cluster.global.mbarrier::complete_tx::bytes [%0], [%1, {%3, %4}], [%2];" :: "r"(dst), "l"(m), "r"(bar), "r"(c0), "r"(c1) : "memory"); }
__device__ __forceinline__ void tma3(uint32_t dst, const CUtensorMap* m, int c0, int c1, int c2, uint32_t bar) {
    asm volatile("cp.async.bulk.tensor.3d.shared::cluster.global.mbarrier::complete_tx::bytes [%0], [%1, {%3, %4, %5}], [%2];" :: "r"(dst), "l"(m), "r"(bar), "r"(c0), "r"(c1), "r"(c2) : "memory"); }
__device__ __forceinline__ void tma4(uint32_t dst, const CUtensorMap* m, int c0, int c1, int c2, int c3, uint32_t bar) {
    asm volatile("cp.async.bulk.tensor.4d.shared::cluster.global.mbarrier::complete_tx::bytes [%0], [%1, {%3, %4, %5, %6}], [%2];" :: "r"(dst), "l"(m), "r"(bar), "r"(c0), "r"(c1), "r"(c2), "r"(c3) : "memory"); }
__device__ __forceinline__ void fence_async_g() { asm volatile("fence.proxy.async.global;" ::: "memory"); }
__device__ __forceinline__ void fence_async_s() { asm volatile("fence.proxy.async.shared::cta;" ::: "memory"); }
__device__ __forceinline__ uint4 lds128(uint32_t a) { uint4 v; asm volatile("ld.shared.v4.u32 {%0,%1,%2,%3}, [%4];" : "=r"(v.x), "=r"(v.y), "=r"(v.z), "=r"(v.w) : "r"(a) : "memory"); return v; }
__device__ __forceinline__ uint32_t lds32(uint32_t a) { uint32_t v; asm volatile("ld.shared.u32 %0, [%1];" : "=r"(v) : "r"(a) : "memory"); return v; }
__device__ __forceinline__ void sts128(uint32_t a, uint4 v) { asm volatile("st.shared.v4.u32 [%0], {%1,%2,%3,%4};" :: "r"(a), "r"(v.x), "r"(v.y), "r"(v.z), "r"(v.w) : "memory"); }
__device__ __forceinline__ void sts32(uint32_t a, uint32_t v) { asm volatile("st.shared.u32 [%0], %1;" :: "r"(a), "r"(v) : "memory"); }
__device__ __forceinline__ void sts16(uint32_t a, uint32_t v) { asm volatile("st.shared.u16 [%0], %1;" :: "r"(a), "h"((uint16_t)v) : "memory"); }
__device__ __forceinline__ uint4 ldx128(const void* p) {
    uint4 v; asm volatile("{.reg .b128 t; .reg .b64 a, b; ld.relaxed.gpu.global.b128 t, [%4]; mov.b128 {a, b}, t; mov.b64 {%0,%1}, a; mov.b64 {%2,%3}, b;}"
        : "=r"(v.x), "=r"(v.y), "=r"(v.z), "=r"(v.w) : "l"(p) : "memory"); return v; }
__device__ __forceinline__ void stx128(void* p, uint4 v) {
    asm volatile("{.reg .b128 t; .reg .b64 a, b; mov.b64 a, {%1,%2}; mov.b64 b, {%3,%4}; mov.b128 t, {a, b}; st.relaxed.gpu.global.b128 [%0], t;}"
        :: "l"(p), "r"(v.x), "r"(v.y), "r"(v.z), "r"(v.w) : "memory"); }
__device__ __forceinline__ uint32_t ld_relaxed(const uint32_t* p) { uint32_t v; asm volatile("ld.relaxed.gpu.global.u32 %0, [%1];" : "=r"(v) : "l"(p) : "memory"); return v; }
__device__ __forceinline__ uint32_t ld_acquire(const uint32_t* p) { uint32_t v; asm volatile("ld.acquire.gpu.global.u32 %0, [%1];" : "=r"(v) : "l"(p) : "memory"); return v; }
__device__ __forceinline__ void st_relaxed(uint32_t* p, uint32_t v) { asm volatile("st.relaxed.gpu.global.u32 [%0], %1;" :: "l"(p), "r"(v) : "memory"); }
__device__ __forceinline__ void red_release(uint32_t* p) { asm volatile("red.release.gpu.global.add.u32 [%0], 1;" :: "l"(p) : "memory"); }
template <int SLEEP> __device__ __forceinline__ void wait_count(const uint32_t* p, uint32_t target) {
    int it = 0; while ((int)(ld_acquire(p) - target) < 0) { if (SLEEP) __nanosleep(SLEEP); if (++it > SPIN_LIMIT) __trap(); }
}
__device__ __forceinline__ uint32_t ldg_nc32(const void* p) { uint32_t v; asm volatile("ld.global.nc.L1::no_allocate.u32 %0, [%1];" : "=r"(v) : "l"(p)); return v; }
__device__ __forceinline__ uint32_t ldg_nc16(const void* p) { uint16_t v; asm volatile("ld.global.nc.u16 %0, [%1];" : "=h"(v) : "l"(p)); return v; }
__device__ __forceinline__ float bf_lo(uint32_t w) { return __uint_as_float(w << 16); }
__device__ __forceinline__ float bf_hi(uint32_t w) { return __uint_as_float(w & 0xFFFF0000u); }
__device__ __forceinline__ uint32_t pack_bf(float lo, float hi) { uint32_t r; asm("cvt.rn.bf16x2.f32 %0, %1, %2;" : "=r"(r) : "f"(hi), "f"(lo)); return r; }
__device__ __forceinline__ uint32_t pack_h(float lo, float hi) { uint32_t r; asm("cvt.rn.f16x2.f32 %0, %1, %2;" : "=r"(r) : "f"(hi), "f"(lo)); return r; }
__device__ __forceinline__ float bf_round(float v) { return bf_lo(pack_bf(v, 0.f)); }
__device__ __forceinline__ uint32_t hmul2(uint32_t a, uint32_t b) { uint32_t r; asm("mul.rn.f16x2 %0, %1, %2;" : "=r"(r) : "r"(a), "r"(b)); return r; }
__device__ __forceinline__ uint32_t hfma2(uint32_t a, uint32_t b, uint32_t c) { uint32_t r; asm("fma.rn.f16x2 %0, %1, %2, %3;" : "=r"(r) : "r"(a), "r"(b), "r"(c)); return r; }
__device__ __forceinline__ uint32_t hfms2(uint32_t a, uint32_t b, uint32_t c) { uint32_t r; asm("{.reg .b32 t; neg.f16x2 t, %3; fma.rn.f16x2 %0, %1, %2, t;}" : "=r"(r) : "r"(a), "r"(b), "r"(c)); return r; }
__device__ __forceinline__ uint32_t hadd2(uint32_t a, uint32_t b) { uint32_t r; asm("add.rn.f16x2 %0, %1, %2;" : "=r"(r) : "r"(a), "r"(b)); return r; }
__device__ __forceinline__ uint32_t hsub2(uint32_t a, uint32_t b) { uint32_t r; asm("sub.rn.f16x2 %0, %1, %2;" : "=r"(r) : "r"(a), "r"(b)); return r; }
__device__ __forceinline__ void cmul_neg(uint32_t& re, uint32_t& im, uint32_t c, uint32_t s) { uint32_t a = hfma2(re, c, hmul2(im, s)), b = hfms2(im, c, hmul2(re, s)); re = a; im = b; }
__device__ __forceinline__ void cmul_pos(uint32_t& re, uint32_t& im, uint32_t c, uint32_t s) { uint32_t a = hfms2(re, c, hmul2(im, s)), b = hfma2(im, c, hmul2(re, s)); re = a; im = b; }
__device__ __forceinline__ void mma_h(uint32_t& d0, uint32_t& d1, uint32_t a0, uint32_t a1, uint32_t a2, uint32_t a3, uint32_t b0, uint32_t b1) {
    asm("mma.sync.aligned.m16n8k16.row.col.f16.f16.f16.f16 {%0,%1}, {%2,%3,%4,%5}, {%6,%7}, {%0,%1};" : "+r"(d0), "+r"(d1) : "r"(a0), "r"(a1), "r"(a2), "r"(a3), "r"(b0), "r"(b1)); }
__device__ __forceinline__ void mma_h8(uint32_t& d0, uint32_t& d1, uint32_t a0, uint32_t a1, uint32_t b0) {
    asm("mma.sync.aligned.m16n8k8.row.col.f16.f16.f16.f16 {%0,%1}, {%2,%3}, {%4}, {%0,%1};" : "+r"(d0), "+r"(d1) : "r"(a0), "r"(a1), "r"(b0)); }
__device__ __forceinline__ void mma_f(float (&d)[4], uint32_t a0, uint32_t a1, uint32_t a2, uint32_t a3, uint32_t b0, uint32_t b1) {
    asm("mma.sync.aligned.m16n8k16.row.col.f32.f16.f16.f32 {%0,%1,%2,%3}, {%4,%5,%6,%7}, {%8,%9}, {%0,%1,%2,%3};"
        : "+f"(d[0]), "+f"(d[1]), "+f"(d[2]), "+f"(d[3]) : "r"(a0), "r"(a1), "r"(a2), "r"(a3), "r"(b0), "r"(b1)); }
template <int NQ> __device__ __forceinline__ void load_tab(uint32_t (&r)[NQ * 4], uint32_t addr) {
    #pragma unroll
    for (int i = 0; i < NQ; i++) { uint4 v = lds128(addr + i * 512); r[4 * i] = v.x; r[4 * i + 1] = v.y; r[4 * i + 2] = v.z; r[4 * i + 3] = v.w; }
}
__device__ __forceinline__ float gelu2(float x) {
    float t = x * fmaf(x * x, 0.044715f * 0.7978845608028654f, 0.7978845608028654f), th;
    asm volatile("tanh.approx.f32 %0, %1;" : "=f"(th) : "f"(t));
    return fmaf(x, th, x);
}
__device__ __forceinline__ uint32_t desc_lo(uint32_t addr, uint32_t lbo) { return ((addr & 0x3FFFF) >> 4) | ((lbo >> 4) << 16); }
constexpr uint32_t DHI_A = (1024 >> 4) | (1u << 30), DHI_H3 = 256 >> 4, DHI_U = 128 >> 4;
#define WG_FENCE() asm volatile("wgmma.fence.sync.aligned;" ::: "memory")
#define WG_COMMIT() asm volatile("wgmma.commit_group.sync.aligned;" ::: "memory")
#define WG_WAIT(n) asm volatile("wgmma.wait_group.sync.aligned %0;" :: "n"(n) : "memory")
#define R4(b) "+f"(d[b]), "+f"(d[b + 1]), "+f"(d[b + 2]), "+f"(d[b + 3])
#define R12(b) R4(b), R4(b + 4), R4(b + 8)
#define R36(b) R12(b), R12(b + 12), R12(b + 24)
template <uint32_t BHI> __device__ __forceinline__ void wgmma144(float (&d)[72], uint32_t da, uint32_t db, int acc) {
    asm volatile("{.reg .pred p; .reg .b64 a, b; setp.ne.b32 p, %74, 0; mov.b64 a, {%72, %75}; mov.b64 b, {%73, %76};\n"
        "wgmma.mma_async.sync.aligned.m64n144k16.f32.bf16.bf16 {%0,%1,%2,%3,%4,%5,%6,%7,%8,%9,%10,%11,%12,%13,%14,%15,%16,%17,%18,%19,%20,%21,%22,%23,"
        "%24,%25,%26,%27,%28,%29,%30,%31,%32,%33,%34,%35,%36,%37,%38,%39,%40,%41,%42,%43,%44,%45,%46,%47,"
        "%48,%49,%50,%51,%52,%53,%54,%55,%56,%57,%58,%59,%60,%61,%62,%63,%64,%65,%66,%67,%68,%69,%70,%71}, a, b, p, 1, 1, 1, 1;}\n"
        : R36(0), R36(36) : "r"(da), "r"(db), "r"(acc), "n"(DHI_A), "n"(BHI));
}
__device__ __forceinline__ void wgmma144x4(float (&d)[72], const uint64_t (&a)[4], const uint64_t (&b)[4], int acc) {
    #define WG144 "wgmma.mma_async.sync.aligned.m64n144k16.f32.bf16.bf16 {%0,%1,%2,%3,%4,%5,%6,%7,%8,%9,%10,%11,%12,%13,%14,%15,%16,%17,%18,%19,%20,%21,%22,%23,%24,%25,%26,%27,%28,%29,%30,%31,%32,%33,%34,%35,%36,%37,%38,%39,%40,%41,%42,%43,%44,%45,%46,%47,%48,%49,%50,%51,%52,%53,%54,%55,%56,%57,%58,%59,%60,%61,%62,%63,%64,%65,%66,%67,%68,%69,%70,%71}, "
    asm volatile("{.reg .pred p; setp.ne.b32 p, %80, 0;\n"
        WG144 "%72, %76, p, 1, 1, 1, 1;\n" WG144 "%73, %77, 1, 1, 1, 1, 1;\n" WG144 "%74, %78, 1, 1, 1, 1, 1;\n" WG144 "%75, %79, 1, 1, 1, 1, 1;}\n"
        : R36(0), R36(36) : "l"(a[0]), "l"(a[1]), "l"(a[2]), "l"(a[3]), "l"(b[0]), "l"(b[1]), "l"(b[2]), "l"(b[3]), "r"(acc));
}
__device__ __forceinline__ void wgmma72(float (&d)[36], uint32_t da, uint32_t db, int acc) {
    asm volatile("{.reg .pred p; .reg .b64 a, b; setp.ne.b32 p, %38, 0; mov.b64 a, {%36, %39}; mov.b64 b, {%37, %40};\n"
        "wgmma.mma_async.sync.aligned.m64n72k16.f32.bf16.bf16 {%0,%1,%2,%3,%4,%5,%6,%7,%8,%9,%10,%11,%12,%13,%14,%15,%16,%17,%18,%19,%20,%21,%22,%23,"
        "%24,%25,%26,%27,%28,%29,%30,%31,%32,%33,%34,%35}, a, b, p, 1, 1, 1, 1;}\n"
        : R36(0) : "r"(da), "r"(db), "r"(acc), "n"(DHI_A), "n"(DHI_H3));
}

__device__ __forceinline__ int g2_kb(int n, int kh) { const int m = n - 4; return 36 * kh + (n < 4 ? 9 * n + 8 : 9 * ((m >> 2) & 3) + 2 * (m & 3) + (m >> 4)); }

template <uint32_t BHI, int I0, int I1, bool ZERO, bool FIRST, bool LAST, class Hook>
__device__ __forceinline__ void mainloop(float (&d)[72], uint32_t bars, uint32_t da0, uint32_t db0, bool lead, Hook hook) {
    uint32_t s = I0 % NST, ph = (I0 / NST) & 1, prev = (I0 + NST - (I0 == IT_P1 ? 2 : 1)) % NST;
    uint32_t ready = 0;
    uint64_t da[4], db[4];
    #pragma unroll
    for (int k = 0; k < 4; k++) { da[k] = ((uint64_t)DHI_A << 32) + da0 + s * (A_BYTES / 16) + k * 128; db[k] = ((uint64_t)BHI << 32) + db0 + s * (B_BYTES / 16) + k * 288; }
    #pragma unroll 1
    for (int i = I0; i < I1; i++) {
        if (!ready) mbar_wait(bars + 8 * BAR_FULL + 8 * s, ph);
        WG_FENCE();
        wgmma144x4(d, da, db, ZERO ? i - I0 : 1);
        WG_COMMIT();
        const uint32_t rel = bars + 8 * BAR_EMPTY + 8 * prev; const int i0 = i;
        prev = s; if (++s == NST) { s = 0; ph ^= 1; }
        if (I1 == IT_P1 && (s == P2S || s == P2S + 3)) {
            mbar_wait(bars + 8 * BAR_FULL + 8 * s, ph);
            i++; if (++s == NST) { s = 0; ph ^= 1; }
        }
        const int64_t adv = (int)s - (int)prev;
        #pragma unroll
        for (int k = 0; k < 4; k++) { da[k] += adv * (A_BYTES / 16); db[k] += adv * (B_BYTES / 16); }
        ready = __shfl_sync(~0u, (uint32_t)mbar_test(bars + 8 * BAR_FULL + 8 * s, ph), 0);
        WG_WAIT(1);
        if (lead && (!FIRST || i0 > I0)) mbar_arrive(rel);
        hook(i0);
    }
    if (LAST) { WG_WAIT(0); if (lead) mbar_arrive(bars + 8 * BAR_EMPTY + 8 * prev); }
}

struct Params {
    const uint16_t *x, *wr, *wi, *w1, *b1, *w2, *b2, *c, *wmod;
    uint16_t* out;
    Scratch* scr;
    const Tab* tab;
};

__device__ __forceinline__ void mma_bf(float (&d)[4], const uint32_t (&a)[4], uint32_t b0, uint32_t b1) {
    asm("mma.sync.aligned.m16n8k16.row.col.f32.bf16.bf16.f32 {%0,%1,%2,%3}, {%4,%5,%6,%7}, {%8,%9}, {%0,%1,%2,%3};"
        : "+f"(d[0]), "+f"(d[1]), "+f"(d[2]), "+f"(d[3]) : "r"(a[0]), "r"(a[1]), "r"(a[2]), "r"(a[3]), "r"(b0), "r"(b1)); }
__device__ __forceinline__ void ldsm4t(uint32_t (&a)[4], uint32_t addr) {
    asm volatile("ldmatrix.sync.aligned.m8n8.x4.trans.shared.b16 {%0,%1,%2,%3}, [%4];" : "=r"(a[0]), "=r"(a[1]), "=r"(a[2]), "=r"(a[3]) : "r"(addr) : "memory"); }
__device__ __forceinline__ void ln_stats(const uint32_t (&w)[9], int g, int q, float& r, float& mr) {
    constexpr uint32_t ONE = 0x3F803F80u;
    float c[2][4] = {};
    #pragma unroll
    for (int p = 0; p < 5; p++) { const uint32_t hi = p < 4 ? w[p < 4 ? 2 * p + 1 : 0] : 0u, a[4] = {w[2 * p], ONE, hi, ONE}; mma_bf(c[p & 1], a, w[2 * p], hi); }
    const float t = (g & 1) ? c[0][1] + c[1][1] : c[0][0] + c[1][0];
    float s1 = (c[0][2] + c[1][2]) + (c[0][3] + c[1][3]), s2 = __shfl_sync(~0u, t, 9 * q) + __shfl_sync(~0u, t, 9 * q + 4);
    #pragma unroll
    for (int o = 1; o < 4; o <<= 1) { s1 += __shfl_xor_sync(~0u, s1, o); s2 += __shfl_xor_sync(~0u, s2, o); }
    const float m = s1 * (1.f / D_);
    asm("rsqrt.approx.ftz.f32 %0, %1;" : "=f"(r) : "f"(fmaxf(fmaf(s2, 1.f / D_, -m * m), 0.f) + 1e-5f));
    mr = -m * r;
}
__device__ __forceinline__ float silu(float v) { return __fdividef(v, 1.f + __expf(-v)); }
__device__ __forceinline__ uint32_t bfma2(uint32_t a, uint32_t b, uint32_t c) { uint32_t r; asm("fma.rn.bf16x2 %0, %1, %2, %3;" : "=r"(r) : "r"(a), "r"(b), "r"(c)); return r; }
__device__ __forceinline__ void radix16(const uint4 (&V)[4], const uint32_t (&B)[16], uint4 (&o)[4]) {
    #pragma unroll
    for (int nt = 0; nt < 4; nt++) {
        o[nt] = make_uint4(0, 0, 0, 0);
        #pragma unroll
        for (int ks = 0; ks < 2; ks++) {
            const uint32_t b0 = B[(ks * 4 + nt) * 2], b1 = B[(ks * 4 + nt) * 2 + 1];
            mma_h(o[nt].x, o[nt].y, V[2 * ks].x, V[2 * ks].y, V[2 * ks + 1].x, V[2 * ks + 1].y, b0, b1);
            mma_h(o[nt].z, o[nt].w, V[2 * ks].z, V[2 * ks].w, V[2 * ks + 1].z, V[2 * ks + 1].w, b0, b1);
        }
    }
}
template <int OFF, int N> __device__ __forceinline__ void gelu_store(const float (&d)[N], char* p, int q) {
    uint32_t w[9];
    #pragma unroll
    for (int blk = 0; blk < 9; blk++) w[blk] = pack_bf(gelu2(d[OFF + 4 * blk]), gelu2(d[OFF + 4 * blk + 1]));
    asm volatile("st.v4.u32 [%0], {%1,%2,%3,%4};" :: "l"(p + q * 128), "r"(w[0]), "r"(w[1]), "r"(w[2]), "r"(w[3]) : "memory");
    asm volatile("st.v4.u32 [%0+512], {%1,%2,%3,%4};" :: "l"(p + q * 128), "r"(w[4]), "r"(w[5]), "r"(w[6]), "r"(w[7]) : "memory");
    asm volatile("st.u32 [%0+1024], %1;" :: "l"(p + q * 4), "r"(w[8]) : "memory");
}

__global__ void __cluster_dims__(2, 1, 1) __launch_bounds__(NTHR, 1)
fused_kernel(const Params p,
             const __grid_constant__ CUtensorMap tm_w1a, const __grid_constant__ CUtensorMap tm_w1b, const __grid_constant__ CUtensorMap tm_w2,
             const __grid_constant__ CUtensorMap tm_h3a, const __grid_constant__ CUtensorMap tm_h3b,
             const __grid_constant__ CUtensorMap tm_wr, const __grid_constant__ CUtensorMap tm_wi, const __grid_constant__ CUtensorMap tm_wm,
             const __grid_constant__ CUtensorMap tm_t, const __grid_constant__ CUtensorMap tm_tx, const __grid_constant__ CUtensorMap tm_o,
             const __grid_constant__ CUtensorMap tm_h3s)
{
    extern __shared__ char smem_raw[];
    const uint32_t t0 = clk32();
    const uint32_t sm = __shfl_sync(~0u, ((uint32_t)__cvta_generic_to_shared(smem_raw) + 1023u) & ~1023u, 0);
    const int tid = threadIdx.x, warp = __shfl_sync(~0u, tid >> 5, 0), lane = tid & 31, g = lane >> 2, q = lane & 3;
    const int b = blockIdx.x;
    const uint32_t rank = b & 1;
    const uint32_t bars = sm + OFF_BAR;
    const bool rowcta = b < 128;

    auto nc_issue = [&](int st, uint32_t sl) {
        const int pass = st >= 18;
        mbar_expect(bars + 8 * (BAR_X + sl), 28672);
        tma3(sm + sl * 28672, &tm_wm, 0, 32 * (st - 18 * pass), 18 + 28 * pass + 7 * (b - 128), bars + 8 * (BAR_X + sl));
    };
    if (warp == 13) hb();
    uint32_t cw = 0, epoch;
    if (warp < 12) {
        if (lane < 24) cw = ldg_nc32(p.c + 48 * warp + 2 * lane);
        epoch = ld_relaxed(g_cnt + CNT_EPOCH * 32);
        if (b < 72) {
            const uint16_t* src = p.wmod + (48 * warp + (lane >> 1)) * 3456 + 16 * b + (lane & 1) * 8;
            const uint32_t dst = sm + OFF_STRIP + (48 * warp + (lane >> 1)) * 48 + (lane & 1) * 16;
            #pragma unroll
            for (int u = 0; u < 3; u++) asm volatile("cp.async.cg.shared.global" CPHINT " [%0], [%1], 16;" :: "r"(dst + u * 768), "l"(src + u * 16 * 3456) : "memory");
            asm volatile("cp.async.commit_group;" ::: "memory");
        }
    } else {
      if (elect()) {
        if (warp == 15) {
            mbar_init(bars + 8 * BAR_TAB, 1); fence_async_s();
            if (rowcta) { mbar_expect(bars + 8 * BAR_TAB, QA * 512); bulk_load(sm + OFF_TAB, p.tab, QA * 512, bars + 8 * BAR_TAB); }
            asm volatile("prefetch.tensormap [%0];" :: "l"(&tm_wr) : "memory"); asm volatile("prefetch.tensormap [%0];" :: "l"(&tm_wi) : "memory");
            asm volatile("prefetch.tensormap [%0];" :: "l"(&tm_t) : "memory"); asm volatile("prefetch.tensormap [%0];" :: "l"(&tm_tx) : "memory");
        } else if (warp == 14) {
            for (int i = BAR_W; i < BAR_X; i++) mbar_init(bars + 8 * i, i == BAR_DONE ? 4 : 1);
            mbar_expect(bars + 8 * BAR_W, 28672); mbar_expect(bars + 8 * BAR_TAB2, (QB + QC) * 512);
            mbar_expect(bars + 8 * BAR_ROLE, 4); mbar_expect(bars + 8 * BAR_P2R, 9216); mbar_expect(bars + 8 * BAR_RECV, 18432); mbar_expect(bars + 8 * BAR_XT, 18432);
        } else if (warp == 13) {
            for (int i = 0; i < 2 * NST; i++) mbar_init(bars + 8 * i, 2);
            for (int i = 0; i < NST; i++) mbar_expect(bars + 8 * (BAR_FULL + i), A_BYTES);
        }
        else {
            for (int i = 0; i < 16; i++) mbar_init(bars + 8 * (BAR_X + i), rowcta || i < 6 ? 1 : 14);
            if (!rowcta) { fence_async_s(); for (int st = 0; st < 6; st++) nc_issue(st, st); }
        }
        asm volatile("fence.mbarrier_init.release.cluster;" ::: "memory");
      }
      __syncwarp();
      epoch = ld_relaxed(g_cnt + CNT_EPOCH * 32);
    }
    __syncthreads();
    asm volatile("barrier.cluster.arrive.relaxed.aligned;" ::: "memory");
    if (warp < 4) sts16(sm + OFF_MODA + ((warp + 1) * 32 + lane) * 16 + warp * 4 + 2, 0);
    if (warp >= 8) {
        const int k1 = tid & 15, s1 = (tid >> 4) & 15;
        float s, c;
        __sincosf((float)(((k1 * (128 * s1 + b) + 1024) & 2047) - 1024) * (3.14159265358979f / 1024.f), &s, &c); s *= 0.25f; c *= 0.25f;
        const int rf = ((s1 >> 3) * 4 + (k1 >> 2)) * 2 + ((s1 >> 2) & 1), ri = ((k1 >> 3) * 4 + (s1 >> 2)) * 2 + ((k1 >> 2) & 1);
        const uint32_t af = sm + OFF_B3 + ((rf >> 2) * 32 + (k1 & 3) * 8 + (s1 & 3)) * 16 + (rf & 3) * 4;
        const uint32_t ai = sm + OFF_B3 + 2048 + ((ri >> 2) * 32 + (s1 & 3) * 8 + (k1 & 3)) * 16 + (ri & 3) * 4;
        sts32(af, pack_h(c, s)); sts32(af + 64, pack_h(-s, c)); sts32(ai, pack_h(c, -s)); sts32(ai + 64, pack_h(s, c));
    }
    if (rowcta) spin_until(t0 + XDELAY);
    if (rowcta && elect()) {
        mbar_expect(bars + 8 * (BAR_X + warp), 1152);
        bulk_load(sm + OFF_STAGE + warp * 1152, p.x + (size_t)(b + 128 * warp) * D_, 1152, bars + 8 * (BAR_X + warp));
    }
    const uint32_t tag = (epoch + 1) & 0xFFFFu;
    if (warp < 12 && lane < 24) sts32(sm + OFF_SILU + (24 * warp + lane) * 4, pack_bf(silu(bf_lo(cw)), silu(bf_hi(cw))));
    hb();
    uint32_t ta[QA * 4];
    const bool ta_early = rowcta && __any_sync(~0u, mbar_test(bars + 8 * BAR_TAB, 0));
    if (ta_early) load_tab<QA>(ta, sm + OFF_TAB + lane * 16);
    if (warp < 12 && b < 72) {
        uint32_t sb[6];
        __syncwarp();
        #pragma unroll
        for (int u = 0; u < 6; u++) sb[u] = lds32(sm + OFF_SILU + (24 * warp + 4 * u + q) * 4);
        asm volatile("cp.async.wait_all;" ::: "memory");
        __syncwarp();
        float acc[4] = {0, 0, 0, 0};
        #pragma unroll
        for (int u = 0; u < 3; u++) {
            uint32_t a[4];
            ldsm4t(a, sm + OFF_STRIP + (48 * warp + 16 * u + (lane & 7) + 8 * (lane >> 4)) * 48 + ((lane >> 3) & 1) * 16);
            mma_bf(acc, a, sb[2 * u], sb[2 * u + 1]);
        }
        if (q == 0) { sts32(sm + OFF_RED + (g * 12 + warp) * 4, __float_as_uint(acc[0])); sts32(sm + OFF_RED + ((g + 8) * 12 + warp) * 4, __float_as_uint(acc[2])); }
        PROF0(0);
        bar_sync(3, 384);
        if (warp == 0) {
            if (lane < 16) {
                float sum = 0;
                #pragma unroll
                for (int u = 0; u < 3; u++) { const uint4 v = lds128(sm + OFF_RED + lane * 48 + u * 16);
                    sum += (__uint_as_float(v.x) + __uint_as_float(v.y)) + (__uint_as_float(v.z) + __uint_as_float(v.w)); }
                sum = bf_round(sum); if (b >= 36) sum = bf_round(1.f + sum);
                st_relaxed(g_mod + b * MODPAD + (lane & 1) * 8 + (lane >> 1), (pack_h(0.f, sum) & 0xFFFF0000u) | tag);
            }
            __syncwarp();
            PROF0(1);
        }
    }

    const int trow = 4 * (b & 7) + ((b >> 4) & 3) + 64 * ((b >> 3) & 1) + 32 * (b >> 6);
    uint32_t* const tptr = g_T + (size_t)trow * TP + (warp < 9 ? q * 288 + 32 * warp : 4608 + 8 * q) + 4 * g;
    const int tstr = warp < 9 ? 1152 : 32;
    const uint32_t scol = sm + OFF_SPEC + (q * SPEC_P + (warp < 8 ? 72 * (warp >> 1) + 40 * (warp & 1) + 4 * g : warp == 8 ? 72 * (g >> 1) + 32 + 4 * (g & 1) : 288 + 4 * g)) * 4;
    const int wc0 = (b >> 3) * 289 + 72 * ((b & 7) >> 1) + 40 * (b & 1);

    uint32_t xw[9], t_st = t0;
    if (!rowcta) {
        const int nst = b < 130 ? 36 : 18;
        __syncthreads();
        if (warp == 14) {
            uint32_t sl = 0, ph = 0;
            #pragma unroll 1
            for (int st = 6; st < nst; st++) {
                mbar_wait(bars + 8 * (BAR_X + 6 + sl), ph);
                if (elect()) nc_issue(st, sl);
                if (++sl == 6) { sl = 0; ph ^= 1; }
            }
        } else if (warp < 14) {
            uint32_t sl = 0, ph = 0;
            const uint32_t ad0 = sm + (warp >> 1) * 4096 + ((lane & 7) + 8 * (lane >> 4)) * 128, ch = (warp & 1) * 4 + ((lane >> 3) & 1);
            #pragma unroll 1
            for (int pass = 0; pass * 18 < nst; pass++) {
                float acc[2][4] = {};
                #pragma unroll 1
                for (int st = 0; st < 18; st++) {
                    const uint32_t sa = sm + OFF_SILU + (16 * st + q) * 4;
                    const uint32_t b0 = lds32(sa), b1 = lds32(sa + 16), b2 = lds32(sa + 32), b3 = lds32(sa + 48);
                    mbar_wait(bars + 8 * (BAR_X + sl), ph);
                    #pragma unroll
                    for (int m = 0; m < 2; m++) {
                        uint32_t a[4], a2[4];
                        const uint32_t ad = ad0 + sl * 28672 + ((ch + 2 * m) ^ (lane & 7)) * 16;
                        ldsm4t(a, ad); ldsm4t(a2, ad + 2048);
                        mma_bf(acc[m], a, b0, b1); mma_bf(acc[m], a2, b2, b3);
                    }
                    if (elect()) mbar_arrive(bars + 8 * (BAR_X + 6 + sl));
                    if (++sl == 6) { sl = 0; ph ^= 1; }
                }
                const int cb = 28 * pass + 7 * (b - 128) + (warp >> 1), gg = (g >> 1) + 4 * q;
                #pragma unroll
                for (int m = 0; m < 2; m++) {
                    const int qq = (warp & 1) * 2 + m;
                    float v = bf_round(q ? acc[m][2] : acc[m][0]); if (cb >= 27) v *= 0.5f; else if (cb >= 18) v += 1.f;
                    const uint32_t w = pack_bf(v, __shfl_xor_sync(~0u, v, 4));
                    if (q < 2 && !(g & 1) && cb < 36) p.scr->modc[cb < 27 ? ((cb >> 2) * 32 + 4 * gg + qq) * 4 + (cb & 3) : 896 + 32 * (cb - 27) + 8 * qq + gg] = w;
                }
                bar_sync(1, 448);
                if (tid == 0) { fence_async_g(); red_release(g_cnt + (CNT_NC + pass) * 32); if (pass == 0) PROFT(25); }
                __syncwarp();
            }
            fence_async_s();
        }
        __syncthreads();
    } else {
        if (!ta_early) { mbar_wait(bars + 8 * BAR_TAB, 0); load_tab<QA>(ta, sm + OFF_TAB + lane * 16); }
        uint32_t nb[2][5];
        uint4 mv = make_uint4(tag, tag, tag, tag);
        const int mc = tid - 224, mst = (mc >> 2) % 36, midx = (mc < 144 ? 10 : 0) + 5 * ((mc >> 1) & 1) + (mst >> 3);
        const uint32_t* mp = g_mod + (mc >> 2) * MODPAD + (mc & 3) * 4;
        const uint32_t ma = sm + OFF_MODA + ((midx >> 2) * 32 + (mc & 1) * 16 + (mst & 3)) * 16 + (midx & 3) * 4 + ((mst >> 2) & 1) * 2;
        #define MOD_MISSING ((((mv.x ^ tag) | (mv.y ^ tag) | (mv.z ^ tag) | (mv.w ^ tag)) & 0xFFFFu) != 0)
        hb();
        mbar_wait(bars + 8 * (BAR_X + warp), 0);
        if (warp >= 7) mv = ldx128(mp);
        PROF0(28);
        #pragma unroll
        for (int i = 0; i < 9; i++) xw[i] = lds32(sm + OFF_STAGE + warp * 1152 + (32 * i + 8 * q + g) * 4);
        {
            float r, mr;
            ln_stats(xw, g, q, r, mr);
            #pragma unroll
            for (int pp = 0; pp < 5; pp++) {
                nb[0][pp] = pack_h(fmaf(bf_lo(xw[2 * pp]), r, mr), pp < 4 ? fmaf(bf_lo(xw[pp < 4 ? 2 * pp + 1 : 0]), r, mr) : 0.f);
                nb[1][pp] = pack_h(fmaf(bf_hi(xw[2 * pp]), r, mr), pp < 4 ? fmaf(bf_hi(xw[pp < 4 ? 2 * pp + 1 : 0]), r, mr) : 0.f);
            }
        }
        PROF0(2);
        if (warp >= 7) {
            for (int it = 0; __any_sync(~0u, MOD_MISSING); it++) { mv = ldx128(mp); hb(); if (it > SPIN_LIMIT) __trap(); }
            sts16(ma, mv.x >> 16); sts16(ma + 64, mv.y >> 16); sts16(ma + 128, mv.z >> 16); sts16(ma + 192, mv.w >> 16);
        }
        __syncthreads();
        PROF0(3);
        if (warp >= 13 && elect()) {
            if (warp == 15) bulk_load(sm + OFF_TAB + QA * 512, p.tab->w + QA * 128, (QB + QC) * 512, bars + 8 * BAR_TAB2);
            else tma3(sm + OFF_WRAW + (warp - 13) * 14336, warp == 13 ? &tm_wr : &tm_wi, wc0 & ~7, 0, 0, bars + 8 * BAR_W);
        }
        __syncwarp();
        {
            uint32_t md[20];
            load_tab<5>(md, sm + OFF_MODA + lane * 16);
            #pragma unroll
            for (int v = 0; v < 2; v++)
                #pragma unroll
                for (int pp = 0; pp < 5; pp++) nb[v][pp] = hfma2(nb[v][pp], md[v * 5 + pp], md[10 + v * 5 + pp]);
        }
        uint32_t re[3][2], im[3][2];
        #pragma unroll
        for (int mt = 0; mt < 3; mt++)
            #pragma unroll
            for (int v = 0; v < 2; v++) {
                re[mt][v] = 0; im[mt][v] = 0;
                mma_h8(re[mt][v], im[mt][v], ta[mt * 10 + 8], ta[mt * 10 + 9], nb[v][4]);
                mma_h(re[mt][v], im[mt][v], ta[mt * 10], ta[mt * 10 + 1], ta[mt * 10 + 2], ta[mt * 10 + 3], nb[v][0], nb[v][1]);
                mma_h(re[mt][v], im[mt][v], ta[mt * 10 + 4], ta[mt * 10 + 5], ta[mt * 10 + 6], ta[mt * 10 + 7], nb[v][2], nb[v][3]);
                cmul_neg(re[mt][v], im[mt][v], ta[30 + (mt * 2 + v) * 2], ta[31 + (mt * 2 + v) * 2]);
            }
        const uint32_t srow = sm + OFF_SPEC + warp * (SPEC_P * 4);
        #pragma unroll
        for (int nt = 0; nt < 2; nt++) {
            uint32_t o[2][4];
            #pragma unroll
            for (int v = 0; v < 2; v++) {
                const uint32_t b0 = ta[42 + (v * 2 + nt) * 2], b1 = ta[43 + (v * 2 + nt) * 2];
                o[v][0] = o[v][1] = o[v][2] = o[v][3] = 0;
                mma_h(o[v][0], o[v][1], re[0][v], re[1][v], im[0][v], im[1][v], b0, b1);
                mma_h(o[v][2], o[v][3], re[2][v], re[2][v], im[2][v], im[2][v], b0, b1);
            }
            const uint32_t a = srow + (g + 72 * q + 36 * nt) * 4, a2 = srow + (288 - g - 72 * q - 36 * nt) * 4;
            sts32(a, hadd2(o[0][0], o[1][0])); sts32(a + 32, hadd2(o[0][1], o[1][1])); if (g < 3) sts32(a + 64, hadd2(o[0][2], o[1][2]));
            if (g > 0 || (q == 0 && nt == 0)) sts32(a2, hsub2(o[0][0], o[1][0]) ^ 0x80000000u);
            sts32(a2 - 32, hsub2(o[0][1], o[1][1]) ^ 0x80000000u); if (g < 2) sts32(a2 - 64, hsub2(o[0][2], o[1][2]) ^ 0x80000000u);
        }
        uint32_t b3[16];
        if (warp < 10) load_tab<4>(b3, sm + OFF_B3 + lane * 16);
        __syncthreads();
        t_st = clk32();
        PROF0(4);
        if (warp < 10) {
            uint4 V[4], o[4];
            #pragma unroll
            for (int u = 0; u < 4; u++) V[u] = lds128(scol + u * (16 * SPEC_P));
            radix16(V, b3, o);
            #pragma unroll
            for (int nt = 0; nt < 4; nt++) { o[nt].x |= 1u; if (warp < 9 || g < 2) stx128(tptr + nt * tstr, o[nt]); }
        }
        PROF0(5);
    }

    int role = 0;
    asm volatile("barrier.cluster.wait.aligned;" ::: "memory");
    if (warp >= 12) {
        const int t = tid - 384;
        if (tid == 448 && rank == 0) {
            uint32_t smid; asm volatile("mov.u32 %0, %%smid;" : "=r"(smid));
            const uint32_t tp = smid >> 1;
            uint32_t pr = tp < 32 ? (tp & 7) * 8 + (tp >> 3) : tp < 60 ? (1 + (tp - 32) % 7) * 8 + 4 + (tp - 32) / 7 : tp < 62 ? 4 + tp : tp < 66 ? tp - 58 : 0;
            while (atomicExch(g_slot + pr, epoch + 1) == epoch + 1) pr = pr == 65 ? 0 : pr + 1;
            #pragma unroll
            for (int r = 0; r < 2; r++)
                asm volatile("st.async.weak.shared::cluster.mbarrier::complete_tx::bytes.u32 [%0], %1, [%2];" :: "r"(mapa(sm + OFF_MISC, r)), "r"(pr), "r"(mapa(bars + 8 * BAR_ROLE, r)) : "memory");
        }
        __syncwarp();
        if (t == 0) {
            asm volatile("prefetch.tensormap [%0];" :: "l"(&tm_w1a) : "memory");
            asm volatile("prefetch.tensormap [%0];" :: "l"(&tm_h3a) : "memory"); asm volatile("prefetch.tensormap [%0];" :: "l"(&tm_w1b) : "memory");
            asm volatile("prefetch.tensormap [%0];" :: "l"(&tm_h3b) : "memory"); asm volatile("prefetch.tensormap [%0];" :: "l"(&tm_w2) : "memory");
            asm volatile("prefetch.tensormap [%0];" :: "l"(&tm_o) : "memory"); asm volatile("prefetch.tensormap [%0];" :: "l"(&tm_h3s) : "memory");
        }
        if (t == 32 && rowcta) {
            for (int it = 0; (int)(ld_acquire(g_cnt + CNT_NC * 32) - (epoch + 1) * 4) < 0; it++) { __nanosleep(100); if (it > SPIN_LIMIT) __trap(); }
            fence_async_g();
            mbar_expect(bars + 8 * BAR_NC, 3584);
            bulk_load(sm + OFF_MODC, p.scr->modc, 3584, bars + 8 * BAR_NC);
            PROFT(29);
        }
        __syncwarp();
    } else if (rowcta && warp < 11) {
        const int nw = !(b & 1) ? 10 : (b & 7) == 7 ? 9 : 8;
        const int cm = (b >> 3) * 288 + (b & 7) * 32, cx = (b & 1) ? 4608 + 8 * (b >> 3) : (b >> 3) * 288 + 256 + 4 * (b & 7);
        auto load_in = [&]() {
            if (elect()) {
                mbar_expect(bars + 8 * BAR_XB, nw > 8 ? 20480 : 16384);
                tma2(sm + OFF_STAGE, &tm_t, cm, 0, bars + 8 * BAR_XB);
                if (nw > 8) tma2(sm + OFF_STX, &tm_tx, cx, 0, bars + 8 * BAR_XB);
            }
            __syncwarp();
        };
        if (warp == 10) { fence_async_s(); spin_until(t_st + X1D); load_in(); }
        uint32_t tb[QB * 4], wre[4][2], wim[4][2];
        if (warp < nw) {
            mbar_wait(bars + 8 * BAR_TAB2, 0);
            load_tab<QB>(tb, sm + OFF_TAB + QA * 512 + lane * 16);
            mbar_wait(bars + 8 * BAR_W, 0);
            const int off = wc0 & 7;
            const uint32_t wa = sm + OFF_WRAW + lane * 112 + ((off >> 1) + 2 * warp) * 4, sh = (off & 1) * 16;
            #pragma unroll
            for (int c = 0; c < 2; c++)
                #pragma unroll
                for (int h = 0; h < 2; h++) {
                    uint32_t y[2][2];
                    #pragma unroll
                    for (int e = 0; e < 2; e++) {
                        const uint32_t a = wa + c * 14336 + (h + 2 * e) * 3584, x0 = lds32(a), x1 = lds32(a + 4), x2 = lds32(a + 8);
                        y[e][0] = __funnelshift_r(x0, x1, sh); y[e][1] = __funnelshift_r(x1, x2, sh);
                    }
                    #pragma unroll
                    for (int x = 0; x < 4; x++) {
                        const uint32_t v = (x & 1) ? pack_h(bf_hi(y[0][x >> 1]), bf_hi(y[1][x >> 1])) : pack_h(bf_lo(y[0][x >> 1]), bf_lo(y[1][x >> 1]));
                        if (c) wim[x][h] = v; else wre[x][h] = v;
                    }
                }
        }
        const uint32_t ca = warp < 8 ? sm + OFF_STAGE + lane * 128 + (warp ^ (lane & 7)) * 16 : sm + OFF_STX + lane * 32 + ((warp ^ g) & 1) * 16, cs = warp < 8 ? 4096 : 1024;
        uint32_t V[4][4];
        for (int it = 0;; it++) {
            mbar_wait(bars + 8 * BAR_XB, it & 1);
            uint32_t ok = 1;
            if (warp < nw) {
                #pragma unroll
                for (int u = 0; u < 4; u++) { uint4 t4 = lds128(ca + u * cs); V[u][0] = t4.x; V[u][1] = t4.y; V[u][2] = t4.z; V[u][3] = t4.w; ok &= t4.x; }
            }
            asm volatile("{.reg .pred p; setp.ne.u32 p, %0, 0; bar.red.and.pred p, 1, 352, p; selp.u32 %0, 1, 0, p;}" : "+r"(ok) :: "memory");
            if (ok) break;
            if (warp == 10) { load_in(); hb(); }
            if (it > SPIN_LIMIT / 64) __trap();
        }
        PROF0(7);
        if (warp < nw) {
            uint32_t zr[4][2], zi[4][2];
            #pragma unroll
            for (int x = 0; x < 4; x++) {
                uint32_t er = 0, ei = 0, or_ = 0, oi = 0;
                mma_h(er, ei, tb[0], tb[1], tb[2], tb[3], V[0][x], V[1][x]);
                mma_h(or_, oi, tb[4], tb[5], tb[6], tb[7], V[2][x], V[3][x]);
                uint32_t r0 = hadd2(er, or_), r1 = hsub2(er, or_), i0 = hadd2(ei, oi), i1 = hsub2(ei, oi);
                cmul_neg(r0, i0, tb[8], tb[9]); cmul_neg(r1, i1, tb[10], tb[11]);
                uint32_t xr0 = 0, xr1 = 0, xi0 = 0, xi1 = 0;
                mma_h(xr0, xr1, r0, r1, i0, i1, tb[12], tb[13]);
                mma_h(xi0, xi1, r0, r1, i0, i1, tb[14], tb[12]);
                cmul_pos(xr0, xi0, wre[x][0], wim[x][0]); cmul_pos(xr1, xi1, wre[x][1], wim[x][1]);
                r0 = 0; i0 = 0; r1 = 0; i1 = 0;
                mma_h(r0, i0, tb[12], tb[13], tb[14], tb[12], xr0, xi0);
                mma_h(r1, i1, tb[12], tb[13], tb[14], tb[12], xr1, xi1);
                cmul_pos(r0, i0, tb[15], tb[16]); cmul_pos(r1, i1, tb[17], tb[18]);
                zr[x][0] = hadd2(r0, r1); zr[x][1] = hsub2(r0, r1); zi[x][0] = hadd2(i0, i1); zi[x][1] = hsub2(i0, i1);
            }
            #pragma unroll
            for (int nt = 0; nt < 4; nt++) {
                uint4 o = make_uint4(0, 0, 0, 0);
                const int h = nt >> 1;
                mma_h(o.x, o.y, zr[0][h], zr[1][h], zi[0][h], zi[1][h], tb[19 + 2 * nt], tb[20 + 2 * nt]);
                mma_h(o.z, o.w, zr[2][h], zr[3][h], zi[2][h], zi[3][h], tb[19 + 2 * nt], tb[20 + 2 * nt]);
                o.x &= ~1u;
                sts128(ca + nt * cs, o);
            }
        }
        fence_async_s();
        bar_sync(1, 352);
        t_st = clk32();
        PROF0(8);
        if (warp == 10 && elect()) {
            asm volatile("cp.async.bulk.tensor.2d.global.shared::cta.bulk_group [%0, {%2, %3}], [%1];" :: "l"(&tm_t), "r"(sm + OFF_STAGE), "r"(cm), "r"(0) : "memory");
            if (nw > 8) asm volatile("cp.async.bulk.tensor.2d.global.shared::cta.bulk_group [%0, {%2, %3}], [%1];" :: "l"(&tm_tx), "r"(sm + OFF_STX), "r"(cx), "r"(0) : "memory");
            asm volatile("cp.async.bulk.commit_group;" ::: "memory");
            asm volatile("cp.async.bulk.wait_group.read 0;" ::: "memory");
        }
        __syncwarp();
    }

    if (warp >= 10) { mbar_wait(bars + 8 * BAR_ROLE, 0); role = __shfl_sync(~0u, lds32(sm + OFF_MISC), 0); fence_async_s(); }
    auto first_a = [&]() {
        if (warp >= 10 && role < 64 && elect()) {
            const int it = warp - 10, hi = it >= 3; const bool p2 = it - 3 * hi == 2;
            tma4(sm + OFF_A + it * A_BYTES, p2 ? &tm_w1b : &tm_w1a, 0, 0, p2 ? 64 * rank + 8 * hi : 4 * (it - hi),
                 9 * (role >> 3) + (p2 ? 8 : (role & 4) + 2 * rank), bars + 8 * (BAR_FULL + it));
        }
        __syncwarp();
    };
    if (!rowcta) first_a();
    else {
        uint32_t tc[QC * 4];
        mbar_wait(bars + 8 * BAR_TAB2, 0);
        load_tab<QC>(tc, sm + OFF_TAB + (QA + QB) * 512 + lane * 16);
        if (warp < 10) {
            uint32_t b3[16];
            load_tab<4>(b3, sm + OFF_B3 + 2048 + lane * 16);
            uint4 V[4], o[4];
            const bool tact = warp < 9 || g == 0;
            spin_until(t_st + X2D);
            #pragma unroll
            for (int u = 0; u < 4; u++) V[u] = make_uint4(tact, 0, 0, 0);
            for (int it = 0; __any_sync(~0u, (V[0].x | V[1].x | V[2].x | V[3].x) & 1u); it++) {
                #pragma unroll
                for (int u = 0; u < 4; u++) if (V[u].x & 1u) V[u] = ldx128(tptr + u * tstr);
                hb();
                if (it > SPIN_LIMIT) __trap();
            }
            PROF0(10);
            radix16(V, b3, o);
            if (tact) {
                #pragma unroll
                for (int nt = 0; nt < 4; nt++) sts128(scol + nt * (16 * SPEC_P), o[nt]);
            }
        }
        __syncthreads();
        PROF0(11);
        first_a();
        const uint32_t srow = sm + OFF_SPEC + warp * (SPEC_P * 4);
        uint32_t re[2][3], im[2][3];
        #pragma unroll
        for (int mt = 0; mt < 3; mt++) {
            const uint32_t a = srow + (g + 72 * q + 8 * mt) * 4, a2 = srow + (288 - g - 72 * q - 8 * mt) * 4;
            const uint32_t z0 = lds32(a), z1 = lds32(a + 144), z2 = lds32(a2), z3 = lds32(a2 - 144);
            #pragma unroll
            for (int m2 = 0; m2 < 2; m2++) {
                re[m2][mt] = 0; im[m2][mt] = 0;
                const uint32_t sg = m2 ? 0x3C00BC00u : 0xBC003C00u;
                mma_h(re[m2][mt], im[m2][mt], tc[m2 * 4], tc[m2 * 4 + 1], tc[m2 * 4 + 2], tc[m2 * 4 + 3], hfma2(z2, sg, z0), hfma2(z3, sg, z1));
                cmul_pos(re[m2][mt], im[m2][mt], tc[8 + (m2 * 3 + mt) * 2], tc[9 + (m2 * 3 + mt) * 2]);
            }
        }
        uint32_t md[28];
        mbar_wait(bars + 8 * BAR_NC, 0);
        load_tab<7>(md, sm + OFF_MODC + lane * 16);
        float y[5][4];
        #pragma unroll
        for (int nt = 0; nt < 5; nt++) {
            y[nt][0] = y[nt][1] = y[nt][2] = y[nt][3] = 0.f;
            #pragma unroll
            for (int mt = 0; mt < 3; mt++)
                mma_f(y[nt], re[0][mt], re[1][mt], im[0][mt], im[1][mt], tc[20 + (mt * 5 + nt) * 2], tc[21 + (mt * 5 + nt) * 2]);
        }
        #pragma unroll
        for (int i = 0; i < 9; i++) xw[i] = bfma2(md[i], pack_bf(y[i >> 1][i & 1], y[i >> 1][2 + (i & 1)]), xw[i]);
        float r, mr;
        ln_stats(xw, g, q, r, mr);
        uint32_t h[9], r2 = pack_bf(r, r), m2 = pack_bf(mr, mr);
        #pragma unroll
        for (int i = 0; i < 9; i++) h[i] = bfma2(bfma2(xw[i], r2, m2), md[18 + i], md[9 + i]);
        ln_stats(h, g, q, r, mr);
        r2 = pack_bf(r, r); m2 = pack_bf(mr, mr);
        {
            const int n7 = 2 * q + (g >> 2);
            const uint32_t a = sm + OFF_STAGE + (warp >> 3) * 9216 + n7 * 128 + ((warp & 7) ^ n7) * 16 + (g & 3) * 4;
            #pragma unroll
            for (int i = 0; i < 9; i++) sts32(a + i * 1024, bfma2(h[i], r2, m2));
        }
        fence_async_s();
        __syncthreads();
        PROF0(12);
        if (tid == 0) {
            asm volatile("cp.async.bulk.tensor.4d.global.shared::cta.bulk_group [%0, {%2, %2, %2, %3}], [%1];" :: "l"(&tm_h3s), "r"(sm + OFF_STAGE), "r"(0), "r"(b) : "memory");
            asm volatile("cp.async.bulk.commit_group;" ::: "memory");
        }
        #pragma unroll
        for (int i = 0; i < 9; i++) sts32(sm + OFF_X1 + warp * 1152 + (32 * i + 8 * q + g) * 4, xw[i]);
    }
    __syncthreads();
    if (rowcta) {
        if (tid == 0) { asm volatile("cp.async.bulk.wait_group 0;" ::: "memory"); fence_async_g(); red_release(g_cnt + CNT_H3 * 32); }
        PROF0(13);
        if (warp == 15) {
            __nanosleep(X1DELAY);
            #pragma unroll 1
            for (int r = 0; r < 16; r++) {
                uint4* dst = (uint4*)(p.out + (size_t)(b + 128 * r) * D_) + lane;
                const uint32_t src = sm + OFF_X1 + r * 1152 + lane * 16;
                dst[0] = lds128(src); dst[32] = lds128(src + 512); if (lane < 8) dst[64] = lds128(src + 1024);
                const uint32_t t1 = clk32(); while ((int)(clk32() - t1) < X1PACE) __nanosleep(50);
            }
            __syncwarp();
            if (lane == 0) { fence_async_g(); red_release(g_cnt + CNT_X1 * 32); }
        }
    }
    role = __shfl_sync(~0u, lds32(sm + OFF_MISC), 0);
    if (role >= 64) { if (warp == 0) PROFDUMP(); return; }

    const int gi = role >> 3, dt = role & 3, c2 = (role >> 2) & 1;
    const int wg = warp >> 2, wi = warp & 3;
    if (wg == 3) {
        uint32_t so = 0, eph = 1;
        #define RING_STEP(BYTES, OFF, ISSUE) do { \
            mbar_wait(bars + 8 * BAR_EMPTY + so, eph); \
            if (elect()) { const uint32_t fb = bars + 8 * BAR_FULL + so, dst = sm + (OFF) + so * ((BYTES) / 8); mbar_expect(fb, BYTES); ISSUE; } \
            so += 8; if (so == 8 * NST) { so = 0; eph ^= 1; } } while (0)
        if (warp == 12) {
            eph = 0;
            const int fb1 = 9 * gi + 4 * c2 + 2 * rank, sb2 = 4 * gi + 2 * c2;
            #pragma unroll 1
            for (int j = 16; j < 128; j += 4) {
                RING_STEP(A_BYTES, OFF_A, tma4(dst, &tm_w1a, 0, 0, j, fb1, fb));
                if (j < 64) { if (j & 4) RING_STEP(A_BYTES, OFF_A, tma4(dst, &tm_w1b, 0, 0, 64 * rank + j - 4, 9 * gi + 8, fb)); }
                else if (PF2 && (j & 28) == 4 * (role & 7) && elect())
                    asm volatile("cp.async.bulk.prefetch.tensor.3d.L2.global [%0, {%1, %2, %3}];" :: "l"(&tm_w2), "r"(0), "r"(64 * g2_kb(dt + ((j >> 3) & 4), rank)), "r"(sb2) : "memory");
            }
            #pragma unroll 1
            for (int n = 0; n < 36; n++) {
                if (n == G2E) mbar_wait(bars + 8 * BAR_REL, 0);
                if (n == A2E) { mbar_wait(bars + 8 * (BAR_UOK + 1), 0); if (A2D) spin_until(clk32() + A2D); }
                RING_STEP(A_BYTES, OFF_A, tma3(dst, &tm_w2, 0, 64 * g2_kb(n, rank), sb2, fb));
            }
        } else if (warp == 13) {
            const uint32_t e1 = __shfl_sync(~0u, epoch + 1, 0);
            fence_async_s();
            wait_count<0>(g_cnt + CNT_H3 * 32, e1 * 128);
            fence_async_g();
            if (lane == 0) PROFT(14);
            #pragma unroll 1
            for (int j = 0; j < 128; j += 4) {
                RING_STEP(B_BYTES, OFF_B, tma3(dst, &tm_h3a, 0, 18 * dt, j, fb));
                if (j < 64 && (j & 4)) RING_STEP(B_BYTES, OFF_B, tma3(dst, &tm_h3b, 0, 18 * dt + 9 * c2, 64 * rank + j - 4, fb));
            }
            int n = 0;
            #pragma unroll 1
            for (int cls = 0; cls < 3; cls++) {
                mbar_wait(bars + 8 * (BAR_UOK + cls), 0);
                fence_async_g();
                if (cls == 1 && lane == 0) PROFT(19);
                if (cls == 0 && lane == 0) PROFT(22);
                #pragma unroll 1
                for (; n < 16 * cls + 4; n++) {
                    if (n == G2E) mbar_wait(bars + 8 * BAR_REL, 0);
                    RING_STEP(B_BYTES, OFF_B, bulk_load(dst, g_U + (g2_kb(n, rank) * 4 + dt) * 1152, B_BYTES, fb));
                }
            }
            if (role == 0 && rank == 0 && lane == 0) st_relaxed(g_cnt + CNT_EPOCH * 32, e1);
        } else if (warp == 15) {
            if (elect()) mbar_arrive_remote(mapa(bars + 8 * BAR_HOLD, rank ^ 1));
            __syncwarp();
            bar_sync(6, 160);
            mbar_wait(bars + 8 * BAR_W1GO, 0);
            if (elect()) {
                char* dst = (char*)(g_U + ((9 * gi + 4 * c2 + 2 * rank + 1) * 4 + dt) * 1152);
                #pragma unroll 1
                for (int i = 0; i < W1N; i++) {
                    asm volatile("cp.async.bulk.global.shared::cta.bulk_group [%0], [%1], %2;" :: "l"(dst + i * (18432 / W1N)), "r"(sm + OFF_X1 + i * (18432 / W1N)), "n"(18432 / W1N) : "memory");
                    const uint32_t t1 = clk32(); while ((int)(clk32() - t1) < W1P) {}
                }
                asm volatile("cp.async.bulk.commit_group;" ::: "memory");
                asm volatile("cp.async.bulk.wait_group 0;" ::: "memory");
                fence_async_g(); red_release(g_cnt + (CNT_U + 16 + UIDX(dt, gi >> 2)) * 32);
                #pragma unroll 1
                for (int n = 0; n < 4; n++) { __nanosleep(300); tma2(sm + OFF_X1 + n * 4608, &tm_o, 144 * dt, 256 * gi + 128 * c2 + 64 * (rank ^ 1) + 16 * n, bars + 8 * BAR_XT); }
            }
        } else {
            const uint32_t e1 = epoch + 1;
            if (lane == 0) {
                __nanosleep(4000);
                wait_count<200>(g_cnt + CNT_NC * 32, e1 * 4); wait_count<200>(g_cnt + (CNT_NC + 1) * 32, e1 * 2);
                fence_async_g();
                mbar_expect(bars + 8 * BAR_GB, 1152);
                bulk_load(sm + OFF_GB, p.scr->modc + 896, 1152, bars + 8 * BAR_GB);
                wait_count<200>(g_cnt + CNT_X1 * 32, e1 * 128);
                wait_count<50>(g_cnt + (CNT_U + dt * 2 + rank) * 32, e1 * 16);
                mbar_arrive(bars + 8 * BAR_UOK);
            }
            __syncwarp();
            bar_sync(4, 160);
            if (lane == 0) {
                fence_async_g(); red_release(g_cnt + (CNT_U + 8 + UIDX(dt, gi >> 2)) * 32);
                mbar_arrive(bars + 8 * BAR_REL);
                PROFT(17);
                wait_count<0>(g_cnt + (CNT_U + 8 + UIDX(dt, rank)) * 32, e1 * UCNT);
                mbar_arrive(bars + 8 * (BAR_UOK + 1));
                __nanosleep(1000);
                wait_count<100>(g_cnt + (CNT_U + 16 + UIDX(dt, rank)) * 32, e1 * UCNT);
                mbar_arrive(bars + 8 * (BAR_UOK + 2));
            }
        }
    } else if (wg == 2) {
        float d0[36];
        const float bias = bf_lo(ldg_nc16(p.b1 + 576 * gi + 512 + 16 * wi + g + 8 * rank));
        for (int it = 0; it < 200 && !__any_sync(~0u, mbar_test(bars + 8 * BAR_FULL, 0)); it++) { hb(); __nanosleep(100); }
        const bool lead = wi == 0 && elect();
        #pragma unroll 1
        for (int i = 0; i < 8; i++) {
            const uint32_t s = P2S + 3 * (i & 1);
            mbar_wait(bars + 8 * BAR_FULL + 8 * s, (i >> 1) & 1);
            const uint32_t da = desc_lo(sm + OFF_A, 8192) + s * (A_BYTES / 16), db = desc_lo(sm + OFF_B, 128) + s * (B_BYTES / 16);
            WG_FENCE();
            wgmma72(d0, da, db, i);
            #pragma unroll
            for (int k = 1; k < 8; k++) wgmma72(d0, da + k * 128, db + k * 144, 1);
            WG_COMMIT();
            WG_WAIT(0);
            if (lead) mbar_arrive_n(bars + 8 * BAR_EMPTY + 8 * s, 2);
        }
        if (lead) PROFT(18);
        const uint32_t slot = sm + OFF_P2R + (tid & 127) * 16, ra = mapa(slot, rank ^ 1), rb = mapa(bars + 8 * BAR_P2R, rank ^ 1);
        float sv[18];
        #pragma unroll
        for (int i = 0; i < 18; i++) { const float lo = d0[4 * (i >> 1) + (i & 1)], hi = d0[4 * (i >> 1) + 2 + (i & 1)];
            sv[i] = rank ? lo : hi; d0[4 * (i >> 1) + (i & 1)] = (rank ? hi : lo) + bias; }
        mbar_wait(bars + 8 * BAR_HOLD, 0);
        #pragma unroll
        for (int i = 0; i < 4; i++)
            asm volatile("st.async.weak.shared::cluster.mbarrier::complete_tx::bytes.v4.f32 [%0], {%1,%2,%3,%4}, [%5];"
                :: "r"(ra + i * 2048), "f"(sv[4 * i]), "f"(sv[4 * i + 1]), "f"(sv[4 * i + 2]), "f"(sv[4 * i + 3]), "r"(rb) : "memory");
        asm volatile("st.async.weak.shared::cluster.mbarrier::complete_tx::bytes.v2.f32 [%0], {%1,%2}, [%3];" :: "r"(ra + 8192), "f"(sv[16]), "f"(sv[17]), "r"(rb) : "memory");
        mbar_wait(bars + 8 * BAR_P2R, 0);
        #pragma unroll
        for (int i = 0; i < 5; i++) {
            const uint4 v = lds128(slot + i * 2048);
            d0[8 * i] += __uint_as_float(v.x); d0[8 * i + 1] += __uint_as_float(v.y);
            if (i < 4) { d0[8 * i + 4] += __uint_as_float(v.z); d0[8 * i + 5] += __uint_as_float(v.w); }
        }
        asm volatile("bar.arrive 5, 256;" ::: "memory");
        gelu_store<0>(d0, (char*)(g_U + ((9 * gi + 8) * 4 + dt) * 1152) + wi * 4608 + rank * 2304 + c2 * 1152 + g * 16, q);
        bar_sync(8, 128);
        if (lead) { fence_async_g(); red_release(g_cnt + (CNT_U + dt * 2 + (gi >> 2)) * 32); PROFT(26); }
    } else {
        float d[72];
        const bool lead = wi == 0 && elect();
        const uint32_t da0 = desc_lo(sm + OFF_A + wg * 8192, 8192);
        const bool owner = (uint32_t)wg == rank;
        const int srow = 256 * gi + 128 * c2 + 64 * wg + 16 * wi;
        const uint32_t b2w0 = ldg_nc16(p.b2 + srow + g), b2w1 = ldg_nc16(p.b2 + srow + g + 8);
        {
            const int fr = 576 * gi + 256 * c2 + 128 * rank + 64 * wg + 16 * wi + g;
            const float bias0 = bf_lo(ldg_nc16(p.b1 + fr)), bias1 = bf_lo(ldg_nc16(p.b1 + fr + 8));
            #pragma unroll
            for (int i = 0; i < 72; i++) d[i] = (i & 2) ? bias1 : bias0;
            const uint32_t db1 = desc_lo(sm + OFF_B, 128);
            mainloop<DHI_H3, 0, IT_P1, false, true, false>(d, bars, da0, db1, lead, [&](int) {});
            mainloop<DHI_H3, IT_P1, IT_G2 - LEAD1, false, false, false>(d, bars, da0, db1, lead, [&](int) {});
            constexpr uint32_t EB = 8 * (BAR_EMPTY + (IT_G2 - LEAD1 - 1) % NST);
            if (wg == 1) { WG_WAIT(0); if (lead) mbar_arrive(bars + EB); bar_sync(9, 256); }
            mainloop<DHI_H3, IT_G2 - LEAD1, IT_G2, false, true, true>(d, bars, da0, db1, lead, [&](int i) {
                if (wg == 0) { if (i == IT_G2 - LEAD1 && lead) mbar_arrive(bars + EB); if (i == IT_G2 - 1) asm volatile("bar.arrive 9, 256;" ::: "memory"); } });
            PROF0(16);
            if (wg == 1) bar_sync(5, 256);
            char* const ub = (wg == 0 ? (char*)(g_U + ((9 * gi + 4 * c2 + 2 * rank) * 4 + dt) * 1152) : (char*)__cvta_shared_to_generic(sm + OFF_X1)) + wi * 4608 + g * 16;
            gelu_store<0>(d, ub, q); gelu_store<2>(d, ub + 2304, q); gelu_store<36>(d, ub + 1152, q); gelu_store<38>(d, ub + 3456, q);
            PROF0(27);
            if (wg == 0) asm volatile("bar.arrive 4, 160;" ::: "memory");
            else { fence_async_s(); asm volatile("bar.arrive 6, 160;" ::: "memory"); }
        }
        const uint32_t db0 = desc_lo(sm + OFF_B, 2304);
        constexpr int IT_L = IT_END - NST, IT_X = IT_L - 4;
        mainloop<DHI_U, IT_G2, IT_X, true, true, false>(d, bars, da0, db0, lead,
            [&](int i) { if (i == IT_G2 + W1S && wg == 0 && lead) mbar_arrive(bars + 8 * BAR_W1GO); });
        const uint32_t ga0 = sm + OFF_GB + (144 * dt + 8 * q) * 2, tile = sm + OFF_X1 + wi * 4608, to = g * 288 + q * 16;
        #define QOFF(i_) (((i_) >> 2) * 2304 + 144 * (((i_) >> 1) & 1) + 64 * ((i_) & 1))
        #define SOFF(k_) (((k_) >> 1) * 2304 + 144 * ((k_) & 1) + 128 - 12 * q)
        #define DIDX(i_, k_) ((i_) < 8 ? 36 * (((i_) >> 1) & 1) + 16 * ((i_) & 1) + 4 * (k_) + 2 * ((i_) >> 2) : 36 * ((k_) & 1) + 32 + 2 * ((k_) >> 1))
        #define FIN(k_, f_) bfma2(g4.f_, pack_bf(d[DIDX(i, k_)], d[DIDX(i, k_) + 1]), xq[i].f_)
        uint4 xq[9];
        auto load_g = [&](int i) { uint4 r; if (i < 4) r = lds128(ga0 + QOFF(i)); else { r.x = r.z = lds32(ga0 + SOFF(0)); r.y = r.w = lds32(ga0 + SOFF(1)); } return r; };
        mainloop<DHI_U, IT_X, IT_L, false, false, false>(d, bars, da0, db0, lead, [&](int i) {
            if (!owner) {
                const uint32_t xa = tile + to;
                if (i == IT_X) { mbar_wait(bars + 8 * BAR_XT, 0); xq[0] = lds128(xa + QOFF(0)); xq[4] = lds128(xa + QOFF(4)); xq[1] = lds128(xa + QOFF(1)); }
                else if (i == IT_X + 1) { xq[5] = lds128(xa + QOFF(5)); xq[2] = lds128(xa + QOFF(2)); xq[6] = lds128(xa + QOFF(6)); }
                else if (i == IT_X + 2) { xq[3] = lds128(xa + QOFF(3)); xq[7] = lds128(xa + QOFF(7));
                    xq[8] = make_uint4(lds32(xa + SOFF(0)), lds32(xa + SOFF(1)), lds32(xa + SOFF(2)), lds32(xa + SOFF(3))); }
                else if (i == IT_X + 3) { if (elect()) mbar_arrive_remote(mapa(bars + 8 * BAR_DONE, rank ^ 1)); }
            } });
        if (owner) { WG_WAIT(0); if (lead) mbar_arrive(bars + 8 * (BAR_EMPTY + (IT_L - 1) % NST)); bar_sync(7, 256); }
        #pragma unroll
        for (int i = IT_L; i < IT_END; i++) {
            mbar_wait(bars + 8 * (BAR_FULL + i % NST), (i / NST) & 1);
            WG_FENCE();
            #pragma unroll
            for (int k = 0; k < 4; k++) wgmma144<DHI_U>(d, da0 + (i % NST) * (A_BYTES / 16) + k * 128, db0 + (i % NST) * (B_BYTES / 16) + k * 288, 1);
            WG_COMMIT();
            if (i == IT_L) { WG_WAIT(1); if (lead && !owner) mbar_arrive(bars + 8 * (BAR_EMPTY + (IT_L - 1) % NST)); }
        }
        PROF0(9);
        mbar_wait(bars + 8 * BAR_GB, 0);
        if (!owner) {
            const uint32_t ra = mapa(tile + lane * 16, rank ^ 1), rb = mapa(bars + 8 * BAR_RECV, rank ^ 1);
            mbar_wait(bars + 8 * BAR_DONE, 0);
            uint4 gn = load_g(0);
            WG_WAIT(1);
            asm volatile("bar.arrive 7, 256;" ::: "memory");
            WG_WAIT(0);
            #pragma unroll
            for (int i = 0; i < 72; i++) d[i] = fmaf(bf_lo((i & 2) ? b2w1 : b2w0), 2.f, d[i]);
            #pragma unroll
            for (int j = 0; j < 5; j++) {
                const uint4 g4 = gn;
                if (j < 4) gn = load_g(j + 1);
                #pragma unroll
                for (int i = j < 4 ? j : 8; i < 9; i += 4) if (i < 8 || j == 4)
                    asm volatile("st.async.weak.shared::cluster.mbarrier::complete_tx::bytes.v4.b32 [%0], {%1,%2,%3,%4}, [%5];"
                        :: "r"(ra + i * 512), "r"(FIN(0, x)), "r"(FIN(1, y)), "r"(FIN(2, z)), "r"(FIN(3, w)), "r"(rb) : "memory");
            }
            PROF0(6);
            if (warp == 0) PROFDUMP();
            return;
        }
        PROF0(24);
        mbar_wait(bars + 8 * BAR_RECV, 0);
        #pragma unroll
        for (int i = 0; i < 9; i++) xq[i] = lds128(tile + lane * 16 + i * 512);
        uint4 gn = load_g(0);
        WG_WAIT(0);
        __syncwarp();
        PROF0(21);
        #pragma unroll
        for (int j = 0; j < 5; j++) {
            const uint4 g4 = gn;
            if (j < 4) gn = load_g(j + 1);
            #pragma unroll
            for (int i = j < 4 ? j : 8; i < 9; i += 4) if (i < 8 || j == 4) {
                const uint4 o = make_uint4(FIN(0, x), FIN(1, y), FIN(2, z), FIN(3, w));
                if (i < 8) sts128(tile + to + QOFF(i), o);
                else { sts32(tile + to + SOFF(0), o.x); sts32(tile + to + SOFF(1), o.y); sts32(tile + to + SOFF(2), o.z); sts32(tile + to + SOFF(3), o.w); }
            }
        }
        fence_async_s();
        __syncwarp();
        if (elect()) {
            asm volatile("cp.async.bulk.tensor.2d.global.shared::cta.bulk_group [%0, {%2, %3}], [%1];" :: "l"(&tm_o), "r"(tile), "r"(144 * dt), "r"(srow) : "memory");
            asm volatile("cp.async.bulk.commit_group;" ::: "memory");
            asm volatile("cp.async.bulk.wait_group.read 0;" ::: "memory");
        }
        PROF0(23);
        if (warp == 0) { __syncwarp(); PROFDUMP(); }
    }
}

typedef CUresult (*EncodeFn)(CUtensorMap*, CUtensorMapDataType, cuuint32_t, void*, const cuuint64_t*, const cuuint64_t*, const cuuint32_t*,
                             const cuuint32_t*, CUtensorMapInterleave, CUtensorMapSwizzle, CUtensorMapL2promotion, CUtensorMapFloatOOBfill);

void encode(EncodeFn fn, CUtensorMap* m, CUtensorMapDataType dt, int rank, const void* ptr, const cuuint64_t* dims, const cuuint64_t* strides,
            const cuuint32_t* box, CUtensorMapSwizzle sw, CUtensorMapL2promotion promo = CU_TENSOR_MAP_L2_PROMOTION_L2_128B) {
    const cuuint32_t es[5] = {1, 1, 1, 1, 1};
    fn(m, dt, rank, (void*)ptr, dims, strides, box, es, CU_TENSOR_MAP_INTERLEAVE_NONE, sw, promo, CU_TENSOR_MAP_FLOAT_OOB_FILL_NONE);
}

}

extern "C" void kernel_launch(void* const* d_in, const int* in_sizes, int n_in, void* d_out, int out_size) {
    (void)in_sizes; (void)n_in; (void)out_size;
    Params p;
    p.x = (const uint16_t*)d_in[0]; p.wr = (const uint16_t*)d_in[1]; p.wi = (const uint16_t*)d_in[2];
    p.w1 = (const uint16_t*)d_in[4]; p.b1 = (const uint16_t*)d_in[5]; p.w2 = (const uint16_t*)d_in[6]; p.b2 = (const uint16_t*)d_in[7];
    p.c = (const uint16_t*)d_in[8]; p.wmod = (const uint16_t*)d_in[9]; p.out = (uint16_t*)d_out;

    void* fnp = nullptr; cudaDriverEntryPointQueryResult qr;
    cudaGetDriverEntryPoint("cuTensorMapEncodeTiled", &fnp, cudaEnableDefault, &qr);
    EncodeFn fn = (EncodeFn)fnp;
    cudaGetSymbolAddress((void**)&p.scr, g_scr); cudaGetSymbolAddress((void**)&p.tab, g_tab);
    void* h3p = p.scr->h3;
    CUtensorMap tw1a, tw1b, tw2, th3a, th3b, twr, twi, twm, tt, ttx, to, th3s;
    {
        const cuuint64_t dims[4] = {64, 16, 128, 72}, st[3] = {128ull * F_ * 2, (cuuint64_t)F_ * 2, 128};
        const cuuint32_t ba[4] = {64, 16, 4, 2}, bb[4] = {64, 16, 8, 1};
        encode(fn, &tw1a, CU_TENSOR_MAP_DATA_TYPE_BFLOAT16, 4, p.w1, dims, st, ba, CU_TENSOR_MAP_SWIZZLE_128B);
        encode(fn, &tw1b, CU_TENSOR_MAP_DATA_TYPE_BFLOAT16, 4, p.w1, dims, st, bb, CU_TENSOR_MAP_SWIZZLE_128B);
    }
    {
        const cuuint64_t dims[3] = {64, F_, 32}, st[2] = {(cuuint64_t)S_ * 2, 128};
        const cuuint32_t bx[3] = {64, 64, 2};
        encode(fn, &tw2, CU_TENSOR_MAP_DATA_TYPE_BFLOAT16, 3, p.w2, dims, st, bx, CU_TENSOR_MAP_SWIZZLE_128B);
    }
    {
        const cuuint64_t dims[3] = {64, 72, 128}, st[2] = {256, 18432};
        const cuuint32_t ba[3] = {64, 18, 4}, bb[3] = {64, 9, 8};
        encode(fn, &th3a, CU_TENSOR_MAP_DATA_TYPE_UINT32, 3, h3p, dims, st, ba, CU_TENSOR_MAP_SWIZZLE_NONE);
        encode(fn, &th3b, CU_TENSOR_MAP_DATA_TYPE_UINT32, 3, h3p, dims, st, bb, CU_TENSOR_MAP_SWIZZLE_NONE);
    }
    {
        const cuuint64_t dims[4] = {32, 72, 2, 128}, st[3] = {256, 128, 18432};
        const cuuint32_t bx[4] = {32, 72, 2, 1};
        encode(fn, &th3s, CU_TENSOR_MAP_DATA_TYPE_UINT32, 4, h3p, dims, st, bx, CU_TENSOR_MAP_SWIZZLE_128B, CU_TENSOR_MAP_L2_PROMOTION_NONE);
    }
    {
        const cuuint64_t dims[3] = {4624, 4, 32}, st[2] = {9248 * 32, 9248};
        const cuuint32_t bx[3] = {56, 4, 32};
        encode(fn, &twr, CU_TENSOR_MAP_DATA_TYPE_BFLOAT16, 3, p.wr, dims, st, bx, CU_TENSOR_MAP_SWIZZLE_NONE);
        encode(fn, &twi, CU_TENSOR_MAP_DATA_TYPE_BFLOAT16, 3, p.wi, dims, st, bx, CU_TENSOR_MAP_SWIZZLE_NONE);
    }
    {
        const cuuint64_t dims[3] = {64, 576, 54}, st[2] = {6912, 128};
        const cuuint32_t bx[3] = {64, 32, 7};
        encode(fn, &twm, CU_TENSOR_MAP_DATA_TYPE_BFLOAT16, 3, p.wmod, dims, st, bx, CU_TENSOR_MAP_SWIZZLE_128B);
    }
    {
        const cuuint64_t dims[2] = {TP, 128}, st[1] = {TP * 4};
        const cuuint32_t ba[2] = {32, 128}, bb[2] = {8, 128};
        encode(fn, &tt, CU_TENSOR_MAP_DATA_TYPE_UINT32, 2, p.scr->T, dims, st, ba, CU_TENSOR_MAP_SWIZZLE_128B, CU_TENSOR_MAP_L2_PROMOTION_NONE);
        encode(fn, &ttx, CU_TENSOR_MAP_DATA_TYPE_UINT32, 2, p.scr->T, dims, st, bb, CU_TENSOR_MAP_SWIZZLE_32B, CU_TENSOR_MAP_L2_PROMOTION_NONE);
    }
    {
        const cuuint64_t dims[2] = {D_, S_}, st[1] = {D_ * 2};
        const cuuint32_t bx[2] = {144, 16};
        encode(fn, &to, CU_TENSOR_MAP_DATA_TYPE_BFLOAT16, 2, p.out, dims, st, bx, CU_TENSOR_MAP_SWIZZLE_NONE, CU_TENSOR_MAP_L2_PROMOTION_NONE);
    }
    cudaFuncSetAttribute(fused_kernel, cudaFuncAttributeMaxDynamicSharedMemorySize, SMEM_BYTES);
    cudaLaunchConfig_t cfg = {};
    cfg.gridDim = dim3(NCTA); cfg.blockDim = dim3(NTHR); cfg.dynamicSmemBytes = SMEM_BYTES; cfg.stream = cudaStreamPerThread;
    cudaLaunchAttribute at[1];
    at[0].id = cudaLaunchAttributeCooperative; at[0].val.cooperative = 1;
    cfg.attrs = at; cfg.numAttrs = 1;
    cudaLaunchKernelEx(&cfg, fused_kernel, p, tw1a, tw1b, tw2, th3a, th3b, twr, twi, twm, tt, ttx, to, th3s);
}
```

```cpp
#include <cuda_runtime.h>
#include <cuda_bf16.h>
#include <cuda_fp16.h>
#include <cuda.h>
#include <stdint.h>

namespace {

constexpr int S_ = 2048, D_ = 576, F_ = 4608;
constexpr int NCTA = 132, NTHR = 512;
constexpr int TP = 4736;
constexpr int SPEC_P = 296;
constexpr int NST = 6;
constexpr int A_BYTES = 16384, B_BYTES = 18432;
constexpr int IT_P1 = 24, IT_G2 = 40, IT_END = 76;
constexpr int SPIN_LIMIT = 1 << 22;
#define MODPAD 16
#define X2D 1300
#define CPHINT ".L2::128B"
constexpr int P2S = 2;
#define G2E 4
#define LEAD1 4
#define A2E 6
#define A2D 100
#define W1N 8
#define W1P 100
#define W1S 4
#define XDELAY 1600
#define X1D 2300
#define PF2 1
#define X1DELAY 2000
#define X1PACE 400

constexpr int OFF_A = 0;
constexpr int OFF_B = NST * A_BYTES;
constexpr int OFF_P = OFF_B + NST * B_BYTES;
constexpr int OFF_BAR = OFF_P;
constexpr int OFF_MISC = OFF_P + 376;
constexpr int OFF_GB = OFF_P + 384;
constexpr int OFF_P2R = OFF_P + 1536;
constexpr int OFF_X1 = OFF_P2R;
constexpr int OFF_PROF = OFF_X1 + 18432;
constexpr int SMEM_BYTES = OFF_PROF + 512 + 1024;
constexpr int QA = 13, QB = 7, QC = 13;
constexpr int TAB_BYTES = (QA + QB + QC) * 512;
constexpr int OFF_STAGE = OFF_B;
constexpr int OFF_STX = OFF_STAGE + 16384;
constexpr int OFF_TAB = OFF_STAGE + 20480;
constexpr int OFF_SPEC = OFF_TAB + TAB_BYTES;
constexpr int OFF_WRAW = OFF_SPEC + 19072;
constexpr int OFF_B3 = OFF_WRAW + 28672;
constexpr int OFF_MODA = OFF_B3 + 4096;
constexpr int OFF_MODC = OFF_MODA + 2560;
constexpr int OFF_RED = OFF_MODC + 3584;
constexpr int OFF_SILU = OFF_RED + 768;
static_assert(OFF_SILU + 1152 <= OFF_P && 6 * 28672 <= OFF_B3, "scratch overflow");
constexpr int OFF_STRIP = OFF_A;
static_assert(OFF_WRAW % 128 == 0 && OFF_STAGE % 128 == 0 && OFF_STX % 128 == 0, "align");
constexpr int BAR_FULL = 0, BAR_EMPTY = 6, BAR_TAB = 12, BAR_W = 13, BAR_REL = 14, BAR_P2R = 16,
              BAR_XT = 17, BAR_RECV = 18, BAR_ROLE = 19, BAR_NC = 20, BAR_TAB2 = 21, BAR_XB = 22, BAR_GB = 23, BAR_HOLD = 24, BAR_W1GO = 25, BAR_UOK = 26, BAR_DONE = 30, BAR_X = 31;

struct Cos1152 { double c[1152]; };
constexpr double cx_cos(double x) { double t = 1, s = 1; for (int i = 1; i < 14; i++) { t *= -x * x / ((2 * i - 1) * (2 * i)); s += t; } return s; }
constexpr Cos1152 make_cos() {
    Cos1152 r{};
    for (int i = 0; i <= 288; i++) {
        double v = (i == 288) ? 0.0 : cx_cos(3.14159265358979323846 * 2.0 * i / 1152.0);
        r.c[i] = v; r.c[576 - i] = -v; r.c[576 + i] = -v; r.c[(1152 - i) % 1152] = v;
    }
    return r;
}
constexpr uint32_t cx_f2h(double v) {
    uint32_t s = v < 0 ? 0x8000u : 0u; double a = v < 0 ? -v : v;
    if (a < 1e-9) return 0;
    int e = 0;
    while (a >= 2.0) { a *= 0.5; e++; }
    while (a < 1.0 && e > -14) { a *= 2.0; e--; }
    double m = a * 1024.0; uint32_t mi = (uint32_t)m; double fr = m - mi;
    if (fr > 0.5 || (fr == 0.5 && (mi & 1))) mi++;
    return s | (uint32_t)(((e + 14) << 10) + mi);
}
struct Tab { uint32_t w[(QA + QB + QC) * 128]; };
constexpr Tab make_tab() {
    Tab t{};
    Cos1152 ct = make_cos();
    auto C = [&](int num, int den) { return ct.c[(num % den) * (1152 / den)]; };
    auto Sn = [&](int num, int den) { return ct.c[((num % den) * (1152 / den) + 864) % 1152]; };
    auto put = [&](int q0, int idx, int lane, double lo, double hi) { t.w[((q0 + idx / 4) * 32 + lane) * 4 + idx % 4] = cx_f2h(lo) | (cx_f2h(hi) << 16); };
    for (int lane = 0; lane < 32; lane++) {
        const int g = lane >> 2, q = lane & 3;
        for (int mt = 0; mt < 3; mt++) {
            const int ka = 8 * mt + g;
            for (int r = 0; r < 10; r++) {
                const int im = r & 1, i0 = (r >> 1) * 2;
                double v[2] = {0, 0};
                for (int e = 0; e < 2; e++) { int i = i0 + e, d1 = 4 * i + q; if (i < 9 && ka <= 18) v[e] = (im ? -Sn(ka * d1, 36) : C(ka * d1, 36)) / 8; }
                put(0, mt * 10 + r, lane, v[0], v[1]);
            }
            for (int v = 0; v < 2; v++) {
                const int d2 = 4 * q + v;
                put(0, 30 + (mt * 2 + v) * 2, lane, C(ka * d2, 576) * 4 / 3, C(ka * (d2 + 2), 576) * 4 / 3);
                put(0, 31 + (mt * 2 + v) * 2, lane, Sn(ka * d2, 576) * 4 / 3, Sn(ka * (d2 + 2), 576) * 4 / 3);
            }
        }
        for (int v = 0; v < 2; v++) for (int nt = 0; nt < 2; nt++) {
            const int kb = 2 * (g >> 1) + nt, part = g & 1;
            double b0[2] = {0, 0}, b1[2] = {0, 0};
            for (int e = 0; e < 2; e++) { int d2 = 4 * q + 2 * e + v; double c = C(kb * d2, 16) / 4, s = Sn(kb * d2, 16) / 4;
                b0[e] = part ? -s : c; b1[e] = part ? c : s; }
            put(0, 42 + (v * 2 + nt) * 2, lane, b0[0], b0[1]); put(0, 43 + (v * 2 + nt) * 2, lane, b1[0], b1[1]);
        }
        for (int par = 0; par < 2; par++) for (int a = 0; a < 4; a++) {
            const int ja = 2 * (q + 4 * (a >> 1)) + par; const double c = C(g * ja, 16) / 4, s = Sn(g * ja, 16) / 4;
            put(QA, par * 4 + a, lane, (a & 1) ? -s : c, (a & 1) ? c : s);
        }
        for (int h = 0; h < 2; h++) {
            put(QA, 8 + 2 * h, lane, C((g + 8 * h) * (2 * q), 128) / 2, C((g + 8 * h) * (2 * q + 1), 128) / 2);
            put(QA, 9 + 2 * h, lane, Sn((g + 8 * h) * (2 * q), 128) / 2, Sn((g + 8 * h) * (2 * q + 1), 128) / 2);
            put(QA, 15 + 2 * h, lane, C(g * (8 * h + 2 * q), 128), C(g * (8 * h + 2 * q + 1), 128));
            put(QA, 16 + 2 * h, lane, Sn(g * (8 * h + 2 * q), 128), Sn(g * (8 * h + 2 * q + 1), 128));
        }
        put(QA, 12, lane, C(g * 2 * q, 8) / 2, C(g * (2 * q + 1), 8) / 2);
        put(QA, 13, lane, Sn(g * 2 * q, 8) / 2, Sn(g * (2 * q + 1), 8) / 2);
        put(QA, 14, lane, -Sn(g * 2 * q, 8) / 2, -Sn(g * (2 * q + 1), 8) / 2);
        for (int u = 0; u < 4; u++) {
            const int ja = 2 * ((g >> 1) + 4 * (u & 1)) + (u >> 1), part = g & 1; double b0[2] = {0, 0}, b1[2] = {0, 0};
            for (int e = 0; e < 2; e++) { int ka = 2 * q + e; double c = C(ja * ka, 16) / 4, s = Sn(ja * ka, 16) / 4;
                b0[e] = part ? s : c; b1[e] = part ? c : -s; }
            put(QA, 19 + u * 2, lane, b0[0], b0[1]); put(QA, 20 + u * 2, lane, b1[0], b1[1]);
        }
        for (int m2 = 0; m2 < 2; m2++) {
            const int d2 = 2 * g + m2;
            for (int a = 0; a < 4; a++) {
                const int kb = 2 * q + (a >> 1); const double c = C(d2 * kb, 16) / 4, s = Sn(d2 * kb, 16) / 4;
                put(QA + QB, m2 * 4 + a, lane, (a & 1) ? s : c, (a & 1) ? c : -s);
            }
            for (int mt = 0; mt < 3; mt++) {
                const int ka = 8 * mt + 2 * q;
                put(QA + QB, 8 + (m2 * 3 + mt) * 2, lane, C(ka * d2, 576) * 4 / 3, C((ka + 1) * d2, 576) * 4 / 3);
                put(QA + QB, 9 + (m2 * 3 + mt) * 2, lane, Sn(ka * d2, 576) * 4 / 3, Sn((ka + 1) * d2, 576) * 4 / 3);
            }
        }
        for (int mt = 0; mt < 3; mt++) for (int nt = 0; nt < 5; nt++) {
            const int i = 2 * nt + (g & 1), d1 = 4 * i + (g >> 1); double b0[2] = {0, 0}, b1[2] = {0, 0};
            for (int e = 0; e < 2; e++) { int ka = 8 * mt + 2 * q + e;
                if (ka <= 18 && i < 9) { double wt = (ka == 0 || ka == 18) ? 0.125 : 0.25; b0[e] = wt * C(ka * d1, 36); b1[e] = -wt * Sn(ka * d1, 36); } }
            put(QA + QB, 20 + (mt * 5 + nt) * 2, lane, b0[0], b0[1]); put(QA + QB, 21 + (mt * 5 + nt) * 2, lane, b1[0], b1[1]);
        }
    }
    return t;
}
__device__ __align__(128) const Tab g_tab = make_tab();

struct Scratch {
    uint32_t cnt[30 * 32];
    uint32_t slot[96];
    uint32_t mod[2304];
    uint32_t modc[896 + 288];
    uint32_t T[128 * TP];
    uint4 h3[128 * 1152];
    uint4 U[72 * 4 * 1152];
};
__device__ __align__(1024) Scratch g_scr;
#define g_cnt (p.scr->cnt)
#define g_slot (p.scr->slot)
#define g_mod (p.scr->mod)
#define g_T (p.scr->T)
#define g_h3 (p.scr->h3)
#define g_U (p.scr->U)
constexpr int CNT_EPOCH = 0, CNT_H3 = 1, CNT_X1 = 26, CNT_NC = 27, CNT_U = 2;
#define PROFT(i) do {} while (0)
#define PROFDUMP() do {} while (0)
#define PROF0(i) do {} while (0)

__device__ __forceinline__ void mbar_init(uint32_t bar, uint32_t cnt) { asm volatile("mbarrier.init.shared::cta.b64 [%0], %1;" :: "r"(bar), "r"(cnt) : "memory"); }
__device__ __forceinline__ void mbar_expect(uint32_t bar, uint32_t bytes) { asm volatile("mbarrier.arrive.expect_tx.shared::cta.b64 _, [%0], %1;" :: "r"(bar), "r"(bytes) : "memory"); }
__device__ __forceinline__ void mbar_arrive(uint32_t bar) { asm volatile("mbarrier.arrive.shared::cta.b64 _, [%0];" :: "r"(bar) : "memory"); }
__device__ __forceinline__ void mbar_arrive_n(uint32_t bar, uint32_t n) { asm volatile("mbarrier.arrive.shared::cta.b64 _, [%0], %1;" :: "r"(bar), "r"(n) : "memory"); }
__device__ __forceinline__ void mbar_arrive_remote(uint32_t rbar) { asm volatile("mbarrier.arrive.relaxed.cluster.shared::cluster.b64 _, [%0];" :: "r"(rbar) : "memory"); }
__device__ __forceinline__ void mbar_wait(uint32_t bar, uint32_t parity) {
    asm volatile("{.reg .pred p; .reg .u32 c;\n"
        "mbarrier.try_wait.parity.shared::cta.b64 p, [%0], %1;\n@p bra.uni DONE;\nmov.u32 c, 0;\n"
        "LOOP: mbarrier.try_wait.parity.shared::cta.b64 p, [%0], %1;\n@p bra.uni DONE;\n"
        "add.u32 c, c, 1;\nsetp.lt.u32 p, c, %2;\n@p bra.uni LOOP;\ntrap;\nDONE:}" :: "r"(bar), "r"(parity), "n"(SPIN_LIMIT) : "memory");
}
__device__ __forceinline__ bool mbar_test(uint32_t bar, uint32_t parity) {
    uint32_t ok; asm volatile("{.reg .pred p; mbarrier.test_wait.parity.shared::cta.b64 p, [%1], %2; selp.u32 %0, 1, 0, p;}" : "=r"(ok) : "r"(bar), "r"(parity) : "memory"); return ok; }
__device__ __forceinline__ uint32_t mapa(uint32_t a, uint32_t rank) { uint32_t r; asm("mapa.shared::cluster.u32 %0, %1, %2;" : "=r"(r) : "r"(a), "r"(rank)); return r; }
__device__ __forceinline__ uint32_t clk32() { uint32_t r; asm volatile("mov.u32 %0, %%clock;" : "=r"(r)); return r; }
__device__ __forceinline__ void hb() {
    asm volatile("{.reg .b32 a, b; .reg .pred p; mma.sync.aligned.m16n8k8.row.col.f16.f16.f16.f16 {a, b}, {%0,%0}, {%0}, {%0,%0};\n"
                 "setp.ne.u32 p, a, 0; @p trap;}" :: "r"(0));
}
__device__ __forceinline__ void spin_until(uint32_t t) { while (__any_sync(~0u, (int)(clk32() - t) < 0)) hb(); }
__device__ __forceinline__ bool elect() { uint32_t r; asm volatile("{.reg .pred p; elect.sync _|p, 0xffffffff; selp.u32 %0, 1, 0, p;}" : "=r"(r)); return r; }
__device__ __forceinline__ void bar_sync(int id, int n) { asm volatile("bar.sync %0, %1;" :: "r"(id), "r"(n) : "memory"); }
__device__ __forceinline__ void bulk_load(uint32_t dst, const void* src, uint32_t bytes, uint32_t bar) {
    asm volatile("cp.async.bulk.shared::cluster.global.mbarrier::complete_tx::bytes [%0], [%1], %2, [%3];" :: "r"(dst), "l"(src), "r"(bytes), "r"(bar) : "memory"); }
__device__ __forceinline__ void tma2(uint32_t dst, const CUtensorMap* m, int c0, int c1, uint32_t bar) {
    asm volatile("cp.async.bulk.tensor.2d.shared::cluster.global.mbarrier::complete_tx::bytes [%0], [%1, {%3, %4}], [%2];" :: "r"(dst), "l"(m), "r"(bar), "r"(c0), "r"(c1) : "memory"); }
__device__ __forceinline__ void tma3(uint32_t dst, const CUtensorMap* m, int c0, int c1, int c2, uint32_t bar) {
    asm volatile("cp.async.bulk.tensor.3d.shared::cluster.global.mbarrier::complete_tx::bytes [%0], [%1, {%3, %4, %5}], [%2];" :: "r"(dst), "l"(m), "r"(bar), "r"(c0), "r"(c1), "r"(c2) : "memory"); }
__device__ __forceinline__ void tma4(uint32_t dst, const CUtensorMap* m, int c0, int c1, int c2, int c3, uint32_t bar) {
    asm volatile("cp.async.bulk.tensor.4d.shared::cluster.global.mbarrier::complete_tx::bytes [%0], [%1, {%3, %4, %5, %6}], [%2];" :: "r"(dst), "l"(m), "r"(bar), "r"(c0), "r"(c1), "r"(c2), "r"(c3) : "memory"); }
__device__ __forceinline__ void fence_async_g() { asm volatile("fence.proxy.async.global;" ::: "memory"); }
__device__ __forceinline__ void fence_async_s() { asm volatile("fence.proxy.async.shared::cta;" ::: "memory"); }
__device__ __forceinline__ uint4 lds128(uint32_t a) { uint4 v; asm volatile("ld.shared.v4.u32 {%0,%1,%2,%3}, [%4];" : "=r"(v.x), "=r"(v.y), "=r"(v.z), "=r"(v.w) : "r"(a) : "memory"); return v; }
__device__ __forceinline__ uint32_t lds32(uint32_t a) { uint32_t v; asm volatile("ld.shared.u32 %0, [%1];" : "=r"(v) : "r"(a) : "memory"); return v; }
__device__ __forceinline__ void sts128(uint32_t a, uint4 v) { asm volatile("st.shared.v4.u32 [%0], {%1,%2,%3,%4};" :: "r"(a), "r"(v.x), "r"(v.y), "r"(v.z), "r"(v.w) : "memory"); }
__device__ __forceinline__ void sts32(uint32_t a, uint32_t v) { asm volatile("st.shared.u32 [%0], %1;" :: "r"(a), "r"(v) : "memory"); }
__device__ __forceinline__ void sts16(uint32_t a, uint32_t v) { asm volatile("st.shared.u16 [%0], %1;" :: "r"(a), "h"((uint16_t)v) : "memory"); }
__device__ __forceinline__ uint4 ldx128(const void* p) {
    uint4 v; asm volatile("{.reg .b128 t; .reg .b64 a, b; ld.relaxed.gpu.global.b128 t, [%4]; mov.b128 {a, b}, t; mov.b64 {%0,%1}, a; mov.b64 {%2,%3}, b;}"
        : "=r"(v.x), "=r"(v.y), "=r"(v.z), "=r"(v.w) : "l"(p) : "memory"); return v; }
__device__ __forceinline__ void stx128(void* p, uint4 v) {
    asm volatile("{.reg .b128 t; .reg .b64 a, b; mov.b64 a, {%1,%2}; mov.b64 b, {%3,%4}; mov.b128 t, {a, b}; st.relaxed.gpu.global.b128 [%0], t;}"
        :: "l"(p), "r"(v.x), "r"(v.y), "r"(v.z), "r"(v.w) : "memory"); }
__device__ __forceinline__ uint32_t ld_relaxed(const uint32_t* p) { uint32_t v; asm volatile("ld.relaxed.gpu.global.u32 %0, [%1];" : "=r"(v) : "l"(p) : "memory"); return v; }
__device__ __forceinline__ uint32_t ld_acquire(const uint32_t* p) { uint32_t v; asm volatile("ld.acquire.gpu.global.u32 %0, [%1];" : "=r"(v) : "l"(p) : "memory"); return v; }
__device__ __forceinline__ void st_relaxed(uint32_t* p, uint32_t v) { asm volatile("st.relaxed.gpu.global.u32 [%0], %1;" :: "l"(p), "r"(v) : "memory"); }
__device__ __forceinline__ void red_release(uint32_t* p) { asm volatile("red.release.gpu.global.add.u32 [%0], 1;" :: "l"(p) : "memory"); }
template <int SLEEP> __device__ __forceinline__ void wait_count(const uint32_t* p, uint32_t target) {
    int it = 0; while ((int)(ld_acquire(p) - target) < 0) { if (SLEEP) __nanosleep(SLEEP); if (++it > SPIN_LIMIT) __trap(); }
}
__device__ __forceinline__ uint32_t ldg_nc32(const void* p) { uint32_t v; asm volatile("ld.global.nc.L1::no_allocate.u32 %0, [%1];" : "=r"(v) : "l"(p)); return v; }
__device__ __forceinline__ uint32_t ldg_nc16(const void* p) { uint16_t v; asm volatile("ld.global.nc.u16 %0, [%1];" : "=h"(v) : "l"(p)); return v; }
__device__ __forceinline__ float bf_lo(uint32_t w) { return __uint_as_float(w << 16); }
__device__ __forceinline__ float bf_hi(uint32_t w) { return __uint_as_float(w & 0xFFFF0000u); }
__device__ __forceinline__ uint32_t pack_bf(float lo, float hi) { uint32_t r; asm("cvt.rn.bf16x2.f32 %0, %1, %2;" : "=r"(r) : "f"(hi), "f"(lo)); return r; }
__device__ __forceinline__ uint32_t pack_h(float lo, float hi) { uint32_t r; asm("cvt.rn.f16x2.f32 %0, %1, %2;" : "=r"(r) : "f"(hi), "f"(lo)); return r; }
__device__ __forceinline__ float bf_round(float v) { return bf_lo(pack_bf(v, 0.f)); }
__device__ __forceinline__ uint32_t hmul2(uint32_t a, uint32_t b) { uint32_t r; asm("mul.rn.f16x2 %0, %1, %2;" : "=r"(r) : "r"(a), "r"(b)); return r; }
__device__ __forceinline__ uint32_t hfma2(uint32_t a, uint32_t b, uint32_t c) { uint32_t r; asm("fma.rn.f16x2 %0, %1, %2, %3;" : "=r"(r) : "r"(a), "r"(b), "r"(c)); return r; }
__device__ __forceinline__ uint32_t hfms2(uint32_t a, uint32_t b, uint32_t c) { uint32_t r; asm("{.reg .b32 t; neg.f16x2 t, %3; fma.rn.f16x2 %0, %1, %2, t;}" : "=r"(r) : "r"(a), "r"(b), "r"(c)); return r; }
__device__ __forceinline__ uint32_t hadd2(uint32_t a, uint32_t b) { uint32_t r; asm("add.rn.f16x2 %0, %1, %2;" : "=r"(r) : "r"(a), "r"(b)); return r; }
__device__ __forceinline__ uint32_t hsub2(uint32_t a, uint32_t b) { uint32_t r; asm("sub.rn.f16x2 %0, %1, %2;" : "=r"(r) : "r"(a), "r"(b)); return r; }
__device__ __forceinline__ void cmul_neg(uint32_t& re, uint32_t& im, uint32_t c, uint32_t s) { uint32_t a = hfma2(re, c, hmul2(im, s)), b = hfms2(im, c, hmul2(re, s)); re = a; im = b; }
__device__ __forceinline__ void cmul_pos(uint32_t& re, uint32_t& im, uint32_t c, uint32_t s) { uint32_t a = hfms2(re, c, hmul2(im, s)), b = hfma2(im, c, hmul2(re, s)); re = a; im = b; }
__device__ __forceinline__ void mma_h(uint32_t& d0, uint32_t& d1, uint32_t a0, uint32_t a1, uint32_t a2, uint32_t a3, uint32_t b0, uint32_t b1) {
    asm("mma.sync.aligned.m16n8k16.row.col.f16.f16.f16.f16 {%0,%1}, {%2,%3,%4,%5}, {%6,%7}, {%0,%1};" : "+r"(d0), "+r"(d1) : "r"(a0), "r"(a1), "r"(a2), "r"(a3), "r"(b0), "r"(b1)); }
__device__ __forceinline__ void mma_h8(uint32_t& d0, uint32_t& d1, uint32_t a0, uint32_t a1, uint32_t b0) {
    asm("mma.sync.aligned.m16n8k8.row.col.f16.f16.f16.f16 {%0,%1}, {%2,%3}, {%4}, {%0,%1};" : "+r"(d0), "+r"(d1) : "r"(a0), "r"(a1), "r"(b0)); }
__device__ __forceinline__ void mma_f(float (&d)[4], uint32_t a0, uint32_t a1, uint32_t a2, uint32_t a3, uint32_t b0, uint32_t b1) {
    asm("mma.sync.aligned.m16n8k16.row.col.f32.f16.f16.f32 {%0,%1,%2,%3}, {%4,%5,%6,%7}, {%8,%9}, {%0,%1,%2,%3};"
        : "+f"(d[0]), "+f"(d[1]), "+f"(d[2]), "+f"(d[3]) : "r"(a0), "r"(a1), "r"(a2), "r"(a3), "r"(b0), "r"(b1)); }
template <int NQ> __device__ __forceinline__ void load_tab(uint32_t (&r)[NQ * 4], uint32_t addr) {
    #pragma unroll
    for (int i = 0; i < NQ; i++) { uint4 v = lds128(addr + i * 512); r[4 * i] = v.x; r[4 * i + 1] = v.y; r[4 * i + 2] = v.z; r[4 * i + 3] = v.w; }
}
__device__ __forceinline__ float gelu2(float x) {
    float t = x * fmaf(x * x, 0.044715f * 0.7978845608028654f, 0.7978845608028654f), th;
    asm volatile("tanh.approx.f32 %0, %1;" : "=f"(th) : "f"(t));
    return fmaf(x, th, x);
}
__device__ __forceinline__ uint32_t desc_lo(uint32_t addr, uint32_t lbo) { return ((addr & 0x3FFFF) >> 4) | ((lbo >> 4) << 16); }
constexpr uint32_t DHI_A = (1024 >> 4) | (1u << 30), DHI_H3 = 256 >> 4, DHI_U = 128 >> 4;
#define WG_FENCE() asm volatile("wgmma.fence.sync.aligned;" ::: "memory")
#define WG_COMMIT() asm volatile("wgmma.commit_group.sync.aligned;" ::: "memory")
#define WG_WAIT(n) asm volatile("wgmma.wait_group.sync.aligned %0;" :: "n"(n) : "memory")
#define R4(b) "+f"(d[b]), "+f"(d[b + 1]), "+f"(d[b + 2]), "+f"(d[b + 3])
#define R12(b) R4(b), R4(b + 4), R4(b + 8)
#define R36(b) R12(b), R12(b + 12), R12(b + 24)
template <uint32_t BHI> __device__ __forceinline__ void wgmma144(float (&d)[72], uint32_t da, uint32_t db, int acc) {
    asm volatile("{.reg .pred p; .reg .b64 a, b; setp.ne.b32 p, %74, 0; mov.b64 a, {%72, %75}; mov.b64 b, {%73, %76};\n"
        "wgmma.mma_async.sync.aligned.m64n144k16.f32.bf16.bf16 {%0,%1,%2,%3,%4,%5,%6,%7,%8,%9,%10,%11,%12,%13,%14,%15,%16,%17,%18,%19,%20,%21,%22,%23,"
        "%24,%25,%26,%27,%28,%29,%30,%31,%32,%33,%34,%35,%36,%37,%38,%39,%40,%41,%42,%43,%44,%45,%46,%47,"
        "%48,%49,%50,%51,%52,%53,%54,%55,%56,%57,%58,%59,%60,%61,%62,%63,%64,%65,%66,%67,%68,%69,%70,%71}, a, b, p, 1, 1, 1, 1;}\n"
        : R36(0), R36(36) : "r"(da), "r"(db), "r"(acc), "n"(DHI_A), "n"(BHI));
}
__device__ __forceinline__ void wgmma144x4(float (&d)[72], const uint64_t (&a)[4], const uint64_t (&b)[4], int acc) {
    #define WG144 "wgmma.mma_async.sync.aligned.m64n144k16.f32.bf16.bf16 {%0,%1,%2,%3,%4,%5,%6,%7,%8,%9,%10,%11,%12,%13,%14,%15,%16,%17,%18,%19,%20,%21,%22,%23,%24,%25,%26,%27,%28,%29,%30,%31,%32,%33,%34,%35,%36,%37,%38,%39,%40,%41,%42,%43,%44,%45,%46,%47,%48,%49,%50,%51,%52,%53,%54,%55,%56,%57,%58,%59,%60,%61,%62,%63,%64,%65,%66,%67,%68,%69,%70,%71}, "
    asm volatile("{.reg .pred p; setp.ne.b32 p, %80, 0;\n"
        WG144 "%72, %76, p, 1, 1, 1, 1;\n" WG144 "%73, %77, 1, 1, 1, 1, 1;\n" WG144 "%74, %78, 1, 1, 1, 1, 1;\n" WG144 "%75, %79, 1, 1, 1, 1, 1;}\n"
        : R36(0), R36(36) : "l"(a[0]), "l"(a[1]), "l"(a[2]), "l"(a[3]), "l"(b[0]), "l"(b[1]), "l"(b[2]), "l"(b[3]), "r"(acc));
}
__device__ __forceinline__ void wgmma72(float (&d)[36], uint32_t da, uint32_t db, int acc) {
    asm volatile("{.reg .pred p; .reg .b64 a, b; setp.ne.b32 p, %38, 0; mov.b64 a, {%36, %39}; mov.b64 b, {%37, %40};\n"
        "wgmma.mma_async.sync.aligned.m64n72k16.f32.bf16.bf16 {%0,%1,%2,%3,%4,%5,%6,%7,%8,%9,%10,%11,%12,%13,%14,%15,%16,%17,%18,%19,%20,%21,%22,%23,"
        "%24,%25,%26,%27,%28,%29,%30,%31,%32,%33,%34,%35}, a, b, p, 1, 1, 1, 1;}\n"
        : R36(0) : "r"(da), "r"(db), "r"(acc), "n"(DHI_A), "n"(DHI_H3));
}

__device__ __forceinline__ int g2_kb(int n, int kh) { const int m = n - 4; return 36 * kh + (n < 4 ? 9 * n + 8 : 9 * ((m >> 2) & 3) + 2 * (m & 3) + (m >> 4)); }

template <uint32_t BHI, int I0, int I1, bool ZERO, bool FIRST, bool LAST, class Hook>
__device__ __forceinline__ void mainloop(float (&d)[72], uint32_t bars, uint32_t da0, uint32_t db0, bool lead, Hook hook) {
    uint32_t s = I0 % NST, ph = (I0 / NST) & 1, prev = (I0 + NST - (I0 == IT_P1 ? 2 : 1)) % NST;
    uint32_t ready = 0;
    uint64_t da[4], db[4];
    #pragma unroll
    for (int k = 0; k < 4; k++) { da[k] = ((uint64_t)DHI_A << 32) + da0 + s * (A_BYTES / 16) + k * 128; db[k] = ((uint64_t)BHI << 32) + db0 + s * (B_BYTES / 16) + k * 288; }
    #pragma unroll 1
    for (int i = I0; i < I1; i++) {
        if (!ready) mbar_wait(bars + 8 * BAR_FULL + 8 * s, ph);
        WG_FENCE();
        wgmma144x4(d, da, db, ZERO ? i - I0 : 1);
        WG_COMMIT();
        const uint32_t rel = bars + 8 * BAR_EMPTY + 8 * prev; const int i0 = i;
        prev = s; if (++s == NST) { s = 0; ph ^= 1; }
        if (I1 == IT_P1 && (s == P2S || s == P2S + 3)) {
            mbar_wait(bars + 8 * BAR_FULL + 8 * s, ph);
            i++; if (++s == NST) { s = 0; ph ^= 1; }
        }
        const int64_t adv = (int)s - (int)prev;
        #pragma unroll
        for (int k = 0; k < 4; k++) { da[k] += adv * (A_BYTES / 16); db[k] += adv * (B_BYTES / 16); }
        ready = __shfl_sync(~0u, (uint32_t)mbar_test(bars + 8 * BAR_FULL + 8 * s, ph), 0);
        WG_WAIT(1);
        if (lead && (!FIRST || i0 > I0)) mbar_arrive(rel);
        hook(i0);
    }
    if (LAST) { WG_WAIT(0); if (lead) mbar_arrive(bars + 8 * BAR_EMPTY + 8 * prev); }
}

struct Params {
    const uint16_t *x, *wr, *wi, *w1, *b1, *w2, *b2, *c, *wmod;
    uint16_t* out;
    Scratch* scr;
    const Tab* tab;
};

__device__ __forceinline__ void mma_bf(float (&d)[4], const uint32_t (&a)[4], uint32_t b0, uint32_t b1) {
    asm("mma.sync.aligned.m16n8k16.row.col.f32.bf16.bf16.f32 {%0,%1,%2,%3}, {%4,%5,%6,%7}, {%8,%9}, {%0,%1,%2,%3};"
        : "+f"(d[0]), "+f"(d[1]), "+f"(d[2]), "+f"(d[3]) : "r"(a[0]), "r"(a[1]), "r"(a[2]), "r"(a[3]), "r"(b0), "r"(b1)); }
__device__ __forceinline__ void ldsm4t(uint32_t (&a)[4], uint32_t addr) {
    asm volatile("ldmatrix.sync.aligned.m8n8.x4.trans.shared.b16 {%0,%1,%2,%3}, [%4];" : "=r"(a[0]), "=r"(a[1]), "=r"(a[2]), "=r"(a[3]) : "r"(addr) : "memory"); }
__device__ __forceinline__ void ln_stats(const uint32_t (&w)[9], int g, int q, float& r, float& mr) {
    constexpr uint32_t ONE = 0x3F803F80u;
    float c[2][4] = {};
    #pragma unroll
    for (int p = 0; p < 5; p++) { const uint32_t hi = p < 4 ? w[p < 4 ? 2 * p + 1 : 0] : 0u, a[4] = {w[2 * p], ONE, hi, ONE}; mma_bf(c[p & 1], a, w[2 * p], hi); }
    const float t = (g & 1) ? c[0][1] + c[1][1] : c[0][0] + c[1][0];
    float s1 = (c[0][2] + c[1][2]) + (c[0][3] + c[1][3]), s2 = __shfl_sync(~0u, t, 9 * q) + __shfl_sync(~0u, t, 9 * q + 4);
    #pragma unroll
    for (int o = 1; o < 4; o <<= 1) { s1 += __shfl_xor_sync(~0u, s1, o); s2 += __shfl_xor_sync(~0u, s2, o); }
    const float m = s1 * (1.f / D_);
    asm("rsqrt.approx.ftz.f32 %0, %1;" : "=f"(r) : "f"(fmaxf(fmaf(s2, 1.f / D_, -m * m), 0.f) + 1e-5f));
    mr = -m * r;
}
__device__ __forceinline__ float silu(float v) { return __fdividef(v, 1.f + __expf(-v)); }
__device__ __forceinline__ uint32_t bfma2(uint32_t a, uint32_t b, uint32_t c) { uint32_t r; asm("fma.rn.bf16x2 %0, %1, %2, %3;" : "=r"(r) : "r"(a), "r"(b), "r"(c)); return r; }
__device__ __forceinline__ void radix16(const uint4 (&V)[4], const uint32_t (&B)[16], uint4 (&o)[4]) {
    #pragma unroll
    for (int nt = 0; nt < 4; nt++) {
        o[nt] = make_uint4(0, 0, 0, 0);
        #pragma unroll
        for (int ks = 0; ks < 2; ks++) {
            const uint32_t b0 = B[(ks * 4 + nt) * 2], b1 = B[(ks * 4 + nt) * 2 + 1];
            mma_h(o[nt].x, o[nt].y, V[2 * ks].x, V[2 * ks].y, V[2 * ks + 1].x, V[2 * ks + 1].y, b0, b1);
            mma_h(o[nt].z, o[nt].w, V[2 * ks].z, V[2 * ks].w, V[2 * ks + 1].z, V[2 * ks + 1].w, b0, b1);
        }
    }
}
template <int OFF, int N> __device__ __forceinline__ void gelu_store(const float (&d)[N], char* p, int q) {
    uint32_t w[9];
    #pragma unroll
    for (int blk = 0; blk < 9; blk++) w[blk] = pack_bf(gelu2(d[OFF + 4 * blk]), gelu2(d[OFF + 4 * blk + 1]));
    asm volatile("st.v4.u32 [%0], {%1,%2,%3,%4};" :: "l"(p + q * 128), "r"(w[0]), "r"(w[1]), "r"(w[2]), "r"(w[3]) : "memory");
    asm volatile("st.v4.u32 [%0+512], {%1,%2,%3,%4};" :: "l"(p + q * 128), "r"(w[4]), "r"(w[5]), "r"(w[6]), "r"(w[7]) : "memory");
    asm volatile("st.u32 [%0+1024], %1;" :: "l"(p + q * 4), "r"(w[8]) : "memory");
}

__global__ void __cluster_dims__(2, 1, 1) __launch_bounds__(NTHR, 1)
fused_kernel(const Params p,
             const __grid_constant__ CUtensorMap tm_w1a, const __grid_constant__ CUtensorMap tm_w1b, const __grid_constant__ CUtensorMap tm_w2,
             const __grid_constant__ CUtensorMap tm_h3a, const __grid_constant__ CUtensorMap tm_h3b,
             const __grid_constant__ CUtensorMap tm_wr, const __grid_constant__ CUtensorMap tm_wi, const __grid_constant__ CUtensorMap tm_wm,
             const __grid_constant__ CUtensorMap tm_t, const __grid_constant__ CUtensorMap tm_tx, const __grid_constant__ CUtensorMap tm_o,
             const __grid_constant__ CUtensorMap tm_h3s)
{
    extern __shared__ char smem_raw[];
    const uint32_t t0 = clk32();
    const uint32_t sm = __shfl_sync(~0u, ((uint32_t)__cvta_generic_to_shared(smem_raw) + 1023u) & ~1023u, 0);
    const int tid = threadIdx.x, warp = __shfl_sync(~0u, tid >> 5, 0), lane = tid & 31, g = lane >> 2, q = lane & 3;
    const int b = blockIdx.x;
    const uint32_t rank = b & 1;
    const uint32_t bars = sm + OFF_BAR;
    const bool rowcta = b < 128;

    auto nc_issue = [&](int st, uint32_t sl) {
        const int pass = st >= 18;
        mbar_expect(bars + 8 * (BAR_X + sl), 28672);
        tma3(sm + sl * 28672, &tm_wm, 0, 32 * (st - 18 * pass), 18 + 28 * pass + 7 * (b - 128), bars + 8 * (BAR_X + sl));
    };
    if (warp == 13) hb();
    uint32_t cw = 0, epoch;
    if (warp < 12) {
        if (lane < 24) cw = ldg_nc32(p.c + 48 * warp + 2 * lane);
        epoch = ld_relaxed(g_cnt + CNT_EPOCH * 32);
        if (b < 72) {
            const uint16_t* src = p.wmod + (48 * warp + (lane >> 1)) * 3456 + 16 * b + (lane & 1) * 8;
            const uint32_t dst = sm + OFF_STRIP + (48 * warp + (lane >> 1)) * 48 + (lane & 1) * 16;
            #pragma unroll
            for (int u = 0; u < 3; u++) asm volatile("cp.async.cg.shared.global" CPHINT " [%0], [%1], 16;" :: "r"(dst + u * 768), "l"(src + u * 16 * 3456) : "memory");
            asm volatile("cp.async.commit_group;" ::: "memory");
        }
    } else {
      if (elect()) {
        if (warp == 15) {
            mbar_init(bars + 8 * BAR_TAB, 1); fence_async_s();
            if (rowcta) { mbar_expect(bars + 8 * BAR_TAB, QA * 512); bulk_load(sm + OFF_TAB, p.tab, QA * 512, bars + 8 * BAR_TAB); }
            asm volatile("prefetch.tensormap [%0];" :: "l"(&tm_wr) : "memory"); asm volatile("prefetch.tensormap [%0];" :: "l"(&tm_wi) : "memory");
            asm volatile("prefetch.tensormap [%0];" :: "l"(&tm_t) : "memory"); asm volatile("prefetch.tensormap [%0];" :: "l"(&tm_tx) : "memory");
        } else if (warp == 14) {
            for (int i = BAR_W; i < BAR_X; i++) mbar_init(bars + 8 * i, i == BAR_DONE ? 4 : 1);
            mbar_expect(bars + 8 * BAR_W, 28672); mbar_expect(bars + 8 * BAR_TAB2, (QB + QC) * 512);
            mbar_expect(bars + 8 * BAR_ROLE, 4); mbar_expect(bars + 8 * BAR_P2R, 9216); mbar_expect(bars + 8 * BAR_RECV, 18432); mbar_expect(bars + 8 * BAR_XT, 18432);
        } else if (warp == 13) {
            for (int i = 0; i < 2 * NST; i++) mbar_init(bars + 8 * i, 2);
            for (int i = 0; i < NST; i++) mbar_expect(bars + 8 * (BAR_FULL + i), A_BYTES);
        }
        else {
            for (int i = 0; i < 16; i++) mbar_init(bars + 8 * (BAR_X + i), rowcta || i < 6 ? 1 : 14);
            if (!rowcta) { fence_async_s(); for (int st = 0; st < 6; st++) nc_issue(st, st); }
        }
        asm volatile("fence.mbarrier_init.release.cluster;" ::: "memory");
      }
      __syncwarp();
      epoch = ld_relaxed(g_cnt + CNT_EPOCH * 32);
    }
    __syncthreads();
    asm volatile("barrier.cluster.arrive.relaxed.aligned;" ::: "memory");
    if (warp < 4) sts16(sm + OFF_MODA + ((warp + 1) * 32 + lane) * 16 + warp * 4 + 2, 0);
    if (warp >= 8) {
        const int k1 = tid & 15, s1 = (tid >> 4) & 15;
        float s, c;
        __sincosf((float)(((k1 * (128 * s1 + b) + 1024) & 2047) - 1024) * (3.14159265358979f / 1024.f), &s, &c); s *= 0.25f; c *= 0.25f;
        const int rf = ((s1 >> 3) * 4 + (k1 >> 2)) * 2 + ((s1 >> 2) & 1), ri = ((k1 >> 3) * 4 + (s1 >> 2)) * 2 + ((k1 >> 2) & 1);
        const uint32_t af = sm + OFF_B3 + ((rf >> 2) * 32 + (k1 & 3) * 8 + (s1 & 3)) * 16 + (rf & 3) * 4;
        const uint32_t ai = sm + OFF_B3 + 2048 + ((ri >> 2) * 32 + (s1 & 3) * 8 + (k1 & 3)) * 16 + (ri & 3) * 4;
        sts32(af, pack_h(c, s)); sts32(af + 64, pack_h(-s, c)); sts32(ai, pack_h(c, -s)); sts32(ai + 64, pack_h(s, c));
    }
    if (rowcta) spin_until(t0 + XDELAY);
    if (rowcta && elect()) {
        mbar_expect(bars + 8 * (BAR_X + warp), 1152);
        bulk_load(sm + OFF_STAGE + warp * 1152, p.x + (size_t)(b + 128 * warp) * D_, 1152, bars + 8 * (BAR_X + warp));
    }
    const uint32_t tag = (epoch + 1) & 0xFFFFu;
    if (warp < 12 && lane < 24) sts32(sm + OFF_SILU + (24 * warp + lane) * 4, pack_bf(silu(bf_lo(cw)), silu(bf_hi(cw))));
    hb();
    uint32_t ta[QA * 4];
    const bool ta_early = rowcta && __any_sync(~0u, mbar_test(bars + 8 * BAR_TAB, 0));
    if (ta_early) load_tab<QA>(ta, sm + OFF_TAB + lane * 16);
    if (warp < 12 && b < 72) {
        uint32_t sb[6];
        __syncwarp();
        #pragma unroll
        for (int u = 0; u < 6; u++) sb[u] = lds32(sm + OFF_SILU + (24 * warp + 4 * u + q) * 4);
        asm volatile("cp.async.wait_all;" ::: "memory");
        __syncwarp();
        float acc[4] = {0, 0, 0, 0};
        #pragma unroll
        for (int u = 0; u < 3; u++) {
            uint32_t a[4];
            ldsm4t(a, sm + OFF_STRIP + (48 * warp + 16 * u + (lane & 7) + 8 * (lane >> 4)) * 48 + ((lane >> 3) & 1) * 16);
            mma_bf(acc, a, sb[2 * u], sb[2 * u + 1]);
        }
        if (q == 0) { sts32(sm + OFF_RED + (g * 12 + warp) * 4, __float_as_uint(acc[0])); sts32(sm + OFF_RED + ((g + 8) * 12 + warp) * 4, __float_as_uint(acc[2])); }
        PROF0(0);
        bar_sync(3, 384);
        if (warp == 0) {
            if (lane < 16) {
                float sum = 0;
                #pragma unroll
                for (int u = 0; u < 3; u++) { const uint4 v = lds128(sm + OFF_RED + lane * 48 + u * 16);
                    sum += (__uint_as_float(v.x) + __uint_as_float(v.y)) + (__uint_as_float(v.z) + __uint_as_float(v.w)); }
                sum = bf_round(sum); if (b >= 36) sum = bf_round(1.f + sum);
                st_relaxed(g_mod + b * MODPAD + (lane & 1) * 8 + (lane >> 1), (pack_h(0.f, sum) & 0xFFFF0000u) | tag);
            }
            __syncwarp();
            PROF0(1);
        }
    }

    const int trow = 4 * (b & 7) + ((b >> 4) & 3) + 64 * ((b >> 3) & 1) + 32 * (b >> 6);
    uint32_t* const tptr = g_T + (size_t)trow * TP + (warp < 9 ? q * 288 + 32 * warp : 4608 + 8 * q) + 4 * g;
    const int tstr = warp < 9 ? 1152 : 32;
    const uint32_t scol = sm + OFF_SPEC + (q * SPEC_P + (warp < 8 ? 72 * (warp >> 1) + 40 * (warp & 1) + 4 * g : warp == 8 ? 72 * (g >> 1) + 32 + 4 * (g & 1) : 288 + 4 * g)) * 4;
    const int wc0 = (b >> 3) * 289 + 72 * ((b & 7) >> 1) + 40 * (b & 1);

    uint32_t xw[9], t_st = t0;
    if (!rowcta) {
        const int nst = b < 130 ? 36 : 18;
        __syncthreads();
        if (warp == 14) {
            uint32_t sl = 0, ph = 0;
            #pragma unroll 1
            for (int st = 6; st < nst; st++) {
                mbar_wait(bars + 8 * (BAR_X + 6 + sl), ph);
                if (elect()) nc_issue(st, sl);
                if (++sl == 6) { sl = 0; ph ^= 1; }
            }
        } else if (warp < 14) {
            uint32_t sl = 0, ph = 0;
            const uint32_t ad0 = sm + (warp >> 1) * 4096 + ((lane & 7) + 8 * (lane >> 4)) * 128, ch = (warp & 1) * 4 + ((lane >> 3) & 1);
            #pragma unroll 1
            for (int pass = 0; pass * 18 < nst; pass++) {
                float acc[2][4] = {};
                #pragma unroll 1
                for (int st = 0; st < 18; st++) {
                    const uint32_t sa = sm + OFF_SILU + (16 * st + q) * 4;
                    const uint32_t b0 = lds32(sa), b1 = lds32(sa + 16), b2 = lds32(sa + 32), b3 = lds32(sa + 48);
                    mbar_wait(bars + 8 * (BAR_X + sl), ph);
                    #pragma unroll
                    for (int m = 0; m < 2; m++) {
                        uint32_t a[4], a2[4];
                        const uint32_t ad = ad0 + sl * 28672 + ((ch + 2 * m) ^ (lane & 7)) * 16;
                        ldsm4t(a, ad); ldsm4t(a2, ad + 2048);
                        mma_bf(acc[m], a, b0, b1); mma_bf(acc[m], a2, b2, b3);
                    }
                    if (elect()) mbar_arrive(bars + 8 * (BAR_X + 6 + sl));
                    if (++sl == 6) { sl = 0; ph ^= 1; }
                }
                const int cb = 28 * pass + 7 * (b - 128) + (warp >> 1), gg = (g >> 1) + 4 * q;
                #pragma unroll
                for (int m = 0; m < 2; m++) {
                    const int qq = (warp & 1) * 2 + m;
                    float v = bf_round(q ? acc[m][2] : acc[m][0]); if (cb >= 27) v *= 0.5f; else if (cb >= 18) v += 1.f;
                    const uint32_t w = pack_bf(v, __shfl_xor_sync(~0u, v, 4));
                    if (q < 2 && !(g & 1) && cb < 36) p.scr->modc[cb < 27 ? ((cb >> 2) * 32 + 4 * gg + qq) * 4 + (cb & 3) : 896 + 32 * (cb - 27) + 8 * qq + gg] = w;
                }
                bar_sync(1, 448);
                if (tid == 0) { fence_async_g(); red_release(g_cnt + (CNT_NC + pass) * 32); if (pass == 0) PROFT(25); }
                __syncwarp();
            }
            fence_async_s();
        }
        __syncthreads();
    } else {
        if (!ta_early) { mbar_wait(bars + 8 * BAR_TAB, 0); load_tab<QA>(ta, sm + OFF_TAB + lane * 16); }
        uint32_t nb[2][5];
        uint4 mv = make_uint4(tag, tag, tag, tag);
        const int mc = tid - 224, mst = (mc >> 2) % 36, midx = (mc < 144 ? 10 : 0) + 5 * ((mc >> 1) & 1) + (mst >> 3);
        const uint32_t* mp = g_mod + (mc >> 2) * MODPAD + (mc & 3) * 4;
        const uint32_t ma = sm + OFF_MODA + ((midx >> 2) * 32 + (mc & 1) * 16 + (mst & 3)) * 16 + (midx & 3) * 4 + ((mst >> 2) & 1) * 2;
        #define MOD_MISSING ((((mv.x ^ tag) | (mv.y ^ tag) | (mv.z ^ tag) | (mv.w ^ tag)) & 0xFFFFu) != 0)
        hb();
        mbar_wait(bars + 8 * (BAR_X + warp), 0);
        if (warp >= 7) mv = ldx128(mp);
        PROF0(28);
        #pragma unroll
        for (int i = 0; i < 9; i++) xw[i] = lds32(sm + OFF_STAGE + warp * 1152 + (32 * i + 8 * q + g) * 4);
        {
            float r, mr;
            ln_stats(xw, g, q, r, mr);
            #pragma unroll
            for (int pp = 0; pp < 5; pp++) {
                nb[0][pp] = pack_h(fmaf(bf_lo(xw[2 * pp]), r, mr), pp < 4 ? fmaf(bf_lo(xw[pp < 4 ? 2 * pp + 1 : 0]), r, mr) : 0.f);
                nb[1][pp] = pack_h(fmaf(bf_hi(xw[2 * pp]), r, mr), pp < 4 ? fmaf(bf_hi(xw[pp < 4 ? 2 * pp + 1 : 0]), r, mr) : 0.f);
            }
        }
        PROF0(2);
        if (warp >= 7) {
            for (int it = 0; __any_sync(~0u, MOD_MISSING); it++) { mv = ldx128(mp); hb(); if (it > SPIN_LIMIT) __trap(); }
            sts16(ma, mv.x >> 16); sts16(ma + 64, mv.y >> 16); sts16(ma + 128, mv.z >> 16); sts16(ma + 192, mv.w >> 16);
        }
        __syncthreads();
        PROF0(3);
        if (warp >= 13 && elect()) {
            if (warp == 15) bulk_load(sm + OFF_TAB + QA * 512, p.tab->w + QA * 128, (QB + QC) * 512, bars + 8 * BAR_TAB2);
            else tma3(sm + OFF_WRAW + (warp - 13) * 14336, warp == 13 ? &tm_wr : &tm_wi, wc0 & ~7, 0, 0, bars + 8 * BAR_W);
        }
        __syncwarp();
        {
            uint32_t md[20];
            load_tab<5>(md, sm + OFF_MODA + lane * 16);
            #pragma unroll
            for (int v = 0; v < 2; v++)
                #pragma unroll
                for (int pp = 0; pp < 5; pp++) nb[v][pp] = hfma2(nb[v][pp], md[v * 5 + pp], md[10 + v * 5 + pp]);
        }
        uint32_t re[3][2], im[3][2];
        #pragma unroll
        for (int mt = 0; mt < 3; mt++)
            #pragma unroll
            for (int v = 0; v < 2; v++) {
                re[mt][v] = 0; im[mt][v] = 0;
                mma_h8(re[mt][v], im[mt][v], ta[mt * 10 + 8], ta[mt * 10 + 9], nb[v][4]);
                mma_h(re[mt][v], im[mt][v], ta[mt * 10], ta[mt * 10 + 1], ta[mt * 10 + 2], ta[mt * 10 + 3], nb[v][0], nb[v][1]);
                mma_h(re[mt][v], im[mt][v], ta[mt * 10 + 4], ta[mt * 10 + 5], ta[mt * 10 + 6], ta[mt * 10 + 7], nb[v][2], nb[v][3]);
                cmul_neg(re[mt][v], im[mt][v], ta[30 + (mt * 2 + v) * 2], ta[31 + (mt * 2 + v) * 2]);
            }
        const uint32_t srow = sm + OFF_SPEC + warp * (SPEC_P * 4);
        #pragma unroll
        for (int nt = 0; nt < 2; nt++) {
            uint32_t o[2][4];
            #pragma unroll
            for (int v = 0; v < 2; v++) {
                const uint32_t b0 = ta[42 + (v * 2 + nt) * 2], b1 = ta[43 + (v * 2 + nt) * 2];
                o[v][0] = o[v][1] = o[v][2] = o[v][3] = 0;
                mma_h(o[v][0], o[v][1], re[0][v], re[1][v], im[0][v], im[1][v], b0, b1);
                mma_h(o[v][2], o[v][3], re[2][v], re[2][v], im[2][v], im[2][v], b0, b1);
            }
            const uint32_t a = srow + (g + 72 * q + 36 * nt) * 4, a2 = srow + (288 - g - 72 * q - 36 * nt) * 4;
            sts32(a, hadd2(o[0][0], o[1][0])); sts32(a + 32, hadd2(o[0][1], o[1][1])); if (g < 3) sts32(a + 64, hadd2(o[0][2], o[1][2]));
            if (g > 0 || (q == 0 && nt == 0)) sts32(a2, hsub2(o[0][0], o[1][0]) ^ 0x80000000u);
            sts32(a2 - 32, hsub2(o[0][1], o[1][1]) ^ 0x80000000u); if (g < 2) sts32(a2 - 64, hsub2(o[0][2], o[1][2]) ^ 0x80000000u);
        }
        uint32_t b3[16];
        if (warp < 10) load_tab<4>(b3, sm + OFF_B3 + lane * 16);
        __syncthreads();
        t_st = clk32();
        PROF0(4);
        if (warp < 10) {
            uint4 V[4], o[4];
            #pragma unroll
            for (int u = 0; u < 4; u++) V[u] = lds128(scol + u * (16 * SPEC_P));
            radix16(V, b3, o);
            #pragma unroll
            for (int nt = 0; nt < 4; nt++) { o[nt].x |= 1u; if (warp < 9 || g < 2) stx128(tptr + nt * tstr, o[nt]); }
        }
        PROF0(5);
    }

    int role = 0;
    asm volatile("barrier.cluster.wait.aligned;" ::: "memory");
    if (warp >= 12) {
        const int t = tid - 384;
        if (tid == 448 && rank == 0) {
            uint32_t smid; asm volatile("mov.u32 %0, %%smid;" : "=r"(smid));
            const uint32_t tp = smid >> 1;
            uint32_t pr = tp < 32 ? (tp & 7) * 8 + (tp >> 3) : tp < 60 ? (1 + (tp - 32) % 7) * 8 + 4 + (tp - 32) / 7 : tp < 62 ? 4 + tp : tp < 66 ? tp - 58 : 0;
            while (atomicExch(g_slot + pr, epoch + 1) == epoch + 1) pr = pr == 65 ? 0 : pr + 1;
            #pragma unroll
            for (int r = 0; r < 2; r++)
                asm volatile("st.async.weak.shared::cluster.mbarrier::complete_tx::bytes.u32 [%0], %1, [%2];" :: "r"(mapa(sm + OFF_MISC, r)), "r"(pr), "r"(mapa(bars + 8 * BAR_ROLE, r)) : "memory");
        }
        __syncwarp();
        if (t == 0) {
            asm volatile("prefetch.tensormap [%0];" :: "l"(&tm_w1a) : "memory");
            asm volatile("prefetch.tensormap [%0];" :: "l"(&tm_h3a) : "memory"); asm volatile("prefetch.tensormap [%0];" :: "l"(&tm_w1b) : "memory");
            asm volatile("prefetch.tensormap [%0];" :: "l"(&tm_h3b) : "memory"); asm volatile("prefetch.tensormap [%0];" :: "l"(&tm_w2) : "memory");
            asm volatile("prefetch.tensormap [%0];" :: "l"(&tm_o) : "memory"); asm volatile("prefetch.tensormap [%0];" :: "l"(&tm_h3s) : "memory");
        }
        if (t == 32 && rowcta) {
            for (int it = 0; (int)(ld_acquire(g_cnt + CNT_NC * 32) - (epoch + 1) * 4) < 0; it++) { __nanosleep(100); if (it > SPIN_LIMIT) __trap(); }
            fence_async_g();
            mbar_expect(bars + 8 * BAR_NC, 3584);
            bulk_load(sm + OFF_MODC, p.scr->modc, 3584, bars + 8 * BAR_NC);
            PROFT(29);
        }
        __syncwarp();
    } else if (rowcta && warp < 11) {
        const int nw = !(b & 1) ? 10 : (b & 7) == 7 ? 9 : 8;
        const int cm = (b >> 3) * 288 + (b & 7) * 32, cx = (b & 1) ? 4608 + 8 * (b >> 3) : (b >> 3) * 288 + 256 + 4 * (b & 7);
        auto load_in = [&]() {
            if (elect()) {
                mbar_expect(bars + 8 * BAR_XB, nw > 8 ? 20480 : 16384);
                tma2(sm + OFF_STAGE, &tm_t, cm, 0, bars + 8 * BAR_XB);
                if (nw > 8) tma2(sm + OFF_STX, &tm_tx, cx, 0, bars + 8 * BAR_XB);
            }
            __syncwarp();
        };
        if (warp == 10) { fence_async_s(); spin_until(t_st + X1D); load_in(); }
        uint32_t tb[QB * 4], wre[4][2], wim[4][2];
        if (warp < nw) {
            mbar_wait(bars + 8 * BAR_TAB2, 0);
            load_tab<QB>(tb, sm + OFF_TAB + QA * 512 + lane * 16);
            mbar_wait(bars + 8 * BAR_W, 0);
            const int off = wc0 & 7;
            const uint32_t wa = sm + OFF_WRAW + lane * 112 + ((off >> 1) + 2 * warp) * 4, sh = (off & 1) * 16;
            #pragma unroll
            for (int c = 0; c < 2; c++)
                #pragma unroll
                for (int h = 0; h < 2; h++) {
                    uint32_t y[2][2];
                    #pragma unroll
                    for (int e = 0; e < 2; e++) {
                        const uint32_t a = wa + c * 14336 + (h + 2 * e) * 3584, x0 = lds32(a), x1 = lds32(a + 4), x2 = lds32(a + 8);
                        y[e][0] = __funnelshift_r(x0, x1, sh); y[e][1] = __funnelshift_r(x1, x2, sh);
                    }
                    #pragma unroll
                    for (int x = 0; x < 4; x++) {
                        const uint32_t v = (x & 1) ? pack_h(bf_hi(y[0][x >> 1]), bf_hi(y[1][x >> 1])) : pack_h(bf_lo(y[0][x >> 1]), bf_lo(y[1][x >> 1]));
                        if (c) wim[x][h] = v; else wre[x][h] = v;
                    }
                }
        }
        const uint32_t ca = warp < 8 ? sm + OFF_STAGE + lane * 128 + (warp ^ (lane & 7)) * 16 : sm + OFF_STX + lane * 32 + ((warp ^ g) & 1) * 16, cs = warp < 8 ? 4096 : 1024;
        uint32_t V[4][4];
        for (int it = 0;; it++) {
            mbar_wait(bars + 8 * BAR_XB, it & 1);
            uint32_t ok = 1;
            if (warp < nw) {
                #pragma unroll
                for (int u = 0; u < 4; u++) { uint4 t4 = lds128(ca + u * cs); V[u][0] = t4.x; V[u][1] = t4.y; V[u][2] = t4.z; V[u][3] = t4.w; ok &= t4.x; }
            }
            asm volatile("{.reg .pred p; setp.ne.u32 p, %0, 0; bar.red.and.pred p, 1, 352, p; selp.u32 %0, 1, 0, p;}" : "+r"(ok) :: "memory");
            if (ok) break;
            if (warp == 10) { load_in(); hb(); }
            if (it > SPIN_LIMIT / 64) __trap();
        }
        PROF0(7);
        if (warp < nw) {
            uint32_t zr[4][2], zi[4][2];
            #pragma unroll
            for (int x = 0; x < 4; x++) {
                uint32_t er = 0, ei = 0, or_ = 0, oi = 0;
                mma_h(er, ei, tb[0], tb[1], tb[2], tb[3], V[0][x], V[1][x]);
                mma_h(or_, oi, tb[4], tb[5], tb[6], tb[7], V[2][x], V[3][x]);
                uint32_t r0 = hadd2(er, or_), r1 = hsub2(er, or_), i0 = hadd2(ei, oi), i1 = hsub2(ei, oi);
                cmul_neg(r0, i0, tb[8], tb[9]); cmul_neg(r1, i1, tb[10], tb[11]);
                uint32_t xr0 = 0, xr1 = 0, xi0 = 0, xi1 = 0;
                mma_h(xr0, xr1, r0, r1, i0, i1, tb[12], tb[13]);
                mma_h(xi0, xi1, r0, r1, i0, i1, tb[14], tb[12]);
                cmul_pos(xr0, xi0, wre[x][0], wim[x][0]); cmul_pos(xr1, xi1, wre[x][1], wim[x][1]);
                r0 = 0; i0 = 0; r1 = 0; i1 = 0;
                mma_h(r0, i0, tb[12], tb[13], tb[14], tb[12], xr0, xi0);
                mma_h(r1, i1, tb[12], tb[13], tb[14], tb[12], xr1, xi1);
                cmul_pos(r0, i0, tb[15], tb[16]); cmul_pos(r1, i1, tb[17], tb[18]);
                zr[x][0] = hadd2(r0, r1); zr[x][1] = hsub2(r0, r1); zi[x][0] = hadd2(i0, i1); zi[x][1] = hsub2(i0, i1);
            }
            #pragma unroll
            for (int nt = 0; nt < 4; nt++) {
                uint4 o = make_uint4(0, 0, 0, 0);
                const int h = nt >> 1;
                mma_h(o.x, o.y, zr[0][h], zr[1][h], zi[0][h], zi[1][h], tb[19 + 2 * nt], tb[20 + 2 * nt]);
                mma_h(o.z, o.w, zr[2][h], zr[3][h], zi[2][h], zi[3][h], tb[19 + 2 * nt], tb[20 + 2 * nt]);
                o.x &= ~1u;
                sts128(ca + nt * cs, o);
            }
        }
        fence_async_s();
        bar_sync(1, 352);
        t_st = clk32();
        PROF0(8);
        if (warp == 10 && elect()) {
            asm volatile("cp.async.bulk.tensor.2d.global.shared::cta.bulk_group [%0, {%2, %3}], [%1];" :: "l"(&tm_t), "r"(sm + OFF_STAGE), "r"(cm), "r"(0) : "memory");
            if (nw > 8) asm volatile("cp.async.bulk.tensor.2d.global.shared::cta.bulk_group [%0, {%2, %3}], [%1];" :: "l"(&tm_tx), "r"(sm + OFF_STX), "r"(cx), "r"(0) : "memory");
            asm volatile("cp.async.bulk.commit_group;" ::: "memory");
            asm volatile("cp.async.bulk.wait_group.read 0;" ::: "memory");
        }
        __syncwarp();
    }

    if (warp >= 10) { mbar_wait(bars + 8 * BAR_ROLE, 0); role = __shfl_sync(~0u, lds32(sm + OFF_MISC), 0); fence_async_s(); }
    auto first_a = [&]() {
        if (warp >= 10 && role < 64 && elect()) {
            const int it = warp - 10, hi = it >= 3; const bool p2 = it - 3 * hi == 2;
            tma4(sm + OFF_A + it * A_BYTES, p2 ? &tm_w1b : &tm_w1a, 0, 0, p2 ? 64 * rank + 8 * hi : 4 * (it - hi),
                 9 * (role >> 3) + (p2 ? 8 : (role & 4) + 2 * rank), bars + 8 * (BAR_FULL + it));
        }
        __syncwarp();
    };
    if (!rowcta) first_a();
    else {
        uint32_t tc[QC * 4];
        mbar_wait(bars + 8 * BAR_TAB2, 0);
        load_tab<QC>(tc, sm + OFF_TAB + (QA + QB) * 512 + lane * 16);
        if (warp < 10) {
            uint32_t b3[16];
            load_tab<4>(b3, sm + OFF_B3 + 2048 + lane * 16);
            uint4 V[4], o[4];
            const bool tact = warp < 9 || g == 0;
            spin_until(t_st + X2D);
            #pragma unroll
            for (int u = 0; u < 4; u++) V[u] = make_uint4(tact, 0, 0, 0);
            for (int it = 0; __any_sync(~0u, (V[0].x | V[1].x | V[2].x | V[3].x) & 1u); it++) {
                #pragma unroll
                for (int u = 0; u < 4; u++) if (V[u].x & 1u) V[u] = ldx128(tptr + u * tstr);
                hb();
                if (it > SPIN_LIMIT) __trap();
            }
            PROF0(10);
            radix16(V, b3, o);
            if (tact) {
                #pragma unroll
                for (int nt = 0; nt < 4; nt++) sts128(scol + nt * (16 * SPEC_P), o[nt]);
            }
        }
        __syncthreads();
        PROF0(11);
        first_a();
        const uint32_t srow = sm + OFF_SPEC + warp * (SPEC_P * 4);
        uint32_t re[2][3], im[2][3];
        #pragma unroll
        for (int mt = 0; mt < 3; mt++) {
            const uint32_t a = srow + (g + 72 * q + 8 * mt) * 4, a2 = srow + (288 - g - 72 * q - 8 * mt) * 4;
            const uint32_t z0 = lds32(a), z1 = lds32(a + 144), z2 = lds32(a2), z3 = lds32(a2 - 144);
            #pragma unroll
            for (int m2 = 0; m2 < 2; m2++) {
                re[m2][mt] = 0; im[m2][mt] = 0;
                const uint32_t sg = m2 ? 0x3C00BC00u : 0xBC003C00u;
                mma_h(re[m2][mt], im[m2][mt], tc[m2 * 4], tc[m2 * 4 + 1], tc[m2 * 4 + 2], tc[m2 * 4 + 3], hfma2(z2, sg, z0), hfma2(z3, sg, z1));
                cmul_pos(re[m2][mt], im[m2][mt], tc[8 + (m2 * 3 + mt) * 2], tc[9 + (m2 * 3 + mt) * 2]);
            }
        }
        uint32_t md[28];
        mbar_wait(bars + 8 * BAR_NC, 0);
        load_tab<7>(md, sm + OFF_MODC + lane * 16);
        float y[5][4];
        #pragma unroll
        for (int nt = 0; nt < 5; nt++) {
            y[nt][0] = y[nt][1] = y[nt][2] = y[nt][3] = 0.f;
            #pragma unroll
            for (int mt = 0; mt < 3; mt++)
                mma_f(y[nt], re[0][mt], re[1][mt], im[0][mt], im[1][mt], tc[20 + (mt * 5 + nt) * 2], tc[21 + (mt * 5 + nt) * 2]);
        }
        #pragma unroll
        for (int i = 0; i < 9; i++) xw[i] = bfma2(md[i], pack_bf(y[i >> 1][i & 1], y[i >> 1][2 + (i & 1)]), xw[i]);
        float r, mr;
        ln_stats(xw, g, q, r, mr);
        uint32_t h[9], r2 = pack_bf(r, r), m2 = pack_bf(mr, mr);
        #pragma unroll
        for (int i = 0; i < 9; i++) h[i] = bfma2(bfma2(xw[i], r2, m2), md[18 + i], md[9 + i]);
        ln_stats(h, g, q, r, mr);
        r2 = pack_bf(r, r); m2 = pack_bf(mr, mr);
        {
            const int n7 = 2 * q + (g >> 2);
            const uint32_t a = sm + OFF_STAGE + (warp >> 3) * 9216 + n7 * 128 + ((warp & 7) ^ n7) * 16 + (g & 3) * 4;
            #pragma unroll
            for (int i = 0; i < 9; i++) sts32(a + i * 1024, bfma2(h[i], r2, m2));
        }
        fence_async_s();
        __syncthreads();
        PROF0(12);
        if (tid == 0) {
            asm volatile("cp.async.bulk.tensor.4d.global.shared::cta.bulk_group [%0, {%2, %2, %2, %3}], [%1];" :: "l"(&tm_h3s), "r"(sm + OFF_STAGE), "r"(0), "r"(b) : "memory");
            asm volatile("cp.async.bulk.commit_group;" ::: "memory");
        }
        #pragma unroll
        for (int i = 0; i < 9; i++) sts32(sm + OFF_X1 + warp * 1152 + (32 * i + 8 * q + g) * 4, xw[i]);
    }
    __syncthreads();
    if (rowcta) {
        if (tid == 0) { asm volatile("cp.async.bulk.wait_group 0;" ::: "memory"); fence_async_g(); red_release(g_cnt + CNT_H3 * 32); }
        PROF0(13);
        if (warp == 15) {
            __nanosleep(X1DELAY);
            #pragma unroll 1
            for (int r = 0; r < 16; r++) {
                uint4* dst = (uint4*)(p.out + (size_t)(b + 128 * r) * D_) + lane;
                const uint32_t src = sm + OFF_X1 + r * 1152 + lane * 16;
                dst[0] = lds128(src); dst[32] = lds128(src + 512); if (lane < 8) dst[64] = lds128(src + 1024);
                const uint32_t t1 = clk32(); while ((int)(clk32() - t1) < X1PACE) __nanosleep(50);
            }
            __syncwarp();
            if (lane == 0) { fence_async_g(); red_release(g_cnt + CNT_X1 * 32); }
        }
    }
    role = __shfl_sync(~0u, lds32(sm + OFF_MISC), 0);
    if (role >= 64) { if (warp == 0) PROFDUMP(); return; }

    const int gi = role >> 3, dt = role & 3, c2 = (role >> 2) & 1;
    const int wg = warp >> 2, wi = warp & 3;
    if (wg == 3) {
        uint32_t so = 0, eph = 1;
        #define RING_STEP(BYTES, OFF, ISSUE) do { \
            mbar_wait(bars + 8 * BAR_EMPTY + so, eph); \
            if (elect()) { const uint32_t fb = bars + 8 * BAR_FULL + so, dst = sm + (OFF) + so * ((BYTES) / 8); mbar_expect(fb, BYTES); ISSUE; } \
            so += 8; if (so == 8 * NST) { so = 0; eph ^= 1; } } while (0)
        if (warp == 12) {
            eph = 0;
            const int fb1 = 9 * gi + 4 * c2 + 2 * rank, sb2 = 4 * gi + 2 * c2;
            #pragma unroll 1
            for (int j = 16; j < 128; j += 4) {
                RING_STEP(A_BYTES, OFF_A, tma4(dst, &tm_w1a, 0, 0, j, fb1, fb));
                if (j < 64) { if (j & 4) RING_STEP(A_BYTES, OFF_A, tma4(dst, &tm_w1b, 0, 0, 64 * rank + j - 4, 9 * gi + 8, fb)); }
                else if (PF2 && (j & 28) == 4 * (role & 7) && elect())
                    asm volatile("cp.async.bulk.prefetch.tensor.3d.L2.global [%0, {%1, %2, %3}];" :: "l"(&tm_w2), "r"(0), "r"(64 * g2_kb(dt + ((j >> 3) & 4), rank)), "r"(sb2) : "memory");
            }
            #pragma unroll 1
            for (int n = 0; n < 36; n++) {
                if (n == G2E) mbar_wait(bars + 8 * BAR_REL, 0);
                if (n == A2E) { mbar_wait(bars + 8 * (BAR_UOK + 1), 0); if (A2D) spin_until(clk32() + A2D); }
                RING_STEP(A_BYTES, OFF_A, tma3(dst, &tm_w2, 0, 64 * g2_kb(n, rank), sb2, fb));
            }
        } else if (warp == 13) {
            const uint32_t e1 = __shfl_sync(~0u, epoch + 1, 0);
            fence_async_s();
            wait_count<0>(g_cnt + CNT_H3 * 32, e1 * 128);
            fence_async_g();
            if (lane == 0) PROFT(14);
            #pragma unroll 1
            for (int j = 0; j < 128; j += 4) {
                RING_STEP(B_BYTES, OFF_B, tma3(dst, &tm_h3a, 0, 18 * dt, j, fb));
                if (j < 64 && (j & 4)) RING_STEP(B_BYTES, OFF_B, tma3(dst, &tm_h3b, 0, 18 * dt + 9 * c2, 64 * rank + j - 4, fb));
            }
            int n = 0;
            #pragma unroll 1
            for (int cls = 0; cls < 3; cls++) {
                mbar_wait(bars + 8 * (BAR_UOK + cls), 0);
                fence_async_g();
                if (cls == 1 && lane == 0) PROFT(19);
                if (cls == 0 && lane == 0) PROFT(22);
                #pragma unroll 1
                for (; n < 16 * cls + 4; n++) {
                    if (n == G2E) mbar_wait(bars + 8 * BAR_REL, 0);
                    RING_STEP(B_BYTES, OFF_B, bulk_load(dst, g_U + (g2_kb(n, rank) * 4 + dt) * 1152, B_BYTES, fb));
                }
            }
            if (role == 0 && rank == 0 && lane == 0) st_relaxed(g_cnt + CNT_EPOCH * 32, e1);
        } else if (warp == 15) {
            if (elect()) mbar_arrive_remote(mapa(bars + 8 * BAR_HOLD, rank ^ 1));
            __syncwarp();
            bar_sync(6, 160);
            mbar_wait(bars + 8 * BAR_W1GO, 0);
            if (elect()) {
                char* dst = (char*)(g_U + ((9 * gi + 4 * c2 + 2 * rank + 1) * 4 + dt) * 1152);
                #pragma unroll 1
                for (int i = 0; i < W1N; i++) {
                    asm volatile("cp.async.bulk.global.shared::cta.bulk_group [%0], [%1], %2;" :: "l"(dst + i * (18432 / W1N)), "r"(sm + OFF_X1 + i * (18432 / W1N)), "n"(18432 / W1N) : "memory");
                    const uint32_t t1 = clk32(); while ((int)(clk32() - t1) < W1P) {}
                }
                asm volatile("cp.async.bulk.commit_group;" ::: "memory");
                asm volatile("cp.async.bulk.wait_group 0;" ::: "memory");
                fence_async_g(); red_release(g_cnt + (CNT_U + 16) * 32);
                #pragma unroll 1
                for (int n = 0; n < 4; n++) { __nanosleep(300); tma2(sm + OFF_X1 + n * 4608, &tm_o, 144 * dt, 256 * gi + 128 * c2 + 64 * (rank ^ 1) + 16 * n, bars + 8 * BAR_XT); }
            }
        } else {
            const uint32_t e1 = epoch + 1;
            if (lane == 0) {
                __nanosleep(4000);
                wait_count<200>(g_cnt + CNT_NC * 32, e1 * 4); wait_count<200>(g_cnt + (CNT_NC + 1) * 32, e1 * 2);
                fence_async_g();
                mbar_expect(bars + 8 * BAR_GB, 1152);
                bulk_load(sm + OFF_GB, p.scr->modc + 896, 1152, bars + 8 * BAR_GB);
                wait_count<200>(g_cnt + CNT_X1 * 32, e1 * 128);
                wait_count<50>(g_cnt + (CNT_U + dt * 2 + rank) * 32, e1 * 16);
                mbar_arrive(bars + 8 * BAR_UOK);
            }
            __syncwarp();
            bar_sync(4, 160);
            if (lane == 0) {
                fence_async_g(); red_release(g_cnt + (CNT_U + 8) * 32);
                mbar_arrive(bars + 8 * BAR_REL);
                PROFT(17);
                wait_count<0>(g_cnt + (CNT_U + 8) * 32, e1 * 128);
                mbar_arrive(bars + 8 * (BAR_UOK + 1));
                __nanosleep(1000);
                wait_count<100>(g_cnt + (CNT_U + 16) * 32, e1 * 128);
                mbar_arrive(bars + 8 * (BAR_UOK + 2));
            }
        }
    } else if (wg == 2) {
        float d0[36];
        const float bias = bf_lo(ldg_nc16(p.b1 + 576 * gi + 512 + 16 * wi + g + 8 * rank));
        for (int it = 0; it < 200 && !__any_sync(~0u, mbar_test(bars + 8 * BAR_FULL, 0)); it++) { hb(); __nanosleep(100); }
        const bool lead = wi == 0 && elect();
        #pragma unroll 1
        for (int i = 0; i < 8; i++) {
            const uint32_t s = P2S + 3 * (i & 1);
            mbar_wait(bars + 8 * BAR_FULL + 8 * s, (i >> 1) & 1);
            const uint32_t da = desc_lo(sm + OFF_A, 8192) + s * (A_BYTES / 16), db = desc_lo(sm + OFF_B, 128) + s * (B_BYTES / 16);
            WG_FENCE();
            wgmma72(d0, da, db, i);
            #pragma unroll
            for (int k = 1; k < 8; k++) wgmma72(d0, da + k * 128, db + k * 144, 1);
            WG_COMMIT();
            WG_WAIT(0);
            if (lead) mbar_arrive_n(bars + 8 * BAR_EMPTY + 8 * s, 2);
        }
        if (lead) PROFT(18);
        const uint32_t slot = sm + OFF_P2R + (tid & 127) * 16, ra = mapa(slot, rank ^ 1), rb = mapa(bars + 8 * BAR_P2R, rank ^ 1);
        float sv[18];
        #pragma unroll
        for (int i = 0; i < 18; i++) { const float lo = d0[4 * (i >> 1) + (i & 1)], hi = d0[4 * (i >> 1) + 2 + (i & 1)];
            sv[i] = rank ? lo : hi; d0[4 * (i >> 1) + (i & 1)] = (rank ? hi : lo) + bias; }
        mbar_wait(bars + 8 * BAR_HOLD, 0);
        #pragma unroll
        for (int i = 0; i < 4; i++)
            asm volatile("st.async.weak.shared::cluster.mbarrier::complete_tx::bytes.v4.f32 [%0], {%1,%2,%3,%4}, [%5];"
                :: "r"(ra + i * 2048), "f"(sv[4 * i]), "f"(sv[4 * i + 1]), "f"(sv[4 * i + 2]), "f"(sv[4 * i + 3]), "r"(rb) : "memory");
        asm volatile("st.async.weak.shared::cluster.mbarrier::complete_tx::bytes.v2.f32 [%0], {%1,%2}, [%3];" :: "r"(ra + 8192), "f"(sv[16]), "f"(sv[17]), "r"(rb) : "memory");
        mbar_wait(bars + 8 * BAR_P2R, 0);
        #pragma unroll
        for (int i = 0; i < 5; i++) {
            const uint4 v = lds128(slot + i * 2048);
            d0[8 * i] += __uint_as_float(v.x); d0[8 * i + 1] += __uint_as_float(v.y);
            if (i < 4) { d0[8 * i + 4] += __uint_as_float(v.z); d0[8 * i + 5] += __uint_as_float(v.w); }
        }
        asm volatile("bar.arrive 5, 256;" ::: "memory");
        gelu_store<0>(d0, (char*)(g_U + ((9 * gi + 8) * 4 + dt) * 1152) + wi * 4608 + rank * 2304 + c2 * 1152 + g * 16, q);
        bar_sync(8, 128);
        if (lead) { fence_async_g(); red_release(g_cnt + (CNT_U + dt * 2 + (gi >> 2)) * 32); PROFT(26); }
    } else {
        float d[72];
        const bool lead = wi == 0 && elect();
        const uint32_t da0 = desc_lo(sm + OFF_A + wg * 8192, 8192);
        const bool owner = (uint32_t)wg == rank;
        const int srow = 256 * gi + 128 * c2 + 64 * wg + 16 * wi;
        const uint32_t b2w0 = ldg_nc16(p.b2 + srow + g), b2w1 = ldg_nc16(p.b2 + srow + g + 8);
        {
            const int fr = 576 * gi + 256 * c2 + 128 * rank + 64 * wg + 16 * wi + g;
            const float bias0 = bf_lo(ldg_nc16(p.b1 + fr)), bias1 = bf_lo(ldg_nc16(p.b1 + fr + 8));
            #pragma unroll
            for (int i = 0; i < 72; i++) d[i] = (i & 2) ? bias1 : bias0;
            const uint32_t db1 = desc_lo(sm + OFF_B, 128);
            mainloop<DHI_H3, 0, IT_P1, false, true, false>(d, bars, da0, db1, lead, [&](int) {});
            mainloop<DHI_H3, IT_P1, IT_G2 - LEAD1, false, false, false>(d, bars, da0, db1, lead, [&](int) {});
            constexpr uint32_t EB = 8 * (BAR_EMPTY + (IT_G2 - LEAD1 - 1) % NST);
            if (wg == 1) { WG_WAIT(0); if (lead) mbar_arrive(bars + EB); bar_sync(9, 256); }
            mainloop<DHI_H3, IT_G2 - LEAD1, IT_G2, false, true, true>(d, bars, da0, db1, lead, [&](int i) {
                if (wg == 0) { if (i == IT_G2 - LEAD1 && lead) mbar_arrive(bars + EB); if (i == IT_G2 - 1) asm volatile("bar.arrive 9, 256;" ::: "memory"); } });
            PROF0(16);
            if (wg == 1) bar_sync(5, 256);
            char* const ub = (wg == 0 ? (char*)(g_U + ((9 * gi + 4 * c2 + 2 * rank) * 4 + dt) * 1152) : (char*)__cvta_shared_to_generic(sm + OFF_X1)) + wi * 4608 + g * 16;
            gelu_store<0>(d, ub, q); gelu_store<2>(d, ub + 2304, q); gelu_store<36>(d, ub + 1152, q); gelu_store<38>(d, ub + 3456, q);
            PROF0(27);
            if (wg == 0) asm volatile("bar.arrive 4, 160;" ::: "memory");
            else { fence_async_s(); asm volatile("bar.arrive 6, 160;" ::: "memory"); }
        }
        const uint32_t db0 = desc_lo(sm + OFF_B, 2304);
        constexpr int IT_L = IT_END - NST, IT_X = IT_L - 4;
        mainloop<DHI_U, IT_G2, IT_X, true, true, false>(d, bars, da0, db0, lead,
            [&](int i) { if (i == IT_G2 + W1S && wg == 0 && lead) mbar_arrive(bars + 8 * BAR_W1GO); });
        const uint32_t ga0 = sm + OFF_GB + (144 * dt + 8 * q) * 2, tile = sm + OFF_X1 + wi * 4608, to = g * 288 + q * 16;
        #define QOFF(i_) (((i_) >> 2) * 2304 + 144 * (((i_) >> 1) & 1) + 64 * ((i_) & 1))
        #define SOFF(k_) (((k_) >> 1) * 2304 + 144 * ((k_) & 1) + 128 - 12 * q)
        #define DIDX(i_, k_) ((i_) < 8 ? 36 * (((i_) >> 1) & 1) + 16 * ((i_) & 1) + 4 * (k_) + 2 * ((i_) >> 2) : 36 * ((k_) & 1) + 32 + 2 * ((k_) >> 1))
        #define FIN(k_, f_) bfma2(g4.f_, pack_bf(d[DIDX(i, k_)], d[DIDX(i, k_) + 1]), xq[i].f_)
        uint4 xq[9];
        auto load_g = [&](int i) { uint4 r; if (i < 4) r = lds128(ga0 + QOFF(i)); else { r.x = r.z = lds32(ga0 + SOFF(0)); r.y = r.w = lds32(ga0 + SOFF(1)); } return r; };
        mainloop<DHI_U, IT_X, IT_L, false, false, false>(d, bars, da0, db0, lead, [&](int i) {
            if (!owner) {
                const uint32_t xa = tile + to;
                if (i == IT_X) { mbar_wait(bars + 8 * BAR_XT, 0); xq[0] = lds128(xa + QOFF(0)); xq[4] = lds128(xa + QOFF(4)); xq[1] = lds128(xa + QOFF(1)); }
                else if (i == IT_X + 1) { xq[5] = lds128(xa + QOFF(5)); xq[2] = lds128(xa + QOFF(2)); xq[6] = lds128(xa + QOFF(6)); }
                else if (i == IT_X + 2) { xq[3] = lds128(xa + QOFF(3)); xq[7] = lds128(xa + QOFF(7));
                    xq[8] = make_uint4(lds32(xa + SOFF(0)), lds32(xa + SOFF(1)), lds32(xa + SOFF(2)), lds32(xa + SOFF(3))); }
                else if (i == IT_X + 3) { if (elect()) mbar_arrive_remote(mapa(bars + 8 * BAR_DONE, rank ^ 1)); }
            } });
        if (owner) { WG_WAIT(0); if (lead) mbar_arrive(bars + 8 * (BAR_EMPTY + (IT_L - 1) % NST)); bar_sync(7, 256); }
        #pragma unroll
        for (int i = IT_L; i < IT_END; i++) {
            mbar_wait(bars + 8 * (BAR_FULL + i % NST), (i / NST) & 1);
            WG_FENCE();
            #pragma unroll
            for (int k = 0; k < 4; k++) wgmma144<DHI_U>(d, da0 + (i % NST) * (A_BYTES / 16) + k * 128, db0 + (i % NST) * (B_BYTES / 16) + k * 288, 1);
            WG_COMMIT();
            if (i == IT_L) { WG_WAIT(1); if (lead && !owner) mbar_arrive(bars + 8 * (BAR_EMPTY + (IT_L - 1) % NST)); }
        }
        PROF0(9);
        mbar_wait(bars + 8 * BAR_GB, 0);
        if (!owner) {
            const uint32_t ra = mapa(tile + lane * 16, rank ^ 1), rb = mapa(bars + 8 * BAR_RECV, rank ^ 1);
            mbar_wait(bars + 8 * BAR_DONE, 0);
            uint4 gn = load_g(0);
            WG_WAIT(1);
            asm volatile("bar.arrive 7, 256;" ::: "memory");
            WG_WAIT(0);
            #pragma unroll
            for (int i = 0; i < 72; i++) d[i] = fmaf(bf_lo((i & 2) ? b2w1 : b2w0), 2.f, d[i]);
            #pragma unroll
            for (int j = 0; j < 5; j++) {
                const uint4 g4 = gn;
                if (j < 4) gn = load_g(j + 1);
                #pragma unroll
                for (int i = j < 4 ? j : 8; i < 9; i += 4) if (i < 8 || j == 4)
                    asm volatile("st.async.weak.shared::cluster.mbarrier::complete_tx::bytes.v4.b32 [%0], {%1,%2,%3,%4}, [%5];"
                        :: "r"(ra + i * 512), "r"(FIN(0, x)), "r"(FIN(1, y)), "r"(FIN(2, z)), "r"(FIN(3, w)), "r"(rb) : "memory");
            }
            PROF0(6);
            if (warp == 0) PROFDUMP();
            return;
        }
        PROF0(24);
        mbar_wait(bars + 8 * BAR_RECV, 0);
        #pragma unroll
        for (int i = 0; i < 9; i++) xq[i] = lds128(tile + lane * 16 + i * 512);
        uint4 gn = load_g(0);
        WG_WAIT(0);
        __syncwarp();
        PROF0(21);
        #pragma unroll
        for (int j = 0; j < 5; j++) {
            const uint4 g4 = gn;
            if (j < 4) gn = load_g(j + 1);
            #pragma unroll
            for (int i = j < 4 ? j : 8; i < 9; i += 4) if (i < 8 || j == 4) {
                const uint4 o = make_uint4(FIN(0, x), FIN(1, y), FIN(2, z), FIN(3, w));
                if (i < 8) sts128(tile + to + QOFF(i), o);
                else { sts32(tile + to + SOFF(0), o.x); sts32(tile + to + SOFF(1), o.y); sts32(tile + to + SOFF(2), o.z); sts32(tile + to + SOFF(3), o.w); }
            }
        }
        fence_async_s();
        __syncwarp();
        if (elect()) {
            asm volatile("cp.async.bulk.tensor.2d.global.shared::cta.bulk_group [%0, {%2, %3}], [%1];" :: "l"(&tm_o), "r"(tile), "r"(144 * dt), "r"(srow) : "memory");
            asm volatile("cp.async.bulk.commit_group;" ::: "memory");
            asm volatile("cp.async.bulk.wait_group.read 0;" ::: "memory");
        }
        PROF0(23);
        if (warp == 0) { __syncwarp(); PROFDUMP(); }
    }
}

typedef CUresult (*EncodeFn)(CUtensorMap*, CUtensorMapDataType, cuuint32_t, void*, const cuuint64_t*, const cuuint64_t*, const cuuint32_t*,
                             const cuuint32_t*, CUtensorMapInterleave, CUtensorMapSwizzle, CUtensorMapL2promotion, CUtensorMapFloatOOBfill);

void encode(EncodeFn fn, CUtensorMap* m, CUtensorMapDataType dt, int rank, const void* ptr, const cuuint64_t* dims, const cuuint64_t* strides,
            const cuuint32_t* box, CUtensorMapSwizzle sw, CUtensorMapL2promotion promo = CU_TENSOR_MAP_L2_PROMOTION_L2_128B) {
    const cuuint32_t es[5] = {1, 1, 1, 1, 1};
    fn(m, dt, rank, (void*)ptr, dims, strides, box, es, CU_TENSOR_MAP_INTERLEAVE_NONE, sw, promo, CU_TENSOR_MAP_FLOAT_OOB_FILL_NONE);
}

}

extern "C" void kernel_launch(void* const* d_in, const int* in_sizes, int n_in, void* d_out, int out_size) {
    (void)in_sizes; (void)n_in; (void)out_size;
    Params p;
    p.x = (const uint16_t*)d_in[0]; p.wr = (const uint16_t*)d_in[1]; p.wi = (const uint16_t*)d_in[2];
    p.w1 = (const uint16_t*)d_in[4]; p.b1 = (const uint16_t*)d_in[5]; p.w2 = (const uint16_t*)d_in[6]; p.b2 = (const uint16_t*)d_in[7];
    p.c = (const uint16_t*)d_in[8]; p.wmod = (const uint16_t*)d_in[9]; p.out = (uint16_t*)d_out;

    void* fnp = nullptr; cudaDriverEntryPointQueryResult qr;
    cudaGetDriverEntryPoint("cuTensorMapEncodeTiled", &fnp, cudaEnableDefault, &qr);
    EncodeFn fn = (EncodeFn)fnp;
    cudaGetSymbolAddress((void**)&p.scr, g_scr); cudaGetSymbolAddress((void**)&p.tab, g_tab);
    void* h3p = p.scr->h3;
    CUtensorMap tw1a, tw1b, tw2, th3a, th3b, twr, twi, twm, tt, ttx, to, th3s;
    {
        const cuuint64_t dims[4] = {64, 16, 128, 72}, st[3] = {128ull * F_ * 2, (cuuint64_t)F_ * 2, 128};
        const cuuint32_t ba[4] = {64, 16, 4, 2}, bb[4] = {64, 16, 8, 1};
        encode(fn, &tw1a, CU_TENSOR_MAP_DATA_TYPE_BFLOAT16, 4, p.w1, dims, st, ba, CU_TENSOR_MAP_SWIZZLE_128B);
        encode(fn, &tw1b, CU_TENSOR_MAP_DATA_TYPE_BFLOAT16, 4, p.w1, dims, st, bb, CU_TENSOR_MAP_SWIZZLE_128B);
    }
    {
        const cuuint64_t dims[3] = {64, F_, 32}, st[2] = {(cuuint64_t)S_ * 2, 128};
        const cuuint32_t bx[3] = {64, 64, 2};
        encode(fn, &tw2, CU_TENSOR_MAP_DATA_TYPE_BFLOAT16, 3, p.w2, dims, st, bx, CU_TENSOR_MAP_SWIZZLE_128B);
    }
    {
        const cuuint64_t dims[3] = {64, 72, 128}, st[2] = {256, 18432};
        const cuuint32_t ba[3] = {64, 18, 4}, bb[3] = {64, 9, 8};
        encode(fn, &th3a, CU_TENSOR_MAP_DATA_TYPE_UINT32, 3, h3p, dims, st, ba, CU_TENSOR_MAP_SWIZZLE_NONE);
        encode(fn, &th3b, CU_TENSOR_MAP_DATA_TYPE_UINT32, 3, h3p, dims, st, bb, CU_TENSOR_MAP_SWIZZLE_NONE);
    }
    {
        const cuuint64_t dims[4] = {32, 72, 2, 128}, st[3] = {256, 128, 18432};
        const cuuint32_t bx[4] = {32, 72, 2, 1};
        encode(fn, &th3s, CU_TENSOR_MAP_DATA_TYPE_UINT32, 4, h3p, dims, st, bx, CU_TENSOR_MAP_SWIZZLE_128B, CU_TENSOR_MAP_L2_PROMOTION_NONE);
    }
    {
        const cuuint64_t dims[3] = {4624, 4, 32}, st[2] = {9248 * 32, 9248};
        const cuuint32_t bx[3] = {56, 4, 32};
        encode(fn, &twr, CU_TENSOR_MAP_DATA_TYPE_BFLOAT16, 3, p.wr, dims, st, bx, CU_TENSOR_MAP_SWIZZLE_NONE);
        encode(fn, &twi, CU_TENSOR_MAP_DATA_TYPE_BFLOAT16, 3, p.wi, dims, st, bx, CU_TENSOR_MAP_SWIZZLE_NONE);
    }
    {
        const cuuint64_t dims[3] = {64, 576, 54}, st[2] = {6912, 128};
        const cuuint32_t bx[3] = {64, 32, 7};
        encode(fn, &twm, CU_TENSOR_MAP_DATA_TYPE_BFLOAT16, 3, p.wmod, dims, st, bx, CU_TENSOR_MAP_SWIZZLE_128B);
    }
    {
        const cuuint64_t dims[2] = {TP, 128}, st[1] = {TP * 4};
        const cuuint32_t ba[2] = {32, 128}, bb[2] = {8, 128};
        encode(fn, &tt, CU_TENSOR_MAP_DATA_TYPE_UINT32, 2, p.scr->T, dims, st, ba, CU_TENSOR_MAP_SWIZZLE_128B, CU_TENSOR_MAP_L2_PROMOTION_NONE);
        encode(fn, &ttx, CU_TENSOR_MAP_DATA_TYPE_UINT32, 2, p.scr->T, dims, st, bb, CU_TENSOR_MAP_SWIZZLE_32B, CU_TENSOR_MAP_L2_PROMOTION_NONE);
    }
    {
        const cuuint64_t dims[2] = {D_, S_}, st[1] = {D_ * 2};
        const cuuint32_t bx[2] = {144, 16};
        encode(fn, &to, CU_TENSOR_MAP_DATA_TYPE_BFLOAT16, 2, p.out, dims, st, bx, CU_TENSOR_MAP_SWIZZLE_NONE, CU_TENSOR_MAP_L2_PROMOTION_NONE);
    }
    cudaFuncSetAttribute(fused_kernel, cudaFuncAttributeMaxDynamicSharedMemorySize, SMEM_BYTES);
    cudaLaunchConfig_t cfg = {};
    cfg.gridDim = dim3(NCTA); cfg.blockDim = dim3(NTHR); cfg.dynamicSmemBytes = SMEM_BYTES; cfg.stream = cudaStreamPerThread;
    cudaLaunchAttribute at[1];
    at[0].id = cudaLaunchAttributeCooperative; at[0].val.cooperative = 1;
    cfg.attrs = at; cfg.numAttrs = 1;
    cudaLaunchKernelEx(&cfg, fused_kernel, p, tw1a, tw1b, tw2, th3a, th3b, twr, twi, twm, tt, ttx, to, th3s);
}
```

```cpp
#include <cuda_runtime.h>
#include <cuda_bf16.h>
#include <cuda_fp16.h>
#include <cuda.h>
#include <stdint.h>

namespace {

constexpr int S_ = 2048, D_ = 576, F_ = 4608;
constexpr int NCTA = 132, NTHR = 512;
constexpr int TP = 4736;
constexpr int SPEC_P = 296;
constexpr int NST = 6;
constexpr int A_BYTES = 16384, B_BYTES = 18432;
constexpr int IT_P1 = 24, IT_G2 = 40, IT_END = 76;
constexpr int SPIN_LIMIT = 1 << 22;
#define MODP 1
#define MODPAD 32
#define X2D 1450
#define CPHINT ".L2::128B"
constexpr int P2S = 2;
#define G2E 4
#define LEAD1 4
#define A2E 6
#define A2D 100
#define W1N 8
#define W1P 100
#define W1S 4
#define XDELAY 0
#define CRITPF 1
#define TALATE 0
#define NCD 0
#define X1D 2300
#define PF2 1
#define X1DELAY 2000
#define X1PACE 400

constexpr int OFF_A = 0;
constexpr int OFF_B = NST * A_BYTES;
constexpr int OFF_P = OFF_B + NST * B_BYTES;
constexpr int OFF_BAR = OFF_P;
constexpr int OFF_MISC = OFF_P + 376;
constexpr int OFF_GB = OFF_P + 384;
constexpr int OFF_P2R = OFF_P + 1536;
constexpr int OFF_X1 = OFF_P2R;
constexpr int OFF_PROF = OFF_X1 + 18432;
constexpr int SMEM_BYTES = OFF_PROF + 512 + 1024;
constexpr int QA = 13, QB = 7, QC = 13;
constexpr int TAB_BYTES = (QA + QB + QC) * 512;
constexpr int OFF_STAGE = OFF_B;
constexpr int OFF_STX = OFF_STAGE + 16384;
constexpr int OFF_TAB = OFF_STAGE + 20480;
constexpr int OFF_SPEC = OFF_TAB + TAB_BYTES;
constexpr int OFF_WRAW = OFF_SPEC + 19072;
constexpr int OFF_B3 = OFF_WRAW + 28672;
constexpr int OFF_MODA = OFF_B3 + 4096;
constexpr int OFF_MODC = OFF_MODA + 2560;
constexpr int OFF_RED = OFF_MODC + 3584;
constexpr int OFF_SILU = OFF_RED + 768;
static_assert(OFF_SILU + 1152 <= OFF_P && 6 * 28672 <= OFF_B3, "scratch overflow");
constexpr int OFF_STRIP = OFF_A;
static_assert(OFF_WRAW % 128 == 0 && OFF_STAGE % 128 == 0 && OFF_STX % 128 == 0, "align");
constexpr int BAR_FULL = 0, BAR_EMPTY = 6, BAR_TAB = 12, BAR_W = 13, BAR_REL = 14, BAR_P2R = 16,
              BAR_XT = 17, BAR_RECV = 18, BAR_ROLE = 19, BAR_NC = 20, BAR_TAB2 = 21, BAR_XB = 22, BAR_GB = 23, BAR_HOLD = 24, BAR_W1GO = 25, BAR_UOK = 26, BAR_DONE = 30, BAR_X = 31;

struct Cos1152 { double c[1152]; };
constexpr double cx_cos(double x) { double t = 1, s = 1; for (int i = 1; i < 14; i++) { t *= -x * x / ((2 * i - 1) * (2 * i)); s += t; } return s; }
constexpr Cos1152 make_cos() {
    Cos1152 r{};
    for (int i = 0; i <= 288; i++) {
        double v = (i == 288) ? 0.0 : cx_cos(3.14159265358979323846 * 2.0 * i / 1152.0);
        r.c[i] = v; r.c[576 - i] = -v; r.c[576 + i] = -v; r.c[(1152 - i) % 1152] = v;
    }
    return r;
}
constexpr uint32_t cx_f2h(double v) {
    uint32_t s = v < 0 ? 0x8000u : 0u; double a = v < 0 ? -v : v;
    if (a < 1e-9) return 0;
    int e = 0;
    while (a >= 2.0) { a *= 0.5; e++; }
    while (a < 1.0 && e > -14) { a *= 2.0; e--; }
    double m = a * 1024.0; uint32_t mi = (uint32_t)m; double fr = m - mi;
    if (fr > 0.5 || (fr == 0.5 && (mi & 1))) mi++;
    return s | (uint32_t)(((e + 14) << 10) + mi);
}
struct Tab { uint32_t w[(QA + QB + QC) * 128]; };
constexpr Tab make_tab() {
    Tab t{};
    Cos1152 ct = make_cos();
    auto C = [&](int num, int den) { return ct.c[(num % den) * (1152 / den)]; };
    auto Sn = [&](int num, int den) { return ct.c[((num % den) * (1152 / den) + 864) % 1152]; };
    auto put = [&](int q0, int idx, int lane, double lo, double hi) { t.w[((q0 + idx / 4) * 32 + lane) * 4 + idx % 4] = cx_f2h(lo) | (cx_f2h(hi) << 16); };
    for (int lane = 0; lane < 32; lane++) {
        const int g = lane >> 2, q = lane & 3;
        for (int mt = 0; mt < 3; mt++) {
            const int ka = 8 * mt + g;
            for (int r = 0; r < 10; r++) {
                const int im = r & 1, i0 = (r >> 1) * 2;
                double v[2] = {0, 0};
                for (int e = 0; e < 2; e++) { int i = i0 + e, d1 = 4 * i + q; if (i < 9 && ka <= 18) v[e] = (im ? -Sn(ka * d1, 36) : C(ka * d1, 36)) / 8; }
                put(0, mt * 10 + r, lane, v[0], v[1]);
            }
            for (int v = 0; v < 2; v++) {
                const int d2 = 4 * q + v;
                put(0, 30 + (mt * 2 + v) * 2, lane, C(ka * d2, 576) * 4 / 3, C(ka * (d2 + 2), 576) * 4 / 3);
                put(0, 31 + (mt * 2 + v) * 2, lane, Sn(ka * d2, 576) * 4 / 3, Sn(ka * (d2 + 2), 576) * 4 / 3);
            }
        }
        for (int v = 0; v < 2; v++) for (int nt = 0; nt < 2; nt++) {
            const int kb = 2 * (g >> 1) + nt, part = g & 1;
            double b0[2] = {0, 0}, b1[2] = {0, 0};
            for (int e = 0; e < 2; e++) { int d2 = 4 * q + 2 * e + v; double c = C(kb * d2, 16) / 4, s = Sn(kb * d2, 16) / 4;
                b0[e] = part ? -s : c; b1[e] = part ? c : s; }
            put(0, 42 + (v * 2 + nt) * 2, lane, b0[0], b0[1]); put(0, 43 + (v * 2 + nt) * 2, lane, b1[0], b1[1]);
        }
        for (int par = 0; par < 2; par++) for (int a = 0; a < 4; a++) {
            const int ja = 2 * (q + 4 * (a >> 1)) + par; const double c = C(g * ja, 16) / 4, s = Sn(g * ja, 16) / 4;
            put(QA, par * 4 + a, lane, (a & 1) ? -s : c, (a & 1) ? c : s);
        }
        for (int h = 0; h < 2; h++) {
            put(QA, 8 + 2 * h, lane, C((g + 8 * h) * (2 * q), 128) / 2, C((g + 8 * h) * (2 * q + 1), 128) / 2);
            put(QA, 9 + 2 * h, lane, Sn((g + 8 * h) * (2 * q), 128) / 2, Sn((g + 8 * h) * (2 * q + 1), 128) / 2);
            put(QA, 15 + 2 * h, lane, C(g * (8 * h + 2 * q), 128), C(g * (8 * h + 2 * q + 1), 128));
            put(QA, 16 + 2 * h, lane, Sn(g * (8 * h + 2 * q), 128), Sn(g * (8 * h + 2 * q + 1), 128));
        }
        put(QA, 12, lane, C(g * 2 * q, 8) / 2, C(g * (2 * q + 1), 8) / 2);
        put(QA, 13, lane, Sn(g * 2 * q, 8) / 2, Sn(g * (2 * q + 1), 8) / 2);
        put(QA, 14, lane, -Sn(g * 2 * q, 8) / 2, -Sn(g * (2 * q + 1), 8) / 2);
        for (int u = 0; u < 4; u++) {
            const int ja = 2 * ((g >> 1) + 4 * (u & 1)) + (u >> 1), part = g & 1; double b0[2] = {0, 0}, b1[2] = {0, 0};
            for (int e = 0; e < 2; e++) { int ka = 2 * q + e; double c = C(ja * ka, 16) / 4, s = Sn(ja * ka, 16) / 4;
                b0[e] = part ? s : c; b1[e] = part ? c : -s; }
            put(QA, 19 + u * 2, lane, b0[0], b0[1]); put(QA, 20 + u * 2, lane, b1[0], b1[1]);
        }
        for (int m2 = 0; m2 < 2; m2++) {
            const int d2 = 2 * g + m2;
            for (int a = 0; a < 4; a++) {
                const int kb = 2 * q + (a >> 1); const double c = C(d2 * kb, 16) / 4, s = Sn(d2 * kb, 16) / 4;
                put(QA + QB, m2 * 4 + a, lane, (a & 1) ? s : c, (a & 1) ? c : -s);
            }
            for (int mt = 0; mt < 3; mt++) {
                const int ka = 8 * mt + 2 * q;
                put(QA + QB, 8 + (m2 * 3 + mt) * 2, lane, C(ka * d2, 576) * 4 / 3, C((ka + 1) * d2, 576) * 4 / 3);
                put(QA + QB, 9 + (m2 * 3 + mt) * 2, lane, Sn(ka * d2, 576) * 4 / 3, Sn((ka + 1) * d2, 576) * 4 / 3);
            }
        }
        for (int mt = 0; mt < 3; mt++) for (int nt = 0; nt < 5; nt++) {
            const int i = 2 * nt + (g & 1), d1 = 4 * i + (g >> 1); double b0[2] = {0, 0}, b1[2] = {0, 0};
            for (int e = 0; e < 2; e++) { int ka = 8 * mt + 2 * q + e;
                if (ka <= 18 && i < 9) { double wt = (ka == 0 || ka == 18) ? 0.125 : 0.25; b0[e] = wt * C(ka * d1, 36); b1[e] = -wt * Sn(ka * d1, 36); } }
            put(QA + QB, 20 + (mt * 5 + nt) * 2, lane, b0[0], b0[1]); put(QA + QB, 21 + (mt * 5 + nt) * 2, lane, b1[0], b1[1]);
        }
    }
    return t;
}
__device__ __align__(128) const Tab g_tab = make_tab();

struct Scratch {
    uint32_t cnt[30 * 32];
    uint32_t slot[96];
    uint32_t mod[2304];
    uint32_t modc[896 + 288];
    uint32_t T[128 * TP];
    uint4 h3[128 * 1152];
    uint4 U[72 * 4 * 1152];
};
__device__ __align__(1024) Scratch g_scr;
#define g_cnt (p.scr->cnt)
#define g_slot (p.scr->slot)
#define g_mod (p.scr->mod)
#define g_T (p.scr->T)
#define g_h3 (p.scr->h3)
#define g_U (p.scr->U)
constexpr int CNT_EPOCH = 0, CNT_H3 = 1, CNT_X1 = 26, CNT_NC = 27, CNT_U = 2;
#define PROFT(i) do {} while (0)
#define PROFDUMP() do {} while (0)
#define PROF0(i) do {} while (0)

__device__ __forceinline__ void mbar_init(uint32_t bar, uint32_t cnt) { asm volatile("mbarrier.init.shared::cta.b64 [%0], %1;" :: "r"(bar), "r"(cnt) : "memory"); }
__device__ __forceinline__ void mbar_expect(uint32_t bar, uint32_t bytes) { asm volatile("mbarrier.arrive.expect_tx.shared::cta.b64 _, [%0], %1;" :: "r"(bar), "r"(bytes) : "memory"); }
__device__ __forceinline__ void mbar_arrive(uint32_t bar) { asm volatile("mbarrier.arrive.shared::cta.b64 _, [%0];" :: "r"(bar) : "memory"); }
__device__ __forceinline__ void mbar_arrive_n(uint32_t bar, uint32_t n) { asm volatile("mbarrier.arrive.shared::cta.b64 _, [%0], %1;" :: "r"(bar), "r"(n) : "memory"); }
__device__ __forceinline__ void mbar_arrive_remote(uint32_t rbar) { asm volatile("mbarrier.arrive.relaxed.cluster.shared::cluster.b64 _, [%0];" :: "r"(rbar) : "memory"); }
__device__ __forceinline__ void mbar_wait(uint32_t bar, uint32_t parity) {
    asm volatile("{.reg .pred p; .reg .u32 c;\n"
        "mbarrier.try_wait.parity.shared::cta.b64 p, [%0], %1;\n@p bra.uni DONE;\nmov.u32 c, 0;\n"
        "LOOP: mbarrier.try_wait.parity.shared::cta.b64 p, [%0], %1;\n@p bra.uni DONE;\n"
        "add.u32 c, c, 1;\nsetp.lt.u32 p, c, %2;\n@p bra.uni LOOP;\ntrap;\nDONE:}" :: "r"(bar), "r"(parity), "n"(SPIN_LIMIT) : "memory");
}
__device__ __forceinline__ bool mbar_test(uint32_t bar, uint32_t parity) {
    uint32_t ok; asm volatile("{.reg .pred p; mbarrier.test_wait.parity.shared::cta.b64 p, [%1], %2; selp.u32 %0, 1, 0, p;}" : "=r"(ok) : "r"(bar), "r"(parity) : "memory"); return ok; }
__device__ __forceinline__ uint32_t mapa(uint32_t a, uint32_t rank) { uint32_t r; asm("mapa.shared::cluster.u32 %0, %1, %2;" : "=r"(r) : "r"(a), "r"(rank)); return r; }
__device__ __forceinline__ uint32_t clk32() { uint32_t r; asm volatile("mov.u32 %0, %%clock;" : "=r"(r)); return r; }
__device__ __forceinline__ void hb() {
    asm volatile("{.reg .b32 a, b; .reg .pred p; mma.sync.aligned.m16n8k8.row.col.f16.f16.f16.f16 {a, b}, {%0,%0}, {%0}, {%0,%0};\n"
                 "setp.ne.u32 p, a, 0; @p trap;}" :: "r"(0));
}
__device__ __forceinline__ void spin_until(uint32_t t) { while (__any_sync(~0u, (int)(clk32() - t) < 0)) hb(); }
__device__ __forceinline__ bool elect() { uint32_t r; asm volatile("{.reg .pred p; elect.sync _|p, 0xffffffff; selp.u32 %0, 1, 0, p;}" : "=r"(r)); return r; }
__device__ __forceinline__ void bar_sync(int id, int n) { asm volatile("bar.sync %0, %1;" :: "r"(id), "r"(n) : "memory"); }
__device__ __forceinline__ void bulk_load(uint32_t dst, const void* src, uint32_t bytes, uint32_t bar) {
    asm volatile("cp.async.bulk.shared::cluster.global.mbarrier::complete_tx::bytes [%0], [%1], %2, [%3];" :: "r"(dst), "l"(src), "r"(bytes), "r"(bar) : "memory"); }
__device__ __forceinline__ void tma2(uint32_t dst, const CUtensorMap* m, int c0, int c1, uint32_t bar) {
    asm volatile("cp.async.bulk.tensor.2d.shared::cluster.global.mbarrier::complete_tx::bytes [%0], [%1, {%3, %4}], [%2];" :: "r"(dst), "l"(m), "r"(bar), "r"(c0), "r"(c1) : "memory"); }
__device__ __forceinline__ void tma3(uint32_t dst, const CUtensorMap* m, int c0, int c1, int c2, uint32_t bar) {
    asm volatile("cp.async.bulk.tensor.3d.shared::cluster.global.mbarrier::complete_tx::bytes [%0], [%1, {%3, %4, %5}], [%2];" :: "r"(dst), "l"(m), "r"(bar), "r"(c0), "r"(c1), "r"(c2) : "memory"); }
__device__ __forceinline__ void tma4(uint32_t dst, const CUtensorMap* m, int c0, int c1, int c2, int c3, uint32_t bar) {
    asm volatile("cp.async.bulk.tensor.4d.shared::cluster.global.mbarrier::complete_tx::bytes [%0], [%1, {%3, %4, %5, %6}], [%2];" :: "r"(dst), "l"(m), "r"(bar), "r"(c0), "r"(c1), "r"(c2), "r"(c3) : "memory"); }
__device__ __forceinline__ void fence_async_g() { asm volatile("fence.proxy.async.global;" ::: "memory"); }
__device__ __forceinline__ void fence_async_s() { asm volatile("fence.proxy.async.shared::cta;" ::: "memory"); }
__device__ __forceinline__ uint4 lds128(uint32_t a) { uint4 v; asm volatile("ld.shared.v4.u32 {%0,%1,%2,%3}, [%4];" : "=r"(v.x), "=r"(v.y), "=r"(v.z), "=r"(v.w) : "r"(a) : "memory"); return v; }
__device__ __forceinline__ uint32_t lds32(uint32_t a) { uint32_t v; asm volatile("ld.shared.u32 %0, [%1];" : "=r"(v) : "r"(a) : "memory"); return v; }
__device__ __forceinline__ void sts128(uint32_t a, uint4 v) { asm volatile("st.shared.v4.u32 [%0], {%1,%2,%3,%4};" :: "r"(a), "r"(v.x), "r"(v.y), "r"(v.z), "r"(v.w) : "memory"); }
__device__ __forceinline__ void sts32(uint32_t a, uint32_t v) { asm volatile("st.shared.u32 [%0], %1;" :: "r"(a), "r"(v) : "memory"); }
__device__ __forceinline__ void sts16(uint32_t a, uint32_t v) { asm volatile("st.shared.u16 [%0], %1;" :: "r"(a), "h"((uint16_t)v) : "memory"); }
__device__ __forceinline__ uint4 ldx128(const void* p) {
    uint4 v; asm volatile("{.reg .b128 t; .reg .b64 a, b; ld.relaxed.gpu.global.b128 t, [%4]; mov.b128 {a, b}, t; mov.b64 {%0,%1}, a; mov.b64 {%2,%3}, b;}"
        : "=r"(v.x), "=r"(v.y), "=r"(v.z), "=r"(v.w) : "l"(p) : "memory"); return v; }
__device__ __forceinline__ void stx128(void* p, uint4 v) {
    asm volatile("{.reg .b128 t; .reg .b64 a, b; mov.b64 a, {%1,%2}; mov.b64 b, {%3,%4}; mov.b128 t, {a, b}; st.relaxed.gpu.global.b128 [%0], t;}"
        :: "l"(p), "r"(v.x), "r"(v.y), "r"(v.z), "r"(v.w) : "memory"); }
__device__ __forceinline__ uint32_t ld_relaxed(const uint32_t* p) { uint32_t v; asm volatile("ld.relaxed.gpu.global.u32 %0, [%1];" : "=r"(v) : "l"(p) : "memory"); return v; }
__device__ __forceinline__ uint32_t ld_acquire(const uint32_t* p) { uint32_t v; asm volatile("ld.acquire.gpu.global.u32 %0, [%1];" : "=r"(v) : "l"(p) : "memory"); return v; }
__device__ __forceinline__ void st_relaxed(uint32_t* p, uint32_t v) { asm volatile("st.relaxed.gpu.global.u32 [%0], %1;" :: "l"(p), "r"(v) : "memory"); }
__device__ __forceinline__ void red_release(uint32_t* p) { asm volatile("red.release.gpu.global.add.u32 [%0], 1;" :: "l"(p) : "memory"); }
template <int SLEEP> __device__ __forceinline__ void wait_count(const uint32_t* p, uint32_t target) {
    int it = 0; while ((int)(ld_acquire(p) - target) < 0) { if (SLEEP) __nanosleep(SLEEP); if (++it > SPIN_LIMIT) __trap(); }
}
__device__ __forceinline__ uint32_t ldg_nc32(const void* p) { uint32_t v; asm volatile("ld.global.nc.L1::no_allocate.u32 %0, [%1];" : "=r"(v) : "l"(p)); return v; }
__device__ __forceinline__ uint32_t ldg_nc16(const void* p) { uint16_t v; asm volatile("ld.global.nc.u16 %0, [%1];" : "=h"(v) : "l"(p)); return v; }
__device__ __forceinline__ float bf_lo(uint32_t w) { return __uint_as_float(w << 16); }
__device__ __forceinline__ float bf_hi(uint32_t w) { return __uint_as_float(w & 0xFFFF0000u); }
__device__ __forceinline__ uint32_t pack_bf(float lo, float hi) { uint32_t r; asm("cvt.rn.bf16x2.f32 %0, %1, %2;" : "=r"(r) : "f"(hi), "f"(lo)); return r; }
__device__ __forceinline__ uint32_t pack_h(float lo, float hi) { uint32_t r; asm("cvt.rn.f16x2.f32 %0, %1, %2;" : "=r"(r) : "f"(hi), "f"(lo)); return r; }
__device__ __forceinline__ float bf_round(float v) { return bf_lo(pack_bf(v, 0.f)); }
__device__ __forceinline__ uint32_t hmul2(uint32_t a, uint32_t b) { uint32_t r; asm("mul.rn.f16x2 %0, %1, %2;" : "=r"(r) : "r"(a), "r"(b)); return r; }
__device__ __forceinline__ uint32_t hfma2(uint32_t a, uint32_t b, uint32_t c) { uint32_t r; asm("fma.rn.f16x2 %0, %1, %2, %3;" : "=r"(r) : "r"(a), "r"(b), "r"(c)); return r; }
__device__ __forceinline__ uint32_t hfms2(uint32_t a, uint32_t b, uint32_t c) { uint32_t r; asm("{.reg .b32 t; neg.f16x2 t, %3; fma.rn.f16x2 %0, %1, %2, t;}" : "=r"(r) : "r"(a), "r"(b), "r"(c)); return r; }
__device__ __forceinline__ uint32_t hadd2(uint32_t a, uint32_t b) { uint32_t r; asm("add.rn.f16x2 %0, %1, %2;" : "=r"(r) : "r"(a), "r"(b)); return r; }
__device__ __forceinline__ uint32_t hsub2(uint32_t a, uint32_t b) { uint32_t r; asm("sub.rn.f16x2 %0, %1, %2;" : "=r"(r) : "r"(a), "r"(b)); return r; }
__device__ __forceinline__ void cmul_neg(uint32_t& re, uint32_t& im, uint32_t c, uint32_t s) { uint32_t a = hfma2(re, c, hmul2(im, s)), b = hfms2(im, c, hmul2(re, s)); re = a; im = b; }
__device__ __forceinline__ void cmul_pos(uint32_t& re, uint32_t& im, uint32_t c, uint32_t s) { uint32_t a = hfms2(re, c, hmul2(im, s)), b = hfma2(im, c, hmul2(re, s)); re = a; im = b; }
__device__ __forceinline__ void mma_h(uint32_t& d0, uint32_t& d1, uint32_t a0, uint32_t a1, uint32_t a2, uint32_t a3, uint32_t b0, uint32_t b1) {
    asm("mma.sync.aligned.m16n8k16.row.col.f16.f16.f16.f16 {%0,%1}, {%2,%3,%4,%5}, {%6,%7}, {%0,%1};" : "+r"(d0), "+r"(d1) : "r"(a0), "r"(a1), "r"(a2), "r"(a3), "r"(b0), "r"(b1)); }
__device__ __forceinline__ void mma_h8(uint32_t& d0, uint32_t& d1, uint32_t a0, uint32_t a1, uint32_t b0) {
    asm("mma.sync.aligned.m16n8k8.row.col.f16.f16.f16.f16 {%0,%1}, {%2,%3}, {%4}, {%0,%1};" : "+r"(d0), "+r"(d1) : "r"(a0), "r"(a1), "r"(b0)); }
__device__ __forceinline__ void mma_f(float (&d)[4], uint32_t a0, uint32_t a1, uint32_t a2, uint32_t a3, uint32_t b0, uint32_t b1) {
    asm("mma.sync.aligned.m16n8k16.row.col.f32.f16.f16.f32 {%0,%1,%2,%3}, {%4,%5,%6,%7}, {%8,%9}, {%0,%1,%2,%3};"
        : "+f"(d[0]), "+f"(d[1]), "+f"(d[2]), "+f"(d[3]) : "r"(a0), "r"(a1), "r"(a2), "r"(a3), "r"(b0), "r"(b1)); }
template <int NQ> __device__ __forceinline__ void load_tab(uint32_t (&r)[NQ * 4], uint32_t addr) {
    #pragma unroll
    for (int i = 0; i < NQ; i++) { uint4 v = lds128(addr + i * 512); r[4 * i] = v.x; r[4 * i + 1] = v.y; r[4 * i + 2] = v.z; r[4 * i + 3] = v.w; }
}
__device__ __forceinline__ float gelu2(float x) {
    float t = x * fmaf(x * x, 0.044715f * 0.7978845608028654f, 0.7978845608028654f), th;
    asm volatile("tanh.approx.f32 %0, %1;" : "=f"(th) : "f"(t));
    return fmaf(x, th, x);
}
__device__ __forceinline__ uint32_t desc_lo(uint32_t addr, uint32_t lbo) { return ((addr & 0x3FFFF) >> 4) | ((lbo >> 4) << 16); }
constexpr uint32_t DHI_A = (1024 >> 4) | (1u << 30), DHI_H3 = 256 >> 4, DHI_U = 128 >> 4;
#define WG_FENCE() asm volatile("wgmma.fence.sync.aligned;" ::: "memory")
#define WG_COMMIT() asm volatile("wgmma.commit_group.sync.aligned;" ::: "memory")
#define WG_WAIT(n) asm volatile("wgmma.wait_group.sync.aligned %0;" :: "n"(n) : "memory")
#define R4(b) "+f"(d[b]), "+f"(d[b + 1]), "+f"(d[b + 2]), "+f"(d[b + 3])
#define R12(b) R4(b), R4(b + 4), R4(b + 8)
#define R36(b) R12(b), R12(b + 12), R12(b + 24)
template <uint32_t BHI> __device__ __forceinline__ void wgmma144(float (&d)[72], uint32_t da, uint32_t db, int acc) {
    asm volatile("{.reg .pred p; .reg .b64 a, b; setp.ne.b32 p, %74, 0; mov.b64 a, {%72, %75}; mov.b64 b, {%73, %76};\n"
        "wgmma.mma_async.sync.aligned.m64n144k16.f32.bf16.bf16 {%0,%1,%2,%3,%4,%5,%6,%7,%8,%9,%10,%11,%12,%13,%14,%15,%16,%17,%18,%19,%20,%21,%22,%23,"
        "%24,%25,%26,%27,%28,%29,%30,%31,%32,%33,%34,%35,%36,%37,%38,%39,%40,%41,%42,%43,%44,%45,%46,%47,"
        "%48,%49,%50,%51,%52,%53,%54,%55,%56,%57,%58,%59,%60,%61,%62,%63,%64,%65,%66,%67,%68,%69,%70,%71}, a, b, p, 1, 1, 1, 1;}\n"
        : R36(0), R36(36) : "r"(da), "r"(db), "r"(acc), "n"(DHI_A), "n"(BHI));
}
__device__ __forceinline__ void wgmma144x4(float (&d)[72], const uint64_t (&a)[4], const uint64_t (&b)[4], int acc) {
    #define WG144 "wgmma.mma_async.sync.aligned.m64n144k16.f32.bf16.bf16 {%0,%1,%2,%3,%4,%5,%6,%7,%8,%9,%10,%11,%12,%13,%14,%15,%16,%17,%18,%19,%20,%21,%22,%23,%24,%25,%26,%27,%28,%29,%30,%31,%32,%33,%34,%35,%36,%37,%38,%39,%40,%41,%42,%43,%44,%45,%46,%47,%48,%49,%50,%51,%52,%53,%54,%55,%56,%57,%58,%59,%60,%61,%62,%63,%64,%65,%66,%67,%68,%69,%70,%71}, "
    asm volatile("{.reg .pred p; setp.ne.b32 p, %80, 0;\n"
        WG144 "%72, %76, p, 1, 1, 1, 1;\n" WG144 "%73, %77, 1, 1, 1, 1, 1;\n" WG144 "%74, %78, 1, 1, 1, 1, 1;\n" WG144 "%75, %79, 1, 1, 1, 1, 1;}\n"
        : R36(0), R36(36) : "l"(a[0]), "l"(a[1]), "l"(a[2]), "l"(a[3]), "l"(b[0]), "l"(b[1]), "l"(b[2]), "l"(b[3]), "r"(acc));
}
__device__ __forceinline__ void wgmma72(float (&d)[36], uint32_t da, uint32_t db, int acc) {
    asm volatile("{.reg .pred p; .reg .b64 a, b; setp.ne.b32 p, %38, 0; mov.b64 a, {%36, %39}; mov.b64 b, {%37, %40};\n"
        "wgmma.mma_async.sync.aligned.m64n72k16.f32.bf16.bf16 {%0,%1,%2,%3,%4,%5,%6,%7,%8,%9,%10,%11,%12,%13,%14,%15,%16,%17,%18,%19,%20,%21,%22,%23,"
        "%24,%25,%26,%27,%28,%29,%30,%31,%32,%33,%34,%35}, a, b, p, 1, 1, 1, 1;}\n"
        : R36(0) : "r"(da), "r"(db), "r"(acc), "n"(DHI_A), "n"(DHI_H3));
}

__device__ __forceinline__ int g2_kb(int n, int kh) { const int m = n - 4; return 36 * kh + (n < 4 ? 9 * n + 8 : 9 * ((m >> 2) & 3) + 2 * (m & 3) + (m >> 4)); }

template <uint32_t BHI, int I0, int I1, bool ZERO, bool FIRST, bool LAST, class Hook>
__device__ __forceinline__ void mainloop(float (&d)[72], uint32_t bars, uint32_t da0, uint32_t db0, bool lead, Hook hook) {
    uint32_t s = I0 % NST, ph = (I0 / NST) & 1, prev = (I0 + NST - (I0 == IT_P1 ? 2 : 1)) % NST;
    uint32_t ready = 0;
    uint64_t da[4], db[4];
    #pragma unroll
    for (int k = 0; k < 4; k++) { da[k] = ((uint64_t)DHI_A << 32) + da0 + s * (A_BYTES / 16) + k * 128; db[k] = ((uint64_t)BHI << 32) + db0 + s * (B_BYTES / 16) + k * 288; }
    #pragma unroll 1
    for (int i = I0; i < I1; i++) {
        if (!ready) mbar_wait(bars + 8 * BAR_FULL + 8 * s, ph);
        WG_FENCE();
        wgmma144x4(d, da, db, ZERO ? i - I0 : 1);
        WG_COMMIT();
        const uint32_t rel = bars + 8 * BAR_EMPTY + 8 * prev; const int i0 = i;
        prev = s; if (++s == NST) { s = 0; ph ^= 1; }
        if (I1 == IT_P1 && (s == P2S || s == P2S + 3)) {
            mbar_wait(bars + 8 * BAR_FULL + 8 * s, ph);
            i++; if (++s == NST) { s = 0; ph ^= 1; }
        }
        const int64_t adv = (int)s - (int)prev;
        #pragma unroll
        for (int k = 0; k < 4; k++) { da[k] += adv * (A_BYTES / 16); db[k] += adv * (B_BYTES / 16); }
        ready = __shfl_sync(~0u, (uint32_t)mbar_test(bars + 8 * BAR_FULL + 8 * s, ph), 0);
        WG_WAIT(1);
        if (lead && (!FIRST || i0 > I0)) mbar_arrive(rel);
        hook(i0);
    }
    if (LAST) { WG_WAIT(0); if (lead) mbar_arrive(bars + 8 * BAR_EMPTY + 8 * prev); }
}

struct Params {
    const uint16_t *x, *wr, *wi, *w1, *b1, *w2, *b2, *c, *wmod;
    uint16_t* out;
    Scratch* scr;
    const Tab* tab;
};

__device__ __forceinline__ void mma_bf(float (&d)[4], const uint32_t (&a)[4], uint32_t b0, uint32_t b1) {
    asm("mma.sync.aligned.m16n8k16.row.col.f32.bf16.bf16.f32 {%0,%1,%2,%3}, {%4,%5,%6,%7}, {%8,%9}, {%0,%1,%2,%3};"
        : "+f"(d[0]), "+f"(d[1]), "+f"(d[2]), "+f"(d[3]) : "r"(a[0]), "r"(a[1]), "r"(a[2]), "r"(a[3]), "r"(b0), "r"(b1)); }
__device__ __forceinline__ void ldsm4t(uint32_t (&a)[4], uint32_t addr) {
    asm volatile("ldmatrix.sync.aligned.m8n8.x4.trans.shared.b16 {%0,%1,%2,%3}, [%4];" : "=r"(a[0]), "=r"(a[1]), "=r"(a[2]), "=r"(a[3]) : "r"(addr) : "memory"); }
__device__ __forceinline__ void ln_stats(const uint32_t (&w)[9], int g, int q, float& r, float& mr) {
    constexpr uint32_t ONE = 0x3F803F80u;
    float c[2][4] = {};
    #pragma unroll
    for (int p = 0; p < 5; p++) { const uint32_t hi = p < 4 ? w[p < 4 ? 2 * p + 1 : 0] : 0u, a[4] = {w[2 * p], ONE, hi, ONE}; mma_bf(c[p & 1], a, w[2 * p], hi); }
    const float t = (g & 1) ? c[0][1] + c[1][1] : c[0][0] + c[1][0];
    float s1 = (c[0][2] + c[1][2]) + (c[0][3] + c[1][3]), s2 = __shfl_sync(~0u, t, 9 * q) + __shfl_sync(~0u, t, 9 * q + 4);
    #pragma unroll
    for (int o = 1; o < 4; o <<= 1) { s1 += __shfl_xor_sync(~0u, s1, o); s2 += __shfl_xor_sync(~0u, s2, o); }
    const float m = s1 * (1.f / D_);
    asm("rsqrt.approx.ftz.f32 %0, %1;" : "=f"(r) : "f"(fmaxf(fmaf(s2, 1.f / D_, -m * m), 0.f) + 1e-5f));
    mr = -m * r;
}
__device__ __forceinline__ float silu(float v) { return __fdividef(v, 1.f + __expf(-v)); }
__device__ __forceinline__ uint32_t bfma2(uint32_t a, uint32_t b, uint32_t c) { uint32_t r; asm("fma.rn.bf16x2 %0, %1, %2, %3;" : "=r"(r) : "r"(a), "r"(b), "r"(c)); return r; }
__device__ __forceinline__ void radix16(const uint4 (&V)[4], const uint32_t (&B)[16], uint4 (&o)[4]) {
    #pragma unroll
    for (int nt = 0; nt < 4; nt++) {
        o[nt] = make_uint4(0, 0, 0, 0);
        #pragma unroll
        for (int ks = 0; ks < 2; ks++) {
            const uint32_t b0 = B[(ks * 4 + nt) * 2], b1 = B[(ks * 4 + nt) * 2 + 1];
            mma_h(o[nt].x, o[nt].y, V[2 * ks].x, V[2 * ks].y, V[2 * ks + 1].x, V[2 * ks + 1].y, b0, b1);
            mma_h(o[nt].z, o[nt].w, V[2 * ks].z, V[2 * ks].w, V[2 * ks + 1].z, V[2 * ks + 1].w, b0, b1);
        }
    }
}
template <int OFF, int N> __device__ __forceinline__ void gelu_store(const float (&d)[N], char* p, int q) {
    uint32_t w[9];
    #pragma unroll
    for (int blk = 0; blk < 9; blk++) w[blk] = pack_bf(gelu2(d[OFF + 4 * blk]), gelu2(d[OFF + 4 * blk + 1]));
    asm volatile("st.v4.u32 [%0], {%1,%2,%3,%4};" :: "l"(p + q * 128), "r"(w[0]), "r"(w[1]), "r"(w[2]), "r"(w[3]) : "memory");
    asm volatile("st.v4.u32 [%0+512], {%1,%2,%3,%4};" :: "l"(p + q * 128), "r"(w[4]), "r"(w[5]), "r"(w[6]), "r"(w[7]) : "memory");
    asm volatile("st.u32 [%0+1024], %1;" :: "l"(p + q * 4), "r"(w[8]) : "memory");
}

__global__ void __cluster_dims__(2, 1, 1) __launch_bounds__(NTHR, 1)
fused_kernel(const Params p,
             const __grid_constant__ CUtensorMap tm_w1a, const __grid_constant__ CUtensorMap tm_w1b, const __grid_constant__ CUtensorMap tm_w2,
             const __grid_constant__ CUtensorMap tm_h3a, const __grid_constant__ CUtensorMap tm_h3b,
             const __grid_constant__ CUtensorMap tm_wr, const __grid_constant__ CUtensorMap tm_wi, const __grid_constant__ CUtensorMap tm_wm,
             const __grid_constant__ CUtensorMap tm_t, const __grid_constant__ CUtensorMap tm_tx, const __grid_constant__ CUtensorMap tm_o,
             const __grid_constant__ CUtensorMap tm_h3s)
{
    extern __shared__ char smem_raw[];
    const uint32_t t0 = clk32();
    const uint32_t sm = __shfl_sync(~0u, ((uint32_t)__cvta_generic_to_shared(smem_raw) + 1023u) & ~1023u, 0);
    const int tid = threadIdx.x, warp = __shfl_sync(~0u, tid >> 5, 0), lane = tid & 31, g = lane >> 2, q = lane & 3;
    const int b = blockIdx.x;
    const uint32_t rank = b & 1;
    const uint32_t bars = sm + OFF_BAR;
    const bool rowcta = b < 128;

    auto nc_issue = [&](int st, uint32_t sl) {
        const int pass = st >= 18;
        mbar_expect(bars + 8 * (BAR_X + sl), 28672);
        tma3(sm + sl * 28672, &tm_wm, 0, 32 * (st - 18 * pass), 18 + 28 * pass + 7 * (b - 128), bars + 8 * (BAR_X + sl));
    };
    uint32_t epoch;
    if (warp < 12) {
        uint32_t cw = 0;
        if (lane < 24) cw = ldg_nc32(p.c + 48 * warp + 2 * lane);
        epoch = ld_relaxed(g_cnt + CNT_EPOCH * 32);
        if (b < 72) {
            const uint16_t* src = p.wmod + (48 * warp + (lane >> 1)) * 3456 + 16 * b + (lane & 1) * 8;
            const uint32_t dst = sm + OFF_STRIP + (48 * warp + (lane >> 1)) * 48 + (lane & 1) * 16;
            #pragma unroll
            for (int u = 0; u < 3; u++) asm volatile("cp.async.cg.shared.global" CPHINT " [%0], [%1], 16;" :: "r"(dst + u * 768), "l"(src + u * 16 * 3456) : "memory");
            asm volatile("cp.async.commit_group;" ::: "memory");
        }
        if (lane < 24) sts32(sm + OFF_SILU + (24 * warp + lane) * 4, pack_bf(silu(bf_lo(cw)), silu(bf_hi(cw))));
        hb();
        if (b < 72) {
            uint32_t sb[6];
            __syncwarp();
            #pragma unroll
            for (int u = 0; u < 6; u++) sb[u] = lds32(sm + OFF_SILU + (24 * warp + 4 * u + q) * 4);
            asm volatile("cp.async.wait_all;" ::: "memory");
            __syncwarp();
            float acc[4] = {0, 0, 0, 0};
            #pragma unroll
            for (int u = 0; u < 3; u++) {
                uint32_t a[4];
                ldsm4t(a, sm + OFF_STRIP + (48 * warp + 16 * u + (lane & 7) + 8 * (lane >> 4)) * 48 + ((lane >> 3) & 1) * 16);
                mma_bf(acc, a, sb[2 * u], sb[2 * u + 1]);
            }
            if (q == 0) { sts32(sm + OFF_RED + (g * 12 + warp) * 4, __float_as_uint(acc[0])); sts32(sm + OFF_RED + ((g + 8) * 12 + warp) * 4, __float_as_uint(acc[2])); }
            PROF0(0);
        }
        bar_sync(2, 512);
        if (warp == 0 && b < 72) {
            if (lane < 16) {
                float sum = 0;
                #pragma unroll
                for (int u = 0; u < 3; u++) { const uint4 v = lds128(sm + OFF_RED + lane * 48 + u * 16);
                    sum += (__uint_as_float(v.x) + __uint_as_float(v.y)) + (__uint_as_float(v.z) + __uint_as_float(v.w)); }
                sum = bf_round(sum); if (b >= 36) sum = bf_round(1.f + sum);
                st_relaxed(g_mod + b * MODPAD + (lane & 1) * 8 + (lane >> 1), (pack_h(0.f, sum) & 0xFFFF0000u) | ((epoch + 1) & 0xFFFFu));
            }
            __syncwarp();
            PROF0(1);
        }
    } else {
        const int w4 = 4 * (warp - 12);
        if (elect()) {
            if (CRITPF) {
                asm volatile("cp.async.bulk.prefetch.L2.global [%0], 2304;" :: "l"(p.wmod + (b + 33 * w4) * 3456) : "memory");
                if (warp == 12 && b < 48) asm volatile("cp.async.bulk.prefetch.L2.global [%0], 2304;" :: "l"(p.wmod + (b + 528) * 3456) : "memory");
            }
        }
        if (warp == 13) hb();
        if (elect()) {
            if (rowcta) {
                for (int i = 0; i < 4; i++) mbar_init(bars + 8 * (BAR_X + w4 + i), 1);
                if (warp == 15) mbar_init(bars + 8 * BAR_TAB, 1);
                fence_async_s();
                if (warp == 15) { mbar_expect(bars + 8 * BAR_TAB, QA * 512); bulk_load(sm + OFF_TAB, p.tab, QA * 512, bars + 8 * BAR_TAB); }
                if (XDELAY) while ((int)(clk32() - t0) < XDELAY) {}
                for (int r = w4; r < w4 + 4; r++) {
                    mbar_expect(bars + 8 * (BAR_X + r), 1152);
                    bulk_load(sm + OFF_STAGE + r * 1152, p.x + (size_t)(b + 128 * r) * D_, 1152, bars + 8 * (BAR_X + r));
                }
            } else if (warp == 12) {
                for (int i = 0; i < 12; i++) mbar_init(bars + 8 * (BAR_X + i), i < 6 ? 1 : 14);
                fence_async_s();
                if (NCD) while ((int)(clk32() - t0) < NCD) {}
                for (int st = 0; st < 6; st++) nc_issue(st, st);
            }
            if (warp == 12) {
                asm volatile("prefetch.tensormap [%0];" :: "l"(&tm_wr) : "memory"); asm volatile("prefetch.tensormap [%0];" :: "l"(&tm_wi) : "memory");
                asm volatile("prefetch.tensormap [%0];" :: "l"(&tm_t) : "memory"); asm volatile("prefetch.tensormap [%0];" :: "l"(&tm_tx) : "memory");
            } else if (warp == 14) {
                for (int i = BAR_W; i < BAR_X; i++) mbar_init(bars + 8 * i, i == BAR_DONE ? 4 : 1);
                mbar_expect(bars + 8 * BAR_W, 28672); mbar_expect(bars + 8 * BAR_TAB2, (QB + QC) * 512);
                mbar_expect(bars + 8 * BAR_ROLE, 4); mbar_expect(bars + 8 * BAR_P2R, 9216); mbar_expect(bars + 8 * BAR_RECV, 18432); mbar_expect(bars + 8 * BAR_XT, 18432);
            } else if (warp == 13) {
                for (int i = 0; i < 2 * NST; i++) mbar_init(bars + 8 * i, 2);
                for (int i = 0; i < NST; i++) mbar_expect(bars + 8 * (BAR_FULL + i), A_BYTES);
            }
            asm volatile("fence.mbarrier_init.release.cluster;" ::: "memory");
        }
        __syncwarp();
        asm volatile("bar.arrive 2, 512;" ::: "memory");
        epoch = ld_relaxed(g_cnt + CNT_EPOCH * 32);
        sts16(sm + OFF_MODA + ((warp - 11) * 32 + lane) * 16 + w4 + 2, 0);
        #pragma unroll 1
        for (int s1 = (tid >> 4) & 7; s1 < 16; s1 += 8) {
            const int k1 = tid & 15;
            float s, c;
            __sincosf((float)(((k1 * (128 * s1 + b) + 1024) & 2047) - 1024) * (3.14159265358979f / 1024.f), &s, &c); s *= 0.25f; c *= 0.25f;
            const int rf = ((s1 >> 3) * 4 + (k1 >> 2)) * 2 + ((s1 >> 2) & 1), ri = ((k1 >> 3) * 4 + (s1 >> 2)) * 2 + ((k1 >> 2) & 1);
            const uint32_t af = sm + OFF_B3 + ((rf >> 2) * 32 + (k1 & 3) * 8 + (s1 & 3)) * 16 + (rf & 3) * 4;
            const uint32_t ai = sm + OFF_B3 + 2048 + ((ri >> 2) * 32 + (s1 & 3) * 8 + (k1 & 3)) * 16 + (ri & 3) * 4;
            sts32(af, pack_h(c, s)); sts32(af + 64, pack_h(-s, c)); sts32(ai, pack_h(c, -s)); sts32(ai + 64, pack_h(s, c));
        }
        hb();
        bar_sync(3, 128);
    }
    asm volatile("barrier.cluster.arrive.relaxed.aligned;" ::: "memory");
    const uint32_t tag = (epoch + 1) & 0xFFFFu;

    const int trow = 4 * (b & 7) + ((b >> 4) & 3) + 64 * ((b >> 3) & 1) + 32 * (b >> 6);
    uint32_t* const tptr = g_T + (size_t)trow * TP + (warp < 9 ? q * 288 + 32 * warp : 4608 + 8 * q) + 4 * g;
    const int tstr = warp < 9 ? 1152 : 32;
    const uint32_t scol = sm + OFF_SPEC + (q * SPEC_P + (warp < 8 ? 72 * (warp >> 1) + 40 * (warp & 1) + 4 * g : warp == 8 ? 72 * (g >> 1) + 32 + 4 * (g & 1) : 288 + 4 * g)) * 4;
    const int wc0 = (b >> 3) * 289 + 72 * ((b & 7) >> 1) + 40 * (b & 1);

    uint32_t xw[9], t_st = t0;
    if (!rowcta) {
        const int nst = b < 130 ? 36 : 18;
        __syncthreads();
        if (warp == 14) {
            uint32_t sl = 0, ph = 0;
            #pragma unroll 1
            for (int st = 6; st < nst; st++) {
                mbar_wait(bars + 8 * (BAR_X + 6 + sl), ph);
                if (elect()) nc_issue(st, sl);
                if (++sl == 6) { sl = 0; ph ^= 1; }
            }
        } else if (warp < 14) {
            uint32_t sl = 0, ph = 0;
            const uint32_t ad0 = sm + (warp >> 1) * 4096 + ((lane & 7) + 8 * (lane >> 4)) * 128, ch = (warp & 1) * 4 + ((lane >> 3) & 1);
            #pragma unroll 1
            for (int pass = 0; pass * 18 < nst; pass++) {
                float acc[2][4] = {};
                #pragma unroll 1
                for (int st = 0; st < 18; st++) {
                    const uint32_t sa = sm + OFF_SILU + (16 * st + q) * 4;
                    const uint32_t b0 = lds32(sa), b1 = lds32(sa + 16), b2 = lds32(sa + 32), b3 = lds32(sa + 48);
                    mbar_wait(bars + 8 * (BAR_X + sl), ph);
                    #pragma unroll
                    for (int m = 0; m < 2; m++) {
                        uint32_t a[4], a2[4];
                        const uint32_t ad = ad0 + sl * 28672 + ((ch + 2 * m) ^ (lane & 7)) * 16;
                        ldsm4t(a, ad); ldsm4t(a2, ad + 2048);
                        mma_bf(acc[m], a, b0, b1); mma_bf(acc[m], a2, b2, b3);
                    }
                    if (elect()) mbar_arrive(bars + 8 * (BAR_X + 6 + sl));
                    if (++sl == 6) { sl = 0; ph ^= 1; }
                }
                const int cb = 28 * pass + 7 * (b - 128) + (warp >> 1), gg = (g >> 1) + 4 * q;
                #pragma unroll
                for (int m = 0; m < 2; m++) {
                    const int qq = (warp & 1) * 2 + m;
                    float v = bf_round(q ? acc[m][2] : acc[m][0]); if (cb >= 27) v *= 0.5f; else if (cb >= 18) v += 1.f;
                    const uint32_t w = pack_bf(v, __shfl_xor_sync(~0u, v, 4));
                    if (q < 2 && !(g & 1) && cb < 36) p.scr->modc[cb < 27 ? ((cb >> 2) * 32 + 4 * gg + qq) * 4 + (cb & 3) : 896 + 32 * (cb - 27) + 8 * qq + gg] = w;
                }
                bar_sync(1, 448);
                if (tid == 0) { fence_async_g(); red_release(g_cnt + (CNT_NC + pass) * 32); if (pass == 0) PROFT(25); }
                __syncwarp();
            }
            fence_async_s();
        }
        __syncthreads();
    } else {
        uint32_t ta[QA * 4];
        if (!TALATE) { mbar_wait(bars + 8 * BAR_TAB, 0); load_tab<QA>(ta, sm + OFF_TAB + lane * 16); }
        uint32_t nb[2][5];
        uint4 mv = make_uint4(tag, tag, tag, tag);
        const int mc = tid - 224, mst = (mc >> 2) % 36, midx = (mc < 144 ? 10 : 0) + 5 * ((mc >> 1) & 1) + (mst >> 3);
        const uint32_t* mp = g_mod + (mc >> 2) * MODPAD + (mc & 3) * 4;
        const uint32_t ma = sm + OFF_MODA + ((midx >> 2) * 32 + (mc & 1) * 16 + (mst & 3)) * 16 + (midx & 3) * 4 + ((mst >> 2) & 1) * 2;
        #define MOD_MISSING ((((mv.x ^ tag) | (mv.y ^ tag) | (mv.z ^ tag) | (mv.w ^ tag)) & 0xFFFFu) != 0)
        hb();
        mbar_wait(bars + 8 * (BAR_X + warp), 0);
        if (warp >= 7) mv = ldx128(mp);
        PROF0(28);
        #pragma unroll
        for (int i = 0; i < 9; i++) xw[i] = lds32(sm + OFF_STAGE + warp * 1152 + (32 * i + 8 * q + g) * 4);
        {
            float r, mr;
            ln_stats(xw, g, q, r, mr);
            #pragma unroll
            for (int pp = 0; pp < 5; pp++) {
                nb[0][pp] = pack_h(fmaf(bf_lo(xw[2 * pp]), r, mr), pp < 4 ? fmaf(bf_lo(xw[pp < 4 ? 2 * pp + 1 : 0]), r, mr) : 0.f);
                nb[1][pp] = pack_h(fmaf(bf_hi(xw[2 * pp]), r, mr), pp < 4 ? fmaf(bf_hi(xw[pp < 4 ? 2 * pp + 1 : 0]), r, mr) : 0.f);
            }
        }
        PROF0(2);
        if (TALATE) { mbar_wait(bars + 8 * BAR_TAB, 0); load_tab<QA>(ta, sm + OFF_TAB + lane * 16); }
        if (warp >= 7) {
            for (int it = 0; __any_sync(~0u, MOD_MISSING); it++) { if (MOD_MISSING) mv = ldx128(mp); hb(); if (it > SPIN_LIMIT) __trap(); }
            sts16(ma, mv.x >> 16); sts16(ma + 64, mv.y >> 16); sts16(ma + 128, mv.z >> 16); sts16(ma + 192, mv.w >> 16);
        }
        __syncthreads();
        PROF0(3);
        if (warp >= 13 && elect()) {
            if (warp == 15) bulk_load(sm + OFF_TAB + QA * 512, p.tab->w + QA * 128, (QB + QC) * 512, bars + 8 * BAR_TAB2);
            else tma3(sm + OFF_WRAW + (warp - 13) * 14336, warp == 13 ? &tm_wr : &tm_wi, wc0 & ~7, 0, 0, bars + 8 * BAR_W);
        }
        __syncwarp();
        {
            uint32_t md[20];
            load_tab<5>(md, sm + OFF_MODA + lane * 16);
            #pragma unroll
            for (int v = 0; v < 2; v++)
                #pragma unroll
                for (int pp = 0; pp < 5; pp++) nb[v][pp] = hfma2(nb[v][pp], md[v * 5 + pp], md[10 + v * 5 + pp]);
        }
        uint32_t re[3][2], im[3][2];
        #pragma unroll
        for (int mt = 0; mt < 3; mt++)
            #pragma unroll
            for (int v = 0; v < 2; v++) {
                re[mt][v] = 0; im[mt][v] = 0;
                mma_h8(re[mt][v], im[mt][v], ta[mt * 10 + 8], ta[mt * 10 + 9], nb[v][4]);
                mma_h(re[mt][v], im[mt][v], ta[mt * 10], ta[mt * 10 + 1], ta[mt * 10 + 2], ta[mt * 10 + 3], nb[v][0], nb[v][1]);
                mma_h(re[mt][v], im[mt][v], ta[mt * 10 + 4], ta[mt * 10 + 5], ta[mt * 10 + 6], ta[mt * 10 + 7], nb[v][2], nb[v][3]);
                cmul_neg(re[mt][v], im[mt][v], ta[30 + (mt * 2 + v) * 2], ta[31 + (mt * 2 + v) * 2]);
            }
        const uint32_t srow = sm + OFF_SPEC + warp * (SPEC_P * 4);
        #pragma unroll
        for (int nt = 0; nt < 2; nt++) {
            uint32_t o[2][4];
            #pragma unroll
            for (int v = 0; v < 2; v++) {
                const uint32_t b0 = ta[42 + (v * 2 + nt) * 2], b1 = ta[43 + (v * 2 + nt) * 2];
                o[v][0] = o[v][1] = o[v][2] = o[v][3] = 0;
                mma_h(o[v][0], o[v][1], re[0][v], re[1][v], im[0][v], im[1][v], b0, b1);
                mma_h(o[v][2], o[v][3], re[2][v], re[2][v], im[2][v], im[2][v], b0, b1);
            }
            const uint32_t a = srow + (g + 72 * q + 36 * nt) * 4, a2 = srow + (288 - g - 72 * q - 36 * nt) * 4;
            sts32(a, hadd2(o[0][0], o[1][0])); sts32(a + 32, hadd2(o[0][1], o[1][1])); if (g < 3) sts32(a + 64, hadd2(o[0][2], o[1][2]));
            if (g > 0 || (q == 0 && nt == 0)) sts32(a2, hsub2(o[0][0], o[1][0]) ^ 0x80000000u);
            sts32(a2 - 32, hsub2(o[0][1], o[1][1]) ^ 0x80000000u); if (g < 2) sts32(a2 - 64, hsub2(o[0][2], o[1][2]) ^ 0x80000000u);
        }
        uint32_t b3[16];
        if (warp < 10) load_tab<4>(b3, sm + OFF_B3 + lane * 16);
        __syncthreads();
        t_st = clk32();
        PROF0(4);
        if (warp < 10) {
            uint4 V[4], o[4];
            #pragma unroll
            for (int u = 0; u < 4; u++) V[u] = lds128(scol + u * (16 * SPEC_P));
            radix16(V, b3, o);
            #pragma unroll
            for (int nt = 0; nt < 4; nt++) { o[nt].x |= 1u; if (warp < 9 || g < 2) stx128(tptr + nt * tstr, o[nt]); }
        }
        PROF0(5);
    }

    int role = 0;
    asm volatile("barrier.cluster.wait.aligned;" ::: "memory");
    if (warp >= 12) {
        const int t = tid - 384;
        if (tid == 448 && rank == 0) {
            uint32_t smid; asm volatile("mov.u32 %0, %%smid;" : "=r"(smid));
            const uint32_t tp = smid >> 1;
            uint32_t pr = tp < 32 ? (tp & 7) * 8 + (tp >> 3) : tp < 60 ? (1 + (tp - 32) % 7) * 8 + 4 + (tp - 32) / 7 : tp < 62 ? 4 + tp : tp < 66 ? tp - 58 : 0;
            while (atomicExch(g_slot + pr, epoch + 1) == epoch + 1) pr = pr == 65 ? 0 : pr + 1;
            #pragma unroll
            for (int r = 0; r < 2; r++)
                asm volatile("st.async.weak.shared::cluster.mbarrier::complete_tx::bytes.u32 [%0], %1, [%2];" :: "r"(mapa(sm + OFF_MISC, r)), "r"(pr), "r"(mapa(bars + 8 * BAR_ROLE, r)) : "memory");
        }
        __syncwarp();
        if (t == 0) {
            asm volatile("prefetch.tensormap [%0];" :: "l"(&tm_w1a) : "memory");
            asm volatile("prefetch.tensormap [%0];" :: "l"(&tm_h3a) : "memory"); asm volatile("prefetch.tensormap [%0];" :: "l"(&tm_w1b) : "memory");
            asm volatile("prefetch.tensormap [%0];" :: "l"(&tm_h3b) : "memory"); asm volatile("prefetch.tensormap [%0];" :: "l"(&tm_w2) : "memory");
            asm volatile("prefetch.tensormap [%0];" :: "l"(&tm_o) : "memory"); asm volatile("prefetch.tensormap [%0];" :: "l"(&tm_h3s) : "memory");
        }
        if (t == 32 && rowcta) {
            for (int it = 0; (int)(ld_acquire(g_cnt + CNT_NC * 32) - (epoch + 1) * 4) < 0; it++) { __nanosleep(100); if (it > SPIN_LIMIT) __trap(); }
            fence_async_g();
            mbar_expect(bars + 8 * BAR_NC, 3584);
            bulk_load(sm + OFF_MODC, p.scr->modc, 3584, bars + 8 * BAR_NC);
            PROFT(29);
        }
        __syncwarp();
    } else if (rowcta && warp < 11) {
        const int nw = !(b & 1) ? 10 : (b & 7) == 7 ? 9 : 8;
        const int cm = (b >> 3) * 288 + (b & 7) * 32, cx = (b & 1) ? 4608 + 8 * (b >> 3) : (b >> 3) * 288 + 256 + 4 * (b & 7);
        auto load_in = [&]() {
            if (elect()) {
                mbar_expect(bars + 8 * BAR_XB, nw > 8 ? 20480 : 16384);
                tma2(sm + OFF_STAGE, &tm_t, cm, 0, bars + 8 * BAR_XB);
                if (nw > 8) tma2(sm + OFF_STX, &tm_tx, cx, 0, bars + 8 * BAR_XB);
            }
            __syncwarp();
        };
        if (warp == 10) { fence_async_s(); spin_until(t_st + X1D); load_in(); }
        uint32_t tb[QB * 4], wre[4][2], wim[4][2];
        if (warp < nw) {
            mbar_wait(bars + 8 * BAR_TAB2, 0);
            load_tab<QB>(tb, sm + OFF_TAB + QA * 512 + lane * 16);
            mbar_wait(bars + 8 * BAR_W, 0);
            const int off = wc0 & 7;
            const uint32_t wa = sm + OFF_WRAW + lane * 112 + ((off >> 1) + 2 * warp) * 4, sh = (off & 1) * 16;
            #pragma unroll
            for (int c = 0; c < 2; c++)
                #pragma unroll
                for (int h = 0; h < 2; h++) {
                    uint32_t y[2][2];
                    #pragma unroll
                    for (int e = 0; e < 2; e++) {
                        const uint32_t a = wa + c * 14336 + (h + 2 * e) * 3584, x0 = lds32(a), x1 = lds32(a + 4), x2 = lds32(a + 8);
                        y[e][0] = __funnelshift_r(x0, x1, sh); y[e][1] = __funnelshift_r(x1, x2, sh);
                    }
                    #pragma unroll
                    for (int x = 0; x < 4; x++) {
                        const uint32_t v = (x & 1) ? pack_h(bf_hi(y[0][x >> 1]), bf_hi(y[1][x >> 1])) : pack_h(bf_lo(y[0][x >> 1]), bf_lo(y[1][x >> 1]));
                        if (c) wim[x][h] = v; else wre[x][h] = v;
                    }
                }
        }
        const uint32_t ca = warp < 8 ? sm + OFF_STAGE + lane * 128 + (warp ^ (lane & 7)) * 16 : sm + OFF_STX + lane * 32 + ((warp ^ g) & 1) * 16, cs = warp < 8 ? 4096 : 1024;
        uint32_t V[4][4];
        for (int it = 0;; it++) {
            mbar_wait(bars + 8 * BAR_XB, it & 1);
            uint32_t ok = 1;
            if (warp < nw) {
                #pragma unroll
                for (int u = 0; u < 4; u++) { uint4 t4 = lds128(ca + u * cs); V[u][0] = t4.x; V[u][1] = t4.y; V[u][2] = t4.z; V[u][3] = t4.w; ok &= t4.x; }
            }
            asm volatile("{.reg .pred p; setp.ne.u32 p, %0, 0; bar.red.and.pred p, 1, 352, p; selp.u32 %0, 1, 0, p;}" : "+r"(ok) :: "memory");
            if (ok) break;
            if (warp == 10) { load_in(); hb(); }
            if (it > SPIN_LIMIT / 64) __trap();
        }
        PROF0(7);
        if (warp < nw) {
            uint32_t zr[4][2], zi[4][2];
            #pragma unroll
            for (int x = 0; x < 4; x++) {
                uint32_t er = 0, ei = 0, or_ = 0, oi = 0;
                mma_h(er, ei, tb[0], tb[1], tb[2], tb[3], V[0][x], V[1][x]);
                mma_h(or_, oi, tb[4], tb[5], tb[6], tb[7], V[2][x], V[3][x]);
                uint32_t r0 = hadd2(er, or_), r1 = hsub2(er, or_), i0 = hadd2(ei, oi), i1 = hsub2(ei, oi);
                cmul_neg(r0, i0, tb[8], tb[9]); cmul_neg(r1, i1, tb[10], tb[11]);
                uint32_t xr0 = 0, xr1 = 0, xi0 = 0, xi1 = 0;
                mma_h(xr0, xr1, r0, r1, i0, i1, tb[12], tb[13]);
                mma_h(xi0, xi1, r0, r1, i0, i1, tb[14], tb[12]);
                cmul_pos(xr0, xi0, wre[x][0], wim[x][0]); cmul_pos(xr1, xi1, wre[x][1], wim[x][1]);
                r0 = 0; i0 = 0; r1 = 0; i1 = 0;
                mma_h(r0, i0, tb[12], tb[13], tb[14], tb[12], xr0, xi0);
                mma_h(r1, i1, tb[12], tb[13], tb[14], tb[12], xr1, xi1);
                cmul_pos(r0, i0, tb[15], tb[16]); cmul_pos(r1, i1, tb[17], tb[18]);
                zr[x][0] = hadd2(r0, r1); zr[x][1] = hsub2(r0, r1); zi[x][0] = hadd2(i0, i1); zi[x][1] = hsub2(i0, i1);
            }
            #pragma unroll
            for (int nt = 0; nt < 4; nt++) {
                uint4 o = make_uint4(0, 0, 0, 0);
                const int h = nt >> 1;
                mma_h(o.x, o.y, zr[0][h], zr[1][h], zi[0][h], zi[1][h], tb[19 + 2 * nt], tb[20 + 2 * nt]);
                mma_h(o.z, o.w, zr[2][h], zr[3][h], zi[2][h], zi[3][h], tb[19 + 2 * nt], tb[20 + 2 * nt]);
                o.x &= ~1u;
                sts128(ca + nt * cs, o);
            }
        }
        fence_async_s();
        bar_sync(1, 352);
        t_st = clk32();
        PROF0(8);
        if (warp == 10 && elect()) {
            asm volatile("cp.async.bulk.tensor.2d.global.shared::cta.bulk_group [%0, {%2, %3}], [%1];" :: "l"(&tm_t), "r"(sm + OFF_STAGE), "r"(cm), "r"(0) : "memory");
            if (nw > 8) asm volatile("cp.async.bulk.tensor.2d.global.shared::cta.bulk_group [%0, {%2, %3}], [%1];" :: "l"(&tm_tx), "r"(sm + OFF_STX), "r"(cx), "r"(0) : "memory");
            asm volatile("cp.async.bulk.commit_group;" ::: "memory");
            asm volatile("cp.async.bulk.wait_group.read 0;" ::: "memory");
        }
        __syncwarp();
    }

    if (warp >= 10) { mbar_wait(bars + 8 * BAR_ROLE, 0); role = __shfl_sync(~0u, lds32(sm + OFF_MISC), 0); fence_async_s(); }
    auto first_a = [&]() {
        if (warp >= 10 && role < 64 && elect()) {
            const int it = warp - 10, hi = it >= 3; const bool p2 = it - 3 * hi == 2;
            tma4(sm + OFF_A + it * A_BYTES, p2 ? &tm_w1b : &tm_w1a, 0, 0, p2 ? 64 * rank + 8 * hi : 4 * (it - hi),
                 9 * (role >> 3) + (p2 ? 8 : (role & 4) + 2 * rank), bars + 8 * (BAR_FULL + it));
        }
        __syncwarp();
    };
    if (!rowcta) first_a();
    else {
        uint32_t tc[QC * 4];
        mbar_wait(bars + 8 * BAR_TAB2, 0);
        load_tab<QC>(tc, sm + OFF_TAB + (QA + QB) * 512 + lane * 16);
        if (warp < 10) {
            uint32_t b3[16];
            load_tab<4>(b3, sm + OFF_B3 + 2048 + lane * 16);
            uint4 V[4], o[4];
            const bool tact = warp < 9 || g == 0;
            spin_until(t_st + X2D);
            #pragma unroll
            for (int u = 0; u < 4; u++) V[u] = make_uint4(tact, 0, 0, 0);
            for (int it = 0; __any_sync(~0u, (V[0].x | V[1].x | V[2].x | V[3].x) & 1u); it++) {
                #pragma unroll
                for (int u = 0; u < 4; u++) if (V[u].x & 1u) V[u] = ldx128(tptr + u * tstr);
                hb();
                if (it > SPIN_LIMIT) __trap();
            }
            PROF0(10);
            radix16(V, b3, o);
            if (tact) {
                #pragma unroll
                for (int nt = 0; nt < 4; nt++) sts128(scol + nt * (16 * SPEC_P), o[nt]);
            }
        }
        __syncthreads();
        PROF0(11);
        first_a();
        const uint32_t srow = sm + OFF_SPEC + warp * (SPEC_P * 4);
        uint32_t re[2][3], im[2][3];
        #pragma unroll
        for (int mt = 0; mt < 3; mt++) {
            const uint32_t a = srow + (g + 72 * q + 8 * mt) * 4, a2 = srow + (288 - g - 72 * q - 8 * mt) * 4;
            const uint32_t z0 = lds32(a), z1 = lds32(a + 144), z2 = lds32(a2), z3 = lds32(a2 - 144);
            #pragma unroll
            for (int m2 = 0; m2 < 2; m2++) {
                re[m2][mt] = 0; im[m2][mt] = 0;
                const uint32_t sg = m2 ? 0x3C00BC00u : 0xBC003C00u;
                mma_h(re[m2][mt], im[m2][mt], tc[m2 * 4], tc[m2 * 4 + 1], tc[m2 * 4 + 2], tc[m2 * 4 + 3], hfma2(z2, sg, z0), hfma2(z3, sg, z1));
                cmul_pos(re[m2][mt], im[m2][mt], tc[8 + (m2 * 3 + mt) * 2], tc[9 + (m2 * 3 + mt) * 2]);
            }
        }
        uint32_t md[28];
        mbar_wait(bars + 8 * BAR_NC, 0);
        load_tab<7>(md, sm + OFF_MODC + lane * 16);
        float y[5][4];
        #pragma unroll
        for (int nt = 0; nt < 5; nt++) {
            y[nt][0] = y[nt][1] = y[nt][2] = y[nt][3] = 0.f;
            #pragma unroll
            for (int mt = 0; mt < 3; mt++)
                mma_f(y[nt], re[0][mt], re[1][mt], im[0][mt], im[1][mt], tc[20 + (mt * 5 + nt) * 2], tc[21 + (mt * 5 + nt) * 2]);
        }
        #pragma unroll
        for (int i = 0; i < 9; i++) xw[i] = bfma2(md[i], pack_bf(y[i >> 1][i & 1], y[i >> 1][2 + (i & 1)]), xw[i]);
        float r, mr;
        ln_stats(xw, g, q, r, mr);
        uint32_t h[9], r2 = pack_bf(r, r), m2 = pack_bf(mr, mr);
        #pragma unroll
        for (int i = 0; i < 9; i++) h[i] = bfma2(bfma2(xw[i], r2, m2), md[18 + i], md[9 + i]);
        ln_stats(h, g, q, r, mr);
        r2 = pack_bf(r, r); m2 = pack_bf(mr, mr);
        {
            const int n7 = 2 * q + (g >> 2);
            const uint32_t a = sm + OFF_STAGE + (warp >> 3) * 9216 + n7 * 128 + ((warp & 7) ^ n7) * 16 + (g & 3) * 4;
            #pragma unroll
            for (int i = 0; i < 9; i++) sts32(a + i * 1024, bfma2(h[i], r2, m2));
        }
        fence_async_s();
        __syncthreads();
        PROF0(12);
        if (tid == 0) {
            asm volatile("cp.async.bulk.tensor.4d.global.shared::cta.bulk_group [%0, {%2, %2, %2, %3}], [%1];" :: "l"(&tm_h3s), "r"(sm + OFF_STAGE), "r"(0), "r"(b) : "memory");
            asm volatile("cp.async.bulk.commit_group;" ::: "memory");
        }
        #pragma unroll
        for (int i = 0; i < 9; i++) sts32(sm + OFF_X1 + warp * 1152 + (32 * i + 8 * q + g) * 4, xw[i]);
    }
    __syncthreads();
    if (rowcta) {
        if (tid == 0) { asm volatile("cp.async.bulk.wait_group 0;" ::: "memory"); fence_async_g(); red_release(g_cnt + CNT_H3 * 32); }
        PROF0(13);
        if (warp == 15) {
            __nanosleep(X1DELAY);
            #pragma unroll 1
            for (int r = 0; r < 16; r++) {
                uint4* dst = (uint4*)(p.out + (size_t)(b + 128 * r) * D_) + lane;
                const uint32_t src = sm + OFF_X1 + r * 1152 + lane * 16;
                dst[0] = lds128(src); dst[32] = lds128(src + 512); if (lane < 8) dst[64] = lds128(src + 1024);
                const uint32_t t1 = clk32(); while ((int)(clk32() - t1) < X1PACE) __nanosleep(50);
            }
            __syncwarp();
            if (lane == 0) { fence_async_g(); red_release(g_cnt + CNT_X1 * 32); }
        }
    }
    role = __shfl_sync(~0u, lds32(sm + OFF_MISC), 0);
    if (role >= 64) { if (warp == 0) PROFDUMP(); return; }

    const int gi = role >> 3, dt = role & 3, c2 = (role >> 2) & 1;
    const int wg = warp >> 2, wi = warp & 3;
    if (wg == 3) {
        uint32_t so = 0, eph = 1;
        #define RING_STEP(BYTES, OFF, ISSUE) do { \
            mbar_wait(bars + 8 * BAR_EMPTY + so, eph); \
            if (elect()) { const uint32_t fb = bars + 8 * BAR_FULL + so, dst = sm + (OFF) + so * ((BYTES) / 8); mbar_expect(fb, BYTES); ISSUE; } \
            so += 8; if (so == 8 * NST) { so = 0; eph ^= 1; } } while (0)
        if (warp == 12) {
            eph = 0;
            const int fb1 = 9 * gi + 4 * c2 + 2 * rank, sb2 = 4 * gi + 2 * c2;
            #pragma unroll 1
            for (int j = 16; j < 128; j += 4) {
                RING_STEP(A_BYTES, OFF_A, tma4(dst, &tm_w1a, 0, 0, j, fb1, fb));
                if (j < 64) { if (j & 4) RING_STEP(A_BYTES, OFF_A, tma4(dst, &tm_w1b, 0, 0, 64 * rank + j - 4, 9 * gi + 8, fb)); }
                else if (PF2 && (j & 28) == 4 * (role & 7) && elect())
                    asm volatile("cp.async.bulk.prefetch.tensor.3d.L2.global [%0, {%1, %2, %3}];" :: "l"(&tm_w2), "r"(0), "r"(64 * g2_kb(dt + ((j >> 3) & 4), rank)), "r"(sb2) : "memory");
            }
            #pragma unroll 1
            for (int n = 0; n < 36; n++) {
                if (n == G2E) mbar_wait(bars + 8 * BAR_REL, 0);
                if (n == A2E) { mbar_wait(bars + 8 * (BAR_UOK + 1), 0); if (A2D) spin_until(clk32() + A2D); }
                RING_STEP(A_BYTES, OFF_A, tma3(dst, &tm_w2, 0, 64 * g2_kb(n, rank), sb2, fb));
            }
        } else if (warp == 13) {
            const uint32_t e1 = __shfl_sync(~0u, epoch + 1, 0);
            fence_async_s();
            wait_count<0>(g_cnt + CNT_H3 * 32, e1 * 128);
            fence_async_g();
            if (lane == 0) PROFT(14);
            #pragma unroll 1
            for (int j = 0; j < 128; j += 4) {
                RING_STEP(B_BYTES, OFF_B, tma3(dst, &tm_h3a, 0, 18 * dt, j, fb));
                if (j < 64 && (j & 4)) RING_STEP(B_BYTES, OFF_B, tma3(dst, &tm_h3b, 0, 18 * dt + 9 * c2, 64 * rank + j - 4, fb));
            }
            int n = 0;
            #pragma unroll 1
            for (int cls = 0; cls < 3; cls++) {
                mbar_wait(bars + 8 * (BAR_UOK + cls), 0);
                fence_async_g();
                if (cls == 1 && lane == 0) PROFT(19);
                if (cls == 0 && lane == 0) PROFT(22);
                #pragma unroll 1
                for (; n < 16 * cls + 4; n++) {
                    if (n == G2E) mbar_wait(bars + 8 * BAR_REL, 0);
                    RING_STEP(B_BYTES, OFF_B, bulk_load(dst, g_U + (g2_kb(n, rank) * 4 + dt) * 1152, B_BYTES, fb));
                }
            }
            if (role == 0 && rank == 0 && lane == 0) st_relaxed(g_cnt + CNT_EPOCH * 32, e1);
        } else if (warp == 15) {
            if (elect()) mbar_arrive_remote(mapa(bars + 8 * BAR_HOLD, rank ^ 1));
            __syncwarp();
            bar_sync(6, 160);
            mbar_wait(bars + 8 * BAR_W1GO, 0);
            if (elect()) {
                char* dst = (char*)(g_U + ((9 * gi + 4 * c2 + 2 * rank + 1) * 4 + dt) * 1152);
                #pragma unroll 1
                for (int i = 0; i < W1N; i++) {
                    asm volatile("cp.async.bulk.global.shared::cta.bulk_group [%0], [%1], %2;" :: "l"(dst + i * (18432 / W1N)), "r"(sm + OFF_X1 + i * (18432 / W1N)), "n"(18432 / W1N) : "memory");
                    const uint32_t t1 = clk32(); while ((int)(clk32() - t1) < W1P) {}
                }
                asm volatile("cp.async.bulk.commit_group;" ::: "memory");
                asm volatile("cp.async.bulk.wait_group 0;" ::: "memory");
                fence_async_g(); red_release(g_cnt + (CNT_U + 16) * 32);
                #pragma unroll 1
                for (int n = 0; n < 4; n++) { __nanosleep(300); tma2(sm + OFF_X1 + n * 4608, &tm_o, 144 * dt, 256 * gi + 128 * c2 + 64 * (rank ^ 1) + 16 * n, bars + 8 * BAR_XT); }
            }
        } else {
            const uint32_t e1 = epoch + 1;
            if (lane == 0) {
                __nanosleep(4000);
                wait_count<200>(g_cnt + CNT_NC * 32, e1 * 4); wait_count<200>(g_cnt + (CNT_NC + 1) * 32, e1 * 2);
                fence_async_g();
                mbar_expect(bars + 8 * BAR_GB, 1152);
                bulk_load(sm + OFF_GB, p.scr->modc + 896, 1152, bars + 8 * BAR_GB);
                wait_count<200>(g_cnt + CNT_X1 * 32, e1 * 128);
                wait_count<50>(g_cnt + (CNT_U + dt * 2 + rank) * 32, e1 * 16);
                mbar_arrive(bars + 8 * BAR_UOK);
            }
            __syncwarp();
            bar_sync(4, 160);
            if (lane == 0) {
                fence_async_g(); red_release(g_cnt + (CNT_U + 8) * 32);
                mbar_arrive(bars + 8 * BAR_REL);
                PROFT(17);
                wait_count<0>(g_cnt + (CNT_U + 8) * 32, e1 * 128);
                mbar_arrive(bars + 8 * (BAR_UOK + 1));
                __nanosleep(1000);
                wait_count<100>(g_cnt + (CNT_U + 16) * 32, e1 * 128);
                mbar_arrive(bars + 8 * (BAR_UOK + 2));
            }
        }
    } else if (wg == 2) {
        float d0[36];
        const float bias = bf_lo(ldg_nc16(p.b1 + 576 * gi + 512 + 16 * wi + g + 8 * rank));
        for (int it = 0; it < 200 && !__any_sync(~0u, mbar_test(bars + 8 * BAR_FULL, 0)); it++) { hb(); __nanosleep(100); }
        const bool lead = wi == 0 && elect();
        #pragma unroll 1
        for (int i = 0; i < 8; i++) {
            const uint32_t s = P2S + 3 * (i & 1);
            mbar_wait(bars + 8 * BAR_FULL + 8 * s, (i >> 1) & 1);
            const uint32_t da = desc_lo(sm + OFF_A, 8192) + s * (A_BYTES / 16), db = desc_lo(sm + OFF_B, 128) + s * (B_BYTES / 16);
            WG_FENCE();
            wgmma72(d0, da, db, i);
            #pragma unroll
            for (int k = 1; k < 8; k++) wgmma72(d0, da + k * 128, db + k * 144, 1);
            WG_COMMIT();
            WG_WAIT(0);
            if (lead) mbar_arrive_n(bars + 8 * BAR_EMPTY + 8 * s, 2);
        }
        if (lead) PROFT(18);
        const uint32_t slot = sm + OFF_P2R + (tid & 127) * 16, ra = mapa(slot, rank ^ 1), rb = mapa(bars + 8 * BAR_P2R, rank ^ 1);
        float sv[18];
        #pragma unroll
        for (int i = 0; i < 18; i++) { const float lo = d0[4 * (i >> 1) + (i & 1)], hi = d0[4 * (i >> 1) + 2 + (i & 1)];
            sv[i] = rank ? lo : hi; d0[4 * (i >> 1) + (i & 1)] = (rank ? hi : lo) + bias; }
        mbar_wait(bars + 8 * BAR_HOLD, 0);
        #pragma unroll
        for (int i = 0; i < 4; i++)
            asm volatile("st.async.weak.shared::cluster.mbarrier::complete_tx::bytes.v4.f32 [%0], {%1,%2,%3,%4}, [%5];"
                :: "r"(ra + i * 2048), "f"(sv[4 * i]), "f"(sv[4 * i + 1]), "f"(sv[4 * i + 2]), "f"(sv[4 * i + 3]), "r"(rb) : "memory");
        asm volatile("st.async.weak.shared::cluster.mbarrier::complete_tx::bytes.v2.f32 [%0], {%1,%2}, [%3];" :: "r"(ra + 8192), "f"(sv[16]), "f"(sv[17]), "r"(rb) : "memory");
        mbar_wait(bars + 8 * BAR_P2R, 0);
        #pragma unroll
        for (int i = 0; i < 5; i++) {
            const uint4 v = lds128(slot + i * 2048);
            d0[8 * i] += __uint_as_float(v.x); d0[8 * i + 1] += __uint_as_float(v.y);
            if (i < 4) { d0[8 * i + 4] += __uint_as_float(v.z); d0[8 * i + 5] += __uint_as_float(v.w); }
        }
        asm volatile("bar.arrive 5, 256;" ::: "memory");
        gelu_store<0>(d0, (char*)(g_U + ((9 * gi + 8) * 4 + dt) * 1152) + wi * 4608 + rank * 2304 + c2 * 1152 + g * 16, q);
        bar_sync(8, 128);
        if (lead) { fence_async_g(); red_release(g_cnt + (CNT_U + dt * 2 + (gi >> 2)) * 32); PROFT(26); }
    } else {
        float d[72];
        const bool lead = wi == 0 && elect();
        const uint32_t da0 = desc_lo(sm + OFF_A + wg * 8192, 8192);
        const bool owner = (uint32_t)wg == rank;
        const int srow = 256 * gi + 128 * c2 + 64 * wg + 16 * wi;
        const uint32_t b2w0 = ldg_nc16(p.b2 + srow + g), b2w1 = ldg_nc16(p.b2 + srow + g + 8);
        {
            const int fr = 576 * gi + 256 * c2 + 128 * rank + 64 * wg + 16 * wi + g;
            const float bias0 = bf_lo(ldg_nc16(p.b1 + fr)), bias1 = bf_lo(ldg_nc16(p.b1 + fr + 8));
            #pragma unroll
            for (int i = 0; i < 72; i++) d[i] = (i & 2) ? bias1 : bias0;
            const uint32_t db1 = desc_lo(sm + OFF_B, 128);
            mainloop<DHI_H3, 0, IT_P1, false, true, false>(d, bars, da0, db1, lead, [&](int) {});
            mainloop<DHI_H3, IT_P1, IT_G2 - LEAD1, false, false, false>(d, bars, da0, db1, lead, [&](int) {});
            constexpr uint32_t EB = 8 * (BAR_EMPTY + (IT_G2 - LEAD1 - 1) % NST);
            if (wg == 1) { WG_WAIT(0); if (lead) mbar_arrive(bars + EB); bar_sync(9, 256); }
            mainloop<DHI_H3, IT_G2 - LEAD1, IT_G2, false, true, true>(d, bars, da0, db1, lead, [&](int i) {
                if (wg == 0) { if (i == IT_G2 - LEAD1 && lead) mbar_arrive(bars + EB); if (i == IT_G2 - 1) asm volatile("bar.arrive 9, 256;" ::: "memory"); } });
            PROF0(16);
            if (wg == 1) bar_sync(5, 256);
            char* const ub = (wg == 0 ? (char*)(g_U + ((9 * gi + 4 * c2 + 2 * rank) * 4 + dt) * 1152) : (char*)__cvta_shared_to_generic(sm + OFF_X1)) + wi * 4608 + g * 16;
            gelu_store<0>(d, ub, q); gelu_store<2>(d, ub + 2304, q); gelu_store<36>(d, ub + 1152, q); gelu_store<38>(d, ub + 3456, q);
            PROF0(27);
            if (wg == 0) asm volatile("bar.arrive 4, 160;" ::: "memory");
            else { fence_async_s(); asm volatile("bar.arrive 6, 160;" ::: "memory"); }
        }
        const uint32_t db0 = desc_lo(sm + OFF_B, 2304);
        constexpr int IT_L = IT_END - NST, IT_X = IT_L - 4;
        mainloop<DHI_U, IT_G2, IT_X, true, true, false>(d, bars, da0, db0, lead,
            [&](int i) { if (i == IT_G2 + W1S && wg == 0 && lead) mbar_arrive(bars + 8 * BAR_W1GO); });
        const uint32_t ga0 = sm + OFF_GB + (144 * dt + 8 * q) * 2, tile = sm + OFF_X1 + wi * 4608, to = g * 288 + q * 16;
        #define QOFF(i_) (((i_) >> 2) * 2304 + 144 * (((i_) >> 1) & 1) + 64 * ((i_) & 1))
        #define SOFF(k_) (((k_) >> 1) * 2304 + 144 * ((k_) & 1) + 128 - 12 * q)
        #define DIDX(i_, k_) ((i_) < 8 ? 36 * (((i_) >> 1) & 1) + 16 * ((i_) & 1) + 4 * (k_) + 2 * ((i_) >> 2) : 36 * ((k_) & 1) + 32 + 2 * ((k_) >> 1))
        #define FIN(k_, f_) bfma2(g4.f_, pack_bf(d[DIDX(i, k_)], d[DIDX(i, k_) + 1]), xq[i].f_)
        uint4 xq[9];
        auto load_g = [&](int i) { uint4 r; if (i < 4) r = lds128(ga0 + QOFF(i)); else { r.x = r.z = lds32(ga0 + SOFF(0)); r.y = r.w = lds32(ga0 + SOFF(1)); } return r; };
        mainloop<DHI_U, IT_X, IT_L, false, false, false>(d, bars, da0, db0, lead, [&](int i) {
            if (!owner) {
                const uint32_t xa = tile + to;
                if (i == IT_X) { mbar_wait(bars + 8 * BAR_XT, 0); xq[0] = lds128(xa + QOFF(0)); xq[4] = lds128(xa + QOFF(4)); xq[1] = lds128(xa + QOFF(1)); }
                else if (i == IT_X + 1) { xq[5] = lds128(xa + QOFF(5)); xq[2] = lds128(xa + QOFF(2)); xq[6] = lds128(xa + QOFF(6)); }
                else if (i == IT_X + 2) { xq[3] = lds128(xa + QOFF(3)); xq[7] = lds128(xa + QOFF(7));
                    xq[8] = make_uint4(lds32(xa + SOFF(0)), lds32(xa + SOFF(1)), lds32(xa + SOFF(2)), lds32(xa + SOFF(3))); }
                else if (i == IT_X + 3) { if (elect()) mbar_arrive_remote(mapa(bars + 8 * BAR_DONE, rank ^ 1)); }
            } });
        if (owner) { WG_WAIT(0); if (lead) mbar_arrive(bars + 8 * (BAR_EMPTY + (IT_L - 1) % NST)); bar_sync(7, 256); }
        #pragma unroll
        for (int i = IT_L; i < IT_END; i++) {
            mbar_wait(bars + 8 * (BAR_FULL + i % NST), (i / NST) & 1);
            WG_FENCE();
            #pragma unroll
            for (int k = 0; k < 4; k++) wgmma144<DHI_U>(d, da0 + (i % NST) * (A_BYTES / 16) + k * 128, db0 + (i % NST) * (B_BYTES / 16) + k * 288, 1);
            WG_COMMIT();
            if (i == IT_L) { WG_WAIT(1); if (lead && !owner) mbar_arrive(bars + 8 * (BAR_EMPTY + (IT_L - 1) % NST)); }
        }
        PROF0(9);
        mbar_wait(bars + 8 * BAR_GB, 0);
        if (!owner) {
            const uint32_t ra = mapa(tile + lane * 16, rank ^ 1), rb = mapa(bars + 8 * BAR_RECV, rank ^ 1);
            mbar_wait(bars + 8 * BAR_DONE, 0);
            uint4 gn = load_g(0);
            WG_WAIT(1);
            asm volatile("bar.arrive 7, 256;" ::: "memory");
            WG_WAIT(0);
            #pragma unroll
            for (int i = 0; i < 72; i++) d[i] = fmaf(bf_lo((i & 2) ? b2w1 : b2w0), 2.f, d[i]);
            #pragma unroll
            for (int j = 0; j < 5; j++) {
                const uint4 g4 = gn;
                if (j < 4) gn = load_g(j + 1);
                #pragma unroll
                for (int i = j < 4 ? j : 8; i < 9; i += 4) if (i < 8 || j == 4)
                    asm volatile("st.async.weak.shared::cluster.mbarrier::complete_tx::bytes.v4.b32 [%0], {%1,%2,%3,%4}, [%5];"
                        :: "r"(ra + i * 512), "r"(FIN(0, x)), "r"(FIN(1, y)), "r"(FIN(2, z)), "r"(FIN(3, w)), "r"(rb) : "memory");
            }
            PROF0(6);
            if (warp == 0) PROFDUMP();
            return;
        }
        PROF0(24);
        mbar_wait(bars + 8 * BAR_RECV, 0);
        #pragma unroll
        for (int i = 0; i < 9; i++) xq[i] = lds128(tile + lane * 16 + i * 512);
        uint4 gn = load_g(0);
        WG_WAIT(0);
        __syncwarp();
        PROF0(21);
        #pragma unroll
        for (int j = 0; j < 5; j++) {
            const uint4 g4 = gn;
            if (j < 4) gn = load_g(j + 1);
            #pragma unroll
            for (int i = j < 4 ? j : 8; i < 9; i += 4) if (i < 8 || j == 4) {
                const uint4 o = make_uint4(FIN(0, x), FIN(1, y), FIN(2, z), FIN(3, w));
                if (i < 8) sts128(tile + to + QOFF(i), o);
                else { sts32(tile + to + SOFF(0), o.x); sts32(tile + to + SOFF(1), o.y); sts32(tile + to + SOFF(2), o.z); sts32(tile + to + SOFF(3), o.w); }
            }
        }
        fence_async_s();
        __syncwarp();
        if (elect()) {
            asm volatile("cp.async.bulk.tensor.2d.global.shared::cta.bulk_group [%0, {%2, %3}], [%1];" :: "l"(&tm_o), "r"(tile), "r"(144 * dt), "r"(srow) : "memory");
            asm volatile("cp.async.bulk.commit_group;" ::: "memory");
            asm volatile("cp.async.bulk.wait_group.read 0;" ::: "memory");
        }
        PROF0(23);
        if (warp == 0) { __syncwarp(); PROFDUMP(); }
    }
}

typedef CUresult (*EncodeFn)(CUtensorMap*, CUtensorMapDataType, cuuint32_t, void*, const cuuint64_t*, const cuuint64_t*, const cuuint32_t*,
                             const cuuint32_t*, CUtensorMapInterleave, CUtensorMapSwizzle, CUtensorMapL2promotion, CUtensorMapFloatOOBfill);

void encode(EncodeFn fn, CUtensorMap* m, CUtensorMapDataType dt, int rank, const void* ptr, const cuuint64_t* dims, const cuuint64_t* strides,
            const cuuint32_t* box, CUtensorMapSwizzle sw, CUtensorMapL2promotion promo = CU_TENSOR_MAP_L2_PROMOTION_L2_128B) {
    const cuuint32_t es[5] = {1, 1, 1, 1, 1};
    fn(m, dt, rank, (void*)ptr, dims, strides, box, es, CU_TENSOR_MAP_INTERLEAVE_NONE, sw, promo, CU_TENSOR_MAP_FLOAT_OOB_FILL_NONE);
}

}

extern "C" void kernel_launch(void* const* d_in, const int* in_sizes, int n_in, void* d_out, int out_size) {
    (void)in_sizes; (void)n_in; (void)out_size;
    Params p;
    p.x = (const uint16_t*)d_in[0]; p.wr = (const uint16_t*)d_in[1]; p.wi = (const uint16_t*)d_in[2];
    p.w1 = (const uint16_t*)d_in[4]; p.b1 = (const uint16_t*)d_in[5]; p.w2 = (const uint16_t*)d_in[6]; p.b2 = (const uint16_t*)d_in[7];
    p.c = (const uint16_t*)d_in[8]; p.wmod = (const uint16_t*)d_in[9]; p.out = (uint16_t*)d_out;

    void* fnp = nullptr; cudaDriverEntryPointQueryResult qr;
    cudaGetDriverEntryPoint("cuTensorMapEncodeTiled", &fnp, cudaEnableDefault, &qr);
    EncodeFn fn = (EncodeFn)fnp;
    cudaGetSymbolAddress((void**)&p.scr, g_scr); cudaGetSymbolAddress((void**)&p.tab, g_tab);
    void* h3p = p.scr->h3;
    CUtensorMap tw1a, tw1b, tw2, th3a, th3b, twr, twi, twm, tt, ttx, to, th3s;
    {
        const cuuint64_t dims[4] = {64, 16, 128, 72}, st[3] = {128ull * F_ * 2, (cuuint64_t)F_ * 2, 128};
        const cuuint32_t ba[4] = {64, 16, 4, 2}, bb[4] = {64, 16, 8, 1};
        encode(fn, &tw1a, CU_TENSOR_MAP_DATA_TYPE_BFLOAT16, 4, p.w1, dims, st, ba, CU_TENSOR_MAP_SWIZZLE_128B);
        encode(fn, &tw1b, CU_TENSOR_MAP_DATA_TYPE_BFLOAT16, 4, p.w1, dims, st, bb, CU_TENSOR_MAP_SWIZZLE_128B);
    }
    {
        const cuuint64_t dims[3] = {64, F_, 32}, st[2] = {(cuuint64_t)S_ * 2, 128};
        const cuuint32_t bx[3] = {64, 64, 2};
        encode(fn, &tw2, CU_TENSOR_MAP_DATA_TYPE_BFLOAT16, 3, p.w2, dims, st, bx, CU_TENSOR_MAP_SWIZZLE_128B);
    }
    {
        const cuuint64_t dims[3] = {64, 72, 128}, st[2] = {256, 18432};
        const cuuint32_t ba[3] = {64, 18, 4}, bb[3] = {64, 9, 8};
        encode(fn, &th3a, CU_TENSOR_MAP_DATA_TYPE_UINT32, 3, h3p, dims, st, ba, CU_TENSOR_MAP_SWIZZLE_NONE);
        encode(fn, &th3b, CU_TENSOR_MAP_DATA_TYPE_UINT32, 3, h3p, dims, st, bb, CU_TENSOR_MAP_SWIZZLE_NONE);
    }
    {
        const cuuint64_t dims[4] = {32, 72, 2, 128}, st[3] = {256, 128, 18432};
        const cuuint32_t bx[4] = {32, 72, 2, 1};
        encode(fn, &th3s, CU_TENSOR_MAP_DATA_TYPE_UINT32, 4, h3p, dims, st, bx, CU_TENSOR_MAP_SWIZZLE_128B, CU_TENSOR_MAP_L2_PROMOTION_NONE);
    }
    {
        const cuuint64_t dims[3] = {4624, 4, 32}, st[2] = {9248 * 32, 9248};
        const cuuint32_t bx[3] = {56, 4, 32};
        encode(fn, &twr, CU_TENSOR_MAP_DATA_TYPE_BFLOAT16, 3, p.wr, dims, st, bx, CU_TENSOR_MAP_SWIZZLE_NONE);
        encode(fn, &twi, CU_TENSOR_MAP_DATA_TYPE_BFLOAT16, 3, p.wi, dims, st, bx, CU_TENSOR_MAP_SWIZZLE_NONE);
    }
    {
        const cuuint64_t dims[3] = {64, 576, 54}, st[2] = {6912, 128};
        const cuuint32_t bx[3] = {64, 32, 7};
        encode(fn, &twm, CU_TENSOR_MAP_DATA_TYPE_BFLOAT16, 3, p.wmod, dims, st, bx, CU_TENSOR_MAP_SWIZZLE_128B);
    }
    {
        const cuuint64_t dims[2] = {TP, 128}, st[1] = {TP * 4};
        const cuuint32_t ba[2] = {32, 128}, bb[2] = {8, 128};
        encode(fn, &tt, CU_TENSOR_MAP_DATA_TYPE_UINT32, 2, p.scr->T, dims, st, ba, CU_TENSOR_MAP_SWIZZLE_128B, CU_TENSOR_MAP_L2_PROMOTION_NONE);
        encode(fn, &ttx, CU_TENSOR_MAP_DATA_TYPE_UINT32, 2, p.scr->T, dims, st, bb, CU_TENSOR_MAP_SWIZZLE_32B, CU_TENSOR_MAP_L2_PROMOTION_NONE);
    }
    {
        const cuuint64_t dims[2] = {D_, S_}, st[1] = {D_ * 2};
        const cuuint32_t bx[2] = {144, 16};
        encode(fn, &to, CU_TENSOR_MAP_DATA_TYPE_BFLOAT16, 2, p.out, dims, st, bx, CU_TENSOR_MAP_SWIZZLE_NONE, CU_TENSOR_MAP_L2_PROMOTION_NONE);
    }
    cudaFuncSetAttribute(fused_kernel, cudaFuncAttributeMaxDynamicSharedMemorySize, SMEM_BYTES);
    cudaLaunchConfig_t cfg = {};
    cfg.gridDim = dim3(NCTA); cfg.blockDim = dim3(NTHR); cfg.dynamicSmemBytes = SMEM_BYTES; cfg.stream = cudaStreamPerThread;
    cudaLaunchAttribute at[1];
    at[0].id = cudaLaunchAttributeCooperative; at[0].val.cooperative = 1;
    cfg.attrs = at; cfg.numAttrs = 1;
    cudaLaunchKernelEx(&cfg, fused_kernel, p, tw1a, tw1b, tw2, th3a, th3b, twr, twi, twm, tt, ttx, to, th3s);
}
```

```cpp
#include <cuda_runtime.h>
#include <cuda_bf16.h>
#include <cuda_fp16.h>
#include <cuda.h>
#include <stdint.h>

namespace {

constexpr int S_ = 2048, D_ = 576, F_ = 4608;
constexpr int NCTA = 132, NTHR = 512;
constexpr int TP = 4736;
constexpr int SPEC_P = 296;
constexpr int NST = 6;
constexpr int A_BYTES = 16384, B_BYTES = 18432;
constexpr int IT_P1 = 24, IT_G2 = 40, IT_END = 76;
constexpr int SPIN_LIMIT = 1 << 22;
#define MODP 1
#define X2D 1450
constexpr int P2S = 2;
#define G2E 4
#define LEAD1 4
#define A2E 6
#define A2D 100
#define W1N 8
#define W1P 100
#define W1S 4
#define XDELAY 900
#define CRITPF 1
#define NCD 0
#define X1D 2300
#define PF2 1
#define X1DELAY 2000
#define X1PACE 400

constexpr int OFF_A = 0;
constexpr int OFF_B = NST * A_BYTES;
constexpr int OFF_P = OFF_B + NST * B_BYTES;
constexpr int OFF_BAR = OFF_P;
constexpr int OFF_MISC = OFF_P + 504;
constexpr int OFF_GB = OFF_P + 512;
constexpr int OFF_P2R = OFF_P + 1664;
constexpr int OFF_X1 = OFF_P2R;
constexpr int OFF_PROF = OFF_X1 + 18432;
constexpr int SMEM_BYTES = OFF_PROF + 512 + 1024;
constexpr int QA = 13, QB = 7, QC = 13;
constexpr int TAB_BYTES = (QA + QB + QC) * 512;
constexpr int OFF_STAGE = OFF_B;
constexpr int OFF_STX = OFF_STAGE + 16384;
constexpr int OFF_TAB = OFF_STAGE + 20480;
constexpr int OFF_SPEC = OFF_TAB + TAB_BYTES;
constexpr int OFF_WRAW = OFF_SPEC + 19072;
constexpr int OFF_B3 = OFF_WRAW + 28672;
constexpr int OFF_MODA = OFF_B3 + 4096;
constexpr int OFF_MODC = OFF_MODA + 2560;
constexpr int OFF_RED = OFF_MODC + 3584;
constexpr int OFF_SILU = OFF_RED + 1536;
static_assert(OFF_SILU + 1152 <= OFF_P && 6 * 28672 <= OFF_B3, "scratch overflow");
constexpr int OFF_STRIP = OFF_A;
static_assert(OFF_WRAW % 128 == 0 && OFF_STAGE % 128 == 0 && OFF_STX % 128 == 0, "align");
constexpr int BAR_FULL = 0, BAR_EMPTY = 6, BAR_TAB = 12, BAR_W = 13, BAR_REL = 14, BAR_P2R = 16,
              BAR_XT = 17, BAR_RECV = 18, BAR_ROLE = 19, BAR_NC = 20, BAR_TAB2 = 21, BAR_XB = 22, BAR_GB = 23, BAR_HOLD = 24, BAR_W1GO = 25, BAR_UOK = 26, BAR_DONE = 30, BAR_X = 31, BAR_ST = 47;

struct Cos1152 { double c[1152]; };
constexpr double cx_cos(double x) { double t = 1, s = 1; for (int i = 1; i < 14; i++) { t *= -x * x / ((2 * i - 1) * (2 * i)); s += t; } return s; }
constexpr Cos1152 make_cos() {
    Cos1152 r{};
    for (int i = 0; i <= 288; i++) {
        double v = (i == 288) ? 0.0 : cx_cos(3.14159265358979323846 * 2.0 * i / 1152.0);
        r.c[i] = v; r.c[576 - i] = -v; r.c[576 + i] = -v; r.c[(1152 - i) % 1152] = v;
    }
    return r;
}
constexpr uint32_t cx_f2h(double v) {
    uint32_t s = v < 0 ? 0x8000u : 0u; double a = v < 0 ? -v : v;
    if (a < 1e-9) return 0;
    int e = 0;
    while (a >= 2.0) { a *= 0.5; e++; }
    while (a < 1.0 && e > -14) { a *= 2.0; e--; }
    double m = a * 1024.0; uint32_t mi = (uint32_t)m; double fr = m - mi;
    if (fr > 0.5 || (fr == 0.5 && (mi & 1))) mi++;
    return s | (uint32_t)(((e + 14) << 10) + mi);
}
struct Tab { uint32_t w[(QA + QB + QC) * 128]; };
constexpr Tab make_tab() {
    Tab t{};
    Cos1152 ct = make_cos();
    auto C = [&](int num, int den) { return ct.c[(num % den) * (1152 / den)]; };
    auto Sn = [&](int num, int den) { return ct.c[((num % den) * (1152 / den) + 864) % 1152]; };
    auto put = [&](int q0, int idx, int lane, double lo, double hi) { t.w[((q0 + idx / 4) * 32 + lane) * 4 + idx % 4] = cx_f2h(lo) | (cx_f2h(hi) << 16); };
    for (int lane = 0; lane < 32; lane++) {
        const int g = lane >> 2, q = lane & 3;
        for (int mt = 0; mt < 3; mt++) {
            const int ka = 8 * mt + g;
            for (int r = 0; r < 10; r++) {
                const int im = r & 1, i0 = (r >> 1) * 2;
                double v[2] = {0, 0};
                for (int e = 0; e < 2; e++) { int i = i0 + e, d1 = 4 * i + q; if (i < 9 && ka <= 18) v[e] = (im ? -Sn(ka * d1, 36) : C(ka * d1, 36)) / 8; }
                put(0, mt * 10 + r, lane, v[0], v[1]);
            }
            for (int v = 0; v < 2; v++) {
                const int d2 = 4 * q + v;
                put(0, 30 + (mt * 2 + v) * 2, lane, C(ka * d2, 576) * 4 / 3, C(ka * (d2 + 2), 576) * 4 / 3);
                put(0, 31 + (mt * 2 + v) * 2, lane, Sn(ka * d2, 576) * 4 / 3, Sn(ka * (d2 + 2), 576) * 4 / 3);
            }
        }
        for (int v = 0; v < 2; v++) for (int nt = 0; nt < 2; nt++) {
            const int kb = 2 * (g >> 1) + nt, part = g & 1;
            double b0[2] = {0, 0}, b1[2] = {0, 0};
            for (int e = 0; e < 2; e++) { int d2 = 4 * q + 2 * e + v; double c = C(kb * d2, 16) / 4, s = Sn(kb * d2, 16) / 4;
                b0[e] = part ? -s : c; b1[e] = part ? c : s; }
            put(0, 42 + (v * 2 + nt) * 2, lane, b0[0], b0[1]); put(0, 43 + (v * 2 + nt) * 2, lane, b1[0], b1[1]);
        }
        for (int par = 0; par < 2; par++) for (int a = 0; a < 4; a++) {
            const int ja = 2 * (q + 4 * (a >> 1)) + par; const double c = C(g * ja, 16) / 4, s = Sn(g * ja, 16) / 4;
            put(QA, par * 4 + a, lane, (a & 1) ? -s : c, (a & 1) ? c : s);
        }
        for (int h = 0; h < 2; h++) {
            put(QA, 8 + 2 * h, lane, C((g + 8 * h) * (2 * q), 128) / 2, C((g + 8 * h) * (2 * q + 1), 128) / 2);
            put(QA, 9 + 2 * h, lane, Sn((g + 8 * h) * (2 * q), 128) / 2, Sn((g + 8 * h) * (2 * q + 1), 128) / 2);
            put(QA, 15 + 2 * h, lane, C(g * (8 * h + 2 * q), 128), C(g * (8 * h + 2 * q + 1), 128));
            put(QA, 16 + 2 * h, lane, Sn(g * (8 * h + 2 * q), 128), Sn(g * (8 * h + 2 * q + 1), 128));
        }
        put(QA, 12, lane, C(g * 2 * q, 8) / 2, C(g * (2 * q + 1), 8) / 2);
        put(QA, 13, lane, Sn(g * 2 * q, 8) / 2, Sn(g * (2 * q + 1), 8) / 2);
        put(QA, 14, lane, -Sn(g * 2 * q, 8) / 2, -Sn(g * (2 * q + 1), 8) / 2);
        for (int u = 0; u < 4; u++) {
            const int ja = 2 * ((g >> 1) + 4 * (u & 1)) + (u >> 1), part = g & 1; double b0[2] = {0, 0}, b1[2] = {0, 0};
            for (int e = 0; e < 2; e++) { int ka = 2 * q + e; double c = C(ja * ka, 16) / 4, s = Sn(ja * ka, 16) / 4;
                b0[e] = part ? s : c; b1[e] = part ? c : -s; }
            put(QA, 19 + u * 2, lane, b0[0], b0[1]); put(QA, 20 + u * 2, lane, b1[0], b1[1]);
        }
        for (int m2 = 0; m2 < 2; m2++) {
            const int d2 = 2 * g + m2;
            for (int a = 0; a < 4; a++) {
                const int kb = 2 * q + (a >> 1); const double c = C(d2 * kb, 16) / 4, s = Sn(d2 * kb, 16) / 4;
                put(QA + QB, m2 * 4 + a, lane, (a & 1) ? s : c, (a & 1) ? c : -s);
            }
            for (int mt = 0; mt < 3; mt++) {
                const int ka = 8 * mt + 2 * q;
                put(QA + QB, 8 + (m2 * 3 + mt) * 2, lane, C(ka * d2, 576) * 4 / 3, C((ka + 1) * d2, 576) * 4 / 3);
                put(QA + QB, 9 + (m2 * 3 + mt) * 2, lane, Sn(ka * d2, 576) * 4 / 3, Sn((ka + 1) * d2, 576) * 4 / 3);
            }
        }
        for (int mt = 0; mt < 3; mt++) for (int nt = 0; nt < 5; nt++) {
            const int i = 2 * nt + (g & 1), d1 = 4 * i + (g >> 1); double b0[2] = {0, 0}, b1[2] = {0, 0};
            for (int e = 0; e < 2; e++) { int ka = 8 * mt + 2 * q + e;
                if (ka <= 18 && i < 9) { double wt = (ka == 0 || ka == 18) ? 0.125 : 0.25; b0[e] = wt * C(ka * d1, 36); b1[e] = -wt * Sn(ka * d1, 36); } }
            put(QA + QB, 20 + (mt * 5 + nt) * 2, lane, b0[0], b0[1]); put(QA + QB, 21 + (mt * 5 + nt) * 2, lane, b1[0], b1[1]);
        }
    }
    return t;
}
__device__ __align__(128) const Tab g_tab = make_tab();

struct Scratch {
    uint32_t cnt[30 * 32];
    uint32_t slot[96];
    uint32_t mod[2304];
    uint32_t modc[896 + 288];
    uint32_t T[128 * TP];
    uint4 h3[128 * 1152];
    uint4 U[72 * 4 * 1152];
};
__device__ __align__(1024) Scratch g_scr;
#define g_cnt (p.scr->cnt)
#define g_slot (p.scr->slot)
#define g_mod (p.scr->mod)
#define g_T (p.scr->T)
#define g_h3 (p.scr->h3)
#define g_U (p.scr->U)
constexpr int CNT_EPOCH = 0, CNT_H3 = 1, CNT_X1 = 26, CNT_NC = 27, CNT_U = 2;
#define PROFT(i) do {} while (0)
#define PROFDUMP() do {} while (0)
#define PROF0(i) do {} while (0)

__device__ __forceinline__ void mbar_init(uint32_t bar, uint32_t cnt) { asm volatile("mbarrier.init.shared::cta.b64 [%0], %1;" :: "r"(bar), "r"(cnt) : "memory"); }
__device__ __forceinline__ void mbar_expect(uint32_t bar, uint32_t bytes) { asm volatile("mbarrier.arrive.expect_tx.shared::cta.b64 _, [%0], %1;" :: "r"(bar), "r"(bytes) : "memory"); }
__device__ __forceinline__ void mbar_arrive(uint32_t bar) { asm volatile("mbarrier.arrive.shared::cta.b64 _, [%0];" :: "r"(bar) : "memory"); }
__device__ __forceinline__ void mbar_arrive_n(uint32_t bar, uint32_t n) { asm volatile("mbarrier.arrive.shared::cta.b64 _, [%0], %1;" :: "r"(bar), "r"(n) : "memory"); }
__device__ __forceinline__ void mbar_arrive_remote(uint32_t rbar) { asm volatile("mbarrier.arrive.relaxed.cluster.shared::cluster.b64 _, [%0];" :: "r"(rbar) : "memory"); }
__device__ __forceinline__ void mbar_wait(uint32_t bar, uint32_t parity) {
    asm volatile("{.reg .pred p; .reg .u32 c;\n"
        "mbarrier.try_wait.parity.shared::cta.b64 p, [%0], %1;\n@p bra.uni DONE;\nmov.u32 c, 0;\n"
        "LOOP: mbarrier.try_wait.parity.shared::cta.b64 p, [%0], %1;\n@p bra.uni DONE;\n"
        "add.u32 c, c, 1;\nsetp.lt.u32 p, c, %2;\n@p bra.uni LOOP;\ntrap;\nDONE:}" :: "r"(bar), "r"(parity), "n"(SPIN_LIMIT) : "memory");
}
__device__ __forceinline__ bool mbar_test(uint32_t bar, uint32_t parity) {
    uint32_t ok; asm volatile("{.reg .pred p; mbarrier.test_wait.parity.shared::cta.b64 p, [%1], %2; selp.u32 %0, 1, 0, p;}" : "=r"(ok) : "r"(bar), "r"(parity) : "memory"); return ok; }
__device__ __forceinline__ uint32_t mapa(uint32_t a, uint32_t rank) { uint32_t r; asm("mapa.shared::cluster.u32 %0, %1, %2;" : "=r"(r) : "r"(a), "r"(rank)); return r; }
__device__ __forceinline__ uint32_t clk32() { uint32_t r; asm volatile("mov.u32 %0, %%clock;" : "=r"(r)); return r; }
__device__ __forceinline__ void hb() {
    asm volatile("{.reg .b32 a, b; .reg .pred p; mma.sync.aligned.m16n8k8.row.col.f16.f16.f16.f16 {a, b}, {%0,%0}, {%0}, {%0,%0};\n"
                 "setp.ne.u32 p, a, 0; @p trap;}" :: "r"(0));
}
__device__ __forceinline__ void spin_until(uint32_t t) { while (__any_sync(~0u, (int)(clk32() - t) < 0)) hb(); }
__device__ __forceinline__ bool elect() { uint32_t r; asm volatile("{.reg .pred p; elect.sync _|p, 0xffffffff; selp.u32 %0, 1, 0, p;}" : "=r"(r)); return r; }
__device__ __forceinline__ void bar_sync(int id, int n) { asm volatile("bar.sync %0, %1;" :: "r"(id), "r"(n) : "memory"); }
__device__ __forceinline__ void bulk_load(uint32_t dst, const void* src, uint32_t bytes, uint32_t bar) {
    asm volatile("cp.async.bulk.shared::cluster.global.mbarrier::complete_tx::bytes [%0], [%1], %2, [%3];" :: "r"(dst), "l"(src), "r"(bytes), "r"(bar) : "memory"); }
__device__ __forceinline__ void tma2(uint32_t dst, const CUtensorMap* m, int c0, int c1, uint32_t bar) {
    asm volatile("cp.async.bulk.tensor.2d.shared::cluster.global.mbarrier::complete_tx::bytes [%0], [%1, {%3, %4}], [%2];" :: "r"(dst), "l"(m), "r"(bar), "r"(c0), "r"(c1) : "memory"); }
__device__ __forceinline__ void tma3(uint32_t dst, const CUtensorMap* m, int c0, int c1, int c2, uint32_t bar) {
    asm volatile("cp.async.bulk.tensor.3d.shared::cluster.global.mbarrier::complete_tx::bytes [%0], [%1, {%3, %4, %5}], [%2];" :: "r"(dst), "l"(m), "r"(bar), "r"(c0), "r"(c1), "r"(c2) : "memory"); }
__device__ __forceinline__ void tma4(uint32_t dst, const CUtensorMap* m, int c0, int c1, int c2, int c3, uint32_t bar) {
    asm volatile("cp.async.bulk.tensor.4d.shared::cluster.global.mbarrier::complete_tx::bytes [%0], [%1, {%3, %4, %5, %6}], [%2];" :: "r"(dst), "l"(m), "r"(bar), "r"(c0), "r"(c1), "r"(c2), "r"(c3) : "memory"); }
__device__ __forceinline__ void fence_async_g() { asm volatile("fence.proxy.async.global;" ::: "memory"); }
__device__ __forceinline__ void fence_async_s() { asm volatile("fence.proxy.async.shared::cta;" ::: "memory"); }
__device__ __forceinline__ uint4 lds128(uint32_t a) { uint4 v; asm volatile("ld.shared.v4.u32 {%0,%1,%2,%3}, [%4];" : "=r"(v.x), "=r"(v.y), "=r"(v.z), "=r"(v.w) : "r"(a) : "memory"); return v; }
__device__ __forceinline__ uint32_t lds32(uint32_t a) { uint32_t v; asm volatile("ld.shared.u32 %0, [%1];" : "=r"(v) : "r"(a) : "memory"); return v; }
__device__ __forceinline__ void sts128(uint32_t a, uint4 v) { asm volatile("st.shared.v4.u32 [%0], {%1,%2,%3,%4};" :: "r"(a), "r"(v.x), "r"(v.y), "r"(v.z), "r"(v.w) : "memory"); }
__device__ __forceinline__ void sts32(uint32_t a, uint32_t v) { asm volatile("st.shared.u32 [%0], %1;" :: "r"(a), "r"(v) : "memory"); }
__device__ __forceinline__ void sts16(uint32_t a, uint32_t v) { asm volatile("st.shared.u16 [%0], %1;" :: "r"(a), "h"((uint16_t)v) : "memory"); }
__device__ __forceinline__ uint4 ldx128(const void* p) {
    uint4 v; asm volatile("{.reg .b128 t; .reg .b64 a, b; ld.relaxed.gpu.global.b128 t, [%4]; mov.b128 {a, b}, t; mov.b64 {%0,%1}, a; mov.b64 {%2,%3}, b;}"
        : "=r"(v.x), "=r"(v.y), "=r"(v.z), "=r"(v.w) : "l"(p) : "memory"); return v; }
__device__ __forceinline__ void stx128(void* p, uint4 v) {
    asm volatile("{.reg .b128 t; .reg .b64 a, b; mov.b64 a, {%1,%2}; mov.b64 b, {%3,%4}; mov.b128 t, {a, b}; st.relaxed.gpu.global.b128 [%0], t;}"
        :: "l"(p), "r"(v.x), "r"(v.y), "r"(v.z), "r"(v.w) : "memory"); }
__device__ __forceinline__ uint32_t ld_relaxed(const uint32_t* p) { uint32_t v; asm volatile("ld.relaxed.gpu.global.u32 %0, [%1];" : "=r"(v) : "l"(p) : "memory"); return v; }
__device__ __forceinline__ uint32_t ld_acquire(const uint32_t* p) { uint32_t v; asm volatile("ld.acquire.gpu.global.u32 %0, [%1];" : "=r"(v) : "l"(p) : "memory"); return v; }
__device__ __forceinline__ void st_relaxed(uint32_t* p, uint32_t v) { asm volatile("st.relaxed.gpu.global.u32 [%0], %1;" :: "l"(p), "r"(v) : "memory"); }
__device__ __forceinline__ void red_release(uint32_t* p) { asm volatile("red.release.gpu.global.add.u32 [%0], 1;" :: "l"(p) : "memory"); }
template <int SLEEP> __device__ __forceinline__ void wait_count(const uint32_t* p, uint32_t target) {
    int it = 0; while ((int)(ld_acquire(p) - target) < 0) { if (SLEEP) __nanosleep(SLEEP); if (++it > SPIN_LIMIT) __trap(); }
}
__device__ __forceinline__ uint32_t ldg_nc32(const void* p) { uint32_t v; asm volatile("ld.global.nc.L1::no_allocate.u32 %0, [%1];" : "=r"(v) : "l"(p)); return v; }
__device__ __forceinline__ uint32_t ldg_nc16(const void* p) { uint16_t v; asm volatile("ld.global.nc.u16 %0, [%1];" : "=h"(v) : "l"(p)); return v; }
__device__ __forceinline__ float bf_lo(uint32_t w) { return __uint_as_float(w << 16); }
__device__ __forceinline__ float bf_hi(uint32_t w) { return __uint_as_float(w & 0xFFFF0000u); }
__device__ __forceinline__ uint32_t pack_bf(float lo, float hi) { uint32_t r; asm("cvt.rn.bf16x2.f32 %0, %1, %2;" : "=r"(r) : "f"(hi), "f"(lo)); return r; }
__device__ __forceinline__ uint32_t pack_h(float lo, float hi) { uint32_t r; asm("cvt.rn.f16x2.f32 %0, %1, %2;" : "=r"(r) : "f"(hi), "f"(lo)); return r; }
__device__ __forceinline__ float bf_round(float v) { return bf_lo(pack_bf(v, 0.f)); }
__device__ __forceinline__ uint32_t hmul2(uint32_t a, uint32_t b) { uint32_t r; asm("mul.rn.f16x2 %0, %1, %2;" : "=r"(r) : "r"(a), "r"(b)); return r; }
__device__ __forceinline__ uint32_t hfma2(uint32_t a, uint32_t b, uint32_t c) { uint32_t r; asm("fma.rn.f16x2 %0, %1, %2, %3;" : "=r"(r) : "r"(a), "r"(b), "r"(c)); return r; }
__device__ __forceinline__ uint32_t hfms2(uint32_t a, uint32_t b, uint32_t c) { uint32_t r; asm("{.reg .b32 t; neg.f16x2 t, %3; fma.rn.f16x2 %0, %1, %2, t;}" : "=r"(r) : "r"(a), "r"(b), "r"(c)); return r; }
__device__ __forceinline__ uint32_t hadd2(uint32_t a, uint32_t b) { uint32_t r; asm("add.rn.f16x2 %0, %1, %2;" : "=r"(r) : "r"(a), "r"(b)); return r; }
__device__ __forceinline__ uint32_t hsub2(uint32_t a, uint32_t b) { uint32_t r; asm("sub.rn.f16x2 %0, %1, %2;" : "=r"(r) : "r"(a), "r"(b)); return r; }
__device__ __forceinline__ void cmul_neg(uint32_t& re, uint32_t& im, uint32_t c, uint32_t s) { uint32_t a = hfma2(re, c, hmul2(im, s)), b = hfms2(im, c, hmul2(re, s)); re = a; im = b; }
__device__ __forceinline__ void cmul_pos(uint32_t& re, uint32_t& im, uint32_t c, uint32_t s) { uint32_t a = hfms2(re, c, hmul2(im, s)), b = hfma2(im, c, hmul2(re, s)); re = a; im = b; }
__device__ __forceinline__ void mma_h(uint32_t& d0, uint32_t& d1, uint32_t a0, uint32_t a1, uint32_t a2, uint32_t a3, uint32_t b0, uint32_t b1) {
    asm("mma.sync.aligned.m16n8k16.row.col.f16.f16.f16.f16 {%0,%1}, {%2,%3,%4,%5}, {%6,%7}, {%0,%1};" : "+r"(d0), "+r"(d1) : "r"(a0), "r"(a1), "r"(a2), "r"(a3), "r"(b0), "r"(b1)); }
__device__ __forceinline__ void mma_h8(uint32_t& d0, uint32_t& d1, uint32_t a0, uint32_t a1, uint32_t b0) {
    asm("mma.sync.aligned.m16n8k8.row.col.f16.f16.f16.f16 {%0,%1}, {%2,%3}, {%4}, {%0,%1};" : "+r"(d0), "+r"(d1) : "r"(a0), "r"(a1), "r"(b0)); }
__device__ __forceinline__ void mma_f(float (&d)[4], uint32_t a0, uint32_t a1, uint32_t a2, uint32_t a3, uint32_t b0, uint32_t b1) {
    asm("mma.sync.aligned.m16n8k16.row.col.f32.f16.f16.f32 {%0,%1,%2,%3}, {%4,%5,%6,%7}, {%8,%9}, {%0,%1,%2,%3};"
        : "+f"(d[0]), "+f"(d[1]), "+f"(d[2]), "+f"(d[3]) : "r"(a0), "r"(a1), "r"(a2), "r"(a3), "r"(b0), "r"(b1)); }
template <int NQ> __device__ __forceinline__ void load_tab(uint32_t (&r)[NQ * 4], uint32_t addr) {
    #pragma unroll
    for (int i = 0; i < NQ; i++) { uint4 v = lds128(addr + i * 512); r[4 * i] = v.x; r[4 * i + 1] = v.y; r[4 * i + 2] = v.z; r[4 * i + 3] = v.w; }
}
__device__ __forceinline__ float gelu2(float x) {
    float t = x * fmaf(x * x, 0.044715f * 0.7978845608028654f, 0.7978845608028654f), th;
    asm volatile("tanh.approx.f32 %0, %1;" : "=f"(th) : "f"(t));
    return fmaf(x, th, x);
}
__device__ __forceinline__ uint32_t desc_lo(uint32_t addr, uint32_t lbo) { return ((addr & 0x3FFFF) >> 4) | ((lbo >> 4) << 16); }
constexpr uint32_t DHI_A = (1024 >> 4) | (1u << 30), DHI_H3 = 256 >> 4, DHI_U = 128 >> 4;
#define WG_FENCE() asm volatile("wgmma.fence.sync.aligned;" ::: "memory")
#define WG_COMMIT() asm volatile("wgmma.commit_group.sync.aligned;" ::: "memory")
#define WG_WAIT(n) asm volatile("wgmma.wait_group.sync.aligned %0;" :: "n"(n) : "memory")
#define R4(b) "+f"(d[b]), "+f"(d[b + 1]), "+f"(d[b + 2]), "+f"(d[b + 3])
#define R12(b) R4(b), R4(b + 4), R4(b + 8)
#define R36(b) R12(b), R12(b + 12), R12(b + 24)
template <uint32_t BHI> __device__ __forceinline__ void wgmma144(float (&d)[72], uint32_t da, uint32_t db, int acc) {
    asm volatile("{.reg .pred p; .reg .b64 a, b; setp.ne.b32 p, %74, 0; mov.b64 a, {%72, %75}; mov.b64 b, {%73, %76};\n"
        "wgmma.mma_async.sync.aligned.m64n144k16.f32.bf16.bf16 {%0,%1,%2,%3,%4,%5,%6,%7,%8,%9,%10,%11,%12,%13,%14,%15,%16,%17,%18,%19,%20,%21,%22,%23,"
        "%24,%25,%26,%27,%28,%29,%30,%31,%32,%33,%34,%35,%36,%37,%38,%39,%40,%41,%42,%43,%44,%45,%46,%47,"
        "%48,%49,%50,%51,%52,%53,%54,%55,%56,%57,%58,%59,%60,%61,%62,%63,%64,%65,%66,%67,%68,%69,%70,%71}, a, b, p, 1, 1, 1, 1;}\n"
        : R36(0), R36(36) : "r"(da), "r"(db), "r"(acc), "n"(DHI_A), "n"(BHI));
}
__device__ __forceinline__ void wgmma144x4(float (&d)[72], const uint64_t (&a)[4], const uint64_t (&b)[4], int acc) {
    #define WG144 "wgmma.mma_async.sync.aligned.m64n144k16.f32.bf16.bf16 {%0,%1,%2,%3,%4,%5,%6,%7,%8,%9,%10,%11,%12,%13,%14,%15,%16,%17,%18,%19,%20,%21,%22,%23,%24,%25,%26,%27,%28,%29,%30,%31,%32,%33,%34,%35,%36,%37,%38,%39,%40,%41,%42,%43,%44,%45,%46,%47,%48,%49,%50,%51,%52,%53,%54,%55,%56,%57,%58,%59,%60,%61,%62,%63,%64,%65,%66,%67,%68,%69,%70,%71}, "
    asm volatile("{.reg .pred p; setp.ne.b32 p, %80, 0;\n"
        WG144 "%72, %76, p, 1, 1, 1, 1;\n" WG144 "%73, %77, 1, 1, 1, 1, 1;\n" WG144 "%74, %78, 1, 1, 1, 1, 1;\n" WG144 "%75, %79, 1, 1, 1, 1, 1;}\n"
        : R36(0), R36(36) : "l"(a[0]), "l"(a[1]), "l"(a[2]), "l"(a[3]), "l"(b[0]), "l"(b[1]), "l"(b[2]), "l"(b[3]), "r"(acc));
}
__device__ __forceinline__ void wgmma72(float (&d)[36], uint32_t da, uint32_t db, int acc) {
    asm volatile("{.reg .pred p; .reg .b64 a, b; setp.ne.b32 p, %38, 0; mov.b64 a, {%36, %39}; mov.b64 b, {%37, %40};\n"
        "wgmma.mma_async.sync.aligned.m64n72k16.f32.bf16.bf16 {%0,%1,%2,%3,%4,%5,%6,%7,%8,%9,%10,%11,%12,%13,%14,%15,%16,%17,%18,%19,%20,%21,%22,%23,"
        "%24,%25,%26,%27,%28,%29,%30,%31,%32,%33,%34,%35}, a, b, p, 1, 1, 1, 1;}\n"
        : R36(0) : "r"(da), "r"(db), "r"(acc), "n"(DHI_A), "n"(DHI_H3));
}

__device__ __forceinline__ int g2_kb(int n, int kh) { const int m = n - 4; return 36 * kh + (n < 4 ? 9 * n + 8 : 9 * ((m >> 2) & 3) + 2 * (m & 3) + (m >> 4)); }

template <uint32_t BHI, int I0, int I1, bool ZERO, bool FIRST, bool LAST, class Hook>
__device__ __forceinline__ void mainloop(float (&d)[72], uint32_t bars, uint32_t da0, uint32_t db0, bool lead, Hook hook) {
    uint32_t s = I0 % NST, ph = (I0 / NST) & 1, prev = (I0 + NST - (I0 == IT_P1 ? 2 : 1)) % NST;
    uint32_t ready = 0;
    uint64_t da[4], db[4];
    #pragma unroll
    for (int k = 0; k < 4; k++) { da[k] = ((uint64_t)DHI_A << 32) + da0 + s * (A_BYTES / 16) + k * 128; db[k] = ((uint64_t)BHI << 32) + db0 + s * (B_BYTES / 16) + k * 288; }
    #pragma unroll 1
    for (int i = I0; i < I1; i++) {
        if (!ready) mbar_wait(bars + 8 * BAR_FULL + 8 * s, ph);
        WG_FENCE();
        wgmma144x4(d, da, db, ZERO ? i - I0 : 1);
        WG_COMMIT();
        const uint32_t rel = bars + 8 * BAR_EMPTY + 8 * prev; const int i0 = i;
        prev = s; if (++s == NST) { s = 0; ph ^= 1; }
        if (I1 == IT_P1 && (s == P2S || s == P2S + 3)) {
            mbar_wait(bars + 8 * BAR_FULL + 8 * s, ph);
            i++; if (++s == NST) { s = 0; ph ^= 1; }
        }
        const int64_t adv = (int)s - (int)prev;
        #pragma unroll
        for (int k = 0; k < 4; k++) { da[k] += adv * (A_BYTES / 16); db[k] += adv * (B_BYTES / 16); }
        ready = __shfl_sync(~0u, (uint32_t)mbar_test(bars + 8 * BAR_FULL + 8 * s, ph), 0);
        WG_WAIT(1);
        if (lead && (!FIRST || i0 > I0)) mbar_arrive(rel);
        hook(i0);
    }
    if (LAST) { WG_WAIT(0); if (lead) mbar_arrive(bars + 8 * BAR_EMPTY + 8 * prev); }
}

struct Params {
    const uint16_t *x, *wr, *wi, *w1, *b1, *w2, *b2, *c, *wmod;
    uint16_t* out;
    Scratch* scr;
    const Tab* tab;
};

__device__ __forceinline__ void mma_bf(float (&d)[4], const uint32_t (&a)[4], uint32_t b0, uint32_t b1) {
    asm("mma.sync.aligned.m16n8k16.row.col.f32.bf16.bf16.f32 {%0,%1,%2,%3}, {%4,%5,%6,%7}, {%8,%9}, {%0,%1,%2,%3};"
        : "+f"(d[0]), "+f"(d[1]), "+f"(d[2]), "+f"(d[3]) : "r"(a[0]), "r"(a[1]), "r"(a[2]), "r"(a[3]), "r"(b0), "r"(b1)); }
__device__ __forceinline__ void ldsm4t(uint32_t (&a)[4], uint32_t addr) {
    asm volatile("ldmatrix.sync.aligned.m8n8.x4.trans.shared.b16 {%0,%1,%2,%3}, [%4];" : "=r"(a[0]), "=r"(a[1]), "=r"(a[2]), "=r"(a[3]) : "r"(addr) : "memory"); }
__device__ __forceinline__ void ln_stats(const uint32_t (&w)[9], int g, int q, float& r, float& mr) {
    constexpr uint32_t ONE = 0x3F803F80u;
    float c[2][4] = {};
    #pragma unroll
    for (int p = 0; p < 5; p++) { const uint32_t hi = p < 4 ? w[p < 4 ? 2 * p + 1 : 0] : 0u, a[4] = {w[2 * p], ONE, hi, ONE}; mma_bf(c[p & 1], a, w[2 * p], hi); }
    const float t = (g & 1) ? c[0][1] + c[1][1] : c[0][0] + c[1][0];
    float s1 = (c[0][2] + c[1][2]) + (c[0][3] + c[1][3]), s2 = __shfl_sync(~0u, t, 9 * q) + __shfl_sync(~0u, t, 9 * q + 4);
    #pragma unroll
    for (int o = 1; o < 4; o <<= 1) { s1 += __shfl_xor_sync(~0u, s1, o); s2 += __shfl_xor_sync(~0u, s2, o); }
    const float m = s1 * (1.f / D_);
    asm("rsqrt.approx.ftz.f32 %0, %1;" : "=f"(r) : "f"(fmaxf(fmaf(s2, 1.f / D_, -m * m), 0.f) + 1e-5f));
    mr = -m * r;
}
__device__ __forceinline__ float silu(float v) { return __fdividef(v, 1.f + __expf(-v)); }
__device__ __forceinline__ uint32_t bfma2(uint32_t a, uint32_t b, uint32_t c) { uint32_t r; asm("fma.rn.bf16x2 %0, %1, %2, %3;" : "=r"(r) : "r"(a), "r"(b), "r"(c)); return r; }
__device__ __forceinline__ void radix16(const uint4 (&V)[4], const uint32_t (&B)[16], uint4 (&o)[4]) {
    #pragma unroll
    for (int nt = 0; nt < 4; nt++) {
        o[nt] = make_uint4(0, 0, 0, 0);
        #pragma unroll
        for (int ks = 0; ks < 2; ks++) {
            const uint32_t b0 = B[(ks * 4 + nt) * 2], b1 = B[(ks * 4 + nt) * 2 + 1];
            mma_h(o[nt].x, o[nt].y, V[2 * ks].x, V[2 * ks].y, V[2 * ks + 1].x, V[2 * ks + 1].y, b0, b1);
            mma_h(o[nt].z, o[nt].w, V[2 * ks].z, V[2 * ks].w, V[2 * ks + 1].z, V[2 * ks + 1].w, b0, b1);
        }
    }
}
template <int OFF, int N> __device__ __forceinline__ void gelu_store(const float (&d)[N], char* p, int q) {
    uint32_t w[9];
    #pragma unroll
    for (int blk = 0; blk < 9; blk++) w[blk] = pack_bf(gelu2(d[OFF + 4 * blk]), gelu2(d[OFF + 4 * blk + 1]));
    asm volatile("st.v4.u32 [%0], {%1,%2,%3,%4};" :: "l"(p + q * 128), "r"(w[0]), "r"(w[1]), "r"(w[2]), "r"(w[3]) : "memory");
    asm volatile("st.v4.u32 [%0+512], {%1,%2,%3,%4};" :: "l"(p + q * 128), "r"(w[4]), "r"(w[5]), "r"(w[6]), "r"(w[7]) : "memory");
    asm volatile("st.u32 [%0+1024], %1;" :: "l"(p + q * 4), "r"(w[8]) : "memory");
}

__global__ void __cluster_dims__(2, 1, 1) __launch_bounds__(NTHR, 1)
fused_kernel(const Params p,
             const __grid_constant__ CUtensorMap tm_w1a, const __grid_constant__ CUtensorMap tm_w1b, const __grid_constant__ CUtensorMap tm_w2,
             const __grid_constant__ CUtensorMap tm_h3a, const __grid_constant__ CUtensorMap tm_h3b,
             const __grid_constant__ CUtensorMap tm_wr, const __grid_constant__ CUtensorMap tm_wi, const __grid_constant__ CUtensorMap tm_wm,
             const __grid_constant__ CUtensorMap tm_t, const __grid_constant__ CUtensorMap tm_tx, const __grid_constant__ CUtensorMap tm_o,
             const __grid_constant__ CUtensorMap tm_h3s, const __grid_constant__ CUtensorMap tm_ws)
{
    extern __shared__ char smem_raw[];
    const uint32_t t0 = clk32();
    const uint32_t sm = __shfl_sync(~0u, ((uint32_t)__cvta_generic_to_shared(smem_raw) + 1023u) & ~1023u, 0);
    const int tid = threadIdx.x, warp = __shfl_sync(~0u, tid >> 5, 0), lane = tid & 31, g = lane >> 2, q = lane & 3;
    const int b = blockIdx.x;
    const uint32_t rank = b & 1;
    const uint32_t bars = sm + OFF_BAR;
    const bool rowcta = b < 128;

    auto nc_issue = [&](int st, uint32_t sl) {
        const int pass = st >= 18;
        mbar_expect(bars + 8 * (BAR_X + sl), 28672);
        tma3(sm + sl * 28672, &tm_wm, 0, 32 * (st - 18 * pass), 18 + 28 * pass + 7 * (b - 128), bars + 8 * (BAR_X + sl));
    };
    uint32_t epoch;
    const bool strip = b < 72 && !(b & 1);
    if (warp < 12) {
        epoch = ld_relaxed(g_cnt + CNT_EPOCH * 32);
        if (warp >= 8 && lane < 24 && (strip || !rowcta)) {
            uint32_t cw[3];
            #pragma unroll
            for (int u = 0; u < 3; u++) cw[u] = ldg_nc32(p.c + 144 * (warp - 8) + 48 * u + 2 * lane);
            #pragma unroll
            for (int u = 0; u < 3; u++) sts32(sm + OFF_SILU + (72 * (warp - 8) + 24 * u + lane) * 4, pack_bf(silu(bf_lo(cw[u])), silu(bf_hi(cw[u]))));
        }
        __syncwarp();
        hb();
        bar_sync(2, 512);
    } else {
        const int w4 = 4 * (warp - 12);
        if (elect()) {
            if (warp == 14 && b < 13) asm volatile("cp.async.bulk.prefetch.L2.global [%0], 512;" :: "l"(p.tab->w + b * 128) : "memory");
            if (strip && warp == 15) asm volatile("prefetch.tensormap [%0];" :: "l"(&tm_ws) : "memory");
            if (CRITPF) {
                asm volatile("cp.async.bulk.prefetch.L2.global [%0], 2304;" :: "l"(p.wmod + (b + 33 * w4) * 3456) : "memory");
                if (warp == 12 && b < 48) asm volatile("cp.async.bulk.prefetch.L2.global [%0], 2304;" :: "l"(p.wmod + (b + 528) * 3456) : "memory");
            }
        }
        if (warp == 13) hb();
        if (elect()) {
            if (rowcta) {
                for (int i = 0; i < 4; i++) mbar_init(bars + 8 * (BAR_X + w4 + i), 1);
                const uint32_t sb = bars + 8 * (BAR_ST + warp - 12);
                mbar_init(sb, 1);
                if (warp == 15) mbar_init(bars + 8 * BAR_TAB, 1);
                fence_async_s();
                if (warp == 15) { mbar_expect(bars + 8 * BAR_TAB, QA * 512); bulk_load(sm + OFF_TAB, p.tab, QA * 512, bars + 8 * BAR_TAB); }
                if (strip) { mbar_expect(sb, 9216); tma2(sm + OFF_STRIP + (warp - 12) * 9216, &tm_ws, 16 * b, 36 * w4, sb); }
            } else if (warp == 12) {
                for (int i = 0; i < 12; i++) mbar_init(bars + 8 * (BAR_X + i), i < 6 ? 1 : 14);
                fence_async_s();
                if (NCD) while ((int)(clk32() - t0) < NCD) {}
                for (int st = 0; st < 6; st++) nc_issue(st, st);
            }
            if (warp == 12) {
                asm volatile("prefetch.tensormap [%0];" :: "l"(&tm_wr) : "memory"); asm volatile("prefetch.tensormap [%0];" :: "l"(&tm_wi) : "memory");
                asm volatile("prefetch.tensormap [%0];" :: "l"(&tm_t) : "memory"); asm volatile("prefetch.tensormap [%0];" :: "l"(&tm_tx) : "memory");
            } else if (warp == 14) {
                for (int i = BAR_W; i < BAR_X; i++) mbar_init(bars + 8 * i, i == BAR_DONE ? 4 : 1);
                mbar_expect(bars + 8 * BAR_W, 28672); mbar_expect(bars + 8 * BAR_TAB2, (QB + QC) * 512);
                mbar_expect(bars + 8 * BAR_ROLE, 4); mbar_expect(bars + 8 * BAR_P2R, 9216); mbar_expect(bars + 8 * BAR_RECV, 18432); mbar_expect(bars + 8 * BAR_XT, 18432);
            } else if (warp == 13) {
                for (int i = 0; i < 2 * NST; i++) mbar_init(bars + 8 * i, 2);
                for (int i = 0; i < NST; i++) mbar_expect(bars + 8 * (BAR_FULL + i), A_BYTES);
            }
            asm volatile("fence.mbarrier_init.release.cluster;" ::: "memory");
        }
        __syncwarp();
        asm volatile("bar.arrive 2, 512;" ::: "memory");
        if (rowcta && elect()) {
            if (XDELAY) while ((int)(clk32() - t0) < XDELAY) {}
            for (int r = w4; r < w4 + 4; r++) {
                mbar_expect(bars + 8 * (BAR_X + r), 1152);
                bulk_load(sm + OFF_STAGE + r * 1152, p.x + (size_t)(b + 128 * r) * D_, 1152, bars + 8 * (BAR_X + r));
            }
        }
        __syncwarp();
        epoch = ld_relaxed(g_cnt + CNT_EPOCH * 32);
        sts16(sm + OFF_MODA + ((warp - 11) * 32 + lane) * 16 + w4 + 2, 0);
        #pragma unroll 1
        for (int s1 = (tid >> 4) & 7; s1 < 16; s1 += 8) {
            const int k1 = tid & 15;
            float s, c;
            __sincosf((float)(((k1 * (128 * s1 + b) + 1024) & 2047) - 1024) * (3.14159265358979f / 1024.f), &s, &c); s *= 0.25f; c *= 0.25f;
            const int rf = ((s1 >> 3) * 4 + (k1 >> 2)) * 2 + ((s1 >> 2) & 1), ri = ((k1 >> 3) * 4 + (s1 >> 2)) * 2 + ((k1 >> 2) & 1);
            const uint32_t af = sm + OFF_B3 + ((rf >> 2) * 32 + (k1 & 3) * 8 + (s1 & 3)) * 16 + (rf & 3) * 4;
            const uint32_t ai = sm + OFF_B3 + 2048 + ((ri >> 2) * 32 + (s1 & 3) * 8 + (k1 & 3)) * 16 + (ri & 3) * 4;
            sts32(af, pack_h(c, s)); sts32(af + 64, pack_h(-s, c)); sts32(ai, pack_h(c, -s)); sts32(ai + 64, pack_h(s, c));
        }
        hb();
        bar_sync(3, 128);
    }
    asm volatile("barrier.cluster.arrive.relaxed.aligned;" ::: "memory");
    const uint32_t tag = (epoch + 1) & 0xFFFFu;

    const int trow = 4 * (b & 7) + ((b >> 4) & 3) + 64 * ((b >> 3) & 1) + 32 * (b >> 6);
    uint32_t* const tptr = g_T + (size_t)trow * TP + (warp < 9 ? q * 288 + 32 * warp : 4608 + 8 * q) + 4 * g;
    const int tstr = warp < 9 ? 1152 : 32;
    const uint32_t scol = sm + OFF_SPEC + (q * SPEC_P + (warp < 8 ? 72 * (warp >> 1) + 40 * (warp & 1) + 4 * g : warp == 8 ? 72 * (g >> 1) + 32 + 4 * (g & 1) : 288 + 4 * g)) * 4;
    const int wc0 = (b >> 3) * 289 + 72 * ((b & 7) >> 1) + 40 * (b & 1);

    uint32_t xw[9], t_st = t0;
    if (!rowcta) {
        const int nst = b < 130 ? 36 : 18;
        __syncthreads();
        if (warp == 14) {
            uint32_t sl = 0, ph = 0;
            #pragma unroll 1
            for (int st = 6; st < nst; st++) {
                mbar_wait(bars + 8 * (BAR_X + 6 + sl), ph);
                if (elect()) nc_issue(st, sl);
                if (++sl == 6) { sl = 0; ph ^= 1; }
            }
        } else if (warp < 14) {
            uint32_t sl = 0, ph = 0;
            const uint32_t ad0 = sm + (warp >> 1) * 4096 + ((lane & 7) + 8 * (lane >> 4)) * 128, ch = (warp & 1) * 4 + ((lane >> 3) & 1);
            #pragma unroll 1
            for (int pass = 0; pass * 18 < nst; pass++) {
                float acc[2][4] = {};
                #pragma unroll 1
                for (int st = 0; st < 18; st++) {
                    const uint32_t sa = sm + OFF_SILU + (16 * st + q) * 4;
                    const uint32_t b0 = lds32(sa), b1 = lds32(sa + 16), b2 = lds32(sa + 32), b3 = lds32(sa + 48);
                    mbar_wait(bars + 8 * (BAR_X + sl), ph);
                    #pragma unroll
                    for (int m = 0; m < 2; m++) {
                        uint32_t a[4], a2[4];
                        const uint32_t ad = ad0 + sl * 28672 + ((ch + 2 * m) ^ (lane & 7)) * 16;
                        ldsm4t(a, ad); ldsm4t(a2, ad + 2048);
                        mma_bf(acc[m], a, b0, b1); mma_bf(acc[m], a2, b2, b3);
                    }
                    if (elect()) mbar_arrive(bars + 8 * (BAR_X + 6 + sl));
                    if (++sl == 6) { sl = 0; ph ^= 1; }
                }
                const int cb = 28 * pass + 7 * (b - 128) + (warp >> 1), gg = (g >> 1) + 4 * q;
                #pragma unroll
                for (int m = 0; m < 2; m++) {
                    const int qq = (warp & 1) * 2 + m;
                    float v = bf_round(q ? acc[m][2] : acc[m][0]); if (cb >= 27) v *= 0.5f; else if (cb >= 18) v += 1.f;
                    const uint32_t w = pack_bf(v, __shfl_xor_sync(~0u, v, 4));
                    if (q < 2 && !(g & 1) && cb < 36) p.scr->modc[cb < 27 ? ((cb >> 2) * 32 + 4 * gg + qq) * 4 + (cb & 3) : 896 + 32 * (cb - 27) + 8 * qq + gg] = w;
                }
                bar_sync(1, 448);
                if (tid == 0) { fence_async_g(); red_release(g_cnt + (CNT_NC + pass) * 32); if (pass == 0) PROFT(25); }
                __syncwarp();
            }
            fence_async_s();
        }
        __syncthreads();
    } else {
        uint32_t ta[QA * 4];
        if (strip && (warp >> 2) == 2) {
            const int w = warp - 8;
            uint32_t sb[18];
            #pragma unroll
            for (int u = 0; u < 18; u++) sb[u] = lds32(sm + OFF_SILU + (72 * w + 4 * u + q) * 4);
            const uint32_t ra = sm + OFF_STRIP + (144 * w + (lane & 7) + 8 * (lane >> 4)) * 64, sw = (lane >> 1) & 3, ch = (lane >> 3) & 1;
            float acc[2][2][4] = {};
            mbar_wait(bars + 8 * (BAR_ST + w), 0);
            #pragma unroll
            for (int u = 0; u < 9; u++)
                #pragma unroll
                for (int m = 0; m < 2; m++) { uint32_t a[4]; ldsm4t(a, ra + u * 1024 + ((ch + 2 * m) ^ sw) * 16); mma_bf(acc[u & 1][m], a, sb[2 * u], sb[2 * u + 1]); }
            #define PICK(a_) ((q & 2) ? ((q & 1) ? a_[1][2] : a_[1][0]) : ((q & 1) ? a_[0][2] : a_[0][0]))
            sts32(sm + OFF_RED + ((8 * q + g) * 4 + w) * 4, __float_as_uint(PICK(acc[0]) + PICK(acc[1])));
            if (tid == 256) PROFT(0);
            bar_sync(10, 128);
            if (warp == 8) {
                const uint4 v = lds128(sm + OFF_RED + lane * 16);
                float sum = bf_round((__uint_as_float(v.x) + __uint_as_float(v.y)) + (__uint_as_float(v.z) + __uint_as_float(v.w)));
                if (b >= 36) sum = bf_round(1.f + sum);
                st_relaxed(g_mod + b * 16 + (lane & 16) + (lane & 1) * 8 + ((lane & 15) >> 1), (pack_h(0.f, sum) & 0xFFFF0000u) | tag);
                if (tid == 256) PROFT(1);
            }
        }
        mbar_wait(bars + 8 * BAR_TAB, 0);
        load_tab<QA>(ta, sm + OFF_TAB + lane * 16);
        uint32_t nb[2][5];
        uint4 mv = make_uint4(tag, tag, tag, tag);
        const bool poller = warp < 8 || warp == 12;
        const int mc = warp < 8 ? tid : tid - 128, mst = (mc >> 2) % 36, midx = (mc < 144 ? 10 : 0) + 5 * ((mc >> 1) & 1) + (mst >> 3);
        const uint32_t* mp = g_mod + mc * 4;
        const uint32_t ma = sm + OFF_MODA + ((midx >> 2) * 32 + (mc & 1) * 16 + (mst & 3)) * 16 + (midx & 3) * 4 + ((mst >> 2) & 1) * 2;
        #define MOD_MISSING ((((mv.x ^ tag) | (mv.y ^ tag) | (mv.z ^ tag) | (mv.w ^ tag)) & 0xFFFFu) != 0)
        hb();
        mbar_wait(bars + 8 * (BAR_X + warp), 0);
        if (poller) mv = ldx128(mp);
        PROF0(28);
        #pragma unroll
        for (int i = 0; i < 9; i++) xw[i] = lds32(sm + OFF_STAGE + warp * 1152 + (32 * i + 8 * q + g) * 4);
        {
            float r, mr;
            ln_stats(xw, g, q, r, mr);
            #pragma unroll
            for (int pp = 0; pp < 5; pp++) {
                nb[0][pp] = pack_h(fmaf(bf_lo(xw[2 * pp]), r, mr), pp < 4 ? fmaf(bf_lo(xw[pp < 4 ? 2 * pp + 1 : 0]), r, mr) : 0.f);
                nb[1][pp] = pack_h(fmaf(bf_hi(xw[2 * pp]), r, mr), pp < 4 ? fmaf(bf_hi(xw[pp < 4 ? 2 * pp + 1 : 0]), r, mr) : 0.f);
            }
        }
        PROF0(2);
        if (poller) {
            for (int it = 0; __any_sync(~0u, MOD_MISSING); it++) { if (MOD_MISSING) mv = ldx128(mp); hb(); if (it > SPIN_LIMIT) __trap(); }
            sts16(ma, mv.x >> 16); sts16(ma + 64, mv.y >> 16); sts16(ma + 128, mv.z >> 16); sts16(ma + 192, mv.w >> 16);
        }
        __syncthreads();
        PROF0(3);
        if (warp >= 13 && elect()) {
            if (warp == 15) bulk_load(sm + OFF_TAB + QA * 512, p.tab->w + QA * 128, (QB + QC) * 512, bars + 8 * BAR_TAB2);
            else tma3(sm + OFF_WRAW + (warp - 13) * 14336, warp == 13 ? &tm_wr : &tm_wi, wc0 & ~7, 0, 0, bars + 8 * BAR_W);
        }
        __syncwarp();
        {
            uint32_t md[20];
            load_tab<5>(md, sm + OFF_MODA + lane * 16);
            #pragma unroll
            for (int v = 0; v < 2; v++)
                #pragma unroll
                for (int pp = 0; pp < 5; pp++) nb[v][pp] = hfma2(nb[v][pp], md[v * 5 + pp], md[10 + v * 5 + pp]);
        }
        uint32_t re[3][2], im[3][2];
        #pragma unroll
        for (int mt = 0; mt < 3; mt++)
            #pragma unroll
            for (int v = 0; v < 2; v++) {
                re[mt][v] = 0; im[mt][v] = 0;
                mma_h8(re[mt][v], im[mt][v], ta[mt * 10 + 8], ta[mt * 10 + 9], nb[v][4]);
                mma_h(re[mt][v], im[mt][v], ta[mt * 10], ta[mt * 10 + 1], ta[mt * 10 + 2], ta[mt * 10 + 3], nb[v][0], nb[v][1]);
                mma_h(re[mt][v], im[mt][v], ta[mt * 10 + 4], ta[mt * 10 + 5], ta[mt * 10 + 6], ta[mt * 10 + 7], nb[v][2], nb[v][3]);
                cmul_neg(re[mt][v], im[mt][v], ta[30 + (mt * 2 + v) * 2], ta[31 + (mt * 2 + v) * 2]);
            }
        const uint32_t srow = sm + OFF_SPEC + warp * (SPEC_P * 4);
        #pragma unroll
        for (int nt = 0; nt < 2; nt++) {
            uint32_t o[2][4];
            #pragma unroll
            for (int v = 0; v < 2; v++) {
                const uint32_t b0 = ta[42 + (v * 2 + nt) * 2], b1 = ta[43 + (v * 2 + nt) * 2];
                o[v][0] = o[v][1] = o[v][2] = o[v][3] = 0;
                mma_h(o[v][0], o[v][1], re[0][v], re[1][v], im[0][v], im[1][v], b0, b1);
                mma_h(o[v][2], o[v][3], re[2][v], re[2][v], im[2][v], im[2][v], b0, b1);
            }
            const uint32_t a = srow + (g + 72 * q + 36 * nt) * 4, a2 = srow + (288 - g - 72 * q - 36 * nt) * 4;
            sts32(a, hadd2(o[0][0], o[1][0])); sts32(a + 32, hadd2(o[0][1], o[1][1])); if (g < 3) sts32(a + 64, hadd2(o[0][2], o[1][2]));
            if (g > 0 || (q == 0 && nt == 0)) sts32(a2, hsub2(o[0][0], o[1][0]) ^ 0x80000000u);
            sts32(a2 - 32, hsub2(o[0][1], o[1][1]) ^ 0x80000000u); if (g < 2) sts32(a2 - 64, hsub2(o[0][2], o[1][2]) ^ 0x80000000u);
        }
        uint32_t b3[16];
        if (warp < 10) load_tab<4>(b3, sm + OFF_B3 + lane * 16);
        __syncthreads();
        t_st = clk32();
        PROF0(4);
        if (warp < 10) {
            uint4 V[4], o[4];
            #pragma unroll
            for (int u = 0; u < 4; u++) V[u] = lds128(scol + u * (16 * SPEC_P));
            radix16(V, b3, o);
            #pragma unroll
            for (int nt = 0; nt < 4; nt++) { o[nt].x |= 1u; if (warp < 9 || g < 2) stx128(tptr + nt * tstr, o[nt]); }
        }
        PROF0(5);
    }

    int role = 0;
    asm volatile("barrier.cluster.wait.aligned;" ::: "memory");
    if (warp >= 12) {
        const int t = tid - 384;
        if (tid == 448 && rank == 0) {
            uint32_t smid; asm volatile("mov.u32 %0, %%smid;" : "=r"(smid));
            const uint32_t tp = smid >> 1;
            uint32_t pr = tp < 32 ? (tp & 7) * 8 + (tp >> 3) : tp < 60 ? (1 + (tp - 32) % 7) * 8 + 4 + (tp - 32) / 7 : tp < 62 ? 4 + tp : tp < 66 ? tp - 58 : 0;
            while (atomicExch(g_slot + pr, epoch + 1) == epoch + 1) pr = pr == 65 ? 0 : pr + 1;
            #pragma unroll
            for (int r = 0; r < 2; r++)
                asm volatile("st.async.weak.shared::cluster.mbarrier::complete_tx::bytes.u32 [%0], %1, [%2];" :: "r"(mapa(sm + OFF_MISC, r)), "r"(pr), "r"(mapa(bars + 8 * BAR_ROLE, r)) : "memory");
        }
        __syncwarp();
        if (t == 0) {
            asm volatile("prefetch.tensormap [%0];" :: "l"(&tm_w1a) : "memory");
            asm volatile("prefetch.tensormap [%0];" :: "l"(&tm_h3a) : "memory"); asm volatile("prefetch.tensormap [%0];" :: "l"(&tm_w1b) : "memory");
            asm volatile("prefetch.tensormap [%0];" :: "l"(&tm_h3b) : "memory"); asm volatile("prefetch.tensormap [%0];" :: "l"(&tm_w2) : "memory");
            asm volatile("prefetch.tensormap [%0];" :: "l"(&tm_o) : "memory"); asm volatile("prefetch.tensormap [%0];" :: "l"(&tm_h3s) : "memory");
        }
        if (t == 32 && rowcta) {
            for (int it = 0; (int)(ld_acquire(g_cnt + CNT_NC * 32) - (epoch + 1) * 4) < 0; it++) { __nanosleep(100); if (it > SPIN_LIMIT) __trap(); }
            fence_async_g();
            mbar_expect(bars + 8 * BAR_NC, 3584);
            bulk_load(sm + OFF_MODC, p.scr->modc, 3584, bars + 8 * BAR_NC);
            PROFT(29);
        }
        __syncwarp();
    } else if (rowcta && warp < 11) {
        const int nw = !(b & 1) ? 10 : (b & 7) == 7 ? 9 : 8;
        const int cm = (b >> 3) * 288 + (b & 7) * 32, cx = (b & 1) ? 4608 + 8 * (b >> 3) : (b >> 3) * 288 + 256 + 4 * (b & 7);
        auto load_in = [&]() {
            if (elect()) {
                mbar_expect(bars + 8 * BAR_XB, nw > 8 ? 20480 : 16384);
                tma2(sm + OFF_STAGE, &tm_t, cm, 0, bars + 8 * BAR_XB);
                if (nw > 8) tma2(sm + OFF_STX, &tm_tx, cx, 0, bars + 8 * BAR_XB);
            }
            __syncwarp();
        };
        if (warp == 10) { fence_async_s(); spin_until(t_st + X1D); load_in(); }
        uint32_t tb[QB * 4], wre[4][2], wim[4][2];
        if (warp < nw) {
            mbar_wait(bars + 8 * BAR_TAB2, 0);
            load_tab<QB>(tb, sm + OFF_TAB + QA * 512 + lane * 16);
            mbar_wait(bars + 8 * BAR_W, 0);
            const int off = wc0 & 7;
            const uint32_t wa = sm + OFF_WRAW + lane * 112 + ((off >> 1) + 2 * warp) * 4, sh = (off & 1) * 16;
            #pragma unroll
            for (int c = 0; c < 2; c++)
                #pragma unroll
                for (int h = 0; h < 2; h++) {
                    uint32_t y[2][2];
                    #pragma unroll
                    for (int e = 0; e < 2; e++) {
                        const uint32_t a = wa + c * 14336 + (h + 2 * e) * 3584, x0 = lds32(a), x1 = lds32(a + 4), x2 = lds32(a + 8);
                        y[e][0] = __funnelshift_r(x0, x1, sh); y[e][1] = __funnelshift_r(x1, x2, sh);
                    }
                    #pragma unroll
                    for (int x = 0; x < 4; x++) {
                        const uint32_t v = (x & 1) ? pack_h(bf_hi(y[0][x >> 1]), bf_hi(y[1][x >> 1])) : pack_h(bf_lo(y[0][x >> 1]), bf_lo(y[1][x >> 1]));
                        if (c) wim[x][h] = v; else wre[x][h] = v;
                    }
                }
        }
        const uint32_t ca = warp < 8 ? sm + OFF_STAGE + lane * 128 + (warp ^ (lane & 7)) * 16 : sm + OFF_STX + lane * 32 + ((warp ^ g) & 1) * 16, cs = warp < 8 ? 4096 : 1024;
        uint32_t V[4][4];
        for (int it = 0;; it++) {
            mbar_wait(bars + 8 * BAR_XB, it & 1);
            uint32_t ok = 1;
            if (warp < nw) {
                #pragma unroll
                for (int u = 0; u < 4; u++) { uint4 t4 = lds128(ca + u * cs); V[u][0] = t4.x; V[u][1] = t4.y; V[u][2] = t4.z; V[u][3] = t4.w; ok &= t4.x; }
            }
            asm volatile("{.reg .pred p; setp.ne.u32 p, %0, 0; bar.red.and.pred p, 1, 352, p; selp.u32 %0, 1, 0, p;}" : "+r"(ok) :: "memory");
            if (ok) break;
            if (warp == 10) { load_in(); hb(); }
            if (it > SPIN_LIMIT / 64) __trap();
        }
        PROF0(7);
        if (warp < nw) {
            uint32_t zr[4][2], zi[4][2];
            #pragma unroll
            for (int x = 0; x < 4; x++) {
                uint32_t er = 0, ei = 0, or_ = 0, oi = 0;
                mma_h(er, ei, tb[0], tb[1], tb[2], tb[3], V[0][x], V[1][x]);
                mma_h(or_, oi, tb[4], tb[5], tb[6], tb[7], V[2][x], V[3][x]);
                uint32_t r0 = hadd2(er, or_), r1 = hsub2(er, or_), i0 = hadd2(ei, oi), i1 = hsub2(ei, oi);
                cmul_neg(r0, i0, tb[8], tb[9]); cmul_neg(r1, i1, tb[10], tb[11]);
                uint32_t xr0 = 0, xr1 = 0, xi0 = 0, xi1 = 0;
                mma_h(xr0, xr1, r0, r1, i0, i1, tb[12], tb[13]);
                mma_h(xi0, xi1, r0, r1, i0, i1, tb[14], tb[12]);
                cmul_pos(xr0, xi0, wre[x][0], wim[x][0]); cmul_pos(xr1, xi1, wre[x][1], wim[x][1]);
                r0 = 0; i0 = 0; r1 = 0; i1 = 0;
                mma_h(r0, i0, tb[12], tb[13], tb[14], tb[12], xr0, xi0);
                mma_h(r1, i1, tb[12], tb[13], tb[14], tb[12], xr1, xi1);
                cmul_pos(r0, i0, tb[15], tb[16]); cmul_pos(r1, i1, tb[17], tb[18]);
                zr[x][0] = hadd2(r0, r1); zr[x][1] = hsub2(r0, r1); zi[x][0] = hadd2(i0, i1); zi[x][1] = hsub2(i0, i1);
            }
            #pragma unroll
            for (int nt = 0; nt < 4; nt++) {
                uint4 o = make_uint4(0, 0, 0, 0);
                const int h = nt >> 1;
                mma_h(o.x, o.y, zr[0][h], zr[1][h], zi[0][h], zi[1][h], tb[19 + 2 * nt], tb[20 + 2 * nt]);
                mma_h(o.z, o.w, zr[2][h], zr[3][h], zi[2][h], zi[3][h], tb[19 + 2 * nt], tb[20 + 2 * nt]);
                o.x &= ~1u;
                sts128(ca + nt * cs, o);
            }
        }
        fence_async_s();
        bar_sync(1, 352);
        t_st = clk32();
        PROF0(8);
        if (warp == 10 && elect()) {
            asm volatile("cp.async.bulk.tensor.2d.global.shared::cta.bulk_group [%0, {%2, %3}], [%1];" :: "l"(&tm_t), "r"(sm + OFF_STAGE), "r"(cm), "r"(0) : "memory");
            if (nw > 8) asm volatile("cp.async.bulk.tensor.2d.global.shared::cta.bulk_group [%0, {%2, %3}], [%1];" :: "l"(&tm_tx), "r"(sm + OFF_STX), "r"(cx), "r"(0) : "memory");
            asm volatile("cp.async.bulk.commit_group;" ::: "memory");
            asm volatile("cp.async.bulk.wait_group.read 0;" ::: "memory");
        }
        __syncwarp();
    }

    if (warp >= 10) { mbar_wait(bars + 8 * BAR_ROLE, 0); role = __shfl_sync(~0u, lds32(sm + OFF_MISC), 0); fence_async_s(); }
    auto first_a = [&]() {
        if (warp >= 10 && role < 64 && elect()) {
            const int it = warp - 10, hi = it >= 3; const bool p2 = it - 3 * hi == 2;
            tma4(sm + OFF_A + it * A_BYTES, p2 ? &tm_w1b : &tm_w1a, 0, 0, p2 ? 64 * rank + 8 * hi : 4 * (it - hi),
                 9 * (role >> 3) + (p2 ? 8 : (role & 4) + 2 * rank), bars + 8 * (BAR_FULL + it));
        }
        __syncwarp();
    };
    if (!rowcta) first_a();
    else {
        uint32_t tc[QC * 4];
        mbar_wait(bars + 8 * BAR_TAB2, 0);
        load_tab<QC>(tc, sm + OFF_TAB + (QA + QB) * 512 + lane * 16);
        if (warp < 10) {
            uint32_t b3[16];
            load_tab<4>(b3, sm + OFF_B3 + 2048 + lane * 16);
            uint4 V[4], o[4];
            const bool tact = warp < 9 || g == 0;
            spin_until(t_st + X2D);
            #pragma unroll
            for (int u = 0; u < 4; u++) V[u] = make_uint4(tact, 0, 0, 0);
            for (int it = 0; __any_sync(~0u, (V[0].x | V[1].x | V[2].x | V[3].x) & 1u); it++) {
                #pragma unroll
                for (int u = 0; u < 4; u++) if (V[u].x & 1u) V[u] = ldx128(tptr + u * tstr);
                hb();
                if (it > SPIN_LIMIT) __trap();
            }
            PROF0(10);
            radix16(V, b3, o);
            if (tact) {
                #pragma unroll
                for (int nt = 0; nt < 4; nt++) sts128(scol + nt * (16 * SPEC_P), o[nt]);
            }
        }
        __syncthreads();
        PROF0(11);
        first_a();
        const uint32_t srow = sm + OFF_SPEC + warp * (SPEC_P * 4);
        uint32_t re[2][3], im[2][3];
        #pragma unroll
        for (int mt = 0; mt < 3; mt++) {
            const uint32_t a = srow + (g + 72 * q + 8 * mt) * 4, a2 = srow + (288 - g - 72 * q - 8 * mt) * 4;
            const uint32_t z0 = lds32(a), z1 = lds32(a + 144), z2 = lds32(a2), z3 = lds32(a2 - 144);
            #pragma unroll
            for (int m2 = 0; m2 < 2; m2++) {
                re[m2][mt] = 0; im[m2][mt] = 0;
                const uint32_t sg = m2 ? 0x3C00BC00u : 0xBC003C00u;
                mma_h(re[m2][mt], im[m2][mt], tc[m2 * 4], tc[m2 * 4 + 1], tc[m2 * 4 + 2], tc[m2 * 4 + 3], hfma2(z2, sg, z0), hfma2(z3, sg, z1));
                cmul_pos(re[m2][mt], im[m2][mt], tc[8 + (m2 * 3 + mt) * 2], tc[9 + (m2 * 3 + mt) * 2]);
            }
        }
        uint32_t md[28];
        mbar_wait(bars + 8 * BAR_NC, 0);
        load_tab<7>(md, sm + OFF_MODC + lane * 16);
        float y[5][4];
        #pragma unroll
        for (int nt = 0; nt < 5; nt++) {
            y[nt][0] = y[nt][1] = y[nt][2] = y[nt][3] = 0.f;
            #pragma unroll
            for (int mt = 0; mt < 3; mt++)
                mma_f(y[nt], re[0][mt], re[1][mt], im[0][mt], im[1][mt], tc[20 + (mt * 5 + nt) * 2], tc[21 + (mt * 5 + nt) * 2]);
        }
        #pragma unroll
        for (int i = 0; i < 9; i++) xw[i] = bfma2(md[i], pack_bf(y[i >> 1][i & 1], y[i >> 1][2 + (i & 1)]), xw[i]);
        float r, mr;
        ln_stats(xw, g, q, r, mr);
        uint32_t h[9], r2 = pack_bf(r, r), m2 = pack_bf(mr, mr);
        #pragma unroll
        for (int i = 0; i < 9; i++) h[i] = bfma2(bfma2(xw[i], r2, m2), md[18 + i], md[9 + i]);
        ln_stats(h, g, q, r, mr);
        r2 = pack_bf(r, r); m2 = pack_bf(mr, mr);
        {
            const int n7 = 2 * q + (g >> 2);
            const uint32_t a = sm + OFF_STAGE + (warp >> 3) * 9216 + n7 * 128 + ((warp & 7) ^ n7) * 16 + (g & 3) * 4;
            #pragma unroll
            for (int i = 0; i < 9; i++) sts32(a + i * 1024, bfma2(h[i], r2, m2));
        }
        fence_async_s();
        __syncthreads();
        PROF0(12);
        if (tid == 0) {
            asm volatile("cp.async.bulk.tensor.4d.global.shared::cta.bulk_group [%0, {%2, %2, %2, %3}], [%1];" :: "l"(&tm_h3s), "r"(sm + OFF_STAGE), "r"(0), "r"(b) : "memory");
            asm volatile("cp.async.bulk.commit_group;" ::: "memory");
        }
        #pragma unroll
        for (int i = 0; i < 9; i++) sts32(sm + OFF_X1 + warp * 1152 + (32 * i + 8 * q + g) * 4, xw[i]);
    }
    __syncthreads();
    if (rowcta) {
        if (tid == 0) { asm volatile("cp.async.bulk.wait_group 0;" ::: "memory"); fence_async_g(); red_release(g_cnt + CNT_H3 * 32); }
        PROF0(13);
        if (warp == 15) {
            __nanosleep(X1DELAY);
            #pragma unroll 1
            for (int r = 0; r < 16; r++) {
                uint4* dst = (uint4*)(p.out + (size_t)(b + 128 * r) * D_) + lane;
                const uint32_t src = sm + OFF_X1 + r * 1152 + lane * 16;
                dst[0] = lds128(src); dst[32] = lds128(src + 512); if (lane < 8) dst[64] = lds128(src + 1024);
                const uint32_t t1 = clk32(); while ((int)(clk32() - t1) < X1PACE) __nanosleep(50);
            }
            __syncwarp();
            if (lane == 0) { fence_async_g(); red_release(g_cnt + CNT_X1 * 32); }
        }
    }
    role = __shfl_sync(~0u, lds32(sm + OFF_MISC), 0);
    if (role >= 64) { if (warp == 0) PROFDUMP(); return; }

    const int gi = role >> 3, dt = role & 3, c2 = (role >> 2) & 1;
    const int wg = warp >> 2, wi = warp & 3;
    if (wg == 3) {
        uint32_t so = 0, eph = 1;
        #define RING_STEP(BYTES, OFF, ISSUE) do { \
            mbar_wait(bars + 8 * BAR_EMPTY + so, eph); \
            if (elect()) { const uint32_t fb = bars + 8 * BAR_FULL + so, dst = sm + (OFF) + so * ((BYTES) / 8); mbar_expect(fb, BYTES); ISSUE; } \
            so += 8; if (so == 8 * NST) { so = 0; eph ^= 1; } } while (0)
        if (warp == 12) {
            eph = 0;
            const int fb1 = 9 * gi + 4 * c2 + 2 * rank, sb2 = 4 * gi + 2 * c2;
            #pragma unroll 1
            for (int j = 16; j < 128; j += 4) {
                RING_STEP(A_BYTES, OFF_A, tma4(dst, &tm_w1a, 0, 0, j, fb1, fb));
                if (j < 64) { if (j & 4) RING_STEP(A_BYTES, OFF_A, tma4(dst, &tm_w1b, 0, 0, 64 * rank + j - 4, 9 * gi + 8, fb)); }
                else if (PF2 && (j & 28) == 4 * (role & 7) && elect())
                    asm volatile("cp.async.bulk.prefetch.tensor.3d.L2.global [%0, {%1, %2, %3}];" :: "l"(&tm_w2), "r"(0), "r"(64 * g2_kb(dt + ((j >> 3) & 4), rank)), "r"(sb2) : "memory");
            }
            #pragma unroll 1
            for (int n = 0; n < 36; n++) {
                if (n == G2E) mbar_wait(bars + 8 * BAR_REL, 0);
                if (n == A2E) { mbar_wait(bars + 8 * (BAR_UOK + 1), 0); if (A2D) spin_until(clk32() + A2D); }
                RING_STEP(A_BYTES, OFF_A, tma3(dst, &tm_w2, 0, 64 * g2_kb(n, rank), sb2, fb));
            }
        } else if (warp == 13) {
            const uint32_t e1 = __shfl_sync(~0u, epoch + 1, 0);
            fence_async_s();
            wait_count<0>(g_cnt + CNT_H3 * 32, e1 * 128);
            fence_async_g();
            if (lane == 0) PROFT(14);
            #pragma unroll 1
            for (int j = 0; j < 128; j += 4) {
                RING_STEP(B_BYTES, OFF_B, tma3(dst, &tm_h3a, 0, 18 * dt, j, fb));
                if (j < 64 && (j & 4)) RING_STEP(B_BYTES, OFF_B, tma3(dst, &tm_h3b, 0, 18 * dt + 9 * c2, 64 * rank + j - 4, fb));
            }
            int n = 0;
            #pragma unroll 1
            for (int cls = 0; cls < 3; cls++) {
                mbar_wait(bars + 8 * (BAR_UOK + cls), 0);
                fence_async_g();
                if (cls == 1 && lane == 0) PROFT(19);
                if (cls == 0 && lane == 0) PROFT(22);
                #pragma unroll 1
                for (; n < 16 * cls + 4; n++) {
                    if (n == G2E) mbar_wait(bars + 8 * BAR_REL, 0);
                    RING_STEP(B_BYTES, OFF_B, bulk_load(dst, g_U + (g2_kb(n, rank) * 4 + dt) * 1152, B_BYTES, fb));
                }
            }
            if (role == 0 && rank == 0 && lane == 0) st_relaxed(g_cnt + CNT_EPOCH * 32, e1);
        } else if (warp == 15) {
            if (elect()) mbar_arrive_remote(mapa(bars + 8 * BAR_HOLD, rank ^ 1));
            __syncwarp();
            bar_sync(6, 160);
            mbar_wait(bars + 8 * BAR_W1GO, 0);
            if (elect()) {
                char* dst = (char*)(g_U + ((9 * gi + 4 * c2 + 2 * rank + 1) * 4 + dt) * 1152);
                #pragma unroll 1
                for (int i = 0; i < W1N; i++) {
                    asm volatile("cp.async.bulk.global.shared::cta.bulk_group [%0], [%1], %2;" :: "l"(dst + i * (18432 / W1N)), "r"(sm + OFF_X1 + i * (18432 / W1N)), "n"(18432 / W1N) : "memory");
                    const uint32_t t1 = clk32(); while ((int)(clk32() - t1) < W1P) {}
                }
                asm volatile("cp.async.bulk.commit_group;" ::: "memory");
                asm volatile("cp.async.bulk.wait_group 0;" ::: "memory");
                fence_async_g(); red_release(g_cnt + (CNT_U + 16) * 32);
                #pragma unroll 1
                for (int n = 0; n < 4; n++) { __nanosleep(300); tma2(sm + OFF_X1 + n * 4608, &tm_o, 144 * dt, 256 * gi + 128 * c2 + 64 * (rank ^ 1) + 16 * n, bars + 8 * BAR_XT); }
            }
        } else {
            const uint32_t e1 = epoch + 1;
            if (lane == 0) {
                __nanosleep(4000);
                wait_count<200>(g_cnt + CNT_NC * 32, e1 * 4); wait_count<200>(g_cnt + (CNT_NC + 1) * 32, e1 * 2);
                fence_async_g();
                mbar_expect(bars + 8 * BAR_GB, 1152);
                bulk_load(sm + OFF_GB, p.scr->modc + 896, 1152, bars + 8 * BAR_GB);
                wait_count<200>(g_cnt + CNT_X1 * 32, e1 * 128);
                wait_count<50>(g_cnt + (CNT_U + dt * 2 + rank) * 32, e1 * 16);
                mbar_arrive(bars + 8 * BAR_UOK);
            }
            __syncwarp();
            bar_sync(4, 160);
            if (lane == 0) {
                fence_async_g(); red_release(g_cnt + (CNT_U + 8) * 32);
                mbar_arrive(bars + 8 * BAR_REL);
                PROFT(17);
                wait_count<0>(g_cnt + (CNT_U + 8) * 32, e1 * 128);
                mbar_arrive(bars + 8 * (BAR_UOK + 1));
                __nanosleep(1000);
                wait_count<100>(g_cnt + (CNT_U + 16) * 32, e1 * 128);
                mbar_arrive(bars + 8 * (BAR_UOK + 2));
            }
        }
    } else if (wg == 2) {
        float d0[36];
        const float bias = bf_lo(ldg_nc16(p.b1 + 576 * gi + 512 + 16 * wi + g + 8 * rank));
        for (int it = 0; it < 200 && !__any_sync(~0u, mbar_test(bars + 8 * BAR_FULL, 0)); it++) { hb(); __nanosleep(100); }
        const bool lead = wi == 0 && elect();
        #pragma unroll 1
        for (int i = 0; i < 8; i++) {
            const uint32_t s = P2S + 3 * (i & 1);
            mbar_wait(bars + 8 * BAR_FULL + 8 * s, (i >> 1) & 1);
            const uint32_t da = desc_lo(sm + OFF_A, 8192) + s * (A_BYTES / 16), db = desc_lo(sm + OFF_B, 128) + s * (B_BYTES / 16);
            WG_FENCE();
            wgmma72(d0, da, db, i);
            #pragma unroll
            for (int k = 1; k < 8; k++) wgmma72(d0, da + k * 128, db + k * 144, 1);
            WG_COMMIT();
            WG_WAIT(0);
            if (lead) mbar_arrive_n(bars + 8 * BAR_EMPTY + 8 * s, 2);
        }
        if (lead) PROFT(18);
        const uint32_t slot = sm + OFF_P2R + (tid & 127) * 16, ra = mapa(slot, rank ^ 1), rb = mapa(bars + 8 * BAR_P2R, rank ^ 1);
        float sv[18];
        #pragma unroll
        for (int i = 0; i < 18; i++) { const float lo = d0[4 * (i >> 1) + (i & 1)], hi = d0[4 * (i >> 1) + 2 + (i & 1)];
            sv[i] = rank ? lo : hi; d0[4 * (i >> 1) + (i & 1)] = (rank ? hi : lo) + bias; }
        mbar_wait(bars + 8 * BAR_HOLD, 0);
        #pragma unroll
        for (int i = 0; i < 4; i++)
            asm volatile("st.async.weak.shared::cluster.mbarrier::complete_tx::bytes.v4.f32 [%0], {%1,%2,%3,%4}, [%5];"
                :: "r"(ra + i * 2048), "f"(sv[4 * i]), "f"(sv[4 * i + 1]), "f"(sv[4 * i + 2]), "f"(sv[4 * i + 3]), "r"(rb) : "memory");
        asm volatile("st.async.weak.shared::cluster.mbarrier::complete_tx::bytes.v2.f32 [%0], {%1,%2}, [%3];" :: "r"(ra + 8192), "f"(sv[16]), "f"(sv[17]), "r"(rb) : "memory");
        mbar_wait(bars + 8 * BAR_P2R, 0);
        #pragma unroll
        for (int i = 0; i < 5; i++) {
            const uint4 v = lds128(slot + i * 2048);
            d0[8 * i] += __uint_as_float(v.x); d0[8 * i + 1] += __uint_as_float(v.y);
            if (i < 4) { d0[8 * i + 4] += __uint_as_float(v.z); d0[8 * i + 5] += __uint_as_float(v.w); }
        }
        asm volatile("bar.arrive 5, 256;" ::: "memory");
        gelu_store<0>(d0, (char*)(g_U + ((9 * gi + 8) * 4 + dt) * 1152) + wi * 4608 + rank * 2304 + c2 * 1152 + g * 16, q);
        bar_sync(8, 128);
        if (lead) { fence_async_g(); red_release(g_cnt + (CNT_U + dt * 2 + (gi >> 2)) * 32); PROFT(26); }
    } else {
        float d[72];
        const bool lead = wi == 0 && elect();
        const uint32_t da0 = desc_lo(sm + OFF_A + wg * 8192, 8192);
        const bool owner = (uint32_t)wg == rank;
        const int srow = 256 * gi + 128 * c2 + 64 * wg + 16 * wi;
        const uint32_t b2w0 = ldg_nc16(p.b2 + srow + g), b2w1 = ldg_nc16(p.b2 + srow + g + 8);
        {
            const int fr = 576 * gi + 256 * c2 + 128 * rank + 64 * wg + 16 * wi + g;
            const float bias0 = bf_lo(ldg_nc16(p.b1 + fr)), bias1 = bf_lo(ldg_nc16(p.b1 + fr + 8));
            #pragma unroll
            for (int i = 0; i < 72; i++) d[i] = (i & 2) ? bias1 : bias0;
            const uint32_t db1 = desc_lo(sm + OFF_B, 128);
            mainloop<DHI_H3, 0, IT_P1, false, true, false>(d, bars, da0, db1, lead, [&](int) {});
            mainloop<DHI_H3, IT_P1, IT_G2 - LEAD1, false, false, false>(d, bars, da0, db1, lead, [&](int) {});
            constexpr uint32_t EB = 8 * (BAR_EMPTY + (IT_G2 - LEAD1 - 1) % NST);
            if (wg == 1) { WG_WAIT(0); if (lead) mbar_arrive(bars + EB); bar_sync(9, 256); }
            mainloop<DHI_H3, IT_G2 - LEAD1, IT_G2, false, true, true>(d, bars, da0, db1, lead, [&](int i) {
                if (wg == 0) { if (i == IT_G2 - LEAD1 && lead) mbar_arrive(bars + EB); if (i == IT_G2 - 1) asm volatile("bar.arrive 9, 256;" ::: "memory"); } });
            PROF0(16);
            if (wg == 1) bar_sync(5, 256);
            char* const ub = (wg == 0 ? (char*)(g_U + ((9 * gi + 4 * c2 + 2 * rank) * 4 + dt) * 1152) : (char*)__cvta_shared_to_generic(sm + OFF_X1)) + wi * 4608 + g * 16;
            gelu_store<0>(d, ub, q); gelu_store<2>(d, ub + 2304, q); gelu_store<36>(d, ub + 1152, q); gelu_store<38>(d, ub + 3456, q);
            PROF0(27);
            if (wg == 0) asm volatile("bar.arrive 4, 160;" ::: "memory");
            else { fence_async_s(); asm volatile("bar.arrive 6, 160;" ::: "memory"); }
        }
        const uint32_t db0 = desc_lo(sm + OFF_B, 2304);
        constexpr int IT_L = IT_END - NST, IT_X = IT_L - 4;
        mainloop<DHI_U, IT_G2, IT_X, true, true, false>(d, bars, da0, db0, lead,
            [&](int i) { if (i == IT_G2 + W1S && wg == 0 && lead) mbar_arrive(bars + 8 * BAR_W1GO); });
        const uint32_t ga0 = sm + OFF_GB + (144 * dt + 8 * q) * 2, tile = sm + OFF_X1 + wi * 4608, to = g * 288 + q * 16;
        #define QOFF(i_) (((i_) >> 2) * 2304 + 144 * (((i_) >> 1) & 1) + 64 * ((i_) & 1))
        #define SOFF(k_) (((k_) >> 1) * 2304 + 144 * ((k_) & 1) + 128 - 12 * q)
        #define DIDX(i_, k_) ((i_) < 8 ? 36 * (((i_) >> 1) & 1) + 16 * ((i_) & 1) + 4 * (k_) + 2 * ((i_) >> 2) : 36 * ((k_) & 1) + 32 + 2 * ((k_) >> 1))
        #define FIN(k_, f_) bfma2(g4.f_, pack_bf(d[DIDX(i, k_)], d[DIDX(i, k_) + 1]), xq[i].f_)
        uint4 xq[9];
        auto load_g = [&](int i) { uint4 r; if (i < 4) r = lds128(ga0 + QOFF(i)); else { r.x = r.z = lds32(ga0 + SOFF(0)); r.y = r.w = lds32(ga0 + SOFF(1)); } return r; };
        mainloop<DHI_U, IT_X, IT_L, false, false, false>(d, bars, da0, db0, lead, [&](int i) {
            if (!owner) {
                const uint32_t xa = tile + to;
                if (i == IT_X) { mbar_wait(bars + 8 * BAR_XT, 0); xq[0] = lds128(xa + QOFF(0)); xq[4] = lds128(xa + QOFF(4)); xq[1] = lds128(xa + QOFF(1)); }
                else if (i == IT_X + 1) { xq[5] = lds128(xa + QOFF(5)); xq[2] = lds128(xa + QOFF(2)); xq[6] = lds128(xa + QOFF(6)); }
                else if (i == IT_X + 2) { xq[3] = lds128(xa + QOFF(3)); xq[7] = lds128(xa + QOFF(7));
                    xq[8] = make_uint4(lds32(xa + SOFF(0)), lds32(xa + SOFF(1)), lds32(xa + SOFF(2)), lds32(xa + SOFF(3))); }
                else if (i == IT_X + 3) { if (elect()) mbar_arrive_remote(mapa(bars + 8 * BAR_DONE, rank ^ 1)); }
            } });
        if (owner) { WG_WAIT(0); if (lead) mbar_arrive(bars + 8 * (BAR_EMPTY + (IT_L - 1) % NST)); bar_sync(7, 256); }
        #pragma unroll
        for (int i = IT_L; i < IT_END; i++) {
            mbar_wait(bars + 8 * (BAR_FULL + i % NST), (i / NST) & 1);
            WG_FENCE();
            #pragma unroll
            for (int k = 0; k < 4; k++) wgmma144<DHI_U>(d, da0 + (i % NST) * (A_BYTES / 16) + k * 128, db0 + (i % NST) * (B_BYTES / 16) + k * 288, 1);
            WG_COMMIT();
            if (i == IT_L) { WG_WAIT(1); if (lead && !owner) mbar_arrive(bars + 8 * (BAR_EMPTY + (IT_L - 1) % NST)); }
        }
        PROF0(9);
        mbar_wait(bars + 8 * BAR_GB, 0);
        if (!owner) {
            const uint32_t ra = mapa(tile + lane * 16, rank ^ 1), rb = mapa(bars + 8 * BAR_RECV, rank ^ 1);
            mbar_wait(bars + 8 * BAR_DONE, 0);
            uint4 gn = load_g(0);
            WG_WAIT(1);
            asm volatile("bar.arrive 7, 256;" ::: "memory");
            WG_WAIT(0);
            #pragma unroll
            for (int i = 0; i < 72; i++) d[i] = fmaf(bf_lo((i & 2) ? b2w1 : b2w0), 2.f, d[i]);
            #pragma unroll
            for (int j = 0; j < 5; j++) {
                const uint4 g4 = gn;
                if (j < 4) gn = load_g(j + 1);
                #pragma unroll
                for (int i = j < 4 ? j : 8; i < 9; i += 4) if (i < 8 || j == 4)
                    asm volatile("st.async.weak.shared::cluster.mbarrier::complete_tx::bytes.v4.b32 [%0], {%1,%2,%3,%4}, [%5];"
                        :: "r"(ra + i * 512), "r"(FIN(0, x)), "r"(FIN(1, y)), "r"(FIN(2, z)), "r"(FIN(3, w)), "r"(rb) : "memory");
            }
            PROF0(6);
            if (warp == 0) PROFDUMP();
            return;
        }
        PROF0(24);
        mbar_wait(bars + 8 * BAR_RECV, 0);
        #pragma unroll
        for (int i = 0; i < 9; i++) xq[i] = lds128(tile + lane * 16 + i * 512);
        uint4 gn = load_g(0);
        WG_WAIT(0);
        __syncwarp();
        PROF0(21);
        #pragma unroll
        for (int j = 0; j < 5; j++) {
            const uint4 g4 = gn;
            if (j < 4) gn = load_g(j + 1);
            #pragma unroll
            for (int i = j < 4 ? j : 8; i < 9; i += 4) if (i < 8 || j == 4) {
                const uint4 o = make_uint4(FIN(0, x), FIN(1, y), FIN(2, z), FIN(3, w));
                if (i < 8) sts128(tile + to + QOFF(i), o);
                else { sts32(tile + to + SOFF(0), o.x); sts32(tile + to + SOFF(1), o.y); sts32(tile + to + SOFF(2), o.z); sts32(tile + to + SOFF(3), o.w); }
            }
        }
        fence_async_s();
        __syncwarp();
        if (elect()) {
            asm volatile("cp.async.bulk.tensor.2d.global.shared::cta.bulk_group [%0, {%2, %3}], [%1];" :: "l"(&tm_o), "r"(tile), "r"(144 * dt), "r"(srow) : "memory");
            asm volatile("cp.async.bulk.commit_group;" ::: "memory");
            asm volatile("cp.async.bulk.wait_group.read 0;" ::: "memory");
        }
        PROF0(23);
        if (warp == 0) { __syncwarp(); PROFDUMP(); }
    }
}

typedef CUresult (*EncodeFn)(CUtensorMap*, CUtensorMapDataType, cuuint32_t, void*, const cuuint64_t*, const cuuint64_t*, const cuuint32_t*,
                             const cuuint32_t*, CUtensorMapInterleave, CUtensorMapSwizzle, CUtensorMapL2promotion, CUtensorMapFloatOOBfill);

void encode(EncodeFn fn, CUtensorMap* m, CUtensorMapDataType dt, int rank, const void* ptr, const cuuint64_t* dims, const cuuint64_t* strides,
            const cuuint32_t* box, CUtensorMapSwizzle sw, CUtensorMapL2promotion promo = CU_TENSOR_MAP_L2_PROMOTION_L2_128B) {
    const cuuint32_t es[5] = {1, 1, 1, 1, 1};
    fn(m, dt, rank, (void*)ptr, dims, strides, box, es, CU_TENSOR_MAP_INTERLEAVE_NONE, sw, promo, CU_TENSOR_MAP_FLOAT_OOB_FILL_NONE);
}

}

extern "C" void kernel_launch(void* const* d_in, const int* in_sizes, int n_in, void* d_out, int out_size) {
    (void)in_sizes; (void)n_in; (void)out_size;
    Params p;
    p.x = (const uint16_t*)d_in[0]; p.wr = (const uint16_t*)d_in[1]; p.wi = (const uint16_t*)d_in[2];
    p.w1 = (const uint16_t*)d_in[4]; p.b1 = (const uint16_t*)d_in[5]; p.w2 = (const uint16_t*)d_in[6]; p.b2 = (const uint16_t*)d_in[7];
    p.c = (const uint16_t*)d_in[8]; p.wmod = (const uint16_t*)d_in[9]; p.out = (uint16_t*)d_out;

    void* fnp = nullptr; cudaDriverEntryPointQueryResult qr;
    cudaGetDriverEntryPoint("cuTensorMapEncodeTiled", &fnp, cudaEnableDefault, &qr);
    EncodeFn fn = (EncodeFn)fnp;
    cudaGetSymbolAddress((void**)&p.scr, g_scr); cudaGetSymbolAddress((void**)&p.tab, g_tab);
    void* h3p = p.scr->h3;
    CUtensorMap tw1a, tw1b, tw2, th3a, th3b, twr, twi, twm, tt, ttx, to, th3s, tws;
    {
        const cuuint64_t dims[4] = {64, 16, 128, 72}, st[3] = {128ull * F_ * 2, (cuuint64_t)F_ * 2, 128};
        const cuuint32_t ba[4] = {64, 16, 4, 2}, bb[4] = {64, 16, 8, 1};
        encode(fn, &tw1a, CU_TENSOR_MAP_DATA_TYPE_BFLOAT16, 4, p.w1, dims, st, ba, CU_TENSOR_MAP_SWIZZLE_128B);
        encode(fn, &tw1b, CU_TENSOR_MAP_DATA_TYPE_BFLOAT16, 4, p.w1, dims, st, bb, CU_TENSOR_MAP_SWIZZLE_128B);
    }
    {
        const cuuint64_t dims[3] = {64, F_, 32}, st[2] = {(cuuint64_t)S_ * 2, 128};
        const cuuint32_t bx[3] = {64, 64, 2};
        encode(fn, &tw2, CU_TENSOR_MAP_DATA_TYPE_BFLOAT16, 3, p.w2, dims, st, bx, CU_TENSOR_MAP_SWIZZLE_128B);
    }
    {
        const cuuint64_t dims[3] = {64, 72, 128}, st[2] = {256, 18432};
        const cuuint32_t ba[3] = {64, 18, 4}, bb[3] = {64, 9, 8};
        encode(fn, &th3a, CU_TENSOR_MAP_DATA_TYPE_UINT32, 3, h3p, dims, st, ba, CU_TENSOR_MAP_SWIZZLE_NONE);
        encode(fn, &th3b, CU_TENSOR_MAP_DATA_TYPE_UINT32, 3, h3p, dims, st, bb, CU_TENSOR_MAP_SWIZZLE_NONE);
    }
    {
        const cuuint64_t dims[4] = {32, 72, 2, 128}, st[3] = {256, 128, 18432};
        const cuuint32_t bx[4] = {32, 72, 2, 1};
        encode(fn, &th3s, CU_TENSOR_MAP_DATA_TYPE_UINT32, 4, h3p, dims, st, bx, CU_TENSOR_MAP_SWIZZLE_128B, CU_TENSOR_MAP_L2_PROMOTION_NONE);
    }
    {
        const cuuint64_t dims[3] = {4624, 4, 32}, st[2] = {9248 * 32, 9248};
        const cuuint32_t bx[3] = {56, 4, 32};
        encode(fn, &twr, CU_TENSOR_MAP_DATA_TYPE_BFLOAT16, 3, p.wr, dims, st, bx, CU_TENSOR_MAP_SWIZZLE_NONE);
        encode(fn, &twi, CU_TENSOR_MAP_DATA_TYPE_BFLOAT16, 3, p.wi, dims, st, bx, CU_TENSOR_MAP_SWIZZLE_NONE);
    }
    {
        const cuuint64_t dims[2] = {3456, 576}, st[1] = {6912};
        const cuuint32_t bx[2] = {32, 144};
        encode(fn, &tws, CU_TENSOR_MAP_DATA_TYPE_BFLOAT16, 2, p.wmod, dims, st, bx, CU_TENSOR_MAP_SWIZZLE_64B);
    }
    {
        const cuuint64_t dims[3] = {64, 576, 54}, st[2] = {6912, 128};
        const cuuint32_t bx[3] = {64, 32, 7};
        encode(fn, &twm, CU_TENSOR_MAP_DATA_TYPE_BFLOAT16, 3, p.wmod, dims, st, bx, CU_TENSOR_MAP_SWIZZLE_128B);
    }
    {
        const cuuint64_t dims[2] = {TP, 128}, st[1] = {TP * 4};
        const cuuint32_t ba[2] = {32, 128}, bb[2] = {8, 128};
        encode(fn, &tt, CU_TENSOR_MAP_DATA_TYPE_UINT32, 2, p.scr->T, dims, st, ba, CU_TENSOR_MAP_SWIZZLE_128B, CU_TENSOR_MAP_L2_PROMOTION_NONE);
        encode(fn, &ttx, CU_TENSOR_MAP_DATA_TYPE_UINT32, 2, p.scr->T, dims, st, bb, CU_TENSOR_MAP_SWIZZLE_32B, CU_TENSOR_MAP_L2_PROMOTION_NONE);
    }
    {
        const cuuint64_t dims[2] = {D_, S_}, st[1] = {D_ * 2};
        const cuuint32_t bx[2] = {144, 16};
        encode(fn, &to, CU_TENSOR_MAP_DATA_TYPE_BFLOAT16, 2, p.out, dims, st, bx, CU_TENSOR_MAP_SWIZZLE_NONE, CU_TENSOR_MAP_L2_PROMOTION_NONE);
    }
    cudaFuncSetAttribute(fused_kernel, cudaFuncAttributeMaxDynamicSharedMemorySize, SMEM_BYTES);
    cudaLaunchConfig_t cfg = {};
    cfg.gridDim = dim3(NCTA); cfg.blockDim = dim3(NTHR); cfg.dynamicSmemBytes = SMEM_BYTES; cfg.stream = cudaStreamPerThread;
    cudaLaunchAttribute at[1];
    at[0].id = cudaLaunchAttributeCooperative; at[0].val.cooperative = 1;
    cfg.attrs = at; cfg.numAttrs = 1;
    cudaLaunchKernelEx(&cfg, fused_kernel, p, tw1a, tw1b, tw2, th3a, th3b, twr, twi, twm, tt, ttx, to, th3s, tws);
}
```

```cpp
#include <cuda_runtime.h>
#include <cuda_bf16.h>
#include <cuda_fp16.h>
#include <cuda.h>
#include <stdint.h>

namespace {

constexpr int S_ = 2048, D_ = 576, F_ = 4608;
constexpr int NCTA = 132, NTHR = 512;
constexpr int TP = 4736;
constexpr int SPEC_P = 296;
constexpr int NST = 6;
constexpr int A_BYTES = 16384, B_BYTES = 18432;
constexpr int IT_P1 = 24, IT_G2 = 40, IT_END = 76;
constexpr int SPIN_LIMIT = 1 << 22;
#define MODP 1
#define X2D 1450
constexpr int P2S = 2;
#define G2E 4
#define LEAD1 4
#define A2E 6
#define A2D 100
#define W1N 8
#define W1P 100
#define W1S 4
#define XDELAY 900
#define WPF 2
#define HOK 2
#define HOK1 2
#define CRITPF 1
#define NCD 0
#define X1D 2200
#define PF2 1
#define X1DELAY 2000
#define X1PACE 400

constexpr int OFF_A = 0;
constexpr int OFF_B = NST * A_BYTES;
constexpr int OFF_P = OFF_B + NST * B_BYTES;
constexpr int OFF_BAR = OFF_P;
constexpr int OFF_MISC = OFF_P + 504;
constexpr int OFF_GB = OFF_P + 512;
constexpr int OFF_P2R = OFF_P + 1664;
constexpr int OFF_X1 = OFF_P2R;
constexpr int OFF_PROF = OFF_X1 + 18432;
constexpr int SMEM_BYTES = OFF_PROF + 512 + 1024;
constexpr int QA = 13, QB = 7, QC = 13;
constexpr int TAB_BYTES = (QA + QB + QC) * 512;
constexpr int OFF_STAGE = OFF_B;
constexpr int OFF_STX = OFF_STAGE + 16384;
constexpr int OFF_TAB = OFF_STAGE + 20480;
constexpr int OFF_SPEC = OFF_TAB + TAB_BYTES;
constexpr int OFF_WRAW = OFF_SPEC + 19072;
constexpr int OFF_B3 = OFF_WRAW + 28672;
constexpr int OFF_MODA = OFF_B3 + 4096;
constexpr int OFF_MODC = OFF_MODA + 2560;
constexpr int OFF_RED = OFF_MODC + 3584;
constexpr int OFF_SILU = OFF_RED + 1536;
static_assert(OFF_SILU + 1152 <= OFF_P && 6 * 28672 <= OFF_B3, "scratch overflow");
constexpr int OFF_STRIP = OFF_A;
static_assert(OFF_WRAW % 128 == 0 && OFF_STAGE % 128 == 0 && OFF_STX % 128 == 0, "align");
constexpr int BAR_FULL = 0, BAR_EMPTY = 6, BAR_TAB = 12, BAR_W = 13, BAR_REL = 14, BAR_P2R = 16,
              BAR_XT = 17, BAR_RECV = 18, BAR_ROLE = 19, BAR_NC = 20, BAR_TAB2 = 21, BAR_XB = 22, BAR_GB = 23, BAR_HOLD = 24, BAR_W1GO = 25, BAR_UOK = 26, BAR_DONE = 30, BAR_X = 31, BAR_ST = 47;

struct Cos1152 { double c[1152]; };
constexpr double cx_cos(double x) { double t = 1, s = 1; for (int i = 1; i < 14; i++) { t *= -x * x / ((2 * i - 1) * (2 * i)); s += t; } return s; }
constexpr Cos1152 make_cos() {
    Cos1152 r{};
    for (int i = 0; i <= 288; i++) {
        double v = (i == 288) ? 0.0 : cx_cos(3.14159265358979323846 * 2.0 * i / 1152.0);
        r.c[i] = v; r.c[576 - i] = -v; r.c[576 + i] = -v; r.c[(1152 - i) % 1152] = v;
    }
    return r;
}
constexpr uint32_t cx_f2h(double v) {
    uint32_t s = v < 0 ? 0x8000u : 0u; double a = v < 0 ? -v : v;
    if (a < 1e-9) return 0;
    int e = 0;
    while (a >= 2.0) { a *= 0.5; e++; }
    while (a < 1.0 && e > -14) { a *= 2.0; e--; }
    double m = a * 1024.0; uint32_t mi = (uint32_t)m; double fr = m - mi;
    if (fr > 0.5 || (fr == 0.5 && (mi & 1))) mi++;
    return s | (uint32_t)(((e + 14) << 10) + mi);
}
struct Tab { uint32_t w[(QA + QB + QC) * 128]; };
constexpr Tab make_tab() {
    Tab t{};
    Cos1152 ct = make_cos();
    auto C = [&](int num, int den) { return ct.c[(num % den) * (1152 / den)]; };
    auto Sn = [&](int num, int den) { return ct.c[((num % den) * (1152 / den) + 864) % 1152]; };
    auto put = [&](int q0, int idx, int lane, double lo, double hi) { t.w[((q0 + idx / 4) * 32 + lane) * 4 + idx % 4] = cx_f2h(lo) | (cx_f2h(hi) << 16); };
    for (int lane = 0; lane < 32; lane++) {
        const int g = lane >> 2, q = lane & 3;
        for (int mt = 0; mt < 3; mt++) {
            const int ka = 8 * mt + g;
            for (int r = 0; r < 10; r++) {
                const int im = r & 1, i0 = (r >> 1) * 2;
                double v[2] = {0, 0};
                for (int e = 0; e < 2; e++) { int i = i0 + e, d1 = 4 * i + q; if (i < 9 && ka <= 18) v[e] = (im ? -Sn(ka * d1, 36) : C(ka * d1, 36)) / 8; }
                put(0, mt * 10 + r, lane, v[0], v[1]);
            }
            for (int v = 0; v < 2; v++) {
                const int d2 = 4 * q + v;
                put(0, 30 + (mt * 2 + v) * 2, lane, C(ka * d2, 576) * 4 / 3, C(ka * (d2 + 2), 576) * 4 / 3);
                put(0, 31 + (mt * 2 + v) * 2, lane, Sn(ka * d2, 576) * 4 / 3, Sn(ka * (d2 + 2), 576) * 4 / 3);
            }
        }
        for (int v = 0; v < 2; v++) for (int nt = 0; nt < 2; nt++) {
            const int kb = 2 * (g >> 1) + nt, part = g & 1;
            double b0[2] = {0, 0}, b1[2] = {0, 0};
            for (int e = 0; e < 2; e++) { int d2 = 4 * q + 2 * e + v; double c = C(kb * d2, 16) / 4, s = Sn(kb * d2, 16) / 4;
                b0[e] = part ? -s : c; b1[e] = part ? c : s; }
            put(0, 42 + (v * 2 + nt) * 2, lane, b0[0], b0[1]); put(0, 43 + (v * 2 + nt) * 2, lane, b1[0], b1[1]);
        }
        for (int par = 0; par < 2; par++) for (int a = 0; a < 4; a++) {
            const int ja = 2 * (q + 4 * (a >> 1)) + par; const double c = C(g * ja, 16) / 4, s = Sn(g * ja, 16) / 4;
            put(QA, par * 4 + a, lane, (a & 1) ? -s : c, (a & 1) ? c : s);
        }
        for (int h = 0; h < 2; h++) {
            put(QA, 8 + 2 * h, lane, C((g + 8 * h) * (2 * q), 128) / 2, C((g + 8 * h) * (2 * q + 1), 128) / 2);
            put(QA, 9 + 2 * h, lane, Sn((g + 8 * h) * (2 * q), 128) / 2, Sn((g + 8 * h) * (2 * q + 1), 128) / 2);
            put(QA, 15 + 2 * h, lane, C(g * (8 * h + 2 * q), 128), C(g * (8 * h + 2 * q + 1), 128));
            put(QA, 16 + 2 * h, lane, Sn(g * (8 * h + 2 * q), 128), Sn(g * (8 * h + 2 * q + 1), 128));
        }
        put(QA, 12, lane, C(g * 2 * q, 8) / 2, C(g * (2 * q + 1), 8) / 2);
        put(QA, 13, lane, Sn(g * 2 * q, 8) / 2, Sn(g * (2 * q + 1), 8) / 2);
        put(QA, 14, lane, -Sn(g * 2 * q, 8) / 2, -Sn(g * (2 * q + 1), 8) / 2);
        for (int u = 0; u < 4; u++) {
            const int ja = 2 * ((g >> 1) + 4 * (u & 1)) + (u >> 1), part = g & 1; double b0[2] = {0, 0}, b1[2] = {0, 0};
            for (int e = 0; e < 2; e++) { int ka = 2 * q + e; double c = C(ja * ka, 16) / 4, s = Sn(ja * ka, 16) / 4;
                b0[e] = part ? s : c; b1[e] = part ? c : -s; }
            put(QA, 19 + u * 2, lane, b0[0], b0[1]); put(QA, 20 + u * 2, lane, b1[0], b1[1]);
        }
        for (int m2 = 0; m2 < 2; m2++) {
            const int d2 = 2 * g + m2;
            for (int a = 0; a < 4; a++) {
                const int kb = 2 * q + (a >> 1); const double c = C(d2 * kb, 16) / 4, s = Sn(d2 * kb, 16) / 4;
                put(QA + QB, m2 * 4 + a, lane, (a & 1) ? s : c, (a & 1) ? c : -s);
            }
            for (int mt = 0; mt < 3; mt++) {
                const int ka = 8 * mt + 2 * q;
                put(QA + QB, 8 + (m2 * 3 + mt) * 2, lane, C(ka * d2, 576) * 4 / 3, C((ka + 1) * d2, 576) * 4 / 3);
                put(QA + QB, 9 + (m2 * 3 + mt) * 2, lane, Sn(ka * d2, 576) * 4 / 3, Sn((ka + 1) * d2, 576) * 4 / 3);
            }
        }
        for (int mt = 0; mt < 3; mt++) for (int nt = 0; nt < 5; nt++) {
            const int i = 2 * nt + (g & 1), d1 = 4 * i + (g >> 1); double b0[2] = {0, 0}, b1[2] = {0, 0};
            for (int e = 0; e < 2; e++) { int ka = 8 * mt + 2 * q + e;
                if (ka <= 18 && i < 9) { double wt = (ka == 0 || ka == 18) ? 0.125 : 0.25; b0[e] = wt * C(ka * d1, 36); b1[e] = -wt * Sn(ka * d1, 36); } }
            put(QA + QB, 20 + (mt * 5 + nt) * 2, lane, b0[0], b0[1]); put(QA + QB, 21 + (mt * 5 + nt) * 2, lane, b1[0], b1[1]);
        }
    }
    return t;
}
__device__ __align__(128) const Tab g_tab = make_tab();

struct Scratch {
    uint32_t cnt[30 * 32];
    uint32_t slot[96];
    uint32_t mod[2304];
    uint32_t modc[896 + 288];
    uint32_t T[128 * TP];
    uint4 h3[128 * 1152];
    uint4 U[72 * 4 * 1152];
};
__device__ __align__(1024) Scratch g_scr;
#define g_cnt (p.scr->cnt)
#define g_slot (p.scr->slot)
#define g_mod (p.scr->mod)
#define g_T (p.scr->T)
#define g_h3 (p.scr->h3)
#define g_U (p.scr->U)
constexpr int CNT_EPOCH = 0, CNT_H3 = 1, CNT_X1 = 26, CNT_NC = 27, CNT_U = 2;
#define PROFT(i) do {} while (0)
#define PROFDUMP() do {} while (0)
#define PROF0(i) do {} while (0)

__device__ __forceinline__ void mbar_init(uint32_t bar, uint32_t cnt) { asm volatile("mbarrier.init.shared::cta.b64 [%0], %1;" :: "r"(bar), "r"(cnt) : "memory"); }
__device__ __forceinline__ void mbar_expect(uint32_t bar, uint32_t bytes) { asm volatile("mbarrier.arrive.expect_tx.shared::cta.b64 _, [%0], %1;" :: "r"(bar), "r"(bytes) : "memory"); }
__device__ __forceinline__ void mbar_arrive(uint32_t bar) { asm volatile("mbarrier.arrive.shared::cta.b64 _, [%0];" :: "r"(bar) : "memory"); }
__device__ __forceinline__ void mbar_arrive_n(uint32_t bar, uint32_t n) { asm volatile("mbarrier.arrive.shared::cta.b64 _, [%0], %1;" :: "r"(bar), "r"(n) : "memory"); }
__device__ __forceinline__ void mbar_arrive_remote(uint32_t rbar) { asm volatile("mbarrier.arrive.relaxed.cluster.shared::cluster.b64 _, [%0];" :: "r"(rbar) : "memory"); }
__device__ __forceinline__ void mbar_wait(uint32_t bar, uint32_t parity) {
    asm volatile("{.reg .pred p; .reg .u32 c;\n"
        "mbarrier.try_wait.parity.shared::cta.b64 p, [%0], %1;\n@p bra.uni DONE;\nmov.u32 c, 0;\n"
        "LOOP: mbarrier.try_wait.parity.shared::cta.b64 p, [%0], %1;\n@p bra.uni DONE;\n"
        "add.u32 c, c, 1;\nsetp.lt.u32 p, c, %2;\n@p bra.uni LOOP;\ntrap;\nDONE:}" :: "r"(bar), "r"(parity), "n"(SPIN_LIMIT) : "memory");
}
__device__ __forceinline__ bool mbar_test(uint32_t bar, uint32_t parity) {
    uint32_t ok; asm volatile("{.reg .pred p; mbarrier.test_wait.parity.shared::cta.b64 p, [%1], %2; selp.u32 %0, 1, 0, p;}" : "=r"(ok) : "r"(bar), "r"(parity) : "memory"); return ok; }
__device__ __forceinline__ uint32_t mapa(uint32_t a, uint32_t rank) { uint32_t r; asm("mapa.shared::cluster.u32 %0, %1, %2;" : "=r"(r) : "r"(a), "r"(rank)); return r; }
__device__ __forceinline__ uint32_t clk32() { uint32_t r; asm volatile("mov.u32 %0, %%clock;" : "=r"(r)); return r; }
__device__ __forceinline__ void hb() {
    asm volatile("{.reg .b32 a, b; .reg .pred p; mma.sync.aligned.m16n8k8.row.col.f16.f16.f16.f16 {a, b}, {%0,%0}, {%0}, {%0,%0};\n"
                 "setp.ne.u32 p, a, 0; @p trap;}" :: "r"(0));
}
__device__ __forceinline__ void spin_until(uint32_t t) { while (__any_sync(~0u, (int)(clk32() - t) < 0)) hb(); }
__device__ __forceinline__ bool elect() { uint32_t r; asm volatile("{.reg .pred p; elect.sync _|p, 0xffffffff; selp.u32 %0, 1, 0, p;}" : "=r"(r)); return r; }
__device__ __forceinline__ void bar_sync(int id, int n) { asm volatile("bar.sync %0, %1;" :: "r"(id), "r"(n) : "memory"); }
__device__ __forceinline__ void bulk_load(uint32_t dst, const void* src, uint32_t bytes, uint32_t bar) {
    asm volatile("cp.async.bulk.shared::cluster.global.mbarrier::complete_tx::bytes [%0], [%1], %2, [%3];" :: "r"(dst), "l"(src), "r"(bytes), "r"(bar) : "memory"); }
__device__ __forceinline__ void tma2(uint32_t dst, const CUtensorMap* m, int c0, int c1, uint32_t bar) {
    asm volatile("cp.async.bulk.tensor.2d.shared::cluster.global.mbarrier::complete_tx::bytes [%0], [%1, {%3, %4}], [%2];" :: "r"(dst), "l"(m), "r"(bar), "r"(c0), "r"(c1) : "memory"); }
__device__ __forceinline__ void tma3(uint32_t dst, const CUtensorMap* m, int c0, int c1, int c2, uint32_t bar) {
    asm volatile("cp.async.bulk.tensor.3d.shared::cluster.global.mbarrier::complete_tx::bytes [%0], [%1, {%3, %4, %5}], [%2];" :: "r"(dst), "l"(m), "r"(bar), "r"(c0), "r"(c1), "r"(c2) : "memory"); }
__device__ __forceinline__ void tma4(uint32_t dst, const CUtensorMap* m, int c0, int c1, int c2, int c3, uint32_t bar) {
    asm volatile("cp.async.bulk.tensor.4d.shared::cluster.global.mbarrier::complete_tx::bytes [%0], [%1, {%3, %4, %5, %6}], [%2];" :: "r"(dst), "l"(m), "r"(bar), "r"(c0), "r"(c1), "r"(c2), "r"(c3) : "memory"); }
__device__ __forceinline__ void fence_async_g() { asm volatile("fence.proxy.async.global;" ::: "memory"); }
__device__ __forceinline__ void fence_async_s() { asm volatile("fence.proxy.async.shared::cta;" ::: "memory"); }
__device__ __forceinline__ uint4 lds128(uint32_t a) { uint4 v; asm volatile("ld.shared.v4.u32 {%0,%1,%2,%3}, [%4];" : "=r"(v.x), "=r"(v.y), "=r"(v.z), "=r"(v.w) : "r"(a) : "memory"); return v; }
__device__ __forceinline__ uint32_t lds32(uint32_t a) { uint32_t v; asm volatile("ld.shared.u32 %0, [%1];" : "=r"(v) : "r"(a) : "memory"); return v; }
__device__ __forceinline__ void sts128(uint32_t a, uint4 v) { asm volatile("st.shared.v4.u32 [%0], {%1,%2,%3,%4};" :: "r"(a), "r"(v.x), "r"(v.y), "r"(v.z), "r"(v.w) : "memory"); }
__device__ __forceinline__ void sts32(uint32_t a, uint32_t v) { asm volatile("st.shared.u32 [%0], %1;" :: "r"(a), "r"(v) : "memory"); }
__device__ __forceinline__ void sts16(uint32_t a, uint32_t v) { asm volatile("st.shared.u16 [%0], %1;" :: "r"(a), "h"((uint16_t)v) : "memory"); }
__device__ __forceinline__ uint4 ldx128(const void* p) {
    uint4 v; asm volatile("{.reg .b128 t; .reg .b64 a, b; ld.relaxed.gpu.global.b128 t, [%4]; mov.b128 {a, b}, t; mov.b64 {%0,%1}, a; mov.b64 {%2,%3}, b;}"
        : "=r"(v.x), "=r"(v.y), "=r"(v.z), "=r"(v.w) : "l"(p) : "memory"); return v; }
__device__ __forceinline__ void stx128(void* p, uint4 v) {
    asm volatile("{.reg .b128 t; .reg .b64 a, b; mov.b64 a, {%1,%2}; mov.b64 b, {%3,%4}; mov.b128 t, {a, b}; st.relaxed.gpu.global.b128 [%0], t;}"
        :: "l"(p), "r"(v.x), "r"(v.y), "r"(v.z), "r"(v.w) : "memory"); }
__device__ __forceinline__ uint32_t ld_relaxed(const uint32_t* p) { uint32_t v; asm volatile("ld.relaxed.gpu.global.u32 %0, [%1];" : "=r"(v) : "l"(p) : "memory"); return v; }
__device__ __forceinline__ uint32_t ld_acquire(const uint32_t* p) { uint32_t v; asm volatile("ld.acquire.gpu.global.u32 %0, [%1];" : "=r"(v) : "l"(p) : "memory"); return v; }
__device__ __forceinline__ void st_relaxed(uint32_t* p, uint32_t v) { asm volatile("st.relaxed.gpu.global.u32 [%0], %1;" :: "l"(p), "r"(v) : "memory"); }
__device__ __forceinline__ void red_release(uint32_t* p) { asm volatile("red.release.gpu.global.add.u32 [%0], 1;" :: "l"(p) : "memory"); }
template <int SLEEP> __device__ __forceinline__ void wait_count(const uint32_t* p, uint32_t target) {
    int it = 0; while ((int)(ld_acquire(p) - target) < 0) { if (SLEEP) __nanosleep(SLEEP); if (++it > SPIN_LIMIT) __trap(); }
}
__device__ __forceinline__ uint32_t ldg_nc32(const void* p) { uint32_t v; asm volatile("ld.global.nc.L1::no_allocate.u32 %0, [%1];" : "=r"(v) : "l"(p)); return v; }
__device__ __forceinline__ uint32_t ldg_nc16(const void* p) { uint16_t v; asm volatile("ld.global.nc.u16 %0, [%1];" : "=h"(v) : "l"(p)); return v; }
__device__ __forceinline__ float bf_lo(uint32_t w) { return __uint_as_float(w << 16); }
__device__ __forceinline__ float bf_hi(uint32_t w) { return __uint_as_float(w & 0xFFFF0000u); }
__device__ __forceinline__ uint32_t pack_bf(float lo, float hi) { uint32_t r; asm("cvt.rn.bf16x2.f32 %0, %1, %2;" : "=r"(r) : "f"(hi), "f"(lo)); return r; }
__device__ __forceinline__ uint32_t pack_h(float lo, float hi) { uint32_t r; asm("cvt.rn.f16x2.f32 %0, %1, %2;" : "=r"(r) : "f"(hi), "f"(lo)); return r; }
__device__ __forceinline__ float bf_round(float v) { return bf_lo(pack_bf(v, 0.f)); }
__device__ __forceinline__ uint32_t hmul2(uint32_t a, uint32_t b) { uint32_t r; asm("mul.rn.f16x2 %0, %1, %2;" : "=r"(r) : "r"(a), "r"(b)); return r; }
__device__ __forceinline__ uint32_t hfma2(uint32_t a, uint32_t b, uint32_t c) { uint32_t r; asm("fma.rn.f16x2 %0, %1, %2, %3;" : "=r"(r) : "r"(a), "r"(b), "r"(c)); return r; }
__device__ __forceinline__ uint32_t hfms2(uint32_t a, uint32_t b, uint32_t c) { uint32_t r; asm("{.reg .b32 t; neg.f16x2 t, %3; fma.rn.f16x2 %0, %1, %2, t;}" : "=r"(r) : "r"(a), "r"(b), "r"(c)); return r; }
__device__ __forceinline__ uint32_t hadd2(uint32_t a, uint32_t b) { uint32_t r; asm("add.rn.f16x2 %0, %1, %2;" : "=r"(r) : "r"(a), "r"(b)); return r; }
__device__ __forceinline__ uint32_t hsub2(uint32_t a, uint32_t b) { uint32_t r; asm("sub.rn.f16x2 %0, %1, %2;" : "=r"(r) : "r"(a), "r"(b)); return r; }
__device__ __forceinline__ void cmul_neg(uint32_t& re, uint32_t& im, uint32_t c, uint32_t s) { uint32_t a = hfma2(re, c, hmul2(im, s)), b = hfms2(im, c, hmul2(re, s)); re = a; im = b; }
__device__ __forceinline__ void cmul_pos(uint32_t& re, uint32_t& im, uint32_t c, uint32_t s) { uint32_t a = hfms2(re, c, hmul2(im, s)), b = hfma2(im, c, hmul2(re, s)); re = a; im = b; }
__device__ __forceinline__ void mma_h(uint32_t& d0, uint32_t& d1, uint32_t a0, uint32_t a1, uint32_t a2, uint32_t a3, uint32_t b0, uint32_t b1) {
    asm("mma.sync.aligned.m16n8k16.row.col.f16.f16.f16.f16 {%0,%1}, {%2,%3,%4,%5}, {%6,%7}, {%0,%1};" : "+r"(d0), "+r"(d1) : "r"(a0), "r"(a1), "r"(a2), "r"(a3), "r"(b0), "r"(b1)); }
__device__ __forceinline__ void mma_h8(uint32_t& d0, uint32_t& d1, uint32_t a0, uint32_t a1, uint32_t b0) {
    asm("mma.sync.aligned.m16n8k8.row.col.f16.f16.f16.f16 {%0,%1}, {%2,%3}, {%4}, {%0,%1};" : "+r"(d0), "+r"(d1) : "r"(a0), "r"(a1), "r"(b0)); }
__device__ __forceinline__ void mma_f(float (&d)[4], uint32_t a0, uint32_t a1, uint32_t a2, uint32_t a3, uint32_t b0, uint32_t b1) {
    asm("mma.sync.aligned.m16n8k16.row.col.f32.f16.f16.f32 {%0,%1,%2,%3}, {%4,%5,%6,%7}, {%8,%9}, {%0,%1,%2,%3};"
        : "+f"(d[0]), "+f"(d[1]), "+f"(d[2]), "+f"(d[3]) : "r"(a0), "r"(a1), "r"(a2), "r"(a3), "r"(b0), "r"(b1)); }
template <int NQ> __device__ __forceinline__ void load_tab(uint32_t (&r)[NQ * 4], uint32_t addr) {
    #pragma unroll
    for (int i = 0; i < NQ; i++) { uint4 v = lds128(addr + i * 512); r[4 * i] = v.x; r[4 * i + 1] = v.y; r[4 * i + 2] = v.z; r[4 * i + 3] = v.w; }
}
__device__ __forceinline__ float gelu2(float x) {
    float t = x * fmaf(x * x, 0.044715f * 0.7978845608028654f, 0.7978845608028654f), th;
    asm volatile("tanh.approx.f32 %0, %1;" : "=f"(th) : "f"(t));
    return fmaf(x, th, x);
}
__device__ __forceinline__ uint32_t desc_lo(uint32_t addr, uint32_t lbo) { return ((addr & 0x3FFFF) >> 4) | ((lbo >> 4) << 16); }
constexpr uint32_t DHI_A = (1024 >> 4) | (1u << 30), DHI_H3 = 256 >> 4, DHI_U = 128 >> 4;
#define WG_FENCE() asm volatile("wgmma.fence.sync.aligned;" ::: "memory")
#define WG_COMMIT() asm volatile("wgmma.commit_group.sync.aligned;" ::: "memory")
#define WG_WAIT(n) asm volatile("wgmma.wait_group.sync.aligned %0;" :: "n"(n) : "memory")
#define R4(b) "+f"(d[b]), "+f"(d[b + 1]), "+f"(d[b + 2]), "+f"(d[b + 3])
#define R12(b) R4(b), R4(b + 4), R4(b + 8)
#define R36(b) R12(b), R12(b + 12), R12(b + 24)
template <uint32_t BHI> __device__ __forceinline__ void wgmma144(float (&d)[72], uint32_t da, uint32_t db, int acc) {
    asm volatile("{.reg .pred p; .reg .b64 a, b; setp.ne.b32 p, %74, 0; mov.b64 a, {%72, %75}; mov.b64 b, {%73, %76};\n"
        "wgmma.mma_async.sync.aligned.m64n144k16.f32.bf16.bf16 {%0,%1,%2,%3,%4,%5,%6,%7,%8,%9,%10,%11,%12,%13,%14,%15,%16,%17,%18,%19,%20,%21,%22,%23,"
        "%24,%25,%26,%27,%28,%29,%30,%31,%32,%33,%34,%35,%36,%37,%38,%39,%40,%41,%42,%43,%44,%45,%46,%47,"
        "%48,%49,%50,%51,%52,%53,%54,%55,%56,%57,%58,%59,%60,%61,%62,%63,%64,%65,%66,%67,%68,%69,%70,%71}, a, b, p, 1, 1, 1, 1;}\n"
        : R36(0), R36(36) : "r"(da), "r"(db), "r"(acc), "n"(DHI_A), "n"(BHI));
}
__device__ __forceinline__ void wgmma144x4(float (&d)[72], const uint64_t (&a)[4], const uint64_t (&b)[4], int acc) {
    #define WG144 "wgmma.mma_async.sync.aligned.m64n144k16.f32.bf16.bf16 {%0,%1,%2,%3,%4,%5,%6,%7,%8,%9,%10,%11,%12,%13,%14,%15,%16,%17,%18,%19,%20,%21,%22,%23,%24,%25,%26,%27,%28,%29,%30,%31,%32,%33,%34,%35,%36,%37,%38,%39,%40,%41,%42,%43,%44,%45,%46,%47,%48,%49,%50,%51,%52,%53,%54,%55,%56,%57,%58,%59,%60,%61,%62,%63,%64,%65,%66,%67,%68,%69,%70,%71}, "
    asm volatile("{.reg .pred p; setp.ne.b32 p, %80, 0;\n"
        WG144 "%72, %76, p, 1, 1, 1, 1;\n" WG144 "%73, %77, 1, 1, 1, 1, 1;\n" WG144 "%74, %78, 1, 1, 1, 1, 1;\n" WG144 "%75, %79, 1, 1, 1, 1, 1;}\n"
        : R36(0), R36(36) : "l"(a[0]), "l"(a[1]), "l"(a[2]), "l"(a[3]), "l"(b[0]), "l"(b[1]), "l"(b[2]), "l"(b[3]), "r"(acc));
}
__device__ __forceinline__ void wgmma72(float (&d)[36], uint32_t da, uint32_t db, int acc) {
    asm volatile("{.reg .pred p; .reg .b64 a, b; setp.ne.b32 p, %38, 0; mov.b64 a, {%36, %39}; mov.b64 b, {%37, %40};\n"
        "wgmma.mma_async.sync.aligned.m64n72k16.f32.bf16.bf16 {%0,%1,%2,%3,%4,%5,%6,%7,%8,%9,%10,%11,%12,%13,%14,%15,%16,%17,%18,%19,%20,%21,%22,%23,"
        "%24,%25,%26,%27,%28,%29,%30,%31,%32,%33,%34,%35}, a, b, p, 1, 1, 1, 1;}\n"
        : R36(0) : "r"(da), "r"(db), "r"(acc), "n"(DHI_A), "n"(DHI_H3));
}

__device__ __forceinline__ int g2_kb(int n, int kh) { const int m = n - 4; return 36 * kh + (n < 4 ? 9 * n + 8 : 9 * ((m >> 2) & 3) + 2 * (m & 3) + (m >> 4)); }

template <uint32_t BHI, int I0, int I1, bool ZERO, bool FIRST, bool LAST, class Hook>
__device__ __forceinline__ void mainloop(float (&d)[72], uint32_t bars, uint32_t da0, uint32_t db0, bool lead, Hook hook) {
    uint32_t s = I0 % NST, ph = (I0 / NST) & 1, prev = (I0 + NST - (I0 == IT_P1 ? 2 : 1)) % NST;
    uint32_t ready = 0;
    uint64_t da[4], db[4];
    #pragma unroll
    for (int k = 0; k < 4; k++) { da[k] = ((uint64_t)DHI_A << 32) + da0 + s * (A_BYTES / 16) + k * 128; db[k] = ((uint64_t)BHI << 32) + db0 + s * (B_BYTES / 16) + k * 288; }
    #pragma unroll 1
    for (int i = I0; i < I1; i++) {
        if (!ready) mbar_wait(bars + 8 * BAR_FULL + 8 * s, ph);
        WG_FENCE();
        wgmma144x4(d, da, db, ZERO ? i - I0 : 1);
        WG_COMMIT();
        const uint32_t rel = bars + 8 * BAR_EMPTY + 8 * prev; const int i0 = i;
        prev = s; if (++s == NST) { s = 0; ph ^= 1; }
        if (I1 == IT_P1 && (s == P2S || s == P2S + 3)) {
            mbar_wait(bars + 8 * BAR_FULL + 8 * s, ph);
            i++; if (++s == NST) { s = 0; ph ^= 1; }
        }
        const int64_t adv = (int)s - (int)prev;
        #pragma unroll
        for (int k = 0; k < 4; k++) { da[k] += adv * (A_BYTES / 16); db[k] += adv * (B_BYTES / 16); }
        ready = __shfl_sync(~0u, (uint32_t)mbar_test(bars + 8 * BAR_FULL + 8 * s, ph), 0);
        WG_WAIT(1);
        if (lead && (!FIRST || i0 > I0)) mbar_arrive(rel);
        hook(i0);
    }
    if (LAST) { WG_WAIT(0); if (lead) mbar_arrive(bars + 8 * BAR_EMPTY + 8 * prev); }
}

struct Params {
    const uint16_t *x, *wr, *wi, *w1, *b1, *w2, *b2, *c, *wmod;
    uint16_t* out;
    Scratch* scr;
    const Tab* tab;
};

__device__ __forceinline__ void mma_bf(float (&d)[4], const uint32_t (&a)[4], uint32_t b0, uint32_t b1) {
    asm("mma.sync.aligned.m16n8k16.row.col.f32.bf16.bf16.f32 {%0,%1,%2,%3}, {%4,%5,%6,%7}, {%8,%9}, {%0,%1,%2,%3};"
        : "+f"(d[0]), "+f"(d[1]), "+f"(d[2]), "+f"(d[3]) : "r"(a[0]), "r"(a[1]), "r"(a[2]), "r"(a[3]), "r"(b0), "r"(b1)); }
__device__ __forceinline__ void ldsm4t(uint32_t (&a)[4], uint32_t addr) {
    asm volatile("ldmatrix.sync.aligned.m8n8.x4.trans.shared.b16 {%0,%1,%2,%3}, [%4];" : "=r"(a[0]), "=r"(a[1]), "=r"(a[2]), "=r"(a[3]) : "r"(addr) : "memory"); }
__device__ __forceinline__ void ln_stats(const uint32_t (&w)[9], int g, int q, float& r, float& mr) {
    constexpr uint32_t ONE = 0x3F803F80u;
    float c[2][4] = {};
    #pragma unroll
    for (int p = 0; p < 5; p++) { const uint32_t hi = p < 4 ? w[p < 4 ? 2 * p + 1 : 0] : 0u, a[4] = {w[2 * p], ONE, hi, ONE}; mma_bf(c[p & 1], a, w[2 * p], hi); }
    const float t = (g & 1) ? c[0][1] + c[1][1] : c[0][0] + c[1][0];
    float s1 = (c[0][2] + c[1][2]) + (c[0][3] + c[1][3]), s2 = __shfl_sync(~0u, t, 9 * q) + __shfl_sync(~0u, t, 9 * q + 4);
    #pragma unroll
    for (int o = 1; o < 4; o <<= 1) { s1 += __shfl_xor_sync(~0u, s1, o); s2 += __shfl_xor_sync(~0u, s2, o); }
    const float m = s1 * (1.f / D_);
    asm("rsqrt.approx.ftz.f32 %0, %1;" : "=f"(r) : "f"(fmaxf(fmaf(s2, 1.f / D_, -m * m), 0.f) + 1e-5f));
    mr = -m * r;
}
__device__ __forceinline__ float silu(float v) { return __fdividef(v, 1.f + __expf(-v)); }
__device__ __forceinline__ uint32_t bfma2(uint32_t a, uint32_t b, uint32_t c) { uint32_t r; asm("fma.rn.bf16x2 %0, %1, %2, %3;" : "=r"(r) : "r"(a), "r"(b), "r"(c)); return r; }
__device__ __forceinline__ void radix16(const uint4 (&V)[4], const uint32_t (&B)[16], uint4 (&o)[4]) {
    #pragma unroll
    for (int nt = 0; nt < 4; nt++) {
        o[nt] = make_uint4(0, 0, 0, 0);
        #pragma unroll
        for (int ks = 0; ks < 2; ks++) {
            const uint32_t b0 = B[(ks * 4 + nt) * 2], b1 = B[(ks * 4 + nt) * 2 + 1];
            mma_h(o[nt].x, o[nt].y, V[2 * ks].x, V[2 * ks].y, V[2 * ks + 1].x, V[2 * ks + 1].y, b0, b1);
            mma_h(o[nt].z, o[nt].w, V[2 * ks].z, V[2 * ks].w, V[2 * ks + 1].z, V[2 * ks + 1].w, b0, b1);
        }
    }
}
template <int OFF, int N> __device__ __forceinline__ void gelu_store(const float (&d)[N], char* p, int q) {
    uint32_t w[9];
    #pragma unroll
    for (int blk = 0; blk < 9; blk++) w[blk] = pack_bf(gelu2(d[OFF + 4 * blk]), gelu2(d[OFF + 4 * blk + 1]));
    asm volatile("st.v4.u32 [%0], {%1,%2,%3,%4};" :: "l"(p + q * 128), "r"(w[0]), "r"(w[1]), "r"(w[2]), "r"(w[3]) : "memory");
    asm volatile("st.v4.u32 [%0+512], {%1,%2,%3,%4};" :: "l"(p + q * 128), "r"(w[4]), "r"(w[5]), "r"(w[6]), "r"(w[7]) : "memory");
    asm volatile("st.u32 [%0+1024], %1;" :: "l"(p + q * 4), "r"(w[8]) : "memory");
}

__global__ void __cluster_dims__(2, 1, 1) __launch_bounds__(NTHR, 1)
fused_kernel(const Params p,
             const __grid_constant__ CUtensorMap tm_w1a, const __grid_constant__ CUtensorMap tm_w1b, const __grid_constant__ CUtensorMap tm_w2,
             const __grid_constant__ CUtensorMap tm_h3a, const __grid_constant__ CUtensorMap tm_h3b,
             const __grid_constant__ CUtensorMap tm_wr, const __grid_constant__ CUtensorMap tm_wi, const __grid_constant__ CUtensorMap tm_wm,
             const __grid_constant__ CUtensorMap tm_t, const __grid_constant__ CUtensorMap tm_tx, const __grid_constant__ CUtensorMap tm_o,
             const __grid_constant__ CUtensorMap tm_h3s, const __grid_constant__ CUtensorMap tm_ws)
{
    extern __shared__ char smem_raw[];
    const uint32_t t0 = clk32();
    const uint32_t sm = __shfl_sync(~0u, ((uint32_t)__cvta_generic_to_shared(smem_raw) + 1023u) & ~1023u, 0);
    const int tid = threadIdx.x, warp = __shfl_sync(~0u, tid >> 5, 0), lane = tid & 31, g = lane >> 2, q = lane & 3;
    const int b = blockIdx.x;
    const uint32_t rank = b & 1;
    const uint32_t bars = sm + OFF_BAR;
    const bool rowcta = b < 128;

    auto nc_issue = [&](int st, uint32_t sl) {
        const int pass = st >= 18;
        mbar_expect(bars + 8 * (BAR_X + sl), 28672);
        tma3(sm + sl * 28672, &tm_wm, 0, 32 * (st - 18 * pass), 18 + 28 * pass + 7 * (b - 128), bars + 8 * (BAR_X + sl));
    };
    uint32_t epoch;
    const bool strip = b < 72 && !(b & 1);
    if (warp < 12) {
        epoch = ld_relaxed(g_cnt + CNT_EPOCH * 32);
        if (warp >= 8 && lane < 24 && (strip || !rowcta)) {
            uint32_t cw[3];
            #pragma unroll
            for (int u = 0; u < 3; u++) cw[u] = ldg_nc32(p.c + 144 * (warp - 8) + 48 * u + 2 * lane);
            #pragma unroll
            for (int u = 0; u < 3; u++) sts32(sm + OFF_SILU + (72 * (warp - 8) + 24 * u + lane) * 4, pack_bf(silu(bf_lo(cw[u])), silu(bf_hi(cw[u]))));
        }
        __syncwarp();
        hb();
        bar_sync(2, 512);
    } else {
        const int w4 = 4 * (warp - 12);
        if (elect()) {
            if (warp == 14 && b < 13) asm volatile("cp.async.bulk.prefetch.L2.global [%0], 512;" :: "l"(p.tab->w + b * 128) : "memory");
            if (strip && warp == 15) asm volatile("prefetch.tensormap [%0];" :: "l"(&tm_ws) : "memory");
            if (CRITPF) {
                asm volatile("cp.async.bulk.prefetch.L2.global [%0], 2304;" :: "l"(p.wmod + (b + 33 * w4) * 3456) : "memory");
                if (warp == 12 && b < 48) asm volatile("cp.async.bulk.prefetch.L2.global [%0], 2304;" :: "l"(p.wmod + (b + 528) * 3456) : "memory");
            }
        }
        if (warp == 13) hb();
        if (elect()) {
            if (rowcta) {
                for (int i = 0; i < 4; i++) mbar_init(bars + 8 * (BAR_X + w4 + i), 1);
                const uint32_t sb = bars + 8 * (BAR_ST + warp - 12);
                mbar_init(sb, 1);
                if (warp == 15) mbar_init(bars + 8 * BAR_TAB, 1);
                fence_async_s();
                if (warp == 15) { mbar_expect(bars + 8 * BAR_TAB, QA * 512); bulk_load(sm + OFF_TAB, p.tab, QA * 512, bars + 8 * BAR_TAB); }
                if (strip) { mbar_expect(sb, 9216); tma2(sm + OFF_STRIP + (warp - 12) * 9216, &tm_ws, 16 * b, 36 * w4, sb); }
            } else if (warp == 12) {
                for (int i = 0; i < 12; i++) mbar_init(bars + 8 * (BAR_X + i), i < 6 ? 1 : 14);
                fence_async_s();
                if (NCD) while ((int)(clk32() - t0) < NCD) {}
                for (int st = 0; st < 6; st++) nc_issue(st, st);
            }
            if (warp == 12) {
                asm volatile("prefetch.tensormap [%0];" :: "l"(&tm_wr) : "memory"); asm volatile("prefetch.tensormap [%0];" :: "l"(&tm_wi) : "memory");
                asm volatile("prefetch.tensormap [%0];" :: "l"(&tm_t) : "memory"); asm volatile("prefetch.tensormap [%0];" :: "l"(&tm_tx) : "memory");
            } else if (warp == 14) {
                for (int i = BAR_W; i < BAR_X; i++) mbar_init(bars + 8 * i, i == BAR_DONE ? 4 : 1);
                mbar_expect(bars + 8 * BAR_W, 28672); mbar_expect(bars + 8 * BAR_TAB2, (QB + QC) * 512);
                mbar_expect(bars + 8 * BAR_ROLE, 4); mbar_expect(bars + 8 * BAR_P2R, 9216); mbar_expect(bars + 8 * BAR_RECV, 18432); mbar_expect(bars + 8 * BAR_XT, 18432);
            } else if (warp == 13) {
                for (int i = 0; i < 2 * NST; i++) mbar_init(bars + 8 * i, 2);
                for (int i = 0; i < NST; i++) mbar_expect(bars + 8 * (BAR_FULL + i), A_BYTES);
            }
            asm volatile("fence.mbarrier_init.release.cluster;" ::: "memory");
        }
        __syncwarp();
        asm volatile("bar.arrive 2, 512;" ::: "memory");
        if (rowcta && elect()) {
            if (XDELAY) while ((int)(clk32() - t0) < XDELAY) {}
            for (int r = w4; r < w4 + 4; r++) {
                mbar_expect(bars + 8 * (BAR_X + r), 1152);
                bulk_load(sm + OFF_STAGE + r * 1152, p.x + (size_t)(b + 128 * r) * D_, 1152, bars + 8 * (BAR_X + r));
            }
        }
        __syncwarp();
        epoch = ld_relaxed(g_cnt + CNT_EPOCH * 32);
        sts16(sm + OFF_MODA + ((warp - 11) * 32 + lane) * 16 + w4 + 2, 0);
        #pragma unroll 1
        for (int s1 = (tid >> 4) & 7; s1 < 16; s1 += 8) {
            const int k1 = tid & 15;
            float s, c;
            __sincosf((float)(((k1 * (128 * s1 + b) + 1024) & 2047) - 1024) * (3.14159265358979f / 1024.f), &s, &c); s *= 0.25f; c *= 0.25f;
            const int rf = ((s1 >> 3) * 4 + (k1 >> 2)) * 2 + ((s1 >> 2) & 1), ri = ((k1 >> 3) * 4 + (s1 >> 2)) * 2 + ((k1 >> 2) & 1);
            const uint32_t af = sm + OFF_B3 + ((rf >> 2) * 32 + (k1 & 3) * 8 + (s1 & 3)) * 16 + (rf & 3) * 4;
            const uint32_t ai = sm + OFF_B3 + 2048 + ((ri >> 2) * 32 + (s1 & 3) * 8 + (k1 & 3)) * 16 + (ri & 3) * 4;
            sts32(af, pack_h(c, s)); sts32(af + 64, pack_h(-s, c)); sts32(ai, pack_h(c, -s)); sts32(ai + 64, pack_h(s, c));
        }
        hb();
        bar_sync(3, 128);
    }
    asm volatile("barrier.cluster.arrive.relaxed.aligned;" ::: "memory");
    const uint32_t tag = (epoch + 1) & 0xFFFFu;

    const int trow = 4 * (b & 7) + ((b >> 4) & 3) + 64 * ((b >> 3) & 1) + 32 * (b >> 6);
    uint32_t* const tptr = g_T + (size_t)trow * TP + (warp < 9 ? q * 288 + 32 * warp : 4608 + 8 * q) + 4 * g;
    const int tstr = warp < 9 ? 1152 : 32;
    const uint32_t scol = sm + OFF_SPEC + (q * SPEC_P + (warp < 8 ? 72 * (warp >> 1) + 40 * (warp & 1) + 4 * g : warp == 8 ? 72 * (g >> 1) + 32 + 4 * (g & 1) : 288 + 4 * g)) * 4;
    const int wc0 = (b >> 3) * 289 + 72 * ((b & 7) >> 1) + 40 * (b & 1);

    uint32_t xw[9], t_st = t0;
    if (!rowcta) {
        const int nst = b < 130 ? 36 : 18;
        __syncthreads();
        if (warp == 14) {
            uint32_t sl = 0, ph = 0;
            #pragma unroll 1
            for (int st = 6; st < nst; st++) {
                mbar_wait(bars + 8 * (BAR_X + 6 + sl), ph);
                if (elect()) nc_issue(st, sl);
                if (++sl == 6) { sl = 0; ph ^= 1; }
            }
        } else if (warp < 14) {
            uint32_t sl = 0, ph = 0;
            const uint32_t ad0 = sm + (warp >> 1) * 4096 + ((lane & 7) + 8 * (lane >> 4)) * 128, ch = (warp & 1) * 4 + ((lane >> 3) & 1);
            #pragma unroll 1
            for (int pass = 0; pass * 18 < nst; pass++) {
                float acc[2][4] = {};
                #pragma unroll 1
                for (int st = 0; st < 18; st++) {
                    const uint32_t sa = sm + OFF_SILU + (16 * st + q) * 4;
                    const uint32_t b0 = lds32(sa), b1 = lds32(sa + 16), b2 = lds32(sa + 32), b3 = lds32(sa + 48);
                    mbar_wait(bars + 8 * (BAR_X + sl), ph);
                    #pragma unroll
                    for (int m = 0; m < 2; m++) {
                        uint32_t a[4], a2[4];
                        const uint32_t ad = ad0 + sl * 28672 + ((ch + 2 * m) ^ (lane & 7)) * 16;
                        ldsm4t(a, ad); ldsm4t(a2, ad + 2048);
                        mma_bf(acc[m], a, b0, b1); mma_bf(acc[m], a2, b2, b3);
                    }
                    if (elect()) mbar_arrive(bars + 8 * (BAR_X + 6 + sl));
                    if (++sl == 6) { sl = 0; ph ^= 1; }
                }
                const int cb = 28 * pass + 7 * (b - 128) + (warp >> 1), gg = (g >> 1) + 4 * q;
                #pragma unroll
                for (int m = 0; m < 2; m++) {
                    const int qq = (warp & 1) * 2 + m;
                    float v = bf_round(q ? acc[m][2] : acc[m][0]); if (cb >= 27) v *= 0.5f; else if (cb >= 18) v += 1.f;
                    const uint32_t w = pack_bf(v, __shfl_xor_sync(~0u, v, 4));
                    if (q < 2 && !(g & 1) && cb < 36) p.scr->modc[cb < 27 ? ((cb >> 2) * 32 + 4 * gg + qq) * 4 + (cb & 3) : 896 + 32 * (cb - 27) + 8 * qq + gg] = w;
                }
                bar_sync(1, 448);
                if (tid == 0) { fence_async_g(); red_release(g_cnt + (CNT_NC + pass) * 32); if (pass == 0) PROFT(25); }
                __syncwarp();
            }
            fence_async_s();
        }
        __syncthreads();
    } else {
        uint32_t ta[QA * 4];
        if (strip && (warp >> 2) == 2) {
            const int w = warp - 8;
            uint32_t sb[18];
            #pragma unroll
            for (int u = 0; u < 18; u++) sb[u] = lds32(sm + OFF_SILU + (72 * w + 4 * u + q) * 4);
            const uint32_t ra = sm + OFF_STRIP + (144 * w + (lane & 7) + 8 * (lane >> 4)) * 64, sw = (lane >> 1) & 3, ch = (lane >> 3) & 1;
            float acc[2][2][4] = {};
            mbar_wait(bars + 8 * (BAR_ST + w), 0);
            #pragma unroll
            for (int u = 0; u < 9; u++)
                #pragma unroll
                for (int m = 0; m < 2; m++) { uint32_t a[4]; ldsm4t(a, ra + u * 1024 + ((ch + 2 * m) ^ sw) * 16); mma_bf(acc[u & 1][m], a, sb[2 * u], sb[2 * u + 1]); }
            #define PICK(a_) ((q & 2) ? ((q & 1) ? a_[1][2] : a_[1][0]) : ((q & 1) ? a_[0][2] : a_[0][0]))
            sts32(sm + OFF_RED + ((8 * q + g) * 4 + w) * 4, __float_as_uint(PICK(acc[0]) + PICK(acc[1])));
            if (tid == 256) PROFT(0);
            bar_sync(10, 128);
            if (warp == 8) {
                const uint4 v = lds128(sm + OFF_RED + lane * 16);
                float sum = bf_round((__uint_as_float(v.x) + __uint_as_float(v.y)) + (__uint_as_float(v.z) + __uint_as_float(v.w)));
                if (b >= 36) sum = bf_round(1.f + sum);
                st_relaxed(g_mod + b * 16 + (lane & 16) + (lane & 1) * 8 + ((lane & 15) >> 1), (pack_h(0.f, sum) & 0xFFFF0000u) | tag);
                if (tid == 256) PROFT(1);
            }
        }
        mbar_wait(bars + 8 * BAR_TAB, 0);
        load_tab<QA>(ta, sm + OFF_TAB + lane * 16);
        auto w_prefetch = [&]() {
            if (warp >= 14 && elect()) asm volatile("cp.async.bulk.prefetch.L2.global [%0], 9248;" :: "l"((warp == 14 ? p.wr : p.wi) + b * 4624) : "memory");
            __syncwarp();
        };
        uint32_t nb[2][5];
        uint4 mv = make_uint4(tag, tag, tag, tag);
        const bool poller = warp < 8 || warp == 12;
        const int mc = warp < 8 ? tid : tid - 128, mst = (mc >> 2) % 36, midx = (mc < 144 ? 10 : 0) + 5 * ((mc >> 1) & 1) + (mst >> 3);
        const uint32_t* mp = g_mod + mc * 4;
        const uint32_t ma = sm + OFF_MODA + ((midx >> 2) * 32 + (mc & 1) * 16 + (mst & 3)) * 16 + (midx & 3) * 4 + ((mst >> 2) & 1) * 2;
        #define MOD_MISSING ((((mv.x ^ tag) | (mv.y ^ tag) | (mv.z ^ tag) | (mv.w ^ tag)) & 0xFFFFu) != 0)
        hb();
        mbar_wait(bars + 8 * (BAR_X + warp), 0);
        if (poller) mv = ldx128(mp);
        if (WPF == 1) w_prefetch();
        PROF0(28);
        #pragma unroll
        for (int i = 0; i < 9; i++) xw[i] = lds32(sm + OFF_STAGE + warp * 1152 + (32 * i + 8 * q + g) * 4);
        {
            float r, mr;
            ln_stats(xw, g, q, r, mr);
            #pragma unroll
            for (int pp = 0; pp < 5; pp++) {
                nb[0][pp] = pack_h(fmaf(bf_lo(xw[2 * pp]), r, mr), pp < 4 ? fmaf(bf_lo(xw[pp < 4 ? 2 * pp + 1 : 0]), r, mr) : 0.f);
                nb[1][pp] = pack_h(fmaf(bf_hi(xw[2 * pp]), r, mr), pp < 4 ? fmaf(bf_hi(xw[pp < 4 ? 2 * pp + 1 : 0]), r, mr) : 0.f);
            }
        }
        PROF0(2);
        if (WPF == 2) w_prefetch();
        if (WPF > 3 && warp >= 14) { spin_until(t0 + WPF); w_prefetch(); }
        if (poller) {
            for (int it = 0; __any_sync(~0u, MOD_MISSING); it++) { if (MOD_MISSING) mv = ldx128(mp); hb(); if (it > SPIN_LIMIT) __trap(); }
            sts16(ma, mv.x >> 16); sts16(ma + 64, mv.y >> 16); sts16(ma + 128, mv.z >> 16); sts16(ma + 192, mv.w >> 16);
        }
        __syncthreads();
        PROF0(3);
        if (WPF == 3) w_prefetch();
        if (warp >= 13 && elect()) {
            if (warp == 15) bulk_load(sm + OFF_TAB + QA * 512, p.tab->w + QA * 128, (QB + QC) * 512, bars + 8 * BAR_TAB2);
            else tma3(sm + OFF_WRAW + (warp - 13) * 14336, warp == 13 ? &tm_wr : &tm_wi, wc0 & ~7, 0, 0, bars + 8 * BAR_W);
        }
        __syncwarp();
        {
            uint32_t md[20];
            load_tab<5>(md, sm + OFF_MODA + lane * 16);
            #pragma unroll
            for (int v = 0; v < 2; v++)
                #pragma unroll
                for (int pp = 0; pp < 5; pp++) nb[v][pp] = hfma2(nb[v][pp], md[v * 5 + pp], md[10 + v * 5 + pp]);
        }
        uint32_t re[3][2], im[3][2];
        #pragma unroll
        for (int mt = 0; mt < 3; mt++)
            #pragma unroll
            for (int v = 0; v < 2; v++) {
                re[mt][v] = 0; im[mt][v] = 0;
                mma_h8(re[mt][v], im[mt][v], ta[mt * 10 + 8], ta[mt * 10 + 9], nb[v][4]);
                mma_h(re[mt][v], im[mt][v], ta[mt * 10], ta[mt * 10 + 1], ta[mt * 10 + 2], ta[mt * 10 + 3], nb[v][0], nb[v][1]);
                mma_h(re[mt][v], im[mt][v], ta[mt * 10 + 4], ta[mt * 10 + 5], ta[mt * 10 + 6], ta[mt * 10 + 7], nb[v][2], nb[v][3]);
                cmul_neg(re[mt][v], im[mt][v], ta[30 + (mt * 2 + v) * 2], ta[31 + (mt * 2 + v) * 2]);
            }
        const uint32_t srow = sm + OFF_SPEC + warp * (SPEC_P * 4);
        #pragma unroll
        for (int nt = 0; nt < 2; nt++) {
            uint32_t o[2][4];
            #pragma unroll
            for (int v = 0; v < 2; v++) {
                const uint32_t b0 = ta[42 + (v * 2 + nt) * 2], b1 = ta[43 + (v * 2 + nt) * 2];
                o[v][0] = o[v][1] = o[v][2] = o[v][3] = 0;
                mma_h(o[v][0], o[v][1], re[0][v], re[1][v], im[0][v], im[1][v], b0, b1);
                mma_h(o[v][2], o[v][3], re[2][v], re[2][v], im[2][v], im[2][v], b0, b1);
            }
            const uint32_t a = srow + (g + 72 * q + 36 * nt) * 4, a2 = srow + (288 - g - 72 * q - 36 * nt) * 4;
            sts32(a, hadd2(o[0][0], o[1][0])); sts32(a + 32, hadd2(o[0][1], o[1][1])); if (g < 3) sts32(a + 64, hadd2(o[0][2], o[1][2]));
            if (g > 0 || (q == 0 && nt == 0)) sts32(a2, hsub2(o[0][0], o[1][0]) ^ 0x80000000u);
            sts32(a2 - 32, hsub2(o[0][1], o[1][1]) ^ 0x80000000u); if (g < 2) sts32(a2 - 64, hsub2(o[0][2], o[1][2]) ^ 0x80000000u);
        }
        uint32_t b3[16];
        if (warp < 10) load_tab<4>(b3, sm + OFF_B3 + lane * 16);
        __syncthreads();
        t_st = clk32();
        PROF0(4);
        if (warp < 10) {
            uint4 V[4], o[4];
            #pragma unroll
            for (int u = 0; u < 4; u++) V[u] = lds128(scol + u * (16 * SPEC_P));
            radix16(V, b3, o);
            #pragma unroll
            for (int nt = 0; nt < 4; nt++) { o[nt].x |= 1u; if (warp < 9 || g < 2) stx128(tptr + nt * tstr, o[nt]); }
        }
        PROF0(5);
    }

    int role = 0;
    asm volatile("barrier.cluster.wait.aligned;" ::: "memory");
    if (warp >= 12) {
        const int t = tid - 384;
        if (tid == 448 && rank == 0) {
            uint32_t smid; asm volatile("mov.u32 %0, %%smid;" : "=r"(smid));
            const uint32_t tp = smid >> 1;
            uint32_t pr = tp < 32 ? (tp & 7) * 8 + (tp >> 3) : tp < 60 ? (1 + (tp - 32) % 7) * 8 + 4 + (tp - 32) / 7 : tp < 62 ? 4 + tp : tp < 66 ? tp - 58 : 0;
            while (atomicExch(g_slot + pr, epoch + 1) == epoch + 1) pr = pr == 65 ? 0 : pr + 1;
            #pragma unroll
            for (int r = 0; r < 2; r++)
                asm volatile("st.async.weak.shared::cluster.mbarrier::complete_tx::bytes.u32 [%0], %1, [%2];" :: "r"(mapa(sm + OFF_MISC, r)), "r"(pr), "r"(mapa(bars + 8 * BAR_ROLE, r)) : "memory");
        }
        __syncwarp();
        if (t == 0) {
            asm volatile("prefetch.tensormap [%0];" :: "l"(&tm_w1a) : "memory");
            asm volatile("prefetch.tensormap [%0];" :: "l"(&tm_h3a) : "memory"); asm volatile("prefetch.tensormap [%0];" :: "l"(&tm_w1b) : "memory");
            asm volatile("prefetch.tensormap [%0];" :: "l"(&tm_h3b) : "memory"); asm volatile("prefetch.tensormap [%0];" :: "l"(&tm_w2) : "memory");
            asm volatile("prefetch.tensormap [%0];" :: "l"(&tm_o) : "memory"); asm volatile("prefetch.tensormap [%0];" :: "l"(&tm_h3s) : "memory");
        }
        if (t == 32 && rowcta) {
            for (int it = 0; (int)(ld_acquire(g_cnt + CNT_NC * 32) - (epoch + 1) * 4) < 0; it++) { __nanosleep(100); if (it > SPIN_LIMIT) __trap(); }
            fence_async_g();
            mbar_expect(bars + 8 * BAR_NC, 3584);
            bulk_load(sm + OFF_MODC, p.scr->modc, 3584, bars + 8 * BAR_NC);
            PROFT(29);
        }
        __syncwarp();
    } else if (rowcta && warp < 11) {
        const int nw = !(b & 1) ? 10 : (b & 7) == 7 ? 9 : 8;
        const int cm = (b >> 3) * 288 + (b & 7) * 32, cx = (b & 1) ? 4608 + 8 * (b >> 3) : (b >> 3) * 288 + 256 + 4 * (b & 7);
        auto load_in = [&]() {
            if (elect()) {
                mbar_expect(bars + 8 * BAR_XB, nw > 8 ? 20480 : 16384);
                tma2(sm + OFF_STAGE, &tm_t, cm, 0, bars + 8 * BAR_XB);
                if (nw > 8) tma2(sm + OFF_STX, &tm_tx, cx, 0, bars + 8 * BAR_XB);
            }
            __syncwarp();
        };
        if (warp == 10) { fence_async_s(); spin_until(t_st + X1D); load_in(); }
        uint32_t tb[QB * 4], wre[4][2], wim[4][2];
        if (warp < nw) {
            mbar_wait(bars + 8 * BAR_TAB2, 0);
            load_tab<QB>(tb, sm + OFF_TAB + QA * 512 + lane * 16);
            mbar_wait(bars + 8 * BAR_W, 0);
            const int off = wc0 & 7;
            const uint32_t wa = sm + OFF_WRAW + lane * 112 + ((off >> 1) + 2 * warp) * 4, sh = (off & 1) * 16;
            #pragma unroll
            for (int c = 0; c < 2; c++)
                #pragma unroll
                for (int h = 0; h < 2; h++) {
                    uint32_t y[2][2];
                    #pragma unroll
                    for (int e = 0; e < 2; e++) {
                        const uint32_t a = wa + c * 14336 + (h + 2 * e) * 3584, x0 = lds32(a), x1 = lds32(a + 4), x2 = lds32(a + 8);
                        y[e][0] = __funnelshift_r(x0, x1, sh); y[e][1] = __funnelshift_r(x1, x2, sh);
                    }
                    #pragma unroll
                    for (int x = 0; x < 4; x++) {
                        const uint32_t v = (x & 1) ? pack_h(bf_hi(y[0][x >> 1]), bf_hi(y[1][x >> 1])) : pack_h(bf_lo(y[0][x >> 1]), bf_lo(y[1][x >> 1]));
                        if (c) wim[x][h] = v; else wre[x][h] = v;
                    }
                }
        }
        const uint32_t ca = warp < 8 ? sm + OFF_STAGE + lane * 128 + (warp ^ (lane & 7)) * 16 : sm + OFF_STX + lane * 32 + ((warp ^ g) & 1) * 16, cs = warp < 8 ? 4096 : 1024;
        uint32_t V[4][4];
        for (int it = 0;; it++) {
            mbar_wait(bars + 8 * BAR_XB, it & 1);
            uint32_t ok = 1;
            if (warp < nw) {
                #pragma unroll
                for (int u = 0; u < 4; u++) { uint4 t4 = lds128(ca + u * cs); V[u][0] = t4.x; V[u][1] = t4.y; V[u][2] = t4.z; V[u][3] = t4.w; ok &= t4.x; }
            }
            asm volatile("{.reg .pred p; setp.ne.u32 p, %0, 0; bar.red.and.pred p, 1, 352, p; selp.u32 %0, 1, 0, p;}" : "+r"(ok) :: "memory");
            if (ok) break;
            if (warp == 10) { load_in(); hb(); }
            if (it > SPIN_LIMIT / 64) __trap();
        }
        PROF0(7);
        if (warp < nw) {
            uint32_t zr[4][2], zi[4][2];
            #pragma unroll
            for (int x = 0; x < 4; x++) {
                uint32_t er = 0, ei = 0, or_ = 0, oi = 0;
                mma_h(er, ei, tb[0], tb[1], tb[2], tb[3], V[0][x], V[1][x]);
                mma_h(or_, oi, tb[4], tb[5], tb[6], tb[7], V[2][x], V[3][x]);
                uint32_t r0 = hadd2(er, or_), r1 = hsub2(er, or_), i0 = hadd2(ei, oi), i1 = hsub2(ei, oi);
                cmul_neg(r0, i0, tb[8], tb[9]); cmul_neg(r1, i1, tb[10], tb[11]);
                uint32_t xr0 = 0, xr1 = 0, xi0 = 0, xi1 = 0;
                mma_h(xr0, xr1, r0, r1, i0, i1, tb[12], tb[13]);
                mma_h(xi0, xi1, r0, r1, i0, i1, tb[14], tb[12]);
                cmul_pos(xr0, xi0, wre[x][0], wim[x][0]); cmul_pos(xr1, xi1, wre[x][1], wim[x][1]);
                r0 = 0; i0 = 0; r1 = 0; i1 = 0;
                mma_h(r0, i0, tb[12], tb[13], tb[14], tb[12], xr0, xi0);
                mma_h(r1, i1, tb[12], tb[13], tb[14], tb[12], xr1, xi1);
                cmul_pos(r0, i0, tb[15], tb[16]); cmul_pos(r1, i1, tb[17], tb[18]);
                zr[x][0] = hadd2(r0, r1); zr[x][1] = hsub2(r0, r1); zi[x][0] = hadd2(i0, i1); zi[x][1] = hsub2(i0, i1);
            }
            #pragma unroll
            for (int nt = 0; nt < 4; nt++) {
                uint4 o = make_uint4(0, 0, 0, 0);
                const int h = nt >> 1;
                mma_h(o.x, o.y, zr[0][h], zr[1][h], zi[0][h], zi[1][h], tb[19 + 2 * nt], tb[20 + 2 * nt]);
                mma_h(o.z, o.w, zr[2][h], zr[3][h], zi[2][h], zi[3][h], tb[19 + 2 * nt], tb[20 + 2 * nt]);
                o.x &= ~1u;
                sts128(ca + nt * cs, o);
            }
        }
        fence_async_s();
        bar_sync(1, 352);
        t_st = clk32();
        PROF0(8);
        if (warp == 10 && elect()) {
            asm volatile("cp.async.bulk.tensor.2d.global.shared::cta.bulk_group [%0, {%2, %3}], [%1];" :: "l"(&tm_t), "r"(sm + OFF_STAGE), "r"(cm), "r"(0) : "memory");
            if (nw > 8) asm volatile("cp.async.bulk.tensor.2d.global.shared::cta.bulk_group [%0, {%2, %3}], [%1];" :: "l"(&tm_tx), "r"(sm + OFF_STX), "r"(cx), "r"(0) : "memory");
            asm volatile("cp.async.bulk.commit_group;" ::: "memory");
            asm volatile("cp.async.bulk.wait_group.read 0;" ::: "memory");
        }
        __syncwarp();
    }

    if (warp >= 10) { mbar_wait(bars + 8 * BAR_ROLE, 0); role = __shfl_sync(~0u, lds32(sm + OFF_MISC), 0); fence_async_s(); }
    auto first_a = [&]() {
        if (warp >= 10 && role < 64 && elect()) {
            const int it = warp - 10, hi = it >= 3; const bool p2 = it - 3 * hi == 2;
            tma4(sm + OFF_A + it * A_BYTES, p2 ? &tm_w1b : &tm_w1a, 0, 0, p2 ? 64 * rank + 8 * hi : 4 * (it - hi),
                 9 * (role >> 3) + (p2 ? 8 : (role & 4) + 2 * rank), bars + 8 * (BAR_FULL + it));
        }
        __syncwarp();
    };
    if (!rowcta) first_a();
    else {
        uint32_t tc[QC * 4];
        mbar_wait(bars + 8 * BAR_TAB2, 0);
        load_tab<QC>(tc, sm + OFF_TAB + (QA + QB) * 512 + lane * 16);
        if (warp < 10) {
            uint32_t b3[16];
            load_tab<4>(b3, sm + OFF_B3 + 2048 + lane * 16);
            uint4 V[4], o[4];
            const bool tact = warp < 9 || g == 0;
            spin_until(t_st + X2D);
            #pragma unroll
            for (int u = 0; u < 4; u++) V[u] = make_uint4(tact, 0, 0, 0);
            for (int it = 0; __any_sync(~0u, (V[0].x | V[1].x | V[2].x | V[3].x) & 1u); it++) {
                #pragma unroll
                for (int u = 0; u < 4; u++) if (V[u].x & 1u) V[u] = ldx128(tptr + u * tstr);
                hb();
                if (it > SPIN_LIMIT) __trap();
            }
            PROF0(10);
            radix16(V, b3, o);
            if (tact) {
                #pragma unroll
                for (int nt = 0; nt < 4; nt++) sts128(scol + nt * (16 * SPEC_P), o[nt]);
            }
        }
        __syncthreads();
        PROF0(11);
        first_a();
        const uint32_t srow = sm + OFF_SPEC + warp * (SPEC_P * 4);
        uint32_t re[2][3], im[2][3];
        #pragma unroll
        for (int mt = 0; mt < 3; mt++) {
            const uint32_t a = srow + (g + 72 * q + 8 * mt) * 4, a2 = srow + (288 - g - 72 * q - 8 * mt) * 4;
            const uint32_t z0 = lds32(a), z1 = lds32(a + 144), z2 = lds32(a2), z3 = lds32(a2 - 144);
            #pragma unroll
            for (int m2 = 0; m2 < 2; m2++) {
                re[m2][mt] = 0; im[m2][mt] = 0;
                const uint32_t sg = m2 ? 0x3C00BC00u : 0xBC003C00u;
                mma_h(re[m2][mt], im[m2][mt], tc[m2 * 4], tc[m2 * 4 + 1], tc[m2 * 4 + 2], tc[m2 * 4 + 3], hfma2(z2, sg, z0), hfma2(z3, sg, z1));
                cmul_pos(re[m2][mt], im[m2][mt], tc[8 + (m2 * 3 + mt) * 2], tc[9 + (m2 * 3 + mt) * 2]);
            }
        }
        uint32_t md[28];
        mbar_wait(bars + 8 * BAR_NC, 0);
        load_tab<7>(md, sm + OFF_MODC + lane * 16);
        float y[5][4];
        #pragma unroll
        for (int nt = 0; nt < 5; nt++) {
            y[nt][0] = y[nt][1] = y[nt][2] = y[nt][3] = 0.f;
            #pragma unroll
            for (int mt = 0; mt < 3; mt++)
                mma_f(y[nt], re[0][mt], re[1][mt], im[0][mt], im[1][mt], tc[20 + (mt * 5 + nt) * 2], tc[21 + (mt * 5 + nt) * 2]);
        }
        #pragma unroll
        for (int i = 0; i < 9; i++) xw[i] = bfma2(md[i], pack_bf(y[i >> 1][i & 1], y[i >> 1][2 + (i & 1)]), xw[i]);
        float r, mr;
        ln_stats(xw, g, q, r, mr);
        uint32_t h[9], r2 = pack_bf(r, r), m2 = pack_bf(mr, mr);
        #pragma unroll
        for (int i = 0; i < 9; i++) h[i] = bfma2(bfma2(xw[i], r2, m2), md[18 + i], md[9 + i]);
        ln_stats(h, g, q, r, mr);
        r2 = pack_bf(r, r); m2 = pack_bf(mr, mr);
        {
            const int n7 = 2 * q + (g >> 2);
            const uint32_t a = sm + OFF_STAGE + (warp >> 3) * 9216 + n7 * 128 + ((warp & 7) ^ n7) * 16 + (g & 3) * 4;
            #pragma unroll
            for (int i = 0; i < 9; i++) sts32(a + i * 1024, bfma2(h[i], r2, m2));
        }
        fence_async_s();
        __syncthreads();
        PROF0(12);
        if (tid == 0) {
            asm volatile("cp.async.bulk.tensor.4d.global.shared::cta.bulk_group [%0, {%2, %2, %2, %3}], [%1];" :: "l"(&tm_h3s), "r"(sm + OFF_STAGE), "r"(0), "r"(b) : "memory");
            asm volatile("cp.async.bulk.commit_group;" ::: "memory");
        }
        #pragma unroll
        for (int i = 0; i < 9; i++) sts32(sm + OFF_X1 + warp * 1152 + (32 * i + 8 * q + g) * 4, xw[i]);
    }
    __syncthreads();
    if (rowcta) {
        if (tid == 0) { asm volatile("cp.async.bulk.wait_group 0;" ::: "memory"); fence_async_g(); red_release(g_cnt + CNT_H3 * 32); }
        PROF0(13);
        if (warp == 15) {
            __nanosleep(X1DELAY);
            #pragma unroll 1
            for (int r = 0; r < 16; r++) {
                uint4* dst = (uint4*)(p.out + (size_t)(b + 128 * r) * D_) + lane;
                const uint32_t src = sm + OFF_X1 + r * 1152 + lane * 16;
                dst[0] = lds128(src); dst[32] = lds128(src + 512); if (lane < 8) dst[64] = lds128(src + 1024);
                const uint32_t t1 = clk32(); while ((int)(clk32() - t1) < X1PACE) __nanosleep(50);
            }
            __syncwarp();
            if (lane == 0) { fence_async_g(); red_release(g_cnt + CNT_X1 * 32); }
        }
    }
    role = __shfl_sync(~0u, lds32(sm + OFF_MISC), 0);
    if (role >= 64) { if (warp == 0) PROFDUMP(); return; }

    const int gi = role >> 3, dt = role & 3, c2 = (role >> 2) & 1;
    const int wg = warp >> 2, wi = warp & 3;
    if (wg == 3) {
        uint32_t so = 0, eph = 1;
        #define RING_STEP(BYTES, OFF, ISSUE) do { \
            mbar_wait(bars + 8 * BAR_EMPTY + so, eph); \
            if (elect()) { const uint32_t fb = bars + 8 * BAR_FULL + so, dst = sm + (OFF) + so * ((BYTES) / 8); mbar_expect(fb, BYTES); ISSUE; } \
            so += 8; if (so == 8 * NST) { so = 0; eph ^= 1; } } while (0)
        if (warp == 12) {
            eph = 0;
            const int fb1 = 9 * gi + 4 * c2 + 2 * rank, sb2 = 4 * gi + 2 * c2;
            #pragma unroll 1
            for (int j = 16; j < 128; j += 4) {
                RING_STEP(A_BYTES, OFF_A, tma4(dst, &tm_w1a, 0, 0, j, fb1, fb));
                if (j < 64) { if (j & 4) RING_STEP(A_BYTES, OFF_A, tma4(dst, &tm_w1b, 0, 0, 64 * rank + j - 4, 9 * gi + 8, fb)); }
                else if (PF2 && (j & 28) == 4 * (role & 7) && elect())
                    asm volatile("cp.async.bulk.prefetch.tensor.3d.L2.global [%0, {%1, %2, %3}];" :: "l"(&tm_w2), "r"(0), "r"(64 * g2_kb(dt + ((j >> 3) & 4), rank)), "r"(sb2) : "memory");
            }
            #pragma unroll 1
            for (int n = 0; n < 36; n++) {
                if (n == G2E) mbar_wait(bars + 8 * BAR_REL, 0);
                if (n == A2E) { mbar_wait(bars + 8 * (BAR_UOK + 1), 0); if (A2D) spin_until(clk32() + A2D); }
                RING_STEP(A_BYTES, OFF_A, tma3(dst, &tm_w2, 0, 64 * g2_kb(n, rank), sb2, fb));
            }
        } else if (warp == 13) {
            const uint32_t e1 = __shfl_sync(~0u, epoch + 1, 0);
            fence_async_s();
            wait_count<0>(g_cnt + CNT_H3 * 32, e1 * 128);
            fence_async_g();
            if (lane == 0) PROFT(14);
            #pragma unroll 1
            for (int j = 0; j < 128; j += 4) {
                RING_STEP(B_BYTES, OFF_B, tma3(dst, &tm_h3a, 0, 18 * dt, j, fb));
                if (j < 64 && (j & 4)) RING_STEP(B_BYTES, OFF_B, tma3(dst, &tm_h3b, 0, 18 * dt + 9 * c2, 64 * rank + j - 4, fb));
            }
            int n = 0;
            #pragma unroll 1
            for (int cls = 0; cls < 3; cls++) {
                mbar_wait(bars + 8 * (BAR_UOK + cls), 0);
                fence_async_g();
                if (cls == 1 && lane == 0) PROFT(19);
                if (cls == 0 && lane == 0) PROFT(22);
                #pragma unroll 1
                for (; n < 16 * cls + 4; n++) {
                    if (n == G2E) mbar_wait(bars + 8 * BAR_REL, 0);
                    RING_STEP(B_BYTES, OFF_B, bulk_load(dst, g_U + (g2_kb(n, rank) * 4 + dt) * 1152, B_BYTES, fb));
                }
            }
            if (role == 0 && rank == 0 && lane == 0) st_relaxed(g_cnt + CNT_EPOCH * 32, e1);
        } else if (warp == 15) {
            if (elect()) mbar_arrive_remote(mapa(bars + 8 * BAR_HOLD, rank ^ 1));
            __syncwarp();
            bar_sync(6, 160);
            mbar_wait(bars + 8 * BAR_W1GO, 0);
            if (elect()) {
                char* dst = (char*)(g_U + ((9 * gi + 4 * c2 + 2 * rank + 1) * 4 + dt) * 1152);
                #pragma unroll 1
                for (int i = 0; i < W1N; i++) {
                    asm volatile("cp.async.bulk.global.shared::cta.bulk_group [%0], [%1], %2;" :: "l"(dst + i * (18432 / W1N)), "r"(sm + OFF_X1 + i * (18432 / W1N)), "n"(18432 / W1N) : "memory");
                    const uint32_t t1 = clk32(); while ((int)(clk32() - t1) < W1P) {}
                }
                asm volatile("cp.async.bulk.commit_group;" ::: "memory");
                asm volatile("cp.async.bulk.wait_group 0;" ::: "memory");
                fence_async_g(); red_release(g_cnt + (CNT_U + 16) * 32);
                #pragma unroll 1
                for (int n = 0; n < 4; n++) { __nanosleep(300); tma2(sm + OFF_X1 + n * 4608, &tm_o, 144 * dt, 256 * gi + 128 * c2 + 64 * (rank ^ 1) + 16 * n, bars + 8 * BAR_XT); }
            }
        } else {
            const uint32_t e1 = epoch + 1;
            if (lane == 0) {
                __nanosleep(4000);
                wait_count<200>(g_cnt + CNT_NC * 32, e1 * 4); wait_count<200>(g_cnt + (CNT_NC + 1) * 32, e1 * 2);
                fence_async_g();
                mbar_expect(bars + 8 * BAR_GB, 1152);
                bulk_load(sm + OFF_GB, p.scr->modc + 896, 1152, bars + 8 * BAR_GB);
                wait_count<200>(g_cnt + CNT_X1 * 32, e1 * 128);
                wait_count<50>(g_cnt + (CNT_U + dt * 2 + rank) * 32, e1 * 16);
                mbar_arrive(bars + 8 * BAR_UOK);
            }
            __syncwarp();
            bar_sync(4, 160);
            if (lane == 0) {
                fence_async_g(); red_release(g_cnt + (CNT_U + 8) * 32);
                mbar_arrive(bars + 8 * BAR_REL);
                PROFT(17);
                wait_count<0>(g_cnt + (CNT_U + 8) * 32, e1 * 128);
                mbar_arrive(bars + 8 * (BAR_UOK + 1));
                __nanosleep(1000);
                wait_count<100>(g_cnt + (CNT_U + 16) * 32, e1 * 128);
                mbar_arrive(bars + 8 * (BAR_UOK + 2));
            }
        }
    } else if (wg == 2) {
        float d0[36];
        const float bias = bf_lo(ldg_nc16(p.b1 + 576 * gi + 512 + 16 * wi + g + 8 * rank));
        for (int it = 0; it < 200 && !__any_sync(~0u, mbar_test(bars + 8 * BAR_FULL, 0)); it++) { hb(); __nanosleep(100); }
        const bool lead = wi == 0 && elect();
        #pragma unroll 1
        for (int i = 0; i < 8; i++) {
            const uint32_t s = P2S + 3 * (i & 1);
            mbar_wait(bars + 8 * BAR_FULL + 8 * s, (i >> 1) & 1);
            const uint32_t da = desc_lo(sm + OFF_A, 8192) + s * (A_BYTES / 16), db = desc_lo(sm + OFF_B, 128) + s * (B_BYTES / 16);
            WG_FENCE();
            wgmma72(d0, da, db, i);
            #pragma unroll
            for (int k = 1; k < 8; k++) wgmma72(d0, da + k * 128, db + k * 144, 1);
            WG_COMMIT();
            WG_WAIT(0);
            if (lead) mbar_arrive_n(bars + 8 * BAR_EMPTY + 8 * s, 2);
        }
        if (lead) PROFT(18);
        const uint32_t slot = sm + OFF_P2R + (tid & 127) * 16, ra = mapa(slot, rank ^ 1), rb = mapa(bars + 8 * BAR_P2R, rank ^ 1);
        float sv[18];
        #pragma unroll
        for (int i = 0; i < 18; i++) { const float lo = d0[4 * (i >> 1) + (i & 1)], hi = d0[4 * (i >> 1) + 2 + (i & 1)];
            sv[i] = rank ? lo : hi; d0[4 * (i >> 1) + (i & 1)] = (rank ? hi : lo) + bias; }
        mbar_wait(bars + 8 * BAR_HOLD, 0);
        #pragma unroll
        for (int i = 0; i < 4; i++)
            asm volatile("st.async.weak.shared::cluster.mbarrier::complete_tx::bytes.v4.f32 [%0], {%1,%2,%3,%4}, [%5];"
                :: "r"(ra + i * 2048), "f"(sv[4 * i]), "f"(sv[4 * i + 1]), "f"(sv[4 * i + 2]), "f"(sv[4 * i + 3]), "r"(rb) : "memory");
        asm volatile("st.async.weak.shared::cluster.mbarrier::complete_tx::bytes.v2.f32 [%0], {%1,%2}, [%3];" :: "r"(ra + 8192), "f"(sv[16]), "f"(sv[17]), "r"(rb) : "memory");
        mbar_wait(bars + 8 * BAR_P2R, 0);
        #pragma unroll
        for (int i = 0; i < 5; i++) {
            const uint4 v = lds128(slot + i * 2048);
            d0[8 * i] += __uint_as_float(v.x); d0[8 * i + 1] += __uint_as_float(v.y);
            if (i < 4) { d0[8 * i + 4] += __uint_as_float(v.z); d0[8 * i + 5] += __uint_as_float(v.w); }
        }
        asm volatile("bar.arrive 5, 256;" ::: "memory");
        gelu_store<0>(d0, (char*)(g_U + ((9 * gi + 8) * 4 + dt) * 1152) + wi * 4608 + rank * 2304 + c2 * 1152 + g * 16, q);
        bar_sync(8, 128);
        if (lead) { fence_async_g(); red_release(g_cnt + (CNT_U + dt * 2 + (gi >> 2)) * 32); PROFT(26); }
    } else {
        float d[72];
        const bool lead = wi == 0 && elect();
        const uint32_t da0 = desc_lo(sm + OFF_A + wg * 8192, 8192);
        const bool owner = (uint32_t)wg == rank;
        const int srow = 256 * gi + 128 * c2 + 64 * wg + 16 * wi;
        const uint32_t b2w0 = ldg_nc16(p.b2 + srow + g), b2w1 = ldg_nc16(p.b2 + srow + g + 8);
        {
            const int fr = 576 * gi + 256 * c2 + 128 * rank + 64 * wg + 16 * wi + g;
            const float bias0 = bf_lo(ldg_nc16(p.b1 + fr)), bias1 = bf_lo(ldg_nc16(p.b1 + fr + 8));
            #pragma unroll
            for (int i = 0; i < 72; i++) d[i] = (i & 2) ? bias1 : bias0;
            const uint32_t db1 = desc_lo(sm + OFF_B, 128);
            mainloop<DHI_H3, 0, IT_P1, false, true, false>(d, bars, da0, db1, lead, [&](int) {});
            mainloop<DHI_H3, IT_P1, IT_G2 - LEAD1, false, false, false>(d, bars, da0, db1, lead, [&](int) {});
            constexpr uint32_t EB = 8 * (BAR_EMPTY + (IT_G2 - LEAD1 - 1) % NST);
            if (wg == 1) { WG_WAIT(0); if (lead) mbar_arrive(bars + EB); bar_sync(9, 256); }
            #pragma unroll
            for (int i = IT_G2 - LEAD1; i < IT_G2; i++) {
                mbar_wait(bars + 8 * (BAR_FULL + i % NST), (i / NST) & 1);
                WG_FENCE();
                #pragma unroll
                for (int k = 0; k < 4; k++) {
                    if (i == IT_G2 - 1 && k == HOK1) WG_COMMIT();
                    wgmma144<DHI_H3>(d, da0 + (i % NST) * (A_BYTES / 16) + k * 128, db1 + (i % NST) * (B_BYTES / 16) + k * 288, 1);
                }
                WG_COMMIT();
                if (i == IT_G2 - 1 && HOK1 < 4) WG_WAIT(2); else WG_WAIT(1);
                if (lead && (i > IT_G2 - LEAD1 || wg == 0)) mbar_arrive(bars + 8 * (BAR_EMPTY + (i - 1) % NST));
            }
            if (wg == 0) { WG_WAIT(1); asm volatile("bar.arrive 9, 256;" ::: "memory"); }
            WG_WAIT(0);
            if (lead) mbar_arrive(bars + 8 * (BAR_EMPTY + (IT_G2 - 1) % NST));
            PROF0(16);
            if (wg == 1) bar_sync(5, 256);
            char* const ub = (wg == 0 ? (char*)(g_U + ((9 * gi + 4 * c2 + 2 * rank) * 4 + dt) * 1152) : (char*)__cvta_shared_to_generic(sm + OFF_X1)) + wi * 4608 + g * 16;
            gelu_store<0>(d, ub, q); gelu_store<2>(d, ub + 2304, q); gelu_store<36>(d, ub + 1152, q); gelu_store<38>(d, ub + 3456, q);
            PROF0(27);
            if (wg == 0) asm volatile("bar.arrive 4, 160;" ::: "memory");
            else { fence_async_s(); asm volatile("bar.arrive 6, 160;" ::: "memory"); }
        }
        const uint32_t db0 = desc_lo(sm + OFF_B, 2304);
        constexpr int IT_L = IT_END - NST, IT_X = IT_L - 4;
        mainloop<DHI_U, IT_G2, IT_X, true, true, false>(d, bars, da0, db0, lead,
            [&](int i) { if (i == IT_G2 + W1S && wg == 0 && lead) mbar_arrive(bars + 8 * BAR_W1GO); });
        const uint32_t ga0 = sm + OFF_GB + (144 * dt + 8 * q) * 2, tile = sm + OFF_X1 + wi * 4608, to = g * 288 + q * 16;
        #define QOFF(i_) (((i_) >> 2) * 2304 + 144 * (((i_) >> 1) & 1) + 64 * ((i_) & 1))
        #define SOFF(k_) (((k_) >> 1) * 2304 + 144 * ((k_) & 1) + 128 - 12 * q)
        #define DIDX(i_, k_) ((i_) < 8 ? 36 * (((i_) >> 1) & 1) + 16 * ((i_) & 1) + 4 * (k_) + 2 * ((i_) >> 2) : 36 * ((k_) & 1) + 32 + 2 * ((k_) >> 1))
        #define FIN(k_, f_) bfma2(g4.f_, pack_bf(d[DIDX(i, k_)], d[DIDX(i, k_) + 1]), xq[i].f_)
        uint4 xq[9];
        auto load_g = [&](int i) { uint4 r; if (i < 4) r = lds128(ga0 + QOFF(i)); else { r.x = r.z = lds32(ga0 + SOFF(0)); r.y = r.w = lds32(ga0 + SOFF(1)); } return r; };
        mainloop<DHI_U, IT_X, IT_L, false, false, false>(d, bars, da0, db0, lead, [&](int i) {
            if (!owner) {
                const uint32_t xa = tile + to;
                if (i == IT_X) { mbar_wait(bars + 8 * BAR_XT, 0); xq[0] = lds128(xa + QOFF(0)); xq[4] = lds128(xa + QOFF(4)); xq[1] = lds128(xa + QOFF(1)); }
                else if (i == IT_X + 1) { xq[5] = lds128(xa + QOFF(5)); xq[2] = lds128(xa + QOFF(2)); xq[6] = lds128(xa + QOFF(6)); }
                else if (i == IT_X + 2) { xq[3] = lds128(xa + QOFF(3)); xq[7] = lds128(xa + QOFF(7));
                    xq[8] = make_uint4(lds32(xa + SOFF(0)), lds32(xa + SOFF(1)), lds32(xa + SOFF(2)), lds32(xa + SOFF(3))); }
                else if (i == IT_X + 3) { if (elect()) mbar_arrive_remote(mapa(bars + 8 * BAR_DONE, rank ^ 1)); }
            } });
        if (owner) { WG_WAIT(0); if (lead) mbar_arrive(bars + 8 * (BAR_EMPTY + (IT_L - 1) % NST)); bar_sync(7, 256); }
        #pragma unroll
        for (int i = IT_L; i < IT_END; i++) {
            mbar_wait(bars + 8 * (BAR_FULL + i % NST), (i / NST) & 1);
            WG_FENCE();
            #pragma unroll
            for (int k = 0; k < 4; k++) {
                if (i == IT_END - 1 && k == HOK) WG_COMMIT();
                wgmma144<DHI_U>(d, da0 + (i % NST) * (A_BYTES / 16) + k * 128, db0 + (i % NST) * (B_BYTES / 16) + k * 288, 1);
            }
            WG_COMMIT();
            if (i == IT_L) { WG_WAIT(1); if (lead && !owner) mbar_arrive(bars + 8 * (BAR_EMPTY + (IT_L - 1) % NST)); }
        }
        PROF0(9);
        mbar_wait(bars + 8 * BAR_GB, 0);
        if (!owner) {
            const uint32_t ra = mapa(tile + lane * 16, rank ^ 1), rb = mapa(bars + 8 * BAR_RECV, rank ^ 1);
            mbar_wait(bars + 8 * BAR_DONE, 0);
            uint4 gn = load_g(0);
            WG_WAIT(1);
            asm volatile("bar.arrive 7, 256;" ::: "memory");
            WG_WAIT(0);
            #pragma unroll
            for (int i = 0; i < 72; i++) d[i] = fmaf(bf_lo((i & 2) ? b2w1 : b2w0), 2.f, d[i]);
            #pragma unroll
            for (int j = 0; j < 5; j++) {
                const uint4 g4 = gn;
                if (j < 4) gn = load_g(j + 1);
                #pragma unroll
                for (int i = j < 4 ? j : 8; i < 9; i += 4) if (i < 8 || j == 4)
                    asm volatile("st.async.weak.shared::cluster.mbarrier::complete_tx::bytes.v4.b32 [%0], {%1,%2,%3,%4}, [%5];"
                        :: "r"(ra + i * 512), "r"(FIN(0, x)), "r"(FIN(1, y)), "r"(FIN(2, z)), "r"(FIN(3, w)), "r"(rb) : "memory");
            }
            PROF0(6);
            if (warp == 0) PROFDUMP();
            return;
        }
        PROF0(24);
        mbar_wait(bars + 8 * BAR_RECV, 0);
        #pragma unroll
        for (int i = 0; i < 9; i++) xq[i] = lds128(tile + lane * 16 + i * 512);
        uint4 gn = load_g(0);
        WG_WAIT(0);
        __syncwarp();
        PROF0(21);
        #pragma unroll
        for (int j = 0; j < 5; j++) {
            const uint4 g4 = gn;
            if (j < 4) gn = load_g(j + 1);
            #pragma unroll
            for (int i = j < 4 ? j : 8; i < 9; i += 4) if (i < 8 || j == 4) {
                const uint4 o = make_uint4(FIN(0, x), FIN(1, y), FIN(2, z), FIN(3, w));
                if (i < 8) sts128(tile + to + QOFF(i), o);
                else { sts32(tile + to + SOFF(0), o.x); sts32(tile + to + SOFF(1), o.y); sts32(tile + to + SOFF(2), o.z); sts32(tile + to + SOFF(3), o.w); }
            }
        }
        fence_async_s();
        __syncwarp();
        if (elect()) {
            asm volatile("cp.async.bulk.tensor.2d.global.shared::cta.bulk_group [%0, {%2, %3}], [%1];" :: "l"(&tm_o), "r"(tile), "r"(144 * dt), "r"(srow) : "memory");
            asm volatile("cp.async.bulk.commit_group;" ::: "memory");
            asm volatile("cp.async.bulk.wait_group.read 0;" ::: "memory");
        }
        PROF0(23);
        if (warp == 0) { __syncwarp(); PROFDUMP(); }
    }
}

typedef CUresult (*EncodeFn)(CUtensorMap*, CUtensorMapDataType, cuuint32_t, void*, const cuuint64_t*, const cuuint64_t*, const cuuint32_t*,
                             const cuuint32_t*, CUtensorMapInterleave, CUtensorMapSwizzle, CUtensorMapL2promotion, CUtensorMapFloatOOBfill);

void encode(EncodeFn fn, CUtensorMap* m, CUtensorMapDataType dt, int rank, const void* ptr, const cuuint64_t* dims, const cuuint64_t* strides,
            const cuuint32_t* box, CUtensorMapSwizzle sw, CUtensorMapL2promotion promo = CU_TENSOR_MAP_L2_PROMOTION_L2_128B) {
    const cuuint32_t es[5] = {1, 1, 1, 1, 1};
    fn(m, dt, rank, (void*)ptr, dims, strides, box, es, CU_TENSOR_MAP_INTERLEAVE_NONE, sw, promo, CU_TENSOR_MAP_FLOAT_OOB_FILL_NONE);
}

}

extern "C" void kernel_launch(void* const* d_in, const int* in_sizes, int n_in, void* d_out, int out_size) {
    (void)in_sizes; (void)n_in; (void)out_size;
    Params p;
    p.x = (const uint16_t*)d_in[0]; p.wr = (const uint16_t*)d_in[1]; p.wi = (const uint16_t*)d_in[2];
    p.w1 = (const uint16_t*)d_in[4]; p.b1 = (const uint16_t*)d_in[5]; p.w2 = (const uint16_t*)d_in[6]; p.b2 = (const uint16_t*)d_in[7];
    p.c = (const uint16_t*)d_in[8]; p.wmod = (const uint16_t*)d_in[9]; p.out = (uint16_t*)d_out;

    void* fnp = nullptr; cudaDriverEntryPointQueryResult qr;
    cudaGetDriverEntryPoint("cuTensorMapEncodeTiled", &fnp, cudaEnableDefault, &qr);
    EncodeFn fn = (EncodeFn)fnp;
    cudaGetSymbolAddress((void**)&p.scr, g_scr); cudaGetSymbolAddress((void**)&p.tab, g_tab);
    void* h3p = p.scr->h3;
    CUtensorMap tw1a, tw1b, tw2, th3a, th3b, twr, twi, twm, tt, ttx, to, th3s, tws;
    {
        const cuuint64_t dims[4] = {64, 16, 128, 72}, st[3] = {128ull * F_ * 2, (cuuint64_t)F_ * 2, 128};
        const cuuint32_t ba[4] = {64, 16, 4, 2}, bb[4] = {64, 16, 8, 1};
        encode(fn, &tw1a, CU_TENSOR_MAP_DATA_TYPE_BFLOAT16, 4, p.w1, dims, st, ba, CU_TENSOR_MAP_SWIZZLE_128B);
        encode(fn, &tw1b, CU_TENSOR_MAP_DATA_TYPE_BFLOAT16, 4, p.w1, dims, st, bb, CU_TENSOR_MAP_SWIZZLE_128B);
    }
    {
        const cuuint64_t dims[3] = {64, F_, 32}, st[2] = {(cuuint64_t)S_ * 2, 128};
        const cuuint32_t bx[3] = {64, 64, 2};
        encode(fn, &tw2, CU_TENSOR_MAP_DATA_TYPE_BFLOAT16, 3, p.w2, dims, st, bx, CU_TENSOR_MAP_SWIZZLE_128B);
    }
    {
        const cuuint64_t dims[3] = {64, 72, 128}, st[2] = {256, 18432};
        const cuuint32_t ba[3] = {64, 18, 4}, bb[3] = {64, 9, 8};
        encode(fn, &th3a, CU_TENSOR_MAP_DATA_TYPE_UINT32, 3, h3p, dims, st, ba, CU_TENSOR_MAP_SWIZZLE_NONE);
        encode(fn, &th3b, CU_TENSOR_MAP_DATA_TYPE_UINT32, 3, h3p, dims, st, bb, CU_TENSOR_MAP_SWIZZLE_NONE);
    }
    {
        const cuuint64_t dims[4] = {32, 72, 2, 128}, st[3] = {256, 128, 18432};
        const cuuint32_t bx[4] = {32, 72, 2, 1};
        encode(fn, &th3s, CU_TENSOR_MAP_DATA_TYPE_UINT32, 4, h3p, dims, st, bx, CU_TENSOR_MAP_SWIZZLE_128B, CU_TENSOR_MAP_L2_PROMOTION_NONE);
    }
    {
        const cuuint64_t dims[3] = {4624, 4, 32}, st[2] = {9248 * 32, 9248};
        const cuuint32_t bx[3] = {56, 4, 32};
        encode(fn, &twr, CU_TENSOR_MAP_DATA_TYPE_BFLOAT16, 3, p.wr, dims, st, bx, CU_TENSOR_MAP_SWIZZLE_NONE);
        encode(fn, &twi, CU_TENSOR_MAP_DATA_TYPE_BFLOAT16, 3, p.wi, dims, st, bx, CU_TENSOR_MAP_SWIZZLE_NONE);
    }
    {
        const cuuint64_t dims[2] = {3456, 576}, st[1] = {6912};
        const cuuint32_t bx[2] = {32, 144};
        encode(fn, &tws, CU_TENSOR_MAP_DATA_TYPE_BFLOAT16, 2, p.wmod, dims, st, bx, CU_TENSOR_MAP_SWIZZLE_64B);
    }
    {
        const cuuint64_t dims[3] = {64, 576, 54}, st[2] = {6912, 128};
        const cuuint32_t bx[3] = {64, 32, 7};
        encode(fn, &twm, CU_TENSOR_MAP_DATA_TYPE_BFLOAT16, 3, p.wmod, dims, st, bx, CU_TENSOR_MAP_SWIZZLE_128B);
    }
    {
        const cuuint64_t dims[2] = {TP, 128}, st[1] = {TP * 4};
        const cuuint32_t ba[2] = {32, 128}, bb[2] = {8, 128};
        encode(fn, &tt, CU_TENSOR_MAP_DATA_TYPE_UINT32, 2, p.scr->T, dims, st, ba, CU_TENSOR_MAP_SWIZZLE_128B, CU_TENSOR_MAP_L2_PROMOTION_NONE);
        encode(fn, &ttx, CU_TENSOR_MAP_DATA_TYPE_UINT32, 2, p.scr->T, dims, st, bb, CU_TENSOR_MAP_SWIZZLE_32B, CU_TENSOR_MAP_L2_PROMOTION_NONE);
    }
    {
        const cuuint64_t dims[2] = {D_, S_}, st[1] = {D_ * 2};
        const cuuint32_t bx[2] = {144, 16};
        encode(fn, &to, CU_TENSOR_MAP_DATA_TYPE_BFLOAT16, 2, p.out, dims, st, bx, CU_TENSOR_MAP_SWIZZLE_NONE, CU_TENSOR_MAP_L2_PROMOTION_NONE);
    }
    cudaFuncSetAttribute(fused_kernel, cudaFuncAttributeMaxDynamicSharedMemorySize, SMEM_BYTES);
    cudaLaunchConfig_t cfg = {};
    cfg.gridDim = dim3(NCTA); cfg.blockDim = dim3(NTHR); cfg.dynamicSmemBytes = SMEM_BYTES; cfg.stream = cudaStreamPerThread;
    cudaLaunchAttribute at[1];
    at[0].id = cudaLaunchAttributeCooperative; at[0].val.cooperative = 1;
    cfg.attrs = at; cfg.numAttrs = 1;
    cudaLaunchKernelEx(&cfg, fused_kernel, p, tw1a, tw1b, tw2, th3a, th3b, twr, twi, twm, tt, ttx, to, th3s, tws);
}
```

```cpp
#include <cuda_runtime.h>
#include <cuda_bf16.h>
#include <cuda_fp16.h>
#include <cuda.h>
#include <stdint.h>

namespace {

constexpr int S_ = 2048, D_ = 576, F_ = 4608;
constexpr int NCTA = 132, NTHR = 512;
constexpr int TP = 4736;
constexpr int SPEC_P = 296;
constexpr int NST = 6;
constexpr int A_BYTES = 16384, B_BYTES = 18432;
constexpr int IT_P1 = 24, IT_G2 = 40, IT_END = 76;
constexpr int SPIN_LIMIT = 1 << 22;
#define X2D 1350
constexpr int P2S = 2;
#define LEAD1 4
#define W1N 8
#define W1P 100
#define W1S 5
#define XDELAY 900
#define HOK 2
#define HOK1 2
#define CRITPF 1
#define NCD 0
#define X1D 2200
#define PF0 4
#define PFS 3
#define PFN 9
#define X1DELAY 2000
#define X1PACE 400

constexpr int OFF_A = 0;
constexpr int OFF_B = NST * A_BYTES;
constexpr int OFF_P = OFF_B + NST * B_BYTES;
constexpr int OFF_BAR = OFF_P;
constexpr int OFF_MISC = OFF_P + 504;
constexpr int OFF_GB = OFF_P + 512;
constexpr int OFF_P2R = OFF_P + 1664;
constexpr int OFF_X1 = OFF_P2R;
constexpr int OFF_PROF = OFF_X1 + 18432;
constexpr int SMEM_BYTES = OFF_PROF + 512 + 1024;
constexpr int QA = 13, QB = 7, QC = 13;
constexpr int TAB_BYTES = (QA + QB + QC) * 512;
constexpr int OFF_STAGE = OFF_B;
constexpr int OFF_STX = OFF_STAGE + 16384;
constexpr int OFF_TAB = OFF_STAGE + 20480;
constexpr int OFF_SPEC = OFF_TAB + TAB_BYTES;
constexpr int OFF_WRAW = OFF_SPEC + 19072;
constexpr int OFF_B3 = OFF_WRAW + 28672;
constexpr int OFF_MODA = OFF_B3 + 4096;
constexpr int OFF_MODC = OFF_MODA + 2560;
constexpr int OFF_RED = OFF_MODC + 3584;
constexpr int OFF_SILU = OFF_RED + 1536;
static_assert(OFF_SILU + 1152 <= OFF_P && 6 * 28672 <= OFF_B3, "scratch overflow");
constexpr int OFF_STRIP = OFF_A;
static_assert(OFF_WRAW % 128 == 0 && OFF_STAGE % 128 == 0 && OFF_STX % 128 == 0, "align");
constexpr int BAR_FULL = 0, BAR_EMPTY = 6, BAR_TAB = 12, BAR_W = 13, BAR_P2R = 16,
              BAR_XT = 17, BAR_RECV = 18, BAR_ROLE = 19, BAR_NC = 20, BAR_TAB2 = 21, BAR_XB = 22, BAR_GB = 23, BAR_HOLD = 24, BAR_W1GO = 25, BAR_UOK = 26, BAR_DONE = 30, BAR_X = 31, BAR_ST = 47;

struct Cos1152 { double c[1152]; };
constexpr double cx_cos(double x) { double t = 1, s = 1; for (int i = 1; i < 14; i++) { t *= -x * x / ((2 * i - 1) * (2 * i)); s += t; } return s; }
constexpr Cos1152 make_cos() {
    Cos1152 r{};
    for (int i = 0; i <= 288; i++) {
        double v = (i == 288) ? 0.0 : cx_cos(3.14159265358979323846 * 2.0 * i / 1152.0);
        r.c[i] = v; r.c[576 - i] = -v; r.c[576 + i] = -v; r.c[(1152 - i) % 1152] = v;
    }
    return r;
}
constexpr uint32_t cx_f2h(double v) {
    uint32_t s = v < 0 ? 0x8000u : 0u; double a = v < 0 ? -v : v;
    if (a < 1e-9) return 0;
    int e = 0;
    while (a >= 2.0) { a *= 0.5; e++; }
    while (a < 1.0 && e > -14) { a *= 2.0; e--; }
    double m = a * 1024.0; uint32_t mi = (uint32_t)m; double fr = m - mi;
    if (fr > 0.5 || (fr == 0.5 && (mi & 1))) mi++;
    return s | (uint32_t)(((e + 14) << 10) + mi);
}
struct Tab { uint32_t w[(QA + QB + QC) * 128]; };
constexpr Tab make_tab() {
    Tab t{};
    Cos1152 ct = make_cos();
    auto C = [&](int num, int den) { return ct.c[(num % den) * (1152 / den)]; };
    auto Sn = [&](int num, int den) { return ct.c[((num % den) * (1152 / den) + 864) % 1152]; };
    auto put = [&](int q0, int idx, int lane, double lo, double hi) { t.w[((q0 + idx / 4) * 32 + lane) * 4 + idx % 4] = cx_f2h(lo) | (cx_f2h(hi) << 16); };
    for (int lane = 0; lane < 32; lane++) {
        const int g = lane >> 2, q = lane & 3;
        for (int mt = 0; mt < 3; mt++) {
            const int ka = 8 * mt + g;
            for (int r = 0; r < 10; r++) {
                const int im = r & 1, i0 = (r >> 1) * 2;
                double v[2] = {0, 0};
                for (int e = 0; e < 2; e++) { int i = i0 + e, d1 = 4 * i + q; if (i < 9 && ka <= 18) v[e] = (im ? -Sn(ka * d1, 36) : C(ka * d1, 36)) / 8; }
                put(0, mt * 10 + r, lane, v[0], v[1]);
            }
            for (int v = 0; v < 2; v++) {
                const int d2 = 4 * q + v;
                put(0, 30 + (mt * 2 + v) * 2, lane, C(ka * d2, 576) * 4 / 3, C(ka * (d2 + 2), 576) * 4 / 3);
                put(0, 31 + (mt * 2 + v) * 2, lane, Sn(ka * d2, 576) * 4 / 3, Sn(ka * (d2 + 2), 576) * 4 / 3);
            }
        }
        for (int v = 0; v < 2; v++) for (int nt = 0; nt < 2; nt++) {
            const int kb = 2 * (g >> 1) + nt, part = g & 1;
            double b0[2] = {0, 0}, b1[2] = {0, 0};
            for (int e = 0; e < 2; e++) { int d2 = 4 * q + 2 * e + v; double c = C(kb * d2, 16) / 4, s = Sn(kb * d2, 16) / 4;
                b0[e] = part ? -s : c; b1[e] = part ? c : s; }
            put(0, 42 + (v * 2 + nt) * 2, lane, b0[0], b0[1]); put(0, 43 + (v * 2 + nt) * 2, lane, b1[0], b1[1]);
        }
        for (int par = 0; par < 2; par++) for (int a = 0; a < 4; a++) {
            const int ja = 2 * (q + 4 * (a >> 1)) + par; const double c = C(g * ja, 16) / 4, s = Sn(g * ja, 16) / 4;
            put(QA, par * 4 + a, lane, (a & 1) ? -s : c, (a & 1) ? c : s);
        }
        for (int h = 0; h < 2; h++) {
            put(QA, 8 + 2 * h, lane, C((g + 8 * h) * (2 * q), 128) / 2, C((g + 8 * h) * (2 * q + 1), 128) / 2);
            put(QA, 9 + 2 * h, lane, Sn((g + 8 * h) * (2 * q), 128) / 2, Sn((g + 8 * h) * (2 * q + 1), 128) / 2);
            put(QA, 15 + 2 * h, lane, C(g * (8 * h + 2 * q), 128), C(g * (8 * h + 2 * q + 1), 128));
            put(QA, 16 + 2 * h, lane, Sn(g * (8 * h + 2 * q), 128), Sn(g * (8 * h + 2 * q + 1), 128));
        }
        put(QA, 12, lane, C(g * 2 * q, 8) / 2, C(g * (2 * q + 1), 8) / 2);
        put(QA, 13, lane, Sn(g * 2 * q, 8) / 2, Sn(g * (2 * q + 1), 8) / 2);
        put(QA, 14, lane, -Sn(g * 2 * q, 8) / 2, -Sn(g * (2 * q + 1), 8) / 2);
        for (int u = 0; u < 4; u++) {
            const int ja = 2 * ((g >> 1) + 4 * (u & 1)) + (u >> 1), part = g & 1; double b0[2] = {0, 0}, b1[2] = {0, 0};
            for (int e = 0; e < 2; e++) { int ka = 2 * q + e; double c = C(ja * ka, 16) / 4, s = Sn(ja * ka, 16) / 4;
                b0[e] = part ? s : c; b1[e] = part ? c : -s; }
            put(QA, 19 + u * 2, lane, b0[0], b0[1]); put(QA, 20 + u * 2, lane, b1[0], b1[1]);
        }
        for (int m2 = 0; m2 < 2; m2++) {
            const int d2 = 2 * g + m2;
            for (int a = 0; a < 4; a++) {
                const int kb = 2 * q + (a >> 1); const double c = C(d2 * kb, 16) / 4, s = Sn(d2 * kb, 16) / 4;
                put(QA + QB, m2 * 4 + a, lane, (a & 1) ? s : c, (a & 1) ? c : -s);
            }
            for (int mt = 0; mt < 3; mt++) {
                const int ka = 8 * mt + 2 * q;
                put(QA + QB, 8 + (m2 * 3 + mt) * 2, lane, C(ka * d2, 576) * 4 / 3, C((ka + 1) * d2, 576) * 4 / 3);
                put(QA + QB, 9 + (m2 * 3 + mt) * 2, lane, Sn(ka * d2, 576) * 4 / 3, Sn((ka + 1) * d2, 576) * 4 / 3);
            }
        }
        for (int mt = 0; mt < 3; mt++) for (int nt = 0; nt < 5; nt++) {
            const int i = 2 * nt + (g & 1), d1 = 4 * i + (g >> 1); double b0[2] = {0, 0}, b1[2] = {0, 0};
            for (int e = 0; e < 2; e++) { int ka = 8 * mt + 2 * q + e;
                if (ka <= 18 && i < 9) { double wt = (ka == 0 || ka == 18) ? 0.125 : 0.25; b0[e] = wt * C(ka * d1, 36); b1[e] = -wt * Sn(ka * d1, 36); } }
            put(QA + QB, 20 + (mt * 5 + nt) * 2, lane, b0[0], b0[1]); put(QA + QB, 21 + (mt * 5 + nt) * 2, lane, b1[0], b1[1]);
        }
    }
    return t;
}
__device__ __align__(128) const Tab g_tab = make_tab();

struct Scratch {
    uint32_t cnt[30 * 32];
    uint32_t slot[96];
    uint32_t mod[2304];
    uint32_t modc[896 + 288];
    uint32_t T[128 * TP];
    uint4 h3[128 * 1152];
    uint4 U[72 * 4 * 1152];
};
__device__ __align__(1024) Scratch g_scr;
#define g_cnt (p.scr->cnt)
#define g_slot (p.scr->slot)
#define g_mod (p.scr->mod)
#define g_T (p.scr->T)
#define g_h3 (p.scr->h3)
#define g_U (p.scr->U)
constexpr int CNT_EPOCH = 0, CNT_H3 = 1, CNT_X1 = 26, CNT_NC = 27, CNT_U = 2;
#define PROFT(i) do {} while (0)
#define PROFDUMP() do {} while (0)
#define PROF0(i) do {} while (0)

__device__ __forceinline__ void mbar_init(uint32_t bar, uint32_t cnt) { asm volatile("mbarrier.init.shared::cta.b64 [%0], %1;" :: "r"(bar), "r"(cnt) : "memory"); }
__device__ __forceinline__ void mbar_expect(uint32_t bar, uint32_t bytes) { asm volatile("mbarrier.arrive.expect_tx.shared::cta.b64 _, [%0], %1;" :: "r"(bar), "r"(bytes) : "memory"); }
__device__ __forceinline__ void mbar_arrive(uint32_t bar) { asm volatile("mbarrier.arrive.shared::cta.b64 _, [%0];" :: "r"(bar) : "memory"); }
__device__ __forceinline__ void mbar_arrive_n(uint32_t bar, uint32_t n) { asm volatile("mbarrier.arrive.shared::cta.b64 _, [%0], %1;" :: "r"(bar), "r"(n) : "memory"); }
__device__ __forceinline__ void mbar_arrive_remote(uint32_t rbar) { asm volatile("mbarrier.arrive.relaxed.cluster.shared::cluster.b64 _, [%0];" :: "r"(rbar) : "memory"); }
__device__ __forceinline__ void mbar_wait(uint32_t bar, uint32_t parity) {
    asm volatile("{.reg .pred p; .reg .u32 c;\n"
        "mbarrier.try_wait.parity.shared::cta.b64 p, [%0], %1;\n@p bra.uni DONE;\nmov.u32 c, 0;\n"
        "LOOP: mbarrier.try_wait.parity.shared::cta.b64 p, [%0], %1;\n@p bra.uni DONE;\n"
        "add.u32 c, c, 1;\nsetp.lt.u32 p, c, %2;\n@p bra.uni LOOP;\ntrap;\nDONE:}" :: "r"(bar), "r"(parity), "n"(SPIN_LIMIT) : "memory");
}
__device__ __forceinline__ bool mbar_test(uint32_t bar, uint32_t parity) {
    uint32_t ok; asm volatile("{.reg .pred p; mbarrier.test_wait.parity.shared::cta.b64 p, [%1], %2; selp.u32 %0, 1, 0, p;}" : "=r"(ok) : "r"(bar), "r"(parity) : "memory"); return ok; }
__device__ __forceinline__ uint32_t mapa(uint32_t a, uint32_t rank) { uint32_t r; asm("mapa.shared::cluster.u32 %0, %1, %2;" : "=r"(r) : "r"(a), "r"(rank)); return r; }
__device__ __forceinline__ uint32_t clk32() { uint32_t r; asm volatile("mov.u32 %0, %%clock;" : "=r"(r)); return r; }
__device__ __forceinline__ void hb() {
    asm volatile("{.reg .b32 a, b; .reg .pred p; mma.sync.aligned.m16n8k8.row.col.f16.f16.f16.f16 {a, b}, {%0,%0}, {%0}, {%0,%0};\n"
                 "setp.ne.u32 p, a, 0; @p trap;}" :: "r"(0));
}
__device__ __forceinline__ void spin_until(uint32_t t) { while (__any_sync(~0u, (int)(clk32() - t) < 0)) hb(); }
__device__ __forceinline__ bool elect() { uint32_t r; asm volatile("{.reg .pred p; elect.sync _|p, 0xffffffff; selp.u32 %0, 1, 0, p;}" : "=r"(r)); return r; }
__device__ __forceinline__ void bar_sync(int id, int n) { asm volatile("bar.sync %0, %1;" :: "r"(id), "r"(n) : "memory"); }
__device__ __forceinline__ void bulk_load(uint32_t dst, const void* src, uint32_t bytes, uint32_t bar) {
    asm volatile("cp.async.bulk.shared::cluster.global.mbarrier::complete_tx::bytes [%0], [%1], %2, [%3];" :: "r"(dst), "l"(src), "r"(bytes), "r"(bar) : "memory"); }
__device__ __forceinline__ void tma2(uint32_t dst, const CUtensorMap* m, int c0, int c1, uint32_t bar) {
    asm volatile("cp.async.bulk.tensor.2d.shared::cluster.global.mbarrier::complete_tx::bytes [%0], [%1, {%3, %4}], [%2];" :: "r"(dst), "l"(m), "r"(bar), "r"(c0), "r"(c1) : "memory"); }
__device__ __forceinline__ void tma3(uint32_t dst, const CUtensorMap* m, int c0, int c1, int c2, uint32_t bar) {
    asm volatile("cp.async.bulk.tensor.3d.shared::cluster.global.mbarrier::complete_tx::bytes [%0], [%1, {%3, %4, %5}], [%2];" :: "r"(dst), "l"(m), "r"(bar), "r"(c0), "r"(c1), "r"(c2) : "memory"); }
__device__ __forceinline__ void tma4(uint32_t dst, const CUtensorMap* m, int c0, int c1, int c2, int c3, uint32_t bar) {
    asm volatile("cp.async.bulk.tensor.4d.shared::cluster.global.mbarrier::complete_tx::bytes [%0], [%1, {%3, %4, %5, %6}], [%2];" :: "r"(dst), "l"(m), "r"(bar), "r"(c0), "r"(c1), "r"(c2), "r"(c3) : "memory"); }
__device__ __forceinline__ void fence_async_g() { asm volatile("fence.proxy.async.global;" ::: "memory"); }
__device__ __forceinline__ void fence_async_s() { asm volatile("fence.proxy.async.shared::cta;" ::: "memory"); }
__device__ __forceinline__ uint4 lds128(uint32_t a) { uint4 v; asm volatile("ld.shared.v4.u32 {%0,%1,%2,%3}, [%4];" : "=r"(v.x), "=r"(v.y), "=r"(v.z), "=r"(v.w) : "r"(a) : "memory"); return v; }
__device__ __forceinline__ uint32_t lds32(uint32_t a) { uint32_t v; asm volatile("ld.shared.u32 %0, [%1];" : "=r"(v) : "r"(a) : "memory"); return v; }
__device__ __forceinline__ void sts128(uint32_t a, uint4 v) { asm volatile("st.shared.v4.u32 [%0], {%1,%2,%3,%4};" :: "r"(a), "r"(v.x), "r"(v.y), "r"(v.z), "r"(v.w) : "memory"); }
__device__ __forceinline__ void sts32(uint32_t a, uint32_t v) { asm volatile("st.shared.u32 [%0], %1;" :: "r"(a), "r"(v) : "memory"); }
__device__ __forceinline__ void sts16(uint32_t a, uint32_t v) { asm volatile("st.shared.u16 [%0], %1;" :: "r"(a), "h"((uint16_t)v) : "memory"); }
__device__ __forceinline__ uint4 ldx128(const void* p) {
    uint4 v; asm volatile("{.reg .b128 t; .reg .b64 a, b; ld.relaxed.gpu.global.b128 t, [%4]; mov.b128 {a, b}, t; mov.b64 {%0,%1}, a; mov.b64 {%2,%3}, b;}"
        : "=r"(v.x), "=r"(v.y), "=r"(v.z), "=r"(v.w) : "l"(p) : "memory"); return v; }
__device__ __forceinline__ void stx128(void* p, uint4 v) {
    asm volatile("{.reg .b128 t; .reg .b64 a, b; mov.b64 a, {%1,%2}; mov.b64 b, {%3,%4}; mov.b128 t, {a, b}; st.relaxed.gpu.global.b128 [%0], t;}"
        :: "l"(p), "r"(v.x), "r"(v.y), "r"(v.z), "r"(v.w) : "memory"); }
__device__ __forceinline__ uint32_t ld_relaxed(const uint32_t* p) { uint32_t v; asm volatile("ld.relaxed.gpu.global.u32 %0, [%1];" : "=r"(v) : "l"(p) : "memory"); return v; }
__device__ __forceinline__ uint32_t ld_acquire(const uint32_t* p) { uint32_t v; asm volatile("ld.acquire.gpu.global.u32 %0, [%1];" : "=r"(v) : "l"(p) : "memory"); return v; }
__device__ __forceinline__ void st_relaxed(uint32_t* p, uint32_t v) { asm volatile("st.relaxed.gpu.global.u32 [%0], %1;" :: "l"(p), "r"(v) : "memory"); }
__device__ __forceinline__ void red_release(uint32_t* p) { asm volatile("red.release.gpu.global.add.u32 [%0], 1;" :: "l"(p) : "memory"); }
template <int SLEEP> __device__ __forceinline__ void wait_count(const uint32_t* p, uint32_t target) {
    int it = 0; while ((int)(ld_acquire(p) - target) < 0) { if (SLEEP) __nanosleep(SLEEP); if (++it > SPIN_LIMIT) __trap(); }
}
__device__ __forceinline__ uint32_t ldg_nc32(const void* p) { uint32_t v; asm volatile("ld.global.nc.L1::no_allocate.u32 %0, [%1];" : "=r"(v) : "l"(p)); return v; }
__device__ __forceinline__ uint32_t ldg_nc16(const void* p) { uint16_t v; asm volatile("ld.global.nc.u16 %0, [%1];" : "=h"(v) : "l"(p)); return v; }
__device__ __forceinline__ float bf_lo(uint32_t w) { return __uint_as_float(w << 16); }
__device__ __forceinline__ float bf_hi(uint32_t w) { return __uint_as_float(w & 0xFFFF0000u); }
__device__ __forceinline__ uint32_t pack_bf(float lo, float hi) { uint32_t r; asm("cvt.rn.bf16x2.f32 %0, %1, %2;" : "=r"(r) : "f"(hi), "f"(lo)); return r; }
__device__ __forceinline__ uint32_t pack_h(float lo, float hi) { uint32_t r; asm("cvt.rn.f16x2.f32 %0, %1, %2;" : "=r"(r) : "f"(hi), "f"(lo)); return r; }
__device__ __forceinline__ float bf_round(float v) { return bf_lo(pack_bf(v, 0.f)); }
__device__ __forceinline__ uint32_t hmul2(uint32_t a, uint32_t b) { uint32_t r; asm("mul.rn.f16x2 %0, %1, %2;" : "=r"(r) : "r"(a), "r"(b)); return r; }
__device__ __forceinline__ uint32_t hfma2(uint32_t a, uint32_t b, uint32_t c) { uint32_t r; asm("fma.rn.f16x2 %0, %1, %2, %3;" : "=r"(r) : "r"(a), "r"(b), "r"(c)); return r; }
__device__ __forceinline__ uint32_t hfms2(uint32_t a, uint32_t b, uint32_t c) { uint32_t r; asm("{.reg .b32 t; neg.f16x2 t, %3; fma.rn.f16x2 %0, %1, %2, t;}" : "=r"(r) : "r"(a), "r"(b), "r"(c)); return r; }
__device__ __forceinline__ uint32_t hadd2(uint32_t a, uint32_t b) { uint32_t r; asm("add.rn.f16x2 %0, %1, %2;" : "=r"(r) : "r"(a), "r"(b)); return r; }
__device__ __forceinline__ uint32_t hsub2(uint32_t a, uint32_t b) { uint32_t r; asm("sub.rn.f16x2 %0, %1, %2;" : "=r"(r) : "r"(a), "r"(b)); return r; }
__device__ __forceinline__ void cmul_neg(uint32_t& re, uint32_t& im, uint32_t c, uint32_t s) { uint32_t a = hfma2(re, c, hmul2(im, s)), b = hfms2(im, c, hmul2(re, s)); re = a; im = b; }
__device__ __forceinline__ void cmul_pos(uint32_t& re, uint32_t& im, uint32_t c, uint32_t s) { uint32_t a = hfms2(re, c, hmul2(im, s)), b = hfma2(im, c, hmul2(re, s)); re = a; im = b; }
__device__ __forceinline__ void mma_h(uint32_t& d0, uint32_t& d1, uint32_t a0, uint32_t a1, uint32_t a2, uint32_t a3, uint32_t b0, uint32_t b1) {
    asm("mma.sync.aligned.m16n8k16.row.col.f16.f16.f16.f16 {%0,%1}, {%2,%3,%4,%5}, {%6,%7}, {%0,%1};" : "+r"(d0), "+r"(d1) : "r"(a0), "r"(a1), "r"(a2), "r"(a3), "r"(b0), "r"(b1)); }
__device__ __forceinline__ void mma_h8(uint32_t& d0, uint32_t& d1, uint32_t a0, uint32_t a1, uint32_t b0) {
    asm("mma.sync.aligned.m16n8k8.row.col.f16.f16.f16.f16 {%0,%1}, {%2,%3}, {%4}, {%0,%1};" : "+r"(d0), "+r"(d1) : "r"(a0), "r"(a1), "r"(b0)); }
__device__ __forceinline__ void mma_f(float (&d)[4], uint32_t a0, uint32_t a1, uint32_t a2, uint32_t a3, uint32_t b0, uint32_t b1) {
    asm("mma.sync.aligned.m16n8k16.row.col.f32.f16.f16.f32 {%0,%1,%2,%3}, {%4,%5,%6,%7}, {%8,%9}, {%0,%1,%2,%3};"
        : "+f"(d[0]), "+f"(d[1]), "+f"(d[2]), "+f"(d[3]) : "r"(a0), "r"(a1), "r"(a2), "r"(a3), "r"(b0), "r"(b1)); }
template <int NQ> __device__ __forceinline__ void load_tab(uint32_t (&r)[NQ * 4], uint32_t addr) {
    #pragma unroll
    for (int i = 0; i < NQ; i++) { uint4 v = lds128(addr + i * 512); r[4 * i] = v.x; r[4 * i + 1] = v.y; r[4 * i + 2] = v.z; r[4 * i + 3] = v.w; }
}
__device__ __forceinline__ float gelu2(float x) {
    float t = x * fmaf(x * x, 0.044715f * 0.7978845608028654f, 0.7978845608028654f), th;
    asm volatile("tanh.approx.f32 %0, %1;" : "=f"(th) : "f"(t));
    return fmaf(x, th, x);
}
__device__ __forceinline__ uint32_t desc_lo(uint32_t addr, uint32_t lbo) { return ((addr & 0x3FFFF) >> 4) | ((lbo >> 4) << 16); }
constexpr uint32_t DHI_A = (1024 >> 4) | (1u << 30), DHI_H3 = 256 >> 4, DHI_U = 128 >> 4;
#define WG_FENCE() asm volatile("wgmma.fence.sync.aligned;" ::: "memory")
#define WG_COMMIT() asm volatile("wgmma.commit_group.sync.aligned;" ::: "memory")
#define WG_WAIT(n) asm volatile("wgmma.wait_group.sync.aligned %0;" :: "n"(n) : "memory")
#define R4(b) "+f"(d[b]), "+f"(d[b + 1]), "+f"(d[b + 2]), "+f"(d[b + 3])
#define R12(b) R4(b), R4(b + 4), R4(b + 8)
#define R36(b) R12(b), R12(b + 12), R12(b + 24)
template <uint32_t BHI> __device__ __forceinline__ void wgmma144(float (&d)[72], uint32_t da, uint32_t db, int acc) {
    asm volatile("{.reg .pred p; .reg .b64 a, b; setp.ne.b32 p, %74, 0; mov.b64 a, {%72, %75}; mov.b64 b, {%73, %76};\n"
        "wgmma.mma_async.sync.aligned.m64n144k16.f32.bf16.bf16 {%0,%1,%2,%3,%4,%5,%6,%7,%8,%9,%10,%11,%12,%13,%14,%15,%16,%17,%18,%19,%20,%21,%22,%23,"
        "%24,%25,%26,%27,%28,%29,%30,%31,%32,%33,%34,%35,%36,%37,%38,%39,%40,%41,%42,%43,%44,%45,%46,%47,"
        "%48,%49,%50,%51,%52,%53,%54,%55,%56,%57,%58,%59,%60,%61,%62,%63,%64,%65,%66,%67,%68,%69,%70,%71}, a, b, p, 1, 1, 1, 1;}\n"
        : R36(0), R36(36) : "r"(da), "r"(db), "r"(acc), "n"(DHI_A), "n"(BHI));
}
__device__ __forceinline__ void wgmma144x4(float (&d)[72], const uint64_t (&a)[4], const uint64_t (&b)[4]) {
    #define WG144 "wgmma.mma_async.sync.aligned.m64n144k16.f32.bf16.bf16 {%0,%1,%2,%3,%4,%5,%6,%7,%8,%9,%10,%11,%12,%13,%14,%15,%16,%17,%18,%19,%20,%21,%22,%23,%24,%25,%26,%27,%28,%29,%30,%31,%32,%33,%34,%35,%36,%37,%38,%39,%40,%41,%42,%43,%44,%45,%46,%47,%48,%49,%50,%51,%52,%53,%54,%55,%56,%57,%58,%59,%60,%61,%62,%63,%64,%65,%66,%67,%68,%69,%70,%71}, "
    asm volatile("{"
        WG144 "%72, %76, 1, 1, 1, 1, 1;\n" WG144 "%73, %77, 1, 1, 1, 1, 1;\n" WG144 "%74, %78, 1, 1, 1, 1, 1;\n" WG144 "%75, %79, 1, 1, 1, 1, 1;}\n"
        : R36(0), R36(36) : "l"(a[0]), "l"(a[1]), "l"(a[2]), "l"(a[3]), "l"(b[0]), "l"(b[1]), "l"(b[2]), "l"(b[3]));
}
__device__ __forceinline__ void wgmma72(float (&d)[36], uint32_t da, uint32_t db, int acc) {
    asm volatile("{.reg .pred p; .reg .b64 a, b; setp.ne.b32 p, %38, 0; mov.b64 a, {%36, %39}; mov.b64 b, {%37, %40};\n"
        "wgmma.mma_async.sync.aligned.m64n72k16.f32.bf16.bf16 {%0,%1,%2,%3,%4,%5,%6,%7,%8,%9,%10,%11,%12,%13,%14,%15,%16,%17,%18,%19,%20,%21,%22,%23,"
        "%24,%25,%26,%27,%28,%29,%30,%31,%32,%33,%34,%35}, a, b, p, 1, 1, 1, 1;}\n"
        : R36(0) : "r"(da), "r"(db), "r"(acc), "n"(DHI_A), "n"(DHI_H3));
}

__device__ __forceinline__ int g2_kb(int n, int kh, int gi, int c2) {
    if (n < 4) return 36 * kh + 9 * n + 8;
    if (n == 4) return 9 * gi + 4 * c2 + 2 * kh + 1;
    const int w = n > 20, m = n - (w ? 19 : 5);
    return 9 * ((gi * w + (m >> 1)) & 7) + 4 * (n == 35 ? 1 - c2 : m & 1) + 2 * kh + w;
}

__device__ __forceinline__ void add_lo(uint64_t& d, uint32_t a) { asm("{.reg .b32 l, h; mov.b64 {l, h}, %0; add.u32 l, l, %1; mov.b64 %0, {l, h};}" : "+l"(d) : "r"(a)); }
template <uint32_t BHI, int I0, int I1, bool FIRST, class Hook>
__device__ __forceinline__ void mainloop(float (&d)[72], uint32_t bars, uint32_t da0, uint32_t db0, bool lead, Hook hook) {
    uint32_t s = I0 % NST, ph = (I0 / NST) & 1, prev = (I0 + NST - (I0 == IT_P1 ? 2 : 1)) % NST;
    uint32_t ready = 0;
    uint64_t da[4], db[4];
    #pragma unroll
    for (int k = 0; k < 4; k++) { da[k] = ((uint64_t)DHI_A << 32) + da0 + s * (A_BYTES / 16) + k * 128; db[k] = ((uint64_t)BHI << 32) + db0 + s * (B_BYTES / 16) + k * 288; }
    #pragma unroll 1
    for (int i = I0; i < I1; i++) {
        if (!ready) mbar_wait(bars + 8 * BAR_FULL + 8 * s, ph);
        const uint32_t rel = bars + 8 * BAR_EMPTY + 8 * prev, ph0 = ph; const int i0 = i;
        const bool skip = I1 == IT_P1 && (s == P2S - 1 || s == P2S + 2);
        prev = s; s += skip ? 2 : 1; if (s >= NST) { s -= NST; ph ^= 1; }
        const uint32_t adva = (s - prev) * (A_BYTES / 16), advb = (s - prev) * (B_BYTES / 16);
        WG_FENCE();
        wgmma144x4(d, da, db);
        WG_COMMIT();
        #pragma unroll
        for (int k = 0; k < 4; k++) { add_lo(da[k], adva); add_lo(db[k], advb); }
        if (skip) { mbar_wait(bars + 8 * BAR_FULL + 8 * prev + 8, ph0); i++; }
        ready = __shfl_sync(~0u, (uint32_t)mbar_test(bars + 8 * BAR_FULL + 8 * s, ph), 0);
        WG_WAIT(1);
        if (lead && (!FIRST || i0 > I0)) mbar_arrive(rel);
        hook(i0);
    }
}

struct Params {
    const uint16_t *x, *wr, *wi, *w1, *b1, *w2, *b2, *c, *wmod;
    uint16_t* out;
    Scratch* scr;
    const Tab* tab;
};

__device__ __forceinline__ void mma_bf(float (&d)[4], const uint32_t (&a)[4], uint32_t b0, uint32_t b1) {
    asm("mma.sync.aligned.m16n8k16.row.col.f32.bf16.bf16.f32 {%0,%1,%2,%3}, {%4,%5,%6,%7}, {%8,%9}, {%0,%1,%2,%3};"
        : "+f"(d[0]), "+f"(d[1]), "+f"(d[2]), "+f"(d[3]) : "r"(a[0]), "r"(a[1]), "r"(a[2]), "r"(a[3]), "r"(b0), "r"(b1)); }
__device__ __forceinline__ void ldsm4t(uint32_t (&a)[4], uint32_t addr) {
    asm volatile("ldmatrix.sync.aligned.m8n8.x4.trans.shared.b16 {%0,%1,%2,%3}, [%4];" : "=r"(a[0]), "=r"(a[1]), "=r"(a[2]), "=r"(a[3]) : "r"(addr) : "memory"); }
__device__ __forceinline__ void ln_stats(const uint32_t (&w)[9], int g, int q, float& r, float& mr) {
    constexpr uint32_t ONE = 0x3F803F80u;
    float c[2][4] = {};
    #pragma unroll
    for (int p = 0; p < 5; p++) { const uint32_t hi = p < 4 ? w[p < 4 ? 2 * p + 1 : 0] : 0u, a[4] = {w[2 * p], ONE, hi, ONE}; mma_bf(c[p & 1], a, w[2 * p], hi); }
    const float t = (g & 1) ? c[0][1] + c[1][1] : c[0][0] + c[1][0];
    float s1 = (c[0][2] + c[1][2]) + (c[0][3] + c[1][3]), s2 = __shfl_sync(~0u, t, 9 * q) + __shfl_sync(~0u, t, 9 * q + 4);
    #pragma unroll
    for (int o = 1; o < 4; o <<= 1) { s1 += __shfl_xor_sync(~0u, s1, o); s2 += __shfl_xor_sync(~0u, s2, o); }
    const float m = s1 * (1.f / D_);
    asm("rsqrt.approx.ftz.f32 %0, %1;" : "=f"(r) : "f"(fmaxf(fmaf(s2, 1.f / D_, -m * m), 0.f) + 1e-5f));
    mr = -m * r;
}
__device__ __forceinline__ float silu(float v) { return __fdividef(v, 1.f + __expf(-v)); }
__device__ __forceinline__ uint32_t bfma2(uint32_t a, uint32_t b, uint32_t c) { uint32_t r; asm("fma.rn.bf16x2 %0, %1, %2, %3;" : "=r"(r) : "r"(a), "r"(b), "r"(c)); return r; }
__device__ __forceinline__ void radix16(const uint4 (&V)[4], const uint32_t (&B)[16], uint4 (&o)[4]) {
    #pragma unroll
    for (int nt = 0; nt < 4; nt++) {
        o[nt] = make_uint4(0, 0, 0, 0);
        #pragma unroll
        for (int ks = 0; ks < 2; ks++) {
            const uint32_t b0 = B[(ks * 4 + nt) * 2], b1 = B[(ks * 4 + nt) * 2 + 1];
            mma_h(o[nt].x, o[nt].y, V[2 * ks].x, V[2 * ks].y, V[2 * ks + 1].x, V[2 * ks + 1].y, b0, b1);
            mma_h(o[nt].z, o[nt].w, V[2 * ks].z, V[2 * ks].w, V[2 * ks + 1].z, V[2 * ks + 1].w, b0, b1);
        }
    }
}
template <int OFF, int N> __device__ __forceinline__ void gelu_store(const float (&d)[N], char* p, int q) {
    uint32_t w[9];
    #pragma unroll
    for (int blk = 0; blk < 9; blk++) w[blk] = pack_bf(gelu2(d[OFF + 4 * blk]), gelu2(d[OFF + 4 * blk + 1]));
    asm volatile("st.v4.u32 [%0], {%1,%2,%3,%4};" :: "l"(p + q * 128), "r"(w[0]), "r"(w[1]), "r"(w[2]), "r"(w[3]) : "memory");
    asm volatile("st.v4.u32 [%0+512], {%1,%2,%3,%4};" :: "l"(p + q * 128), "r"(w[4]), "r"(w[5]), "r"(w[6]), "r"(w[7]) : "memory");
    asm volatile("st.u32 [%0+1024], %1;" :: "l"(p + q * 4), "r"(w[8]) : "memory");
}

__global__ void __cluster_dims__(2, 1, 1) __launch_bounds__(NTHR, 1)
fused_kernel(const Params p,
             const __grid_constant__ CUtensorMap tm_w1a, const __grid_constant__ CUtensorMap tm_w1b, const __grid_constant__ CUtensorMap tm_w2,
             const __grid_constant__ CUtensorMap tm_h3a, const __grid_constant__ CUtensorMap tm_h3b,
             const __grid_constant__ CUtensorMap tm_wr, const __grid_constant__ CUtensorMap tm_wi, const __grid_constant__ CUtensorMap tm_wm,
             const __grid_constant__ CUtensorMap tm_t, const __grid_constant__ CUtensorMap tm_tx, const __grid_constant__ CUtensorMap tm_o,
             const __grid_constant__ CUtensorMap tm_h3s, const __grid_constant__ CUtensorMap tm_ws)
{
    extern __shared__ char smem_raw[];
    const uint32_t t0 = clk32();
    const uint32_t sm = __shfl_sync(~0u, ((uint32_t)__cvta_generic_to_shared(smem_raw) + 1023u) & ~1023u, 0);
    const int tid = threadIdx.x, warp = __shfl_sync(~0u, tid >> 5, 0), lane = tid & 31, g = lane >> 2, q = lane & 3;
    const int b = blockIdx.x;
    const uint32_t rank = b & 1;
    const uint32_t bars = sm + OFF_BAR;
    const bool rowcta = b < 128;

    auto nc_issue = [&](int st, uint32_t sl) {
        const int pass = st >= 18;
        mbar_expect(bars + 8 * (BAR_X + sl), 28672);
        tma3(sm + sl * 28672, &tm_wm, 0, 32 * (st - 18 * pass), 18 + 28 * pass + 7 * (b - 128), bars + 8 * (BAR_X + sl));
    };
    uint32_t epoch;
    const bool strip = b < 72 && !(b & 1);
    if (warp < 12) {
        epoch = ld_relaxed(g_cnt + CNT_EPOCH * 32);
        if (warp >= 8 && lane < 24 && (strip || !rowcta)) {
            uint32_t cw[3];
            #pragma unroll
            for (int u = 0; u < 3; u++) cw[u] = ldg_nc32(p.c + 144 * (warp - 8) + 48 * u + 2 * lane);
            #pragma unroll
            for (int u = 0; u < 3; u++) sts32(sm + OFF_SILU + (72 * (warp - 8) + 24 * u + lane) * 4, pack_bf(silu(bf_lo(cw[u])), silu(bf_hi(cw[u]))));
        }
        __syncwarp();
        hb();
        bar_sync(2, 512);
    } else {
        const int w4 = 4 * (warp - 12);
        if (elect()) {
            if (warp == 14 && b < 13) asm volatile("cp.async.bulk.prefetch.L2.global [%0], 512;" :: "l"(p.tab->w + b * 128) : "memory");
            if (strip && warp == 15) asm volatile("prefetch.tensormap [%0];" :: "l"(&tm_ws) : "memory");
            if (CRITPF) {
                asm volatile("cp.async.bulk.prefetch.L2.global [%0], 2304;" :: "l"(p.wmod + (b + 33 * w4) * 3456) : "memory");
                if (warp == 12 && b < 48) asm volatile("cp.async.bulk.prefetch.L2.global [%0], 2304;" :: "l"(p.wmod + (b + 528) * 3456) : "memory");
            }
        }
        if (warp == 13) hb();
        if (elect()) {
            if (rowcta) {
                for (int i = 0; i < 4; i++) mbar_init(bars + 8 * (BAR_X + w4 + i), 1);
                const uint32_t sb = bars + 8 * (BAR_ST + warp - 12);
                mbar_init(sb, 1);
                if (warp == 15) mbar_init(bars + 8 * BAR_TAB, 1);
                fence_async_s();
                if (warp == 15) { mbar_expect(bars + 8 * BAR_TAB, QA * 512); bulk_load(sm + OFF_TAB, p.tab, QA * 512, bars + 8 * BAR_TAB); }
                if (strip) { mbar_expect(sb, 9216); tma2(sm + OFF_STRIP + (warp - 12) * 9216, &tm_ws, 16 * b, 36 * w4, sb); }
            } else if (warp == 12) {
                for (int i = 0; i < 12; i++) mbar_init(bars + 8 * (BAR_X + i), i < 6 ? 1 : 14);
                fence_async_s();
                if (NCD) while ((int)(clk32() - t0) < NCD) {}
                for (int st = 0; st < 6; st++) nc_issue(st, st);
            }
            if (warp == 12) {
                asm volatile("prefetch.tensormap [%0];" :: "l"(&tm_wr) : "memory"); asm volatile("prefetch.tensormap [%0];" :: "l"(&tm_wi) : "memory");
                asm volatile("prefetch.tensormap [%0];" :: "l"(&tm_t) : "memory"); asm volatile("prefetch.tensormap [%0];" :: "l"(&tm_tx) : "memory");
            } else if (warp == 14) {
                for (int i = BAR_W; i < BAR_X; i++) mbar_init(bars + 8 * i, i == BAR_DONE ? 4 : i == BAR_W1GO ? 2 : 1);
                mbar_expect(bars + 8 * BAR_W, 28672); mbar_expect(bars + 8 * BAR_TAB2, (QB + QC) * 512);
                mbar_expect(bars + 8 * BAR_ROLE, 4); mbar_expect(bars + 8 * BAR_P2R, 9216); mbar_expect(bars + 8 * BAR_RECV, 18432); mbar_expect(bars + 8 * BAR_XT, 18432);
            } else if (warp == 13) {
                for (int i = 0; i < 2 * NST; i++) mbar_init(bars + 8 * i, 2);
                for (int i = 0; i < NST; i++) mbar_expect(bars + 8 * (BAR_FULL + i), A_BYTES);
            }
            asm volatile("fence.mbarrier_init.release.cluster;" ::: "memory");
        }
        __syncwarp();
        asm volatile("bar.arrive 2, 512;" ::: "memory");
        if (rowcta && elect()) {
            if (XDELAY) while ((int)(clk32() - t0) < XDELAY) {}
            for (int r = w4; r < w4 + 4; r++) {
                mbar_expect(bars + 8 * (BAR_X + r), 1152);
                bulk_load(sm + OFF_STAGE + r * 1152, p.x + (size_t)(b + 128 * r) * D_, 1152, bars + 8 * (BAR_X + r));
            }
        }
        __syncwarp();
        epoch = ld_relaxed(g_cnt + CNT_EPOCH * 32);
        sts16(sm + OFF_MODA + ((warp - 11) * 32 + lane) * 16 + w4 + 2, 0);
        #pragma unroll 1
        for (int s1 = (tid >> 4) & 7; s1 < 16; s1 += 8) {
            const int k1 = tid & 15;
            float s, c;
            __sincosf((float)(((k1 * (128 * s1 + b) + 1024) & 2047) - 1024) * (3.14159265358979f / 1024.f), &s, &c); s *= 0.25f; c *= 0.25f;
            const int rf = ((s1 >> 3) * 4 + (k1 >> 2)) * 2 + ((s1 >> 2) & 1), ri = ((k1 >> 3) * 4 + (s1 >> 2)) * 2 + ((k1 >> 2) & 1);
            const uint32_t af = sm + OFF_B3 + ((rf >> 2) * 32 + (k1 & 3) * 8 + (s1 & 3)) * 16 + (rf & 3) * 4;
            const uint32_t ai = sm + OFF_B3 + 2048 + ((ri >> 2) * 32 + (s1 & 3) * 8 + (k1 & 3)) * 16 + (ri & 3) * 4;
            sts32(af, pack_h(c, s)); sts32(af + 64, pack_h(-s, c)); sts32(ai, pack_h(c, -s)); sts32(ai + 64, pack_h(s, c));
        }
        hb();
        bar_sync(3, 128);
    }
    asm volatile("barrier.cluster.arrive.relaxed.aligned;" ::: "memory");
    const uint32_t tag = (epoch + 1) & 0xFFFFu;

    const int trow = 4 * (b & 7) + ((b >> 4) & 3) + 64 * ((b >> 3) & 1) + 32 * (b >> 6);
    uint32_t* const tptr = g_T + (size_t)trow * TP + (warp < 9 ? q * 288 + 32 * warp : 4608 + 8 * q) + 4 * g;
    const int tstr = warp < 9 ? 1152 : 32;
    const uint32_t scol = sm + OFF_SPEC + (q * SPEC_P + (warp < 8 ? 72 * (warp >> 1) + 40 * (warp & 1) + 4 * g : warp == 8 ? 72 * (g >> 1) + 32 + 4 * (g & 1) : 288 + 4 * g)) * 4;
    const int wc0 = (b >> 3) * 289 + 72 * ((b & 7) >> 1) + 40 * (b & 1);

    uint32_t xw[9], t_st = t0;
    if (!rowcta) {
        const int nst = b < 130 ? 36 : 18;
        __syncthreads();
        if (warp == 14) {
            uint32_t sl = 0, ph = 0;
            #pragma unroll 1
            for (int st = 6; st < nst; st++) {
                mbar_wait(bars + 8 * (BAR_X + 6 + sl), ph);
                if (elect()) nc_issue(st, sl);
                if (++sl == 6) { sl = 0; ph ^= 1; }
            }
        } else if (warp < 14) {
            uint32_t sl = 0, ph = 0;
            const uint32_t ad0 = sm + (warp >> 1) * 4096 + ((lane & 7) + 8 * (lane >> 4)) * 128, ch = (warp & 1) * 4 + ((lane >> 3) & 1);
            #pragma unroll 1
            for (int pass = 0; pass * 18 < nst; pass++) {
                float acc[2][4] = {};
                #pragma unroll 1
                for (int st = 0; st < 18; st++) {
                    const uint32_t sa = sm + OFF_SILU + (16 * st + q) * 4;
                    const uint32_t b0 = lds32(sa), b1 = lds32(sa + 16), b2 = lds32(sa + 32), b3 = lds32(sa + 48);
                    mbar_wait(bars + 8 * (BAR_X + sl), ph);
                    #pragma unroll
                    for (int m = 0; m < 2; m++) {
                        uint32_t a[4], a2[4];
                        const uint32_t ad = ad0 + sl * 28672 + ((ch + 2 * m) ^ (lane & 7)) * 16;
                        ldsm4t(a, ad); ldsm4t(a2, ad + 2048);
                        mma_bf(acc[m], a, b0, b1); mma_bf(acc[m], a2, b2, b3);
                    }
                    if (elect()) mbar_arrive(bars + 8 * (BAR_X + 6 + sl));
                    if (++sl == 6) { sl = 0; ph ^= 1; }
                }
                const int cb = 28 * pass + 7 * (b - 128) + (warp >> 1), gg = (g >> 1) + 4 * q;
                #pragma unroll
                for (int m = 0; m < 2; m++) {
                    const int qq = (warp & 1) * 2 + m;
                    float v = bf_round(q ? acc[m][2] : acc[m][0]); if (cb >= 27) v *= 0.5f; else if (cb >= 18) v += 1.f;
                    const uint32_t w = pack_bf(v, __shfl_xor_sync(~0u, v, 4));
                    if (q < 2 && !(g & 1) && cb < 36) p.scr->modc[cb < 27 ? ((cb >> 2) * 32 + 4 * gg + qq) * 4 + (cb & 3) : 896 + 32 * (cb - 27) + 8 * qq + gg] = w;
                }
                bar_sync(1, 448);
                if (tid == 0) { fence_async_g(); red_release(g_cnt + (CNT_NC + pass) * 32); if (pass == 0) PROFT(25); }
                __syncwarp();
            }
            fence_async_s();
        }
        __syncthreads();
    } else {
        uint32_t ta[QA * 4];
        if (strip && (warp >> 2) == 2) {
            const int w = warp - 8;
            uint32_t sb[18];
            #pragma unroll
            for (int u = 0; u < 18; u++) sb[u] = lds32(sm + OFF_SILU + (72 * w + 4 * u + q) * 4);
            const uint32_t ra = sm + OFF_STRIP + (144 * w + (lane & 7) + 8 * (lane >> 4)) * 64, sw = (lane >> 1) & 3, ch = (lane >> 3) & 1;
            float acc[2][2][4] = {};
            mbar_wait(bars + 8 * (BAR_ST + w), 0);
            #pragma unroll
            for (int u = 0; u < 9; u++)
                #pragma unroll
                for (int m = 0; m < 2; m++) { uint32_t a[4]; ldsm4t(a, ra + u * 1024 + ((ch + 2 * m) ^ sw) * 16); mma_bf(acc[u & 1][m], a, sb[2 * u], sb[2 * u + 1]); }
            #define PICK(a_) ((q & 2) ? ((q & 1) ? a_[1][2] : a_[1][0]) : ((q & 1) ? a_[0][2] : a_[0][0]))
            sts32(sm + OFF_RED + ((8 * q + g) * 4 + w) * 4, __float_as_uint(PICK(acc[0]) + PICK(acc[1])));
            if (tid == 256) PROFT(0);
            bar_sync(10, 128);
            if (warp == 8) {
                const uint4 v = lds128(sm + OFF_RED + lane * 16);
                float sum = bf_round((__uint_as_float(v.x) + __uint_as_float(v.y)) + (__uint_as_float(v.z) + __uint_as_float(v.w)));
                if (b >= 36) sum = bf_round(1.f + sum);
                st_relaxed(g_mod + b * 16 + (lane & 16) + (lane & 1) * 8 + ((lane & 15) >> 1), (pack_h(0.f, sum) & 0xFFFF0000u) | tag);
                if (tid == 256) PROFT(1);
            }
        }
        mbar_wait(bars + 8 * BAR_TAB, 0);
        load_tab<QA>(ta, sm + OFF_TAB + lane * 16);
        auto w_prefetch = [&]() {
            if (warp >= 14 && elect()) asm volatile("cp.async.bulk.prefetch.L2.global [%0], 9248;" :: "l"((warp == 14 ? p.wr : p.wi) + b * 4624) : "memory");
            __syncwarp();
        };
        uint32_t nb[2][5];
        uint4 mv = make_uint4(tag, tag, tag, tag);
        const bool poller = warp < 8 || warp == 12;
        const int mc = warp < 8 ? tid : tid - 128, mst = (mc >> 2) % 36, midx = (mc < 144 ? 10 : 0) + 5 * ((mc >> 1) & 1) + (mst >> 3);
        const uint32_t* mp = g_mod + mc * 4;
        const uint32_t ma = sm + OFF_MODA + ((midx >> 2) * 32 + (mc & 1) * 16 + (mst & 3)) * 16 + (midx & 3) * 4 + ((mst >> 2) & 1) * 2;
        #define MOD_MISSING ((((mv.x ^ tag) | (mv.y ^ tag) | (mv.z ^ tag) | (mv.w ^ tag)) & 0xFFFFu) != 0)
        hb();
        mbar_wait(bars + 8 * (BAR_X + warp), 0);
        if (poller) mv = ldx128(mp);
        PROF0(28);
        #pragma unroll
        for (int i = 0; i < 9; i++) xw[i] = lds32(sm + OFF_STAGE + warp * 1152 + (32 * i + 8 * q + g) * 4);
        {
            float r, mr;
            ln_stats(xw, g, q, r, mr);
            #pragma unroll
            for (int pp = 0; pp < 5; pp++) {
                nb[0][pp] = pack_h(fmaf(bf_lo(xw[2 * pp]), r, mr), pp < 4 ? fmaf(bf_lo(xw[pp < 4 ? 2 * pp + 1 : 0]), r, mr) : 0.f);
                nb[1][pp] = pack_h(fmaf(bf_hi(xw[2 * pp]), r, mr), pp < 4 ? fmaf(bf_hi(xw[pp < 4 ? 2 * pp + 1 : 0]), r, mr) : 0.f);
            }
        }
        PROF0(2);
        w_prefetch();
        if (poller) {
            for (int it = 0; __any_sync(~0u, MOD_MISSING); it++) { if (MOD_MISSING) mv = ldx128(mp); hb(); if (it > SPIN_LIMIT) __trap(); }
            sts16(ma, mv.x >> 16); sts16(ma + 64, mv.y >> 16); sts16(ma + 128, mv.z >> 16); sts16(ma + 192, mv.w >> 16);
        }
        __syncthreads();
        PROF0(3);
        if (warp >= 13 && elect()) {
            if (warp == 15) bulk_load(sm + OFF_TAB + QA * 512, p.tab->w + QA * 128, (QB + QC) * 512, bars + 8 * BAR_TAB2);
            else tma3(sm + OFF_WRAW + (warp - 13) * 14336, warp == 13 ? &tm_wr : &tm_wi, wc0 & ~7, 0, 0, bars + 8 * BAR_W);
        }
        __syncwarp();
        {
            uint32_t md[20];
            load_tab<5>(md, sm + OFF_MODA + lane * 16);
            #pragma unroll
            for (int v = 0; v < 2; v++)
                #pragma unroll
                for (int pp = 0; pp < 5; pp++) nb[v][pp] = hfma2(nb[v][pp], md[v * 5 + pp], md[10 + v * 5 + pp]);
        }
        uint32_t re[3][2], im[3][2];
        #pragma unroll
        for (int mt = 0; mt < 3; mt++)
            #pragma unroll
            for (int v = 0; v < 2; v++) {
                re[mt][v] = 0; im[mt][v] = 0;
                mma_h8(re[mt][v], im[mt][v], ta[mt * 10 + 8], ta[mt * 10 + 9], nb[v][4]);
                mma_h(re[mt][v], im[mt][v], ta[mt * 10], ta[mt * 10 + 1], ta[mt * 10 + 2], ta[mt * 10 + 3], nb[v][0], nb[v][1]);
                mma_h(re[mt][v], im[mt][v], ta[mt * 10 + 4], ta[mt * 10 + 5], ta[mt * 10 + 6], ta[mt * 10 + 7], nb[v][2], nb[v][3]);
                cmul_neg(re[mt][v], im[mt][v], ta[30 + (mt * 2 + v) * 2], ta[31 + (mt * 2 + v) * 2]);
            }
        const uint32_t srow = sm + OFF_SPEC + warp * (SPEC_P * 4);
        #pragma unroll
        for (int nt = 0; nt < 2; nt++) {
            uint32_t o[2][4];
            #pragma unroll
            for (int v = 0; v < 2; v++) {
                const uint32_t b0 = ta[42 + (v * 2 + nt) * 2], b1 = ta[43 + (v * 2 + nt) * 2];
                o[v][0] = o[v][1] = o[v][2] = o[v][3] = 0;
                mma_h(o[v][0], o[v][1], re[0][v], re[1][v], im[0][v], im[1][v], b0, b1);
                mma_h(o[v][2], o[v][3], re[2][v], re[2][v], im[2][v], im[2][v], b0, b1);
            }
            const uint32_t a = srow + (g + 72 * q + 36 * nt) * 4, a2 = srow + (288 - g - 72 * q - 36 * nt) * 4;
            sts32(a, hadd2(o[0][0], o[1][0])); sts32(a + 32, hadd2(o[0][1], o[1][1])); if (g < 3) sts32(a + 64, hadd2(o[0][2], o[1][2]));
            if (g > 0 || (q == 0 && nt == 0)) sts32(a2, hsub2(o[0][0], o[1][0]) ^ 0x80000000u);
            sts32(a2 - 32, hsub2(o[0][1], o[1][1]) ^ 0x80000000u); if (g < 2) sts32(a2 - 64, hsub2(o[0][2], o[1][2]) ^ 0x80000000u);
        }
        uint32_t b3[16];
        if (warp < 10) load_tab<4>(b3, sm + OFF_B3 + lane * 16);
        __syncthreads();
        t_st = clk32();
        PROF0(4);
        if (warp < 10) {
            uint4 V[4], o[4];
            #pragma unroll
            for (int u = 0; u < 4; u++) V[u] = lds128(scol + u * (16 * SPEC_P));
            radix16(V, b3, o);
            #pragma unroll
            for (int nt = 0; nt < 4; nt++) { o[nt].x |= 1u; if (warp < 9 || g < 2) stx128(tptr + nt * tstr, o[nt]); }
        }
        PROF0(5);
    }

    int role = 0;
    asm volatile("barrier.cluster.wait.aligned;" ::: "memory");
    if (warp >= 12) {
        const int t = tid - 384;
        if (tid == 448 && rank == 0) {
            uint32_t smid; asm volatile("mov.u32 %0, %%smid;" : "=r"(smid));
            const uint32_t tp = smid >> 1;
            uint32_t pr = tp < 32 ? (tp & 7) * 8 + (tp >> 3) : tp < 60 ? (1 + (tp - 32) % 7) * 8 + 4 + (tp - 32) / 7 : tp < 62 ? 4 + tp : tp < 66 ? tp - 58 : 0;
            while (atomicExch(g_slot + pr, epoch + 1) == epoch + 1) pr = pr == 65 ? 0 : pr + 1;
            #pragma unroll
            for (int r = 0; r < 2; r++)
                asm volatile("st.async.weak.shared::cluster.mbarrier::complete_tx::bytes.u32 [%0], %1, [%2];" :: "r"(mapa(sm + OFF_MISC, r)), "r"(pr), "r"(mapa(bars + 8 * BAR_ROLE, r)) : "memory");
        }
        __syncwarp();
        if (t == 0) {
            asm volatile("prefetch.tensormap [%0];" :: "l"(&tm_w1a) : "memory");
            asm volatile("prefetch.tensormap [%0];" :: "l"(&tm_h3a) : "memory"); asm volatile("prefetch.tensormap [%0];" :: "l"(&tm_w1b) : "memory");
            asm volatile("prefetch.tensormap [%0];" :: "l"(&tm_h3b) : "memory"); asm volatile("prefetch.tensormap [%0];" :: "l"(&tm_w2) : "memory");
            asm volatile("prefetch.tensormap [%0];" :: "l"(&tm_o) : "memory"); asm volatile("prefetch.tensormap [%0];" :: "l"(&tm_h3s) : "memory");
        }
        if (t == 32 && rowcta) {
            for (int it = 0; (int)(ld_acquire(g_cnt + CNT_NC * 32) - (epoch + 1) * 4) < 0; it++) { __nanosleep(100); if (it > SPIN_LIMIT) __trap(); }
            fence_async_g();
            mbar_expect(bars + 8 * BAR_NC, 3584);
            bulk_load(sm + OFF_MODC, p.scr->modc, 3584, bars + 8 * BAR_NC);
            PROFT(29);
        }
        __syncwarp();
    } else if (rowcta && warp < 11) {
        const int nw = !(b & 1) ? 10 : (b & 7) == 7 ? 9 : 8;
        const int cm = (b >> 3) * 288 + (b & 7) * 32, cx = (b & 1) ? 4608 + 8 * (b >> 3) : (b >> 3) * 288 + 256 + 4 * (b & 7);
        auto load_in = [&]() {
            if (elect()) {
                mbar_expect(bars + 8 * BAR_XB, nw > 8 ? 20480 : 16384);
                tma2(sm + OFF_STAGE, &tm_t, cm, 0, bars + 8 * BAR_XB);
                if (nw > 8) tma2(sm + OFF_STX, &tm_tx, cx, 0, bars + 8 * BAR_XB);
            }
            __syncwarp();
        };
        if (warp == 10) { fence_async_s(); spin_until(t_st + X1D); load_in(); }
        uint32_t tb[QB * 4], wre[4][2], wim[4][2];
        if (warp < nw) {
            mbar_wait(bars + 8 * BAR_TAB2, 0);
            load_tab<QB>(tb, sm + OFF_TAB + QA * 512 + lane * 16);
            mbar_wait(bars + 8 * BAR_W, 0);
            const int off = wc0 & 7;
            const uint32_t wa = sm + OFF_WRAW + lane * 112 + ((off >> 1) + 2 * warp) * 4, sh = (off & 1) * 16;
            #pragma unroll
            for (int c = 0; c < 2; c++)
                #pragma unroll
                for (int h = 0; h < 2; h++) {
                    uint32_t y[2][2];
                    #pragma unroll
                    for (int e = 0; e < 2; e++) {
                        const uint32_t a = wa + c * 14336 + (h + 2 * e) * 3584, x0 = lds32(a), x1 = lds32(a + 4), x2 = lds32(a + 8);
                        y[e][0] = __funnelshift_r(x0, x1, sh); y[e][1] = __funnelshift_r(x1, x2, sh);
                    }
                    #pragma unroll
                    for (int x = 0; x < 4; x++) {
                        const uint32_t v = (x & 1) ? pack_h(bf_hi(y[0][x >> 1]), bf_hi(y[1][x >> 1])) : pack_h(bf_lo(y[0][x >> 1]), bf_lo(y[1][x >> 1]));
                        if (c) wim[x][h] = v; else wre[x][h] = v;
                    }
                }
        }
        const uint32_t ca = warp < 8 ? sm + OFF_STAGE + lane * 128 + (warp ^ (lane & 7)) * 16 : sm + OFF_STX + lane * 32 + ((warp ^ g) & 1) * 16, cs = warp < 8 ? 4096 : 1024;
        uint32_t V[4][4];
        for (int it = 0;; it++) {
            mbar_wait(bars + 8 * BAR_XB, it & 1);
            uint32_t ok = 1;
            if (warp < nw) {
                #pragma unroll
                for (int u = 0; u < 4; u++) { uint4 t4 = lds128(ca + u * cs); V[u][0] = t4.x; V[u][1] = t4.y; V[u][2] = t4.z; V[u][3] = t4.w; ok &= t4.x; }
            }
            asm volatile("{.reg .pred p; setp.ne.u32 p, %0, 0; bar.red.and.pred p, 1, 352, p; selp.u32 %0, 1, 0, p;}" : "+r"(ok) :: "memory");
            if (ok) break;
            if (warp == 10) { load_in(); hb(); }
            if (it > SPIN_LIMIT / 64) __trap();
        }
        PROF0(7);
        if (warp < nw) {
            uint32_t zr[4][2], zi[4][2];
            #pragma unroll
            for (int x = 0; x < 4; x++) {
                uint32_t er = 0, ei = 0, or_ = 0, oi = 0;
                mma_h(er, ei, tb[0], tb[1], tb[2], tb[3], V[0][x], V[1][x]);
                mma_h(or_, oi, tb[4], tb[5], tb[6], tb[7], V[2][x], V[3][x]);
                uint32_t r0 = hadd2(er, or_), r1 = hsub2(er, or_), i0 = hadd2(ei, oi), i1 = hsub2(ei, oi);
                cmul_neg(r0, i0, tb[8], tb[9]); cmul_neg(r1, i1, tb[10], tb[11]);
                uint32_t xr0 = 0, xr1 = 0, xi0 = 0, xi1 = 0;
                mma_h(xr0, xr1, r0, r1, i0, i1, tb[12], tb[13]);
                mma_h(xi0, xi1, r0, r1, i0, i1, tb[14], tb[12]);
                cmul_pos(xr0, xi0, wre[x][0], wim[x][0]); cmul_pos(xr1, xi1, wre[x][1], wim[x][1]);
                r0 = 0; i0 = 0; r1 = 0; i1 = 0;
                mma_h(r0, i0, tb[12], tb[13], tb[14], tb[12], xr0, xi0);
                mma_h(r1, i1, tb[12], tb[13], tb[14], tb[12], xr1, xi1);
                cmul_pos(r0, i0, tb[15], tb[16]); cmul_pos(r1, i1, tb[17], tb[18]);
                zr[x][0] = hadd2(r0, r1); zr[x][1] = hsub2(r0, r1); zi[x][0] = hadd2(i0, i1); zi[x][1] = hsub2(i0, i1);
            }
            #pragma unroll
            for (int nt = 0; nt < 4; nt++) {
                uint4 o = make_uint4(0, 0, 0, 0);
                const int h = nt >> 1;
                mma_h(o.x, o.y, zr[0][h], zr[1][h], zi[0][h], zi[1][h], tb[19 + 2 * nt], tb[20 + 2 * nt]);
                mma_h(o.z, o.w, zr[2][h], zr[3][h], zi[2][h], zi[3][h], tb[19 + 2 * nt], tb[20 + 2 * nt]);
                o.x &= ~1u;
                sts128(ca + nt * cs, o);
            }
        }
        fence_async_s();
        bar_sync(1, 352);
        t_st = clk32();
        PROF0(8);
        if (warp == 10 && elect()) {
            asm volatile("cp.async.bulk.tensor.2d.global.shared::cta.bulk_group [%0, {%2, %3}], [%1];" :: "l"(&tm_t), "r"(sm + OFF_STAGE), "r"(cm), "r"(0) : "memory");
            if (nw > 8) asm volatile("cp.async.bulk.tensor.2d.global.shared::cta.bulk_group [%0, {%2, %3}], [%1];" :: "l"(&tm_tx), "r"(sm + OFF_STX), "r"(cx), "r"(0) : "memory");
            asm volatile("cp.async.bulk.commit_group;" ::: "memory");
            asm volatile("cp.async.bulk.wait_group.read 0;" ::: "memory");
        }
        __syncwarp();
    }

    if (warp >= 10) { mbar_wait(bars + 8 * BAR_ROLE, 0); role = __shfl_sync(~0u, lds32(sm + OFF_MISC), 0); fence_async_s(); }
    auto first_a = [&]() {
        if (warp >= 10 && role < 64 && elect()) {
            const int it = warp - 10, hi = it >= 3; const bool p2 = it - 3 * hi == 2;
            tma4(sm + OFF_A + it * A_BYTES, p2 ? &tm_w1b : &tm_w1a, 0, 0, p2 ? 64 * rank + 8 * hi : 4 * (it - hi),
                 9 * (role >> 3) + (p2 ? 8 : (role & 4) + 2 * rank), bars + 8 * (BAR_FULL + it));
        }
        __syncwarp();
    };
    if (!rowcta) first_a();
    else {
        uint32_t tc[QC * 4];
        mbar_wait(bars + 8 * BAR_TAB2, 0);
        load_tab<QC>(tc, sm + OFF_TAB + (QA + QB) * 512 + lane * 16);
        if (warp < 10) {
            uint32_t b3[16];
            load_tab<4>(b3, sm + OFF_B3 + 2048 + lane * 16);
            uint4 V[4], o[4];
            const bool tact = warp < 9 || g == 0;
            spin_until(t_st + X2D);
            #pragma unroll
            for (int u = 0; u < 4; u++) V[u] = make_uint4(tact, 0, 0, 0);
            for (int it = 0; __any_sync(~0u, (V[0].x | V[1].x | V[2].x | V[3].x) & 1u); it++) {
                #pragma unroll
                for (int u = 0; u < 4; u++) if (V[u].x & 1u) V[u] = ldx128(tptr + u * tstr);
                hb();
                if (it > SPIN_LIMIT) __trap();
            }
            PROF0(10);
            radix16(V, b3, o);
            if (tact) {
                #pragma unroll
                for (int nt = 0; nt < 4; nt++) sts128(scol + nt * (16 * SPEC_P), o[nt]);
            }
        }
        __syncthreads();
        PROF0(11);
        first_a();
        const uint32_t srow = sm + OFF_SPEC + warp * (SPEC_P * 4);
        uint32_t re[2][3], im[2][3];
        #pragma unroll
        for (int mt = 0; mt < 3; mt++) {
            const uint32_t a = srow + (g + 72 * q + 8 * mt) * 4, a2 = srow + (288 - g - 72 * q - 8 * mt) * 4;
            const uint32_t z0 = lds32(a), z1 = lds32(a + 144), z2 = lds32(a2), z3 = lds32(a2 - 144);
            #pragma unroll
            for (int m2 = 0; m2 < 2; m2++) {
                re[m2][mt] = 0; im[m2][mt] = 0;
                const uint32_t sg = m2 ? 0x3C00BC00u : 0xBC003C00u;
                mma_h(re[m2][mt], im[m2][mt], tc[m2 * 4], tc[m2 * 4 + 1], tc[m2 * 4 + 2], tc[m2 * 4 + 3], hfma2(z2, sg, z0), hfma2(z3, sg, z1));
                cmul_pos(re[m2][mt], im[m2][mt], tc[8 + (m2 * 3 + mt) * 2], tc[9 + (m2 * 3 + mt) * 2]);
            }
        }
        uint32_t md[28];
        mbar_wait(bars + 8 * BAR_NC, 0);
        load_tab<7>(md, sm + OFF_MODC + lane * 16);
        float y[5][4];
        #pragma unroll
        for (int nt = 0; nt < 5; nt++) {
            y[nt][0] = y[nt][1] = y[nt][2] = y[nt][3] = 0.f;
            #pragma unroll
            for (int mt = 0; mt < 3; mt++)
                mma_f(y[nt], re[0][mt], re[1][mt], im[0][mt], im[1][mt], tc[20 + (mt * 5 + nt) * 2], tc[21 + (mt * 5 + nt) * 2]);
        }
        #pragma unroll
        for (int i = 0; i < 9; i++) xw[i] = bfma2(md[i], pack_bf(y[i >> 1][i & 1], y[i >> 1][2 + (i & 1)]), xw[i]);
        float r, mr;
        ln_stats(xw, g, q, r, mr);
        uint32_t h[9], r2 = pack_bf(r, r), m2 = pack_bf(mr, mr);
        #pragma unroll
        for (int i = 0; i < 9; i++) h[i] = bfma2(bfma2(xw[i], r2, m2), md[18 + i], md[9 + i]);
        ln_stats(h, g, q, r, mr);
        r2 = pack_bf(r, r); m2 = pack_bf(mr, mr);
        {
            const int n7 = 2 * q + (g >> 2);
            const uint32_t a = sm + OFF_STAGE + (warp >> 3) * 9216 + n7 * 128 + ((warp & 7) ^ n7) * 16 + (g & 3) * 4;
            #pragma unroll
            for (int i = 0; i < 9; i++) sts32(a + i * 1024, bfma2(h[i], r2, m2));
        }
        fence_async_s();
        __syncthreads();
        PROF0(12);
        if (tid == 0) {
            asm volatile("cp.async.bulk.tensor.4d.global.shared::cta.bulk_group [%0, {%2, %2, %2, %3}], [%1];" :: "l"(&tm_h3s), "r"(sm + OFF_STAGE), "r"(0), "r"(b) : "memory");
            asm volatile("cp.async.bulk.commit_group;" ::: "memory");
        }
        #pragma unroll
        for (int i = 0; i < 9; i++) sts32(sm + OFF_X1 + warp * 1152 + (32 * i + 8 * q + g) * 4, xw[i]);
    }
    __syncthreads();
    if (rowcta) {
        if (tid == 0) { asm volatile("cp.async.bulk.wait_group 0;" ::: "memory"); fence_async_g(); red_release(g_cnt + CNT_H3 * 32); }
        PROF0(13);
        if (warp == 15) {
            __nanosleep(X1DELAY);
            #pragma unroll 1
            for (int r = 0; r < 16; r++) {
                uint4* dst = (uint4*)(p.out + (size_t)(b + 128 * r) * D_) + lane;
                const uint32_t src = sm + OFF_X1 + r * 1152 + lane * 16;
                dst[0] = lds128(src); dst[32] = lds128(src + 512); if (lane < 8) dst[64] = lds128(src + 1024);
                const uint32_t t1 = clk32(); while ((int)(clk32() - t1) < X1PACE) __nanosleep(50);
            }
            __syncwarp();
            if (lane == 0) { fence_async_g(); red_release(g_cnt + CNT_X1 * 32); }
        }
    }
    role = __shfl_sync(~0u, lds32(sm + OFF_MISC), 0);
    if (role >= 64) { if (warp == 0) PROFDUMP(); return; }

    const int gi = role >> 3, dt = role & 3, c2 = (role >> 2) & 1;
    const int wg = warp >> 2, wi = warp & 3;
    if (wg == 3) {
        uint32_t so = 0, eph = 1;
        #define RING_STEP(BYTES, OFF, ISSUE) do { \
            mbar_wait(bars + 8 * BAR_EMPTY + so, eph); \
            if (elect()) { const uint32_t fb = bars + 8 * BAR_FULL + so, dst = sm + (OFF) + so * ((BYTES) / 8); mbar_expect(fb, BYTES); ISSUE; } \
            so += 8; if (so == 8 * NST) { so = 0; eph ^= 1; } } while (0)
        const uint32_t kbt = g2_kb(lane, rank, gi, c2) | (g2_kb(32 + (lane & 3), rank, gi, c2) << 8);
        #define KB(n_) ((__shfl_sync(~0u, kbt, (n_) & 31) >> (((n_) >> 2) & 8)) & 255)
        if (warp == 12) {
            eph = 0;
            const int fb1 = 9 * gi + 4 * c2 + 2 * rank, sb2 = 4 * gi + 2 * c2;
            int pft = dt, pfj = 4 * (PF0 + PFS * dt);
            #pragma unroll 1
            for (int j = 16; j < 128; j += 4) {
                RING_STEP(A_BYTES, OFF_A, tma4(dst, &tm_w1a, 0, 0, j, fb1, fb));
                if (j < 64) { if (j & 4) RING_STEP(A_BYTES, OFF_A, tma4(dst, &tm_w1b, 0, 0, 64 * rank + j - 4, 9 * gi + 8, fb)); }
                if (j == pfj && pft < PFN) {
                    const int kb = KB(pft); pft += 4; pfj += 16 * PFS;
                    if (elect()) asm volatile("cp.async.bulk.prefetch.tensor.3d.L2.global [%0, {%1, %2, %3}];" :: "l"(&tm_w2), "r"(0), "r"(64 * kb), "r"(sb2) : "memory");
                }
            }
            #pragma unroll 1
            for (int n = 0; n < 36; n++) {
                const int kb = KB(n);
                RING_STEP(A_BYTES, OFF_A, tma3(dst, &tm_w2, 0, 64 * kb, sb2, fb));
            }
        } else if (warp == 13) {
            const uint32_t e1 = __shfl_sync(~0u, epoch + 1, 0);
            fence_async_s();
            wait_count<0>(g_cnt + CNT_H3 * 32, e1 * 128);
            fence_async_g();
            if (lane == 0) PROFT(14);
            #pragma unroll 1
            for (int j = 0; j < 128; j += 4) {
                RING_STEP(B_BYTES, OFF_B, tma3(dst, &tm_h3a, 0, 18 * dt, j, fb));
                if (j < 64 && (j & 4)) RING_STEP(B_BYTES, OFF_B, tma3(dst, &tm_h3b, 0, 18 * dt + 9 * c2, 64 * rank + j - 4, fb));
            }
            int n = 0;
            #pragma unroll 1
            for (int cls = 0; cls < 3; cls++) {
                mbar_wait(bars + 8 * (BAR_UOK + cls), 0);
                fence_async_g();
                if (cls == 1 && lane == 0) PROFT(19);
                if (cls == 0 && lane == 0) PROFT(22);
                static_assert((IT_G2 + 4) % NST != NST - 1, "no wrap at the skipped stage");
                if (cls == 1) { n++; so += 8; }
                #pragma unroll 1
                for (; n < (cls == 0 ? 4 : cls == 1 ? 21 : 36); n++) {
                    const int kb = KB(n);
                    RING_STEP(B_BYTES, OFF_B, bulk_load(dst, g_U + (kb * 4 + dt) * 1152, B_BYTES, fb));
                }
            }
            if (role == 0 && rank == 0 && lane == 0) st_relaxed(g_cnt + CNT_EPOCH * 32, e1);
        } else if (warp == 15) {
            if (elect()) mbar_arrive_remote(mapa(bars + 8 * BAR_HOLD, rank ^ 1));
            __syncwarp();
            bar_sync(6, 160);
            if (elect()) mbar_arrive(bars + 8 * (BAR_FULL + (IT_G2 + 4) % NST));
            __syncwarp();
            mbar_wait(bars + 8 * BAR_W1GO, 0);
            if (elect()) {
                char* dst = (char*)(g_U + ((9 * gi + 4 * c2 + 2 * rank + 1) * 4 + dt) * 1152);
                #pragma unroll 1
                for (int i = 0; i < W1N; i++) {
                    asm volatile("cp.async.bulk.global.shared::cta.bulk_group [%0], [%1], %2;" :: "l"(dst + i * (18432 / W1N)), "r"(sm + OFF_X1 + i * (18432 / W1N)), "n"(18432 / W1N) : "memory");
                    const uint32_t t1 = clk32(); while ((int)(clk32() - t1) < W1P) {}
                }
                asm volatile("cp.async.bulk.commit_group;" ::: "memory");
                asm volatile("cp.async.bulk.wait_group 0;" ::: "memory");
                fence_async_g(); red_release(g_cnt + (CNT_U + 16) * 32);
                #pragma unroll 1
                for (int n = 0; n < 4; n++) { __nanosleep(300); tma2(sm + OFF_X1 + n * 4608, &tm_o, 144 * dt, 256 * gi + 128 * c2 + 64 * (rank ^ 1) + 16 * n, bars + 8 * BAR_XT); }
            }
        } else {
            const uint32_t e1 = epoch + 1;
            if (lane == 0) {
                __nanosleep(4000);
                wait_count<200>(g_cnt + CNT_NC * 32, e1 * 4); wait_count<200>(g_cnt + (CNT_NC + 1) * 32, e1 * 2);
                fence_async_g();
                mbar_expect(bars + 8 * BAR_GB, 1152);
                bulk_load(sm + OFF_GB, p.scr->modc + 896, 1152, bars + 8 * BAR_GB);
                wait_count<200>(g_cnt + CNT_X1 * 32, e1 * 128);
                wait_count<50>(g_cnt + (CNT_U + dt * 2 + rank) * 32, e1 * 16);
                mbar_arrive(bars + 8 * BAR_UOK);
            }
            __syncwarp();
            bar_sync(4, 160);
            if (lane == 0) {
                fence_async_g(); red_release(g_cnt + (CNT_U + 8) * 32);
                PROFT(17);
                wait_count<0>(g_cnt + (CNT_U + 8) * 32, e1 * 128);
                mbar_arrive(bars + 8 * (BAR_UOK + 1));
                __nanosleep(1000);
                wait_count<100>(g_cnt + (CNT_U + 16) * 32, e1 * 128);
                mbar_arrive(bars + 8 * (BAR_UOK + 2));
            }
        }
    } else if (wg == 2) {
        float d0[36];
        const float bias = bf_lo(ldg_nc16(p.b1 + 576 * gi + 512 + 16 * wi + g + 8 * rank));
        for (int it = 0; it < 200 && !__any_sync(~0u, mbar_test(bars + 8 * BAR_FULL, 0)); it++) { hb(); __nanosleep(100); }
        const bool lead = wi == 0 && elect();
        #pragma unroll 1
        for (int i = 0; i < 8; i++) {
            const uint32_t s = P2S + 3 * (i & 1);
            mbar_wait(bars + 8 * BAR_FULL + 8 * s, (i >> 1) & 1);
            const uint32_t da = desc_lo(sm + OFF_A, 8192) + s * (A_BYTES / 16), db = desc_lo(sm + OFF_B, 128) + s * (B_BYTES / 16);
            WG_FENCE();
            wgmma72(d0, da, db, i);
            #pragma unroll
            for (int k = 1; k < 8; k++) wgmma72(d0, da + k * 128, db + k * 144, 1);
            WG_COMMIT();
            WG_WAIT(0);
            if (lead) mbar_arrive_n(bars + 8 * BAR_EMPTY + 8 * s, 2);
        }
        if (lead) PROFT(18);
        const uint32_t slot = sm + OFF_P2R + (tid & 127) * 16, ra = mapa(slot, rank ^ 1), rb = mapa(bars + 8 * BAR_P2R, rank ^ 1);
        float sv[18];
        #pragma unroll
        for (int i = 0; i < 18; i++) { const float lo = d0[4 * (i >> 1) + (i & 1)], hi = d0[4 * (i >> 1) + 2 + (i & 1)];
            sv[i] = rank ? lo : hi; d0[4 * (i >> 1) + (i & 1)] = (rank ? hi : lo) + bias; }
        mbar_wait(bars + 8 * BAR_HOLD, 0);
        #pragma unroll
        for (int i = 0; i < 4; i++)
            asm volatile("st.async.weak.shared::cluster.mbarrier::complete_tx::bytes.v4.f32 [%0], {%1,%2,%3,%4}, [%5];"
                :: "r"(ra + i * 2048), "f"(sv[4 * i]), "f"(sv[4 * i + 1]), "f"(sv[4 * i + 2]), "f"(sv[4 * i + 3]), "r"(rb) : "memory");
        asm volatile("st.async.weak.shared::cluster.mbarrier::complete_tx::bytes.v2.f32 [%0], {%1,%2}, [%3];" :: "r"(ra + 8192), "f"(sv[16]), "f"(sv[17]), "r"(rb) : "memory");
        mbar_wait(bars + 8 * BAR_P2R, 0);
        #pragma unroll
        for (int i = 0; i < 5; i++) {
            const uint4 v = lds128(slot + i * 2048);
            d0[8 * i] += __uint_as_float(v.x); d0[8 * i + 1] += __uint_as_float(v.y);
            if (i < 4) { d0[8 * i + 4] += __uint_as_float(v.z); d0[8 * i + 5] += __uint_as_float(v.w); }
        }
        asm volatile("bar.arrive 5, 256;" ::: "memory");
        gelu_store<0>(d0, (char*)(g_U + ((9 * gi + 8) * 4 + dt) * 1152) + wi * 4608 + rank * 2304 + c2 * 1152 + g * 16, q);
        bar_sync(8, 128);
        if (lead) { fence_async_g(); red_release(g_cnt + (CNT_U + dt * 2 + (gi >> 2)) * 32); PROFT(26); }
    } else {
        float d[72];
        const bool lead = wi == 0 && elect();
        const uint32_t da0 = desc_lo(sm + OFF_A + wg * 8192, 8192);
        const bool owner = (uint32_t)wg == rank;
        const int srow = 256 * gi + 128 * c2 + 64 * wg + 16 * wi;
        const uint32_t b2w0 = ldg_nc16(p.b2 + srow + g), b2w1 = ldg_nc16(p.b2 + srow + g + 8);
        {
            const int fr = 576 * gi + 256 * c2 + 128 * rank + 64 * wg + 16 * wi + g;
            const float bias0 = bf_lo(ldg_nc16(p.b1 + fr)), bias1 = bf_lo(ldg_nc16(p.b1 + fr + 8));
            #pragma unroll
            for (int i = 0; i < 72; i++) d[i] = (i & 2) ? bias1 : bias0;
            const uint32_t db1 = desc_lo(sm + OFF_B, 128);
            mainloop<DHI_H3, 0, IT_P1, true>(d, bars, da0, db1, lead, [&](int) {});
            mainloop<DHI_H3, IT_P1, IT_G2 - LEAD1, false>(d, bars, da0, db1, lead, [&](int) {});
            constexpr uint32_t EB = 8 * (BAR_EMPTY + (IT_G2 - LEAD1 - 1) % NST);
            if (wg == 1) { WG_WAIT(0); if (lead) mbar_arrive(bars + EB); bar_sync(9, 256); }
            #pragma unroll
            for (int i = IT_G2 - LEAD1; i < IT_G2; i++) {
                mbar_wait(bars + 8 * (BAR_FULL + i % NST), (i / NST) & 1);
                WG_FENCE();
                #pragma unroll
                for (int k = 0; k < 4; k++) {
                    if (i == IT_G2 - 1 && k == HOK1) WG_COMMIT();
                    wgmma144<DHI_H3>(d, da0 + (i % NST) * (A_BYTES / 16) + k * 128, db1 + (i % NST) * (B_BYTES / 16) + k * 288, 1);
                }
                WG_COMMIT();
                if (i == IT_G2 - 1 && HOK1 < 4) WG_WAIT(2); else WG_WAIT(1);
                if (lead && (i > IT_G2 - LEAD1 || wg == 0)) mbar_arrive(bars + 8 * (BAR_EMPTY + (i - 1) % NST));
            }
            if (wg == 0) { WG_WAIT(1); asm volatile("bar.arrive 9, 256;" ::: "memory"); }
            WG_WAIT(0);
            if (lead) mbar_arrive(bars + 8 * (BAR_EMPTY + (IT_G2 - 1) % NST));
            PROF0(16);
            if (wg == 1) bar_sync(5, 256);
            char* const ub = (wg == 0 ? (char*)(g_U + ((9 * gi + 4 * c2 + 2 * rank) * 4 + dt) * 1152) : (char*)__cvta_shared_to_generic(sm + OFF_X1)) + wi * 4608 + g * 16;
            gelu_store<0>(d, ub, q); gelu_store<2>(d, ub + 2304, q); gelu_store<36>(d, ub + 1152, q); gelu_store<38>(d, ub + 3456, q);
            PROF0(27);
            if (wg == 0) asm volatile("bar.arrive 4, 160;" ::: "memory");
            else { fence_async_s(); asm volatile("bar.arrive 6, 160;" ::: "memory"); }
        }
        const uint32_t db0 = desc_lo(sm + OFF_B, 2304);
        const bool keep = role > 64;
        constexpr int IT_L = IT_END - NST, IT_X = IT_L - 4;
        #pragma unroll
        for (int i = IT_G2; i <= IT_G2 + W1S; i++) {
            const uint32_t db = db0 + (i == IT_G2 + 4 ? OFF_X1 - OFF_B : (i % NST) * B_BYTES) / 16;
            mbar_wait(bars + 8 * (BAR_FULL + i % NST), (i / NST) & 1);
            WG_FENCE();
            #pragma unroll
            for (int k = 0; k < 4; k++) wgmma144<DHI_U>(d, da0 + (i % NST) * (A_BYTES / 16) + k * 128, db + k * 288, i > IT_G2 || k > 0 || keep);
            WG_COMMIT();
            if (i > IT_G2) { WG_WAIT(1); if (lead) mbar_arrive(bars + 8 * (BAR_EMPTY + (i - 1) % NST)); }
        }
        if (lead) mbar_arrive(bars + 8 * BAR_W1GO);
        mainloop<DHI_U, IT_G2 + W1S + 1, IT_X, false>(d, bars, da0, db0, lead, [&](int) {});
        const uint32_t ga0 = sm + OFF_GB + (144 * dt + 8 * q) * 2, tile = sm + OFF_X1 + wi * 4608, to = g * 288 + q * 16;
        #define QOFF(i_) (((i_) >> 2) * 2304 + 144 * (((i_) >> 1) & 1) + 64 * ((i_) & 1))
        #define SOFF(k_) (((k_) >> 1) * 2304 + 144 * ((k_) & 1) + 128 - 12 * q)
        #define DIDX(i_, k_) ((i_) < 8 ? 36 * (((i_) >> 1) & 1) + 16 * ((i_) & 1) + 4 * (k_) + 2 * ((i_) >> 2) : 36 * ((k_) & 1) + 32 + 2 * ((k_) >> 1))
        #define FIN(k_, f_) bfma2(g4.f_, pack_bf(d[DIDX(i, k_)], d[DIDX(i, k_) + 1]), xq[i].f_)
        uint4 xq[9];
        auto load_g = [&](int i) { uint4 r; if (i < 4) r = lds128(ga0 + QOFF(i)); else { r.x = r.z = lds32(ga0 + SOFF(0)); r.y = r.w = lds32(ga0 + SOFF(1)); } return r; };
        mainloop<DHI_U, IT_X, IT_L, false>(d, bars, da0, db0, lead, [&](int i) {
            if (!owner) {
                const uint32_t xa = tile + to;
                if (i == IT_X) { mbar_wait(bars + 8 * BAR_XT, 0); xq[0] = lds128(xa + QOFF(0)); xq[4] = lds128(xa + QOFF(4)); xq[1] = lds128(xa + QOFF(1)); }
                else if (i == IT_X + 1) { xq[5] = lds128(xa + QOFF(5)); xq[2] = lds128(xa + QOFF(2)); xq[6] = lds128(xa + QOFF(6)); }
                else if (i == IT_X + 2) { xq[3] = lds128(xa + QOFF(3)); xq[7] = lds128(xa + QOFF(7));
                    xq[8] = make_uint4(lds32(xa + SOFF(0)), lds32(xa + SOFF(1)), lds32(xa + SOFF(2)), lds32(xa + SOFF(3))); }
                else if (i == IT_X + 3) { if (elect()) mbar_arrive_remote(mapa(bars + 8 * BAR_DONE, rank ^ 1)); }
            } });
        if (owner) { WG_WAIT(0); if (lead) mbar_arrive(bars + 8 * (BAR_EMPTY + (IT_L - 1) % NST)); bar_sync(7, 256); }
        #pragma unroll
        for (int i = IT_L; i < IT_END; i++) {
            mbar_wait(bars + 8 * (BAR_FULL + i % NST), (i / NST) & 1);
            WG_FENCE();
            #pragma unroll
            for (int k = 0; k < 4; k++) {
                if (i == IT_END - 1 && k == HOK) WG_COMMIT();
                wgmma144<DHI_U>(d, da0 + (i % NST) * (A_BYTES / 16) + k * 128, db0 + (i % NST) * (B_BYTES / 16) + k * 288, 1);
            }
            WG_COMMIT();
            if (i == IT_L) { WG_WAIT(1); if (lead && !owner) mbar_arrive(bars + 8 * (BAR_EMPTY + (IT_L - 1) % NST)); }
        }
        PROF0(9);
        mbar_wait(bars + 8 * BAR_GB, 0);
        if (!owner) {
            const uint32_t ra = mapa(tile + lane * 16, rank ^ 1), rb = mapa(bars + 8 * BAR_RECV, rank ^ 1);
            mbar_wait(bars + 8 * BAR_DONE, 0);
            uint4 gn = load_g(0);
            WG_WAIT(1);
            asm volatile("bar.arrive 7, 256;" ::: "memory");
            WG_WAIT(0);
            #pragma unroll
            for (int i = 0; i < 72; i++) d[i] = fmaf(bf_lo((i & 2) ? b2w1 : b2w0), 2.f, d[i]);
            #pragma unroll
            for (int j = 0; j < 5; j++) {
                const uint4 g4 = gn;
                if (j < 4) gn = load_g(j + 1);
                #pragma unroll
                for (int i = j < 4 ? j : 8; i < 9; i += 4) if (i < 8 || j == 4)
                    asm volatile("st.async.weak.shared::cluster.mbarrier::complete_tx::bytes.v4.b32 [%0], {%1,%2,%3,%4}, [%5];"
                        :: "r"(ra + i * 512), "r"(FIN(0, x)), "r"(FIN(1, y)), "r"(FIN(2, z)), "r"(FIN(3, w)), "r"(rb) : "memory");
            }
            PROF0(6);
            if (warp == 0) PROFDUMP();
            return;
        }
        PROF0(24);
        mbar_wait(bars + 8 * BAR_RECV, 0);
        #pragma unroll
        for (int i = 0; i < 9; i++) xq[i] = lds128(tile + lane * 16 + i * 512);
        uint4 gn = load_g(0);
        WG_WAIT(0);
        __syncwarp();
        PROF0(21);
        #pragma unroll
        for (int j = 0; j < 5; j++) {
            const uint4 g4 = gn;
            if (j < 4) gn = load_g(j + 1);
            #pragma unroll
            for (int i = j < 4 ? j : 8; i < 9; i += 4) if (i < 8 || j == 4) {
                const uint4 o = make_uint4(FIN(0, x), FIN(1, y), FIN(2, z), FIN(3, w));
                if (i < 8) sts128(tile + to + QOFF(i), o);
                else { sts32(tile + to + SOFF(0), o.x); sts32(tile + to + SOFF(1), o.y); sts32(tile + to + SOFF(2), o.z); sts32(tile + to + SOFF(3), o.w); }
            }
        }
        fence_async_s();
        __syncwarp();
        if (elect()) {
            asm volatile("cp.async.bulk.tensor.2d.global.shared::cta.bulk_group [%0, {%2, %3}], [%1];" :: "l"(&tm_o), "r"(tile), "r"(144 * dt), "r"(srow) : "memory");
            asm volatile("cp.async.bulk.commit_group;" ::: "memory");
            asm volatile("cp.async.bulk.wait_group.read 0;" ::: "memory");
        }
        PROF0(23);
        if (warp == 0) { __syncwarp(); PROFDUMP(); }
    }
}

typedef CUresult (*EncodeFn)(CUtensorMap*, CUtensorMapDataType, cuuint32_t, void*, const cuuint64_t*, const cuuint64_t*, const cuuint32_t*,
                             const cuuint32_t*, CUtensorMapInterleave, CUtensorMapSwizzle, CUtensorMapL2promotion, CUtensorMapFloatOOBfill);

void encode(EncodeFn fn, CUtensorMap* m, CUtensorMapDataType dt, int rank, const void* ptr, const cuuint64_t* dims, const cuuint64_t* strides,
            const cuuint32_t* box, CUtensorMapSwizzle sw, CUtensorMapL2promotion promo = CU_TENSOR_MAP_L2_PROMOTION_L2_128B) {
    const cuuint32_t es[5] = {1, 1, 1, 1, 1};
    fn(m, dt, rank, (void*)ptr, dims, strides, box, es, CU_TENSOR_MAP_INTERLEAVE_NONE, sw, promo, CU_TENSOR_MAP_FLOAT_OOB_FILL_NONE);
}

}

extern "C" void kernel_launch(void* const* d_in, const int* in_sizes, int n_in, void* d_out, int out_size) {
    (void)in_sizes; (void)n_in; (void)out_size;
    Params p;
    p.x = (const uint16_t*)d_in[0]; p.wr = (const uint16_t*)d_in[1]; p.wi = (const uint16_t*)d_in[2];
    p.w1 = (const uint16_t*)d_in[4]; p.b1 = (const uint16_t*)d_in[5]; p.w2 = (const uint16_t*)d_in[6]; p.b2 = (const uint16_t*)d_in[7];
    p.c = (const uint16_t*)d_in[8]; p.wmod = (const uint16_t*)d_in[9]; p.out = (uint16_t*)d_out;

    void* fnp = nullptr; cudaDriverEntryPointQueryResult qr;
    cudaGetDriverEntryPoint("cuTensorMapEncodeTiled", &fnp, cudaEnableDefault, &qr);
    EncodeFn fn = (EncodeFn)fnp;
    cudaGetSymbolAddress((void**)&p.scr, g_scr); cudaGetSymbolAddress((void**)&p.tab, g_tab);
    void* h3p = p.scr->h3;
    CUtensorMap tw1a, tw1b, tw2, th3a, th3b, twr, twi, twm, tt, ttx, to, th3s, tws;
    {
        const cuuint64_t dims[4] = {64, 16, 128, 72}, st[3] = {128ull * F_ * 2, (cuuint64_t)F_ * 2, 128};
        const cuuint32_t ba[4] = {64, 16, 4, 2}, bb[4] = {64, 16, 8, 1};
        encode(fn, &tw1a, CU_TENSOR_MAP_DATA_TYPE_BFLOAT16, 4, p.w1, dims, st, ba, CU_TENSOR_MAP_SWIZZLE_128B);
        encode(fn, &tw1b, CU_TENSOR_MAP_DATA_TYPE_BFLOAT16, 4, p.w1, dims, st, bb, CU_TENSOR_MAP_SWIZZLE_128B);
    }
    {
        const cuuint64_t dims[3] = {64, F_, 32}, st[2] = {(cuuint64_t)S_ * 2, 128};
        const cuuint32_t bx[3] = {64, 64, 2};
        encode(fn, &tw2, CU_TENSOR_MAP_DATA_TYPE_BFLOAT16, 3, p.w2, dims, st, bx, CU_TENSOR_MAP_SWIZZLE_128B);
    }
    {
        const cuuint64_t dims[3] = {64, 72, 128}, st[2] = {256, 18432};
        const cuuint32_t ba[3] = {64, 18, 4}, bb[3] = {64, 9, 8};
        encode(fn, &th3a, CU_TENSOR_MAP_DATA_TYPE_UINT32, 3, h3p, dims, st, ba, CU_TENSOR_MAP_SWIZZLE_NONE);
        encode(fn, &th3b, CU_TENSOR_MAP_DATA_TYPE_UINT32, 3, h3p, dims, st, bb, CU_TENSOR_MAP_SWIZZLE_NONE);
    }
    {
        const cuuint64_t dims[4] = {32, 72, 2, 128}, st[3] = {256, 128, 18432};
        const cuuint32_t bx[4] = {32, 72, 2, 1};
        encode(fn, &th3s, CU_TENSOR_MAP_DATA_TYPE_UINT32, 4, h3p, dims, st, bx, CU_TENSOR_MAP_SWIZZLE_128B, CU_TENSOR_MAP_L2_PROMOTION_NONE);
    }
    {
        const cuuint64_t dims[3] = {4624, 4, 32}, st[2] = {9248 * 32, 9248};
        const cuuint32_t bx[3] = {56, 4, 32};
        encode(fn, &twr, CU_TENSOR_MAP_DATA_TYPE_BFLOAT16, 3, p.wr, dims, st, bx, CU_TENSOR_MAP_SWIZZLE_NONE);
        encode(fn, &twi, CU_TENSOR_MAP_DATA_TYPE_BFLOAT16, 3, p.wi, dims, st, bx, CU_TENSOR_MAP_SWIZZLE_NONE);
    }
    {
        const cuuint64_t dims[2] = {3456, 576}, st[1] = {6912};
        const cuuint32_t bx[2] = {32, 144};
        encode(fn, &tws, CU_TENSOR_MAP_DATA_TYPE_BFLOAT16, 2, p.wmod, dims, st, bx, CU_TENSOR_MAP_SWIZZLE_64B);
    }
    {
        const cuuint64_t dims[3] = {64, 576, 54}, st[2] = {6912, 128};
        const cuuint32_t bx[3] = {64, 32, 7};
        encode(fn, &twm, CU_TENSOR_MAP_DATA_TYPE_BFLOAT16, 3, p.wmod, dims, st, bx, CU_TENSOR_MAP_SWIZZLE_128B);
    }
    {
        const cuuint64_t dims[2] = {TP, 128}, st[1] = {TP * 4};
        const cuuint32_t ba[2] = {32, 128}, bb[2] = {8, 128};
        encode(fn, &tt, CU_TENSOR_MAP_DATA_TYPE_UINT32, 2, p.scr->T, dims, st, ba, CU_TENSOR_MAP_SWIZZLE_128B, CU_TENSOR_MAP_L2_PROMOTION_NONE);
        encode(fn, &ttx, CU_TENSOR_MAP_DATA_TYPE_UINT32, 2, p.scr->T, dims, st, bb, CU_TENSOR_MAP_SWIZZLE_32B, CU_TENSOR_MAP_L2_PROMOTION_NONE);
    }
    {
        const cuuint64_t dims[2] = {D_, S_}, st[1] = {D_ * 2};
        const cuuint32_t bx[2] = {144, 16};
        encode(fn, &to, CU_TENSOR_MAP_DATA_TYPE_BFLOAT16, 2, p.out, dims, st, bx, CU_TENSOR_MAP_SWIZZLE_NONE, CU_TENSOR_MAP_L2_PROMOTION_NONE);
    }
    cudaFuncSetAttribute(fused_kernel, cudaFuncAttributeMaxDynamicSharedMemorySize, SMEM_BYTES);
    cudaLaunchConfig_t cfg = {};
    cfg.gridDim = dim3(NCTA); cfg.blockDim = dim3(NTHR); cfg.dynamicSmemBytes = SMEM_BYTES; cfg.stream = cudaStreamPerThread;
    cudaLaunchAttribute at[1];
    at[0].id = cudaLaunchAttributeCooperative; at[0].val.cooperative = 1;
    cfg.attrs = at; cfg.numAttrs = 1;
    cudaLaunchKernelEx(&cfg, fused_kernel, p, tw1a, tw1b, tw2, th3a, th3b, twr, twi, twm, tt, ttx, to, th3s, tws);
}
```

```cpp
#include <cuda_runtime.h>
#include <cuda_bf16.h>
#include <cuda_fp16.h>
#include <cuda.h>
#include <stdint.h>

namespace {

constexpr int S_ = 2048, D_ = 576, F_ = 4608;
constexpr int NCTA = 132, NTHR = 512;
constexpr int TP = 4736;
constexpr int SPEC_P = 296;
constexpr int NST = 6;
constexpr int A_BYTES = 16384, B_BYTES = 18432;
constexpr int IT_P1 = 24, IT_G2 = 40, IT_END = 76;
constexpr int SPIN_LIMIT = 1 << 22;
#define X2D 1350
constexpr int P2S = 2;
#define LEAD1 4
#define W1N 8
#define W1P 100
#define W1S 5
#define XDELAY 900
#define HOK 2
#define HOK1 2
#define NCP 10800
#define SLP 64
#define CRITPF 1
#define NCD 0
#define X1D 2200
#define PF0 4
#define PFS 3
#define PFN 9
#define X1DELAY 2000
#define X1PACE 400

constexpr int OFF_A = 0;
constexpr int OFF_B = NST * A_BYTES;
constexpr int OFF_P = OFF_B + NST * B_BYTES;
constexpr int OFF_BAR = OFF_P;
constexpr int OFF_MISC = OFF_P + 504;
constexpr int OFF_GB = OFF_P + 512;
constexpr int OFF_P2R = OFF_P + 1664;
constexpr int OFF_X1 = OFF_P2R;
constexpr int OFF_PROF = OFF_X1 + 18432;
constexpr int SMEM_BYTES = OFF_PROF + 512 + 1024;
constexpr int QA = 13, QB = 7, QC = 13;
constexpr int TAB_BYTES = (QA + QB + QC) * 512;
constexpr int OFF_STAGE = OFF_B;
constexpr int OFF_STX = OFF_STAGE + 16384;
constexpr int OFF_TAB = OFF_STAGE + 20480;
constexpr int OFF_SPEC = OFF_TAB + TAB_BYTES;
constexpr int OFF_WRAW = OFF_SPEC + 19072;
constexpr int OFF_B3 = OFF_WRAW + 28672;
constexpr int OFF_MODA = OFF_B3 + 4096;
constexpr int OFF_MODC = OFF_MODA + 2560;
constexpr int OFF_RED = OFF_MODC + 3584;
constexpr int OFF_SILU = OFF_RED + 1536;
static_assert(OFF_SILU + 1152 <= OFF_P && 6 * 28672 <= OFF_B3, "scratch overflow");
constexpr int OFF_STRIP = OFF_A;
static_assert(OFF_WRAW % 128 == 0 && OFF_STAGE % 128 == 0 && OFF_STX % 128 == 0, "align");
constexpr int BAR_FULL = 0, BAR_EMPTY = 6, BAR_TAB = 12, BAR_W = 13, BAR_P2R = 16,
              BAR_XT = 17, BAR_RECV = 18, BAR_ROLE = 19, BAR_NC = 20, BAR_TAB2 = 21, BAR_XB = 22, BAR_GB = 23, BAR_HOLD = 24, BAR_W1GO = 25, BAR_UOK = 26, BAR_DONE = 30, BAR_X = 31, BAR_ST = 47;

struct Cos1152 { double c[1152]; };
constexpr double cx_cos(double x) { double t = 1, s = 1; for (int i = 1; i < 14; i++) { t *= -x * x / ((2 * i - 1) * (2 * i)); s += t; } return s; }
constexpr Cos1152 make_cos() {
    Cos1152 r{};
    for (int i = 0; i <= 288; i++) {
        double v = (i == 288) ? 0.0 : cx_cos(3.14159265358979323846 * 2.0 * i / 1152.0);
        r.c[i] = v; r.c[576 - i] = -v; r.c[576 + i] = -v; r.c[(1152 - i) % 1152] = v;
    }
    return r;
}
constexpr uint32_t cx_f2h(double v) {
    uint32_t s = v < 0 ? 0x8000u : 0u; double a = v < 0 ? -v : v;
    if (a < 1e-9) return 0;
    int e = 0;
    while (a >= 2.0) { a *= 0.5; e++; }
    while (a < 1.0 && e > -14) { a *= 2.0; e--; }
    double m = a * 1024.0; uint32_t mi = (uint32_t)m; double fr = m - mi;
    if (fr > 0.5 || (fr == 0.5 && (mi & 1))) mi++;
    return s | (uint32_t)(((e + 14) << 10) + mi);
}
struct Tab { uint32_t w[(QA + QB + QC) * 128]; };
constexpr Tab make_tab() {
    Tab t{};
    Cos1152 ct = make_cos();
    auto C = [&](int num, int den) { return ct.c[(num % den) * (1152 / den)]; };
    auto Sn = [&](int num, int den) { return ct.c[((num % den) * (1152 / den) + 864) % 1152]; };
    auto put = [&](int q0, int idx, int lane, double lo, double hi) { t.w[((q0 + idx / 4) * 32 + lane) * 4 + idx % 4] = cx_f2h(lo) | (cx_f2h(hi) << 16); };
    for (int lane = 0; lane < 32; lane++) {
        const int g = lane >> 2, q = lane & 3;
        for (int mt = 0; mt < 3; mt++) {
            const int ka = 8 * mt + g;
            for (int r = 0; r < 10; r++) {
                const int im = r & 1, i0 = (r >> 1) * 2;
                double v[2] = {0, 0};
                for (int e = 0; e < 2; e++) { int i = i0 + e, d1 = 4 * i + q; if (i < 9 && ka <= 18) v[e] = (im ? -Sn(ka * d1, 36) : C(ka * d1, 36)) / 8; }
                put(0, mt * 10 + r, lane, v[0], v[1]);
            }
            for (int v = 0; v < 2; v++) {
                const int d2 = 4 * q + v;
                put(0, 30 + (mt * 2 + v) * 2, lane, C(ka * d2, 576) * 4 / 3, C(ka * (d2 + 2), 576) * 4 / 3);
                put(0, 31 + (mt * 2 + v) * 2, lane, Sn(ka * d2, 576) * 4 / 3, Sn(ka * (d2 + 2), 576) * 4 / 3);
            }
        }
        for (int v = 0; v < 2; v++) for (int nt = 0; nt < 2; nt++) {
            const int kb = 2 * (g >> 1) + nt, part = g & 1;
            double b0[2] = {0, 0}, b1[2] = {0, 0};
            for (int e = 0; e < 2; e++) { int d2 = 4 * q + 2 * e + v; double c = C(kb * d2, 16) / 4, s = Sn(kb * d2, 16) / 4;
                b0[e] = part ? -s : c; b1[e] = part ? c : s; }
            put(0, 42 + (v * 2 + nt) * 2, lane, b0[0], b0[1]); put(0, 43 + (v * 2 + nt) * 2, lane, b1[0], b1[1]);
        }
        for (int par = 0; par < 2; par++) for (int a = 0; a < 4; a++) {
            const int ja = 2 * (q + 4 * (a >> 1)) + par; const double c = C(g * ja, 16) / 4, s = Sn(g * ja, 16) / 4;
            put(QA, par * 4 + a, lane, (a & 1) ? -s : c, (a & 1) ? c : s);
        }
        for (int h = 0; h < 2; h++) {
            put(QA, 8 + 2 * h, lane, C((g + 8 * h) * (2 * q), 128) / 2, C((g + 8 * h) * (2 * q + 1), 128) / 2);
            put(QA, 9 + 2 * h, lane, Sn((g + 8 * h) * (2 * q), 128) / 2, Sn((g + 8 * h) * (2 * q + 1), 128) / 2);
            put(QA, 15 + 2 * h, lane, C(g * (8 * h + 2 * q), 128), C(g * (8 * h + 2 * q + 1), 128));
            put(QA, 16 + 2 * h, lane, Sn(g * (8 * h + 2 * q), 128), Sn(g * (8 * h + 2 * q + 1), 128));
        }
        put(QA, 12, lane, C(g * 2 * q, 8) / 2, C(g * (2 * q + 1), 8) / 2);
        put(QA, 13, lane, Sn(g * 2 * q, 8) / 2, Sn(g * (2 * q + 1), 8) / 2);
        put(QA, 14, lane, -Sn(g * 2 * q, 8) / 2, -Sn(g * (2 * q + 1), 8) / 2);
        for (int u = 0; u < 4; u++) {
            const int ja = 2 * ((g >> 1) + 4 * (u & 1)) + (u >> 1), part = g & 1; double b0[2] = {0, 0}, b1[2] = {0, 0};
            for (int e = 0; e < 2; e++) { int ka = 2 * q + e; double c = C(ja * ka, 16) / 4, s = Sn(ja * ka, 16) / 4;
                b0[e] = part ? s : c; b1[e] = part ? c : -s; }
            put(QA, 19 + u * 2, lane, b0[0], b0[1]); put(QA, 20 + u * 2, lane, b1[0], b1[1]);
        }
        for (int m2 = 0; m2 < 2; m2++) {
            const int d2 = 2 * g + m2;
            for (int a = 0; a < 4; a++) {
                const int kb = 2 * q + (a >> 1); const double c = C(d2 * kb, 16) / 4, s = Sn(d2 * kb, 16) / 4;
                put(QA + QB, m2 * 4 + a, lane, (a & 1) ? s : c, (a & 1) ? c : -s);
            }
            for (int mt = 0; mt < 3; mt++) {
                const int ka = 8 * mt + 2 * q;
                put(QA + QB, 8 + (m2 * 3 + mt) * 2, lane, C(ka * d2, 576) * 4 / 3, C((ka + 1) * d2, 576) * 4 / 3);
                put(QA + QB, 9 + (m2 * 3 + mt) * 2, lane, Sn(ka * d2, 576) * 4 / 3, Sn((ka + 1) * d2, 576) * 4 / 3);
            }
        }
        for (int mt = 0; mt < 3; mt++) for (int nt = 0; nt < 5; nt++) {
            const int i = 2 * nt + (g & 1), d1 = 4 * i + (g >> 1); double b0[2] = {0, 0}, b1[2] = {0, 0};
            for (int e = 0; e < 2; e++) { int ka = 8 * mt + 2 * q + e;
                if (ka <= 18 && i < 9) { double wt = (ka == 0 || ka == 18) ? 0.125 : 0.25; b0[e] = wt * C(ka * d1, 36); b1[e] = -wt * Sn(ka * d1, 36); } }
            const int o = (QA + QB + 5) * 128 + (mt * 5 + nt) * 64 + lane;
            t.w[o] = cx_f2h(b0[0]) | (cx_f2h(b0[1]) << 16); t.w[o + 32] = cx_f2h(b1[0]) | (cx_f2h(b1[1]) << 16);
        }
    }
    return t;
}
__device__ __align__(128) const Tab g_tab = make_tab();

struct Scratch {
    uint32_t cnt[30 * 32];
    uint32_t slot[96];
    uint32_t mod[2304];
    uint32_t modc[896 + 288];
    uint32_t T[128 * TP];
    uint4 h3[128 * 1152];
    uint4 U[72 * 4 * 1152];
};
__device__ __align__(1024) Scratch g_scr;
#define g_cnt (p.scr->cnt)
#define g_slot (p.scr->slot)
#define g_mod (p.scr->mod)
#define g_T (p.scr->T)
#define g_h3 (p.scr->h3)
#define g_U (p.scr->U)
constexpr int CNT_EPOCH = 0, CNT_H3 = 1, CNT_X1 = 26, CNT_NC = 27, CNT_U = 2;
#define PROFT(i) do {} while (0)
#define PROFDUMP() do {} while (0)
#define PROF0(i) do {} while (0)

__device__ __forceinline__ void mbar_init(uint32_t bar, uint32_t cnt) { asm volatile("mbarrier.init.shared::cta.b64 [%0], %1;" :: "r"(bar), "r"(cnt) : "memory"); }
__device__ __forceinline__ void mbar_expect(uint32_t bar, uint32_t bytes) { asm volatile("mbarrier.arrive.expect_tx.shared::cta.b64 _, [%0], %1;" :: "r"(bar), "r"(bytes) : "memory"); }
__device__ __forceinline__ void mbar_arrive(uint32_t bar) { asm volatile("mbarrier.arrive.shared::cta.b64 _, [%0];" :: "r"(bar) : "memory"); }
__device__ __forceinline__ void mbar_arrive_n(uint32_t bar, uint32_t n) { asm volatile("mbarrier.arrive.shared::cta.b64 _, [%0], %1;" :: "r"(bar), "r"(n) : "memory"); }
__device__ __forceinline__ void mbar_arrive_remote(uint32_t rbar) { asm volatile("mbarrier.arrive.relaxed.cluster.shared::cluster.b64 _, [%0];" :: "r"(rbar) : "memory"); }
__device__ __forceinline__ void mbar_wait(uint32_t bar, uint32_t parity) {
    asm volatile("{.reg .pred p; .reg .u32 c;\n"
        "mbarrier.try_wait.parity.shared::cta.b64 p, [%0], %1;\n@p bra.uni DONE;\nmov.u32 c, 0;\n"
        "LOOP: mbarrier.try_wait.parity.shared::cta.b64 p, [%0], %1;\n@p bra.uni DONE;\n"
        "add.u32 c, c, 1;\nsetp.lt.u32 p, c, %2;\n@p bra.uni LOOP;\ntrap;\nDONE:}" :: "r"(bar), "r"(parity), "n"(SPIN_LIMIT) : "memory");
}
__device__ __forceinline__ bool mbar_test(uint32_t bar, uint32_t parity) {
    uint32_t ok; asm volatile("{.reg .pred p; mbarrier.test_wait.parity.shared::cta.b64 p, [%1], %2; selp.u32 %0, 1, 0, p;}" : "=r"(ok) : "r"(bar), "r"(parity) : "memory"); return ok; }
__device__ __forceinline__ uint32_t mapa(uint32_t a, uint32_t rank) { uint32_t r; asm("mapa.shared::cluster.u32 %0, %1, %2;" : "=r"(r) : "r"(a), "r"(rank)); return r; }
__device__ __forceinline__ uint32_t clk32() { uint32_t r; asm volatile("mov.u32 %0, %%clock;" : "=r"(r)); return r; }
__device__ __forceinline__ void hb() {
    asm volatile("{.reg .b32 a, b; .reg .pred p; mma.sync.aligned.m16n8k8.row.col.f16.f16.f16.f16 {a, b}, {%0,%0}, {%0}, {%0,%0};\n"
                 "setp.ne.u32 p, a, 0; @p trap;}" :: "r"(0));
}
__device__ __forceinline__ void spin_until(uint32_t t) {
    while (__any_sync(~0u, (int)(clk32() - t) < -SLP * 4)) { __nanosleep(SLP); hb(); }
    while (__any_sync(~0u, (int)(clk32() - t) < 0)) {}
}
__device__ __forceinline__ bool elect() { uint32_t r; asm volatile("{.reg .pred p; elect.sync _|p, 0xffffffff; selp.u32 %0, 1, 0, p;}" : "=r"(r)); return r; }
__device__ __forceinline__ void bar_sync(int id, int n) { asm volatile("bar.sync %0, %1;" :: "r"(id), "r"(n) : "memory"); }
__device__ __forceinline__ void bulk_load(uint32_t dst, const void* src, uint32_t bytes, uint32_t bar) {
    asm volatile("cp.async.bulk.shared::cluster.global.mbarrier::complete_tx::bytes [%0], [%1], %2, [%3];" :: "r"(dst), "l"(src), "r"(bytes), "r"(bar) : "memory"); }
__device__ __forceinline__ void tma2(uint32_t dst, const CUtensorMap* m, int c0, int c1, uint32_t bar) {
    asm volatile("cp.async.bulk.tensor.2d.shared::cluster.global.mbarrier::complete_tx::bytes [%0], [%1, {%3, %4}], [%2];" :: "r"(dst), "l"(m), "r"(bar), "r"(c0), "r"(c1) : "memory"); }
__device__ __forceinline__ void tma3(uint32_t dst, const CUtensorMap* m, int c0, int c1, int c2, uint32_t bar) {
    asm volatile("cp.async.bulk.tensor.3d.shared::cluster.global.mbarrier::complete_tx::bytes [%0], [%1, {%3, %4, %5}], [%2];" :: "r"(dst), "l"(m), "r"(bar), "r"(c0), "r"(c1), "r"(c2) : "memory"); }
__device__ __forceinline__ void tma4(uint32_t dst, const CUtensorMap* m, int c0, int c1, int c2, int c3, uint32_t bar) {
    asm volatile("cp.async.bulk.tensor.4d.shared::cluster.global.mbarrier::complete_tx::bytes [%0], [%1, {%3, %4, %5, %6}], [%2];" :: "r"(dst), "l"(m), "r"(bar), "r"(c0), "r"(c1), "r"(c2), "r"(c3) : "memory"); }
__device__ __forceinline__ void fence_async_g() { asm volatile("fence.proxy.async.global;" ::: "memory"); }
__device__ __forceinline__ void fence_async_s() { asm volatile("fence.proxy.async.shared::cta;" ::: "memory"); }
__device__ __forceinline__ uint4 lds128(uint32_t a) { uint4 v; asm volatile("ld.shared.v4.u32 {%0,%1,%2,%3}, [%4];" : "=r"(v.x), "=r"(v.y), "=r"(v.z), "=r"(v.w) : "r"(a) : "memory"); return v; }
__device__ __forceinline__ uint32_t lds32(uint32_t a) { uint32_t v; asm volatile("ld.shared.u32 %0, [%1];" : "=r"(v) : "r"(a) : "memory"); return v; }
__device__ __forceinline__ void sts128(uint32_t a, uint4 v) { asm volatile("st.shared.v4.u32 [%0], {%1,%2,%3,%4};" :: "r"(a), "r"(v.x), "r"(v.y), "r"(v.z), "r"(v.w) : "memory"); }
__device__ __forceinline__ void sts32(uint32_t a, uint32_t v) { asm volatile("st.shared.u32 [%0], %1;" :: "r"(a), "r"(v) : "memory"); }
__device__ __forceinline__ void sts16(uint32_t a, uint32_t v) { asm volatile("st.shared.u16 [%0], %1;" :: "r"(a), "h"((uint16_t)v) : "memory"); }
__device__ __forceinline__ uint4 ldx128(const void* p) {
    uint4 v; asm volatile("{.reg .b128 t; .reg .b64 a, b; ld.relaxed.gpu.global.b128 t, [%4]; mov.b128 {a, b}, t; mov.b64 {%0,%1}, a; mov.b64 {%2,%3}, b;}"
        : "=r"(v.x), "=r"(v.y), "=r"(v.z), "=r"(v.w) : "l"(p) : "memory"); return v; }
__device__ __forceinline__ void stx128(void* p, uint4 v) {
    asm volatile("{.reg .b128 t; .reg .b64 a, b; mov.b64 a, {%1,%2}; mov.b64 b, {%3,%4}; mov.b128 t, {a, b}; st.relaxed.gpu.global.b128 [%0], t;}"
        :: "l"(p), "r"(v.x), "r"(v.y), "r"(v.z), "r"(v.w) : "memory"); }
__device__ __forceinline__ uint32_t ld_relaxed(const uint32_t* p) { uint32_t v; asm volatile("ld.relaxed.gpu.global.u32 %0, [%1];" : "=r"(v) : "l"(p) : "memory"); return v; }
__device__ __forceinline__ uint32_t ld_acquire(const uint32_t* p) { uint32_t v; asm volatile("ld.acquire.gpu.global.u32 %0, [%1];" : "=r"(v) : "l"(p) : "memory"); return v; }
__device__ __forceinline__ void st_relaxed(uint32_t* p, uint32_t v) { asm volatile("st.relaxed.gpu.global.u32 [%0], %1;" :: "l"(p), "r"(v) : "memory"); }
__device__ __forceinline__ void red_release(uint32_t* p) { asm volatile("red.release.gpu.global.add.u32 [%0], 1;" :: "l"(p) : "memory"); }
template <int SLEEP> __device__ __forceinline__ void wait_count(const uint32_t* p, uint32_t target) {
    int it = 0; while ((int)(ld_acquire(p) - target) < 0) { if (SLEEP) __nanosleep(SLEEP); if (++it > SPIN_LIMIT) __trap(); }
}
__device__ __forceinline__ uint32_t ldg_nc32(const void* p) { uint32_t v; asm volatile("ld.global.nc.L1::no_allocate.u32 %0, [%1];" : "=r"(v) : "l"(p)); return v; }
__device__ __forceinline__ uint32_t ldg_nc16(const void* p) { uint16_t v; asm volatile("ld.global.nc.u16 %0, [%1];" : "=h"(v) : "l"(p)); return v; }
__device__ __forceinline__ float bf_lo(uint32_t w) { return __uint_as_float(w << 16); }
__device__ __forceinline__ float bf_hi(uint32_t w) { return __uint_as_float(w & 0xFFFF0000u); }
__device__ __forceinline__ uint32_t pack_bf(float lo, float hi) { uint32_t r; asm("cvt.rn.bf16x2.f32 %0, %1, %2;" : "=r"(r) : "f"(hi), "f"(lo)); return r; }
__device__ __forceinline__ uint32_t pack_h(float lo, float hi) { uint32_t r; asm("cvt.rn.f16x2.f32 %0, %1, %2;" : "=r"(r) : "f"(hi), "f"(lo)); return r; }
__device__ __forceinline__ float bf_round(float v) { return bf_lo(pack_bf(v, 0.f)); }
__device__ __forceinline__ uint32_t hmul2(uint32_t a, uint32_t b) { uint32_t r; asm("mul.rn.f16x2 %0, %1, %2;" : "=r"(r) : "r"(a), "r"(b)); return r; }
__device__ __forceinline__ uint32_t hfma2(uint32_t a, uint32_t b, uint32_t c) { uint32_t r; asm("fma.rn.f16x2 %0, %1, %2, %3;" : "=r"(r) : "r"(a), "r"(b), "r"(c)); return r; }
__device__ __forceinline__ uint32_t hfms2(uint32_t a, uint32_t b, uint32_t c) { uint32_t r; asm("{.reg .b32 t; neg.f16x2 t, %3; fma.rn.f16x2 %0, %1, %2, t;}" : "=r"(r) : "r"(a), "r"(b), "r"(c)); return r; }
__device__ __forceinline__ uint32_t hadd2(uint32_t a, uint32_t b) { uint32_t r; asm("add.rn.f16x2 %0, %1, %2;" : "=r"(r) : "r"(a), "r"(b)); return r; }
__device__ __forceinline__ uint32_t hsub2(uint32_t a, uint32_t b) { uint32_t r; asm("sub.rn.f16x2 %0, %1, %2;" : "=r"(r) : "r"(a), "r"(b)); return r; }
__device__ __forceinline__ void cmul_neg(uint32_t& re, uint32_t& im, uint32_t c, uint32_t s) { uint32_t a = hfma2(re, c, hmul2(im, s)), b = hfms2(im, c, hmul2(re, s)); re = a; im = b; }
__device__ __forceinline__ void cmul_pos(uint32_t& re, uint32_t& im, uint32_t c, uint32_t s) { uint32_t a = hfms2(re, c, hmul2(im, s)), b = hfma2(im, c, hmul2(re, s)); re = a; im = b; }
__device__ __forceinline__ void mma_h(uint32_t& d0, uint32_t& d1, uint32_t a0, uint32_t a1, uint32_t a2, uint32_t a3, uint32_t b0, uint32_t b1) {
    asm("mma.sync.aligned.m16n8k16.row.col.f16.f16.f16.f16 {%0,%1}, {%2,%3,%4,%5}, {%6,%7}, {%0,%1};" : "+r"(d0), "+r"(d1) : "r"(a0), "r"(a1), "r"(a2), "r"(a3), "r"(b0), "r"(b1)); }
__device__ __forceinline__ void mma_h8(uint32_t& d0, uint32_t& d1, uint32_t a0, uint32_t a1, uint32_t b0) {
    asm("mma.sync.aligned.m16n8k8.row.col.f16.f16.f16.f16 {%0,%1}, {%2,%3}, {%4}, {%0,%1};" : "+r"(d0), "+r"(d1) : "r"(a0), "r"(a1), "r"(b0)); }
template <int NQ> __device__ __forceinline__ void load_tab(uint32_t (&r)[NQ * 4], uint32_t addr) {
    #pragma unroll
    for (int i = 0; i < NQ; i++) { uint4 v = lds128(addr + i * 512); r[4 * i] = v.x; r[4 * i + 1] = v.y; r[4 * i + 2] = v.z; r[4 * i + 3] = v.w; }
}
__device__ __forceinline__ float gelu2(float x) {
    float t = x * fmaf(x * x, 0.044715f * 0.7978845608028654f, 0.7978845608028654f), th;
    asm volatile("tanh.approx.f32 %0, %1;" : "=f"(th) : "f"(t));
    return fmaf(x, th, x);
}
__device__ __forceinline__ uint32_t desc_lo(uint32_t addr, uint32_t lbo) { return ((addr & 0x3FFFF) >> 4) | ((lbo >> 4) << 16); }
constexpr uint32_t DHI_A = (1024 >> 4) | (1u << 30), DHI_H3 = 256 >> 4, DHI_U = 128 >> 4;
#define WG_FENCE() asm volatile("wgmma.fence.sync.aligned;" ::: "memory")
#define WG_COMMIT() asm volatile("wgmma.commit_group.sync.aligned;" ::: "memory")
#define WG_WAIT(n) asm volatile("wgmma.wait_group.sync.aligned %0;" :: "n"(n) : "memory")
#define R4(b) "+f"(d[b]), "+f"(d[b + 1]), "+f"(d[b + 2]), "+f"(d[b + 3])
#define R12(b) R4(b), R4(b + 4), R4(b + 8)
#define R36(b) R12(b), R12(b + 12), R12(b + 24)
template <uint32_t BHI> __device__ __forceinline__ void wgmma144(float (&d)[72], uint32_t da, uint32_t db, int acc) {
    asm volatile("{.reg .pred p; .reg .b64 a, b; setp.ne.b32 p, %74, 0; mov.b64 a, {%72, %75}; mov.b64 b, {%73, %76};\n"
        "wgmma.mma_async.sync.aligned.m64n144k16.f32.bf16.bf16 {%0,%1,%2,%3,%4,%5,%6,%7,%8,%9,%10,%11,%12,%13,%14,%15,%16,%17,%18,%19,%20,%21,%22,%23,"
        "%24,%25,%26,%27,%28,%29,%30,%31,%32,%33,%34,%35,%36,%37,%38,%39,%40,%41,%42,%43,%44,%45,%46,%47,"
        "%48,%49,%50,%51,%52,%53,%54,%55,%56,%57,%58,%59,%60,%61,%62,%63,%64,%65,%66,%67,%68,%69,%70,%71}, a, b, p, 1, 1, 1, 1;}\n"
        : R36(0), R36(36) : "r"(da), "r"(db), "r"(acc), "n"(DHI_A), "n"(BHI));
}
__device__ __forceinline__ void wgmma144x4(float (&d)[72], const uint64_t (&a)[4], const uint64_t (&b)[4]) {
    #define WG144 "wgmma.mma_async.sync.aligned.m64n144k16.f32.bf16.bf16 {%0,%1,%2,%3,%4,%5,%6,%7,%8,%9,%10,%11,%12,%13,%14,%15,%16,%17,%18,%19,%20,%21,%22,%23,%24,%25,%26,%27,%28,%29,%30,%31,%32,%33,%34,%35,%36,%37,%38,%39,%40,%41,%42,%43,%44,%45,%46,%47,%48,%49,%50,%51,%52,%53,%54,%55,%56,%57,%58,%59,%60,%61,%62,%63,%64,%65,%66,%67,%68,%69,%70,%71}, "
    asm volatile("{"
        WG144 "%72, %76, 1, 1, 1, 1, 1;\n" WG144 "%73, %77, 1, 1, 1, 1, 1;\n" WG144 "%74, %78, 1, 1, 1, 1, 1;\n" WG144 "%75, %79, 1, 1, 1, 1, 1;}\n"
        : R36(0), R36(36) : "l"(a[0]), "l"(a[1]), "l"(a[2]), "l"(a[3]), "l"(b[0]), "l"(b[1]), "l"(b[2]), "l"(b[3]));
}
__device__ __forceinline__ void wgmma40_rs(float (&d)[20], uint32_t a0, uint32_t a1, uint32_t a2, uint32_t a3, uint32_t db, int acc) {
    asm volatile("{.reg .pred p; .reg .b64 b; setp.ne.b32 p, %25, 0; mov.b64 b, {%24, %26};\n"
        "wgmma.mma_async.sync.aligned.m64n40k16.f32.f16.f16 {%0,%1,%2,%3,%4,%5,%6,%7,%8,%9,%10,%11,%12,%13,%14,%15,%16,%17,%18,%19}, {%20,%21,%22,%23}, b, p, 1, 1, 0;}\n"
        : R12(0), R4(12), R4(16) : "r"(a0), "r"(a1), "r"(a2), "r"(a3), "r"(db), "r"(acc), "n"(DHI_H3));
}
__device__ __forceinline__ void wgmma72(float (&d)[36], uint32_t da, uint32_t db, int acc) {
    asm volatile("{.reg .pred p; .reg .b64 a, b; setp.ne.b32 p, %38, 0; mov.b64 a, {%36, %39}; mov.b64 b, {%37, %40};\n"
        "wgmma.mma_async.sync.aligned.m64n72k16.f32.bf16.bf16 {%0,%1,%2,%3,%4,%5,%6,%7,%8,%9,%10,%11,%12,%13,%14,%15,%16,%17,%18,%19,%20,%21,%22,%23,"
        "%24,%25,%26,%27,%28,%29,%30,%31,%32,%33,%34,%35}, a, b, p, 1, 1, 1, 1;}\n"
        : R36(0) : "r"(da), "r"(db), "r"(acc), "n"(DHI_A), "n"(DHI_H3));
}

__device__ __forceinline__ int g2_kb(int n, int kh, int gi, int c2) {
    if (n < 4) return 36 * kh + 9 * n + 8;
    if (n == 4) return 9 * gi + 4 * c2 + 2 * kh + 1;
    const int w = n > 20, m = n - (w ? 19 : 5);
    return 9 * ((gi * w + (m >> 1)) & 7) + 4 * (n == 35 ? 1 - c2 : m & 1) + 2 * kh + w;
}

__device__ __forceinline__ void add_lo(uint64_t& d, uint32_t a) { asm("{.reg .b32 l, h; mov.b64 {l, h}, %0; add.u32 l, l, %1; mov.b64 %0, {l, h};}" : "+l"(d) : "r"(a)); }
template <uint32_t BHI, int I0, int I1, bool FIRST, class Hook>
__device__ __forceinline__ void mainloop(float (&d)[72], uint32_t bars, uint32_t da0, uint32_t db0, bool lead, Hook hook) {
    uint32_t s = I0 % NST, ph = (I0 / NST) & 1, prev = (I0 + NST - (I0 == IT_P1 ? 2 : 1)) % NST;
    uint32_t ready = 0;
    uint64_t da[4], db[4];
    #pragma unroll
    for (int k = 0; k < 4; k++) { da[k] = ((uint64_t)DHI_A << 32) + da0 + s * (A_BYTES / 16) + k * 128; db[k] = ((uint64_t)BHI << 32) + db0 + s * (B_BYTES / 16) + k * 288; }
    #pragma unroll 1
    for (int i = I0; i < I1; i++) {
        if (!ready) mbar_wait(bars + 8 * BAR_FULL + 8 * s, ph);
        const uint32_t rel = bars + 8 * BAR_EMPTY + 8 * prev, ph0 = ph; const int i0 = i;
        const bool skip = I1 == IT_P1 && (s == P2S - 1 || s == P2S + 2);
        prev = s; s += skip ? 2 : 1; if (s >= NST) { s -= NST; ph ^= 1; }
        const uint32_t adva = (s - prev) * (A_BYTES / 16), advb = (s - prev) * (B_BYTES / 16);
        WG_FENCE();
        wgmma144x4(d, da, db);
        WG_COMMIT();
        #pragma unroll
        for (int k = 0; k < 4; k++) { add_lo(da[k], adva); add_lo(db[k], advb); }
        if (skip) { mbar_wait(bars + 8 * BAR_FULL + 8 * prev + 8, ph0); i++; }
        ready = __shfl_sync(~0u, (uint32_t)mbar_test(bars + 8 * BAR_FULL + 8 * s, ph), 0);
        WG_WAIT(1);
        if (lead && (!FIRST || i0 > I0)) mbar_arrive(rel);
        hook(i0);
    }
}

struct Params {
    const uint16_t *x, *wr, *wi, *w1, *b1, *w2, *b2, *c, *wmod;
    uint16_t* out;
    Scratch* scr;
    const Tab* tab;
};

__device__ __forceinline__ void mma_bf(float (&d)[4], const uint32_t (&a)[4], uint32_t b0, uint32_t b1) {
    asm("mma.sync.aligned.m16n8k16.row.col.f32.bf16.bf16.f32 {%0,%1,%2,%3}, {%4,%5,%6,%7}, {%8,%9}, {%0,%1,%2,%3};"
        : "+f"(d[0]), "+f"(d[1]), "+f"(d[2]), "+f"(d[3]) : "r"(a[0]), "r"(a[1]), "r"(a[2]), "r"(a[3]), "r"(b0), "r"(b1)); }
__device__ __forceinline__ void ldsm4t(uint32_t (&a)[4], uint32_t addr) {
    asm volatile("ldmatrix.sync.aligned.m8n8.x4.trans.shared.b16 {%0,%1,%2,%3}, [%4];" : "=r"(a[0]), "=r"(a[1]), "=r"(a[2]), "=r"(a[3]) : "r"(addr) : "memory"); }
__device__ __forceinline__ void ln_stats(const uint32_t (&w)[9], int g, int q, float& r, float& mr) {
    constexpr uint32_t ONE = 0x3F803F80u;
    float c[2][4] = {};
    #pragma unroll
    for (int p = 0; p < 5; p++) { const uint32_t hi = p < 4 ? w[p < 4 ? 2 * p + 1 : 0] : 0u, a[4] = {w[2 * p], ONE, hi, ONE}; mma_bf(c[p & 1], a, w[2 * p], hi); }
    const float t = (g & 1) ? c[0][1] + c[1][1] : c[0][0] + c[1][0];
    float s1 = (c[0][2] + c[1][2]) + (c[0][3] + c[1][3]), s2 = __shfl_sync(~0u, t, 9 * q) + __shfl_sync(~0u, t, 9 * q + 4);
    #pragma unroll
    for (int o = 1; o < 4; o <<= 1) { s1 += __shfl_xor_sync(~0u, s1, o); s2 += __shfl_xor_sync(~0u, s2, o); }
    const float m = s1 * (1.f / D_);
    asm("rsqrt.approx.ftz.f32 %0, %1;" : "=f"(r) : "f"(fmaxf(fmaf(s2, 1.f / D_, -m * m), 0.f) + 1e-5f));
    mr = -m * r;
}
__device__ __forceinline__ float silu(float v) { return __fdividef(v, 1.f + __expf(-v)); }
__device__ __forceinline__ uint32_t bfma2(uint32_t a, uint32_t b, uint32_t c) { uint32_t r; asm("fma.rn.bf16x2 %0, %1, %2, %3;" : "=r"(r) : "r"(a), "r"(b), "r"(c)); return r; }
__device__ __forceinline__ void radix16(const uint4 (&V)[4], const uint32_t (&B)[16], uint4 (&o)[4]) {
    #pragma unroll
    for (int nt = 0; nt < 4; nt++) {
        o[nt] = make_uint4(0, 0, 0, 0);
        #pragma unroll
        for (int ks = 0; ks < 2; ks++) {
            const uint32_t b0 = B[(ks * 4 + nt) * 2], b1 = B[(ks * 4 + nt) * 2 + 1];
            mma_h(o[nt].x, o[nt].y, V[2 * ks].x, V[2 * ks].y, V[2 * ks + 1].x, V[2 * ks + 1].y, b0, b1);
            mma_h(o[nt].z, o[nt].w, V[2 * ks].z, V[2 * ks].w, V[2 * ks + 1].z, V[2 * ks + 1].w, b0, b1);
        }
    }
}
template <int OFF, int N> __device__ __forceinline__ void gelu_store(const float (&d)[N], char* p, int q) {
    uint32_t w[9];
    #pragma unroll
    for (int blk = 0; blk < 9; blk++) w[blk] = pack_bf(gelu2(d[OFF + 4 * blk]), gelu2(d[OFF + 4 * blk + 1]));
    asm volatile("st.v4.u32 [%0], {%1,%2,%3,%4};" :: "l"(p + q * 128), "r"(w[0]), "r"(w[1]), "r"(w[2]), "r"(w[3]) : "memory");
    asm volatile("st.v4.u32 [%0+512], {%1,%2,%3,%4};" :: "l"(p + q * 128), "r"(w[4]), "r"(w[5]), "r"(w[6]), "r"(w[7]) : "memory");
    asm volatile("st.u32 [%0+1024], %1;" :: "l"(p + q * 4), "r"(w[8]) : "memory");
}

__global__ void __cluster_dims__(2, 1, 1) __launch_bounds__(NTHR, 1)
fused_kernel(const Params p,
             const __grid_constant__ CUtensorMap tm_w1a, const __grid_constant__ CUtensorMap tm_w1b, const __grid_constant__ CUtensorMap tm_w2,
             const __grid_constant__ CUtensorMap tm_h3a, const __grid_constant__ CUtensorMap tm_h3b,
             const __grid_constant__ CUtensorMap tm_wr, const __grid_constant__ CUtensorMap tm_wi, const __grid_constant__ CUtensorMap tm_wm,
             const __grid_constant__ CUtensorMap tm_t, const __grid_constant__ CUtensorMap tm_tx, const __grid_constant__ CUtensorMap tm_o,
             const __grid_constant__ CUtensorMap tm_h3s, const __grid_constant__ CUtensorMap tm_ws)
{
    extern __shared__ char smem_raw[];
    const uint32_t t0 = clk32();
    const uint32_t sm = __shfl_sync(~0u, ((uint32_t)__cvta_generic_to_shared(smem_raw) + 1023u) & ~1023u, 0);
    const int tid = threadIdx.x, warp = __shfl_sync(~0u, tid >> 5, 0), lane = tid & 31, g = lane >> 2, q = lane & 3;
    const int b = blockIdx.x;
    const uint32_t rank = b & 1;
    const uint32_t bars = sm + OFF_BAR;
    const bool rowcta = b < 128;

    auto nc_issue = [&](int st, uint32_t sl) {
        const int pass = st >= 18;
        mbar_expect(bars + 8 * (BAR_X + sl), 28672);
        tma3(sm + sl * 28672, &tm_wm, 0, 32 * (st - 18 * pass), 18 + 28 * pass + 7 * (b - 128), bars + 8 * (BAR_X + sl));
    };
    uint32_t epoch;
    const bool strip = b < 72 && !(b & 1);
    if (warp < 12) {
        epoch = ld_relaxed(g_cnt + CNT_EPOCH * 32);
        if (warp >= 8 && lane < 24 && (strip || !rowcta)) {
            uint32_t cw[3];
            #pragma unroll
            for (int u = 0; u < 3; u++) cw[u] = ldg_nc32(p.c + 144 * (warp - 8) + 48 * u + 2 * lane);
            #pragma unroll
            for (int u = 0; u < 3; u++) sts32(sm + OFF_SILU + (72 * (warp - 8) + 24 * u + lane) * 4, pack_bf(silu(bf_lo(cw[u])), silu(bf_hi(cw[u]))));
        }
        __syncwarp();
        hb();
        bar_sync(2, 512);
    } else {
        const int w4 = 4 * (warp - 12);
        if (elect()) {
            if (warp == 14 && b < 13) asm volatile("cp.async.bulk.prefetch.L2.global [%0], 512;" :: "l"(p.tab->w + b * 128) : "memory");
            if (strip && warp == 15) asm volatile("prefetch.tensormap [%0];" :: "l"(&tm_ws) : "memory");
            if (CRITPF) {
                asm volatile("cp.async.bulk.prefetch.L2.global [%0], 2304;" :: "l"(p.wmod + (b + 33 * w4) * 3456) : "memory");
                if (warp == 12 && b < 48) asm volatile("cp.async.bulk.prefetch.L2.global [%0], 2304;" :: "l"(p.wmod + (b + 528) * 3456) : "memory");
            }
        }
        if (warp == 13) hb();
        if (elect()) {
            if (rowcta) {
                for (int i = 0; i < 4; i++) mbar_init(bars + 8 * (BAR_X + w4 + i), 1);
                const uint32_t sb = bars + 8 * (BAR_ST + warp - 12);
                mbar_init(sb, 1);
                if (warp == 15) mbar_init(bars + 8 * BAR_TAB, 1);
                fence_async_s();
                if (warp == 15) { mbar_expect(bars + 8 * BAR_TAB, QA * 512); bulk_load(sm + OFF_TAB, p.tab, QA * 512, bars + 8 * BAR_TAB); }
                if (strip) { mbar_expect(sb, 9216); tma2(sm + OFF_STRIP + (warp - 12) * 9216, &tm_ws, 16 * b, 36 * w4, sb); }
            } else if (warp == 12) {
                for (int i = 0; i < 12; i++) mbar_init(bars + 8 * (BAR_X + i), i < 6 ? 1 : 14);
                fence_async_s();
                if (NCD) while ((int)(clk32() - t0) < NCD) {}
                for (int st = 0; st < 6; st++) nc_issue(st, st);
            }
            if (warp == 12) {
                asm volatile("prefetch.tensormap [%0];" :: "l"(&tm_wr) : "memory"); asm volatile("prefetch.tensormap [%0];" :: "l"(&tm_wi) : "memory");
                asm volatile("prefetch.tensormap [%0];" :: "l"(&tm_t) : "memory"); asm volatile("prefetch.tensormap [%0];" :: "l"(&tm_tx) : "memory");
            } else if (warp == 14) {
                for (int i = BAR_W; i < BAR_X; i++) mbar_init(bars + 8 * i, i == BAR_DONE || i == BAR_NC ? 4 : i == BAR_W1GO ? 2 : 1);
                mbar_expect(bars + 8 * BAR_W, 28672); mbar_expect(bars + 8 * BAR_TAB2, (QB + QC) * 512);
                mbar_expect(bars + 8 * BAR_ROLE, 4); mbar_expect(bars + 8 * BAR_P2R, 9216); mbar_expect(bars + 8 * BAR_RECV, 18432); mbar_expect(bars + 8 * BAR_XT, 18432);
            } else if (warp == 13) {
                for (int i = 0; i < 2 * NST; i++) mbar_init(bars + 8 * i, 2);
                for (int i = 0; i < NST; i++) mbar_expect(bars + 8 * (BAR_FULL + i), A_BYTES);
            }
            asm volatile("fence.mbarrier_init.release.cluster;" ::: "memory");
        }
        __syncwarp();
        asm volatile("bar.arrive 2, 512;" ::: "memory");
        if (rowcta && elect()) {
            if (XDELAY) while ((int)(clk32() - t0) < XDELAY) {}
            for (int r = w4; r < w4 + 4; r++) {
                mbar_expect(bars + 8 * (BAR_X + r), 1152);
                bulk_load(sm + OFF_STAGE + r * 1152, p.x + (size_t)(b + 128 * r) * D_, 1152, bars + 8 * (BAR_X + r));
            }
        }
        __syncwarp();
        epoch = ld_relaxed(g_cnt + CNT_EPOCH * 32);
        sts16(sm + OFF_MODA + ((warp - 11) * 32 + lane) * 16 + w4 + 2, 0);
        #pragma unroll 1
        for (int s1 = (tid >> 4) & 7; s1 < 16; s1 += 8) {
            const int k1 = tid & 15;
            float s, c;
            __sincosf((float)(((k1 * (128 * s1 + b) + 1024) & 2047) - 1024) * (3.14159265358979f / 1024.f), &s, &c); s *= 0.25f; c *= 0.25f;
            const int rf = ((s1 >> 3) * 4 + (k1 >> 2)) * 2 + ((s1 >> 2) & 1), ri = ((k1 >> 3) * 4 + (s1 >> 2)) * 2 + ((k1 >> 2) & 1);
            const uint32_t af = sm + OFF_B3 + ((rf >> 2) * 32 + (k1 & 3) * 8 + (s1 & 3)) * 16 + (rf & 3) * 4;
            const uint32_t ai = sm + OFF_B3 + 2048 + ((ri >> 2) * 32 + (s1 & 3) * 8 + (k1 & 3)) * 16 + (ri & 3) * 4;
            sts32(af, pack_h(c, s)); sts32(af + 64, pack_h(-s, c)); sts32(ai, pack_h(c, -s)); sts32(ai + 64, pack_h(s, c));
        }
        hb();
        bar_sync(3, 128);
    }
    asm volatile("barrier.cluster.arrive.relaxed.aligned;" ::: "memory");
    const uint32_t tag = (epoch + 1) & 0xFFFFu;

    const int trow = 4 * (b & 7) + ((b >> 4) & 3) + 64 * ((b >> 3) & 1) + 32 * (b >> 6);
    uint32_t* const tptr = g_T + (size_t)trow * TP + (warp < 9 ? q * 288 + 32 * warp : 4608 + 8 * q) + 4 * g;
    const int tstr = warp < 9 ? 1152 : 32;
    const uint32_t scol = sm + OFF_SPEC + (q * SPEC_P + (warp < 8 ? 72 * (warp >> 1) + 40 * (warp & 1) + 4 * g : warp == 8 ? 72 * (g >> 1) + 32 + 4 * (g & 1) : 288 + 4 * g)) * 4;
    const int wc0 = (b >> 3) * 289 + 72 * ((b & 7) >> 1) + 40 * (b & 1);

    uint32_t xw[9], t_st = t0;
    if (!rowcta) {
        const int nst = b < 130 ? 36 : 18;
        __syncthreads();
        if (warp == 14) {
            uint32_t sl = 0, ph = 0;
            #pragma unroll 1
            for (int st = 6; st < nst; st++) {
                mbar_wait(bars + 8 * (BAR_X + 6 + sl), ph);
                if (elect()) nc_issue(st, sl);
                if (++sl == 6) { sl = 0; ph ^= 1; }
            }
        } else if (warp < 14) {
            uint32_t sl = 0, ph = 0;
            const uint32_t ad0 = sm + (warp >> 1) * 4096 + ((lane & 7) + 8 * (lane >> 4)) * 128, ch = (warp & 1) * 4 + ((lane >> 3) & 1);
            #pragma unroll 1
            for (int pass = 0; pass * 18 < nst; pass++) {
                float acc[2][4] = {};
                #pragma unroll 1
                for (int st = 0; st < 18; st++) {
                    const uint32_t sa = sm + OFF_SILU + (16 * st + q) * 4;
                    const uint32_t b0 = lds32(sa), b1 = lds32(sa + 16), b2 = lds32(sa + 32), b3 = lds32(sa + 48);
                    mbar_wait(bars + 8 * (BAR_X + sl), ph);
                    #pragma unroll
                    for (int m = 0; m < 2; m++) {
                        uint32_t a[4], a2[4];
                        const uint32_t ad = ad0 + sl * 28672 + ((ch + 2 * m) ^ (lane & 7)) * 16;
                        ldsm4t(a, ad); ldsm4t(a2, ad + 2048);
                        mma_bf(acc[m], a, b0, b1); mma_bf(acc[m], a2, b2, b3);
                    }
                    if (elect()) mbar_arrive(bars + 8 * (BAR_X + 6 + sl));
                    if (++sl == 6) { sl = 0; ph ^= 1; }
                }
                const int cb = 28 * pass + 7 * (b - 128) + (warp >> 1), gg = (g >> 1) + 4 * q;
                uint32_t w[2];
                #pragma unroll
                for (int m = 0; m < 2; m++) {
                    float v = bf_round(q ? acc[m][2] : acc[m][0]); if (cb >= 27) v *= 0.5f; else if (cb >= 18) v += 1.f;
                    w[m] = max(pack_bf(v, __shfl_xor_sync(~0u, v, 4)), 1u);
                }
                if (q < 2 && !(g & 1)) {
                    const int qq = (warp & 1) * 2;
                    if (cb < 27) asm volatile("st.relaxed.gpu.global.v2.u32 [%0], {%1, %2};" :: "l"(p.scr->modc + 32 * cb + 4 * gg + qq), "r"(w[0]), "r"(w[1]) : "memory");
                    else if (cb < 36) { uint32_t* o = p.scr->modc + 896 + 32 * (cb - 27) + 8 * qq + gg; o[0] = w[0]; o[8] = w[1]; }
                }
                if (tid == 0 && pass == 0) PROFT(25);
                bar_sync(1, 448);
                if (tid == 0) { fence_async_g(); red_release(g_cnt + (CNT_NC + pass) * 32); }
                __syncwarp();
            }
            fence_async_s();
        }
        __syncthreads();
    } else {
        uint32_t ta[QA * 4];
        if (strip && (warp >> 2) == 2) {
            const int w = warp - 8;
            uint32_t sb[18];
            #pragma unroll
            for (int u = 0; u < 18; u++) sb[u] = lds32(sm + OFF_SILU + (72 * w + 4 * u + q) * 4);
            const uint32_t ra = sm + OFF_STRIP + (144 * w + (lane & 7) + 8 * (lane >> 4)) * 64, sw = (lane >> 1) & 3, ch = (lane >> 3) & 1;
            float acc[2][2][4] = {};
            mbar_wait(bars + 8 * (BAR_ST + w), 0);
            #pragma unroll
            for (int u = 0; u < 9; u++)
                #pragma unroll
                for (int m = 0; m < 2; m++) { uint32_t a[4]; ldsm4t(a, ra + u * 1024 + ((ch + 2 * m) ^ sw) * 16); mma_bf(acc[u & 1][m], a, sb[2 * u], sb[2 * u + 1]); }
            #define PICK(a_) ((q & 2) ? ((q & 1) ? a_[1][2] : a_[1][0]) : ((q & 1) ? a_[0][2] : a_[0][0]))
            sts32(sm + OFF_RED + ((8 * q + g) * 4 + w) * 4, __float_as_uint(PICK(acc[0]) + PICK(acc[1])));
            if (tid == 256) PROFT(0);
            bar_sync(10, 128);
            if (warp == 8) {
                const uint4 v = lds128(sm + OFF_RED + lane * 16);
                float sum = bf_round((__uint_as_float(v.x) + __uint_as_float(v.y)) + (__uint_as_float(v.z) + __uint_as_float(v.w)));
                if (b >= 36) sum = bf_round(1.f + sum);
                st_relaxed(g_mod + b * 16 + (lane & 16) + (lane & 1) * 8 + ((lane & 15) >> 1), (pack_h(0.f, sum) & 0xFFFF0000u) | tag);
                if (tid == 256) PROFT(1);
            }
        }
        mbar_wait(bars + 8 * BAR_TAB, 0);
        load_tab<QA>(ta, sm + OFF_TAB + lane * 16);
        auto w_prefetch = [&]() {
            if (warp >= 14 && elect()) asm volatile("cp.async.bulk.prefetch.L2.global [%0], 9248;" :: "l"((warp == 14 ? p.wr : p.wi) + b * 4624) : "memory");
            __syncwarp();
        };
        uint32_t nb[2][5];
        uint4 mv = make_uint4(tag, tag, tag, tag);
        const bool poller = warp < 8 || warp == 12;
        const int mc = warp < 8 ? tid : tid - 128, mst = (mc >> 2) % 36, midx = (mc < 144 ? 10 : 0) + 5 * ((mc >> 1) & 1) + (mst >> 3);
        const uint32_t* mp = g_mod + mc * 4;
        const uint32_t ma = sm + OFF_MODA + ((midx >> 2) * 32 + (mc & 1) * 16 + (mst & 3)) * 16 + (midx & 3) * 4 + ((mst >> 2) & 1) * 2;
        #define MOD_MISSING ((((mv.x ^ tag) | (mv.y ^ tag) | (mv.z ^ tag) | (mv.w ^ tag)) & 0xFFFFu) != 0)
        hb();
        mbar_wait(bars + 8 * (BAR_X + warp), 0);
        if (poller) mv = ldx128(mp);
        PROF0(28);
        #pragma unroll
        for (int i = 0; i < 9; i++) xw[i] = lds32(sm + OFF_STAGE + warp * 1152 + (32 * i + 8 * q + g) * 4);
        {
            float r, mr;
            ln_stats(xw, g, q, r, mr);
            #pragma unroll
            for (int pp = 0; pp < 5; pp++) {
                nb[0][pp] = pack_h(fmaf(bf_lo(xw[2 * pp]), r, mr), pp < 4 ? fmaf(bf_lo(xw[pp < 4 ? 2 * pp + 1 : 0]), r, mr) : 0.f);
                nb[1][pp] = pack_h(fmaf(bf_hi(xw[2 * pp]), r, mr), pp < 4 ? fmaf(bf_hi(xw[pp < 4 ? 2 * pp + 1 : 0]), r, mr) : 0.f);
            }
        }
        PROF0(2);
        w_prefetch();
        if (poller) {
            for (int it = 0; __any_sync(~0u, MOD_MISSING); it++) { if (MOD_MISSING) mv = ldx128(mp); hb(); if (it > SPIN_LIMIT) __trap(); }
            sts16(ma, mv.x >> 16); sts16(ma + 64, mv.y >> 16); sts16(ma + 128, mv.z >> 16); sts16(ma + 192, mv.w >> 16);
        }
        __syncthreads();
        PROF0(3);
        if (warp >= 13 && elect()) {
            if (warp == 15) bulk_load(sm + OFF_TAB + QA * 512, p.tab->w + QA * 128, (QB + QC) * 512, bars + 8 * BAR_TAB2);
            else tma3(sm + OFF_WRAW + (warp - 13) * 14336, warp == 13 ? &tm_wr : &tm_wi, wc0 & ~7, 0, 0, bars + 8 * BAR_W);
        }
        __syncwarp();
        {
            uint32_t md[20];
            load_tab<5>(md, sm + OFF_MODA + lane * 16);
            #pragma unroll
            for (int v = 0; v < 2; v++)
                #pragma unroll
                for (int pp = 0; pp < 5; pp++) nb[v][pp] = hfma2(nb[v][pp], md[v * 5 + pp], md[10 + v * 5 + pp]);
        }
        uint32_t re[3][2], im[3][2];
        #pragma unroll
        for (int mt = 0; mt < 3; mt++)
            #pragma unroll
            for (int v = 0; v < 2; v++) {
                re[mt][v] = 0; im[mt][v] = 0;
                mma_h8(re[mt][v], im[mt][v], ta[mt * 10 + 8], ta[mt * 10 + 9], nb[v][4]);
                mma_h(re[mt][v], im[mt][v], ta[mt * 10], ta[mt * 10 + 1], ta[mt * 10 + 2], ta[mt * 10 + 3], nb[v][0], nb[v][1]);
                mma_h(re[mt][v], im[mt][v], ta[mt * 10 + 4], ta[mt * 10 + 5], ta[mt * 10 + 6], ta[mt * 10 + 7], nb[v][2], nb[v][3]);
                cmul_neg(re[mt][v], im[mt][v], ta[30 + (mt * 2 + v) * 2], ta[31 + (mt * 2 + v) * 2]);
            }
        const uint32_t srow = sm + OFF_SPEC + warp * (SPEC_P * 4);
        #pragma unroll
        for (int nt = 0; nt < 2; nt++) {
            uint32_t o[2][4];
            #pragma unroll
            for (int v = 0; v < 2; v++) {
                const uint32_t b0 = ta[42 + (v * 2 + nt) * 2], b1 = ta[43 + (v * 2 + nt) * 2];
                o[v][0] = o[v][1] = o[v][2] = o[v][3] = 0;
                mma_h(o[v][0], o[v][1], re[0][v], re[1][v], im[0][v], im[1][v], b0, b1);
                mma_h(o[v][2], o[v][3], re[2][v], re[2][v], im[2][v], im[2][v], b0, b1);
            }
            const uint32_t a = srow + (g + 72 * q + 36 * nt) * 4, a2 = srow + (288 - g - 72 * q - 36 * nt) * 4;
            sts32(a, hadd2(o[0][0], o[1][0])); sts32(a + 32, hadd2(o[0][1], o[1][1])); if (g < 3) sts32(a + 64, hadd2(o[0][2], o[1][2]));
            if (g > 0 || (q == 0 && nt == 0)) sts32(a2, hsub2(o[0][0], o[1][0]) ^ 0x80000000u);
            sts32(a2 - 32, hsub2(o[0][1], o[1][1]) ^ 0x80000000u); if (g < 2) sts32(a2 - 64, hsub2(o[0][2], o[1][2]) ^ 0x80000000u);
        }
        uint32_t b3[16];
        if (warp < 10) load_tab<4>(b3, sm + OFF_B3 + lane * 16);
        __syncthreads();
        t_st = clk32();
        PROF0(4);
        if (warp < 10) {
            uint4 V[4], o[4];
            #pragma unroll
            for (int u = 0; u < 4; u++) V[u] = lds128(scol + u * (16 * SPEC_P));
            radix16(V, b3, o);
            #pragma unroll
            for (int nt = 0; nt < 4; nt++) { o[nt].x |= 1u; if (warp < 9 || g < 2) stx128(tptr + nt * tstr, o[nt]); }
        }
        PROF0(5);
    }

    int role = 0;
    asm volatile("barrier.cluster.wait.aligned;" ::: "memory");
    if (warp >= 12) {
        const int t = tid - 384;
        if (tid == 448 && rank == 0) {
            uint32_t smid; asm volatile("mov.u32 %0, %%smid;" : "=r"(smid));
            const uint32_t tp = smid >> 1;
            uint32_t pr = tp < 32 ? (tp & 7) * 8 + (tp >> 3) : tp < 60 ? (1 + (tp - 32) % 7) * 8 + 4 + (tp - 32) / 7 : tp < 62 ? 4 + tp : tp < 66 ? tp - 58 : 0;
            while (atomicExch(g_slot + pr, epoch + 1) == epoch + 1) pr = pr == 65 ? 0 : pr + 1;
            #pragma unroll
            for (int r = 0; r < 2; r++)
                asm volatile("st.async.weak.shared::cluster.mbarrier::complete_tx::bytes.u32 [%0], %1, [%2];" :: "r"(mapa(sm + OFF_MISC, r)), "r"(pr), "r"(mapa(bars + 8 * BAR_ROLE, r)) : "memory");
        }
        __syncwarp();
        if (t == 0) {
            asm volatile("prefetch.tensormap [%0];" :: "l"(&tm_w1a) : "memory");
            asm volatile("prefetch.tensormap [%0];" :: "l"(&tm_h3a) : "memory"); asm volatile("prefetch.tensormap [%0];" :: "l"(&tm_w1b) : "memory");
            asm volatile("prefetch.tensormap [%0];" :: "l"(&tm_h3b) : "memory"); asm volatile("prefetch.tensormap [%0];" :: "l"(&tm_w2) : "memory");
            asm volatile("prefetch.tensormap [%0];" :: "l"(&tm_o) : "memory"); asm volatile("prefetch.tensormap [%0];" :: "l"(&tm_h3s) : "memory");
        }
        __syncwarp();
        if (rowcta) {
            spin_until(t0 + NCP);
            uint4 v[2];
            v[1] = make_uint4(1, 1, 1, 1);
            for (int it = 0;; it++) {
                v[0] = ldx128(p.scr->modc + 4 * t); if (t < 88) v[1] = ldx128(p.scr->modc + 512 + 4 * t);
                if (__all_sync(~0u, min(min(min(v[0].x, v[0].y), min(v[0].z, v[0].w)), min(min(v[1].x, v[1].y), min(v[1].z, v[1].w))) != 0)) break;
                __nanosleep(100); if (it > SPIN_LIMIT) __trap();
            }
            #pragma unroll
            for (int u = 0; u < 2; u++) if (u == 0 || t < 88) {
                const uint32_t a = sm + OFF_MODC + (((t >> 5) + 4 * u) * 32 + 4 * (t & 7)) * 16 + ((t >> 3) & 3) * 4;
                sts32(a, v[u].x); sts32(a + 16, v[u].y); sts32(a + 32, v[u].z); sts32(a + 48, v[u].w);
            }
            __syncwarp();
            if (elect()) mbar_arrive(bars + 8 * BAR_NC);
            if (t == 0) PROFT(29);
        }
    } else if (rowcta && warp < 11) {
        const int nw = !(b & 1) ? 10 : (b & 7) == 7 ? 9 : 8;
        const int cm = (b >> 3) * 288 + (b & 7) * 32, cx = (b & 1) ? 4608 + 8 * (b >> 3) : (b >> 3) * 288 + 256 + 4 * (b & 7);
        auto load_in = [&]() {
            if (elect()) {
                mbar_expect(bars + 8 * BAR_XB, nw > 8 ? 20480 : 16384);
                tma2(sm + OFF_STAGE, &tm_t, cm, 0, bars + 8 * BAR_XB);
                if (nw > 8) tma2(sm + OFF_STX, &tm_tx, cx, 0, bars + 8 * BAR_XB);
            }
            __syncwarp();
        };
        if (warp == 10) { fence_async_s(); spin_until(t_st + X1D); load_in(); }
        uint32_t tb[QB * 4], wre[4][2], wim[4][2];
        if (warp < nw) {
            mbar_wait(bars + 8 * BAR_TAB2, 0);
            load_tab<QB>(tb, sm + OFF_TAB + QA * 512 + lane * 16);
            mbar_wait(bars + 8 * BAR_W, 0);
            const int off = wc0 & 7;
            const uint32_t wa = sm + OFF_WRAW + lane * 112 + ((off >> 1) + 2 * warp) * 4, sh = (off & 1) * 16;
            #pragma unroll
            for (int c = 0; c < 2; c++)
                #pragma unroll
                for (int h = 0; h < 2; h++) {
                    uint32_t y[2][2];
                    #pragma unroll
                    for (int e = 0; e < 2; e++) {
                        const uint32_t a = wa + c * 14336 + (h + 2 * e) * 3584, x0 = lds32(a), x1 = lds32(a + 4), x2 = lds32(a + 8);
                        y[e][0] = __funnelshift_r(x0, x1, sh); y[e][1] = __funnelshift_r(x1, x2, sh);
                    }
                    #pragma unroll
                    for (int x = 0; x < 4; x++) {
                        const uint32_t v = (x & 1) ? pack_h(bf_hi(y[0][x >> 1]), bf_hi(y[1][x >> 1])) : pack_h(bf_lo(y[0][x >> 1]), bf_lo(y[1][x >> 1]));
                        if (c) wim[x][h] = v; else wre[x][h] = v;
                    }
                }
        }
        const uint32_t ca = warp < 8 ? sm + OFF_STAGE + lane * 128 + (warp ^ (lane & 7)) * 16 : sm + OFF_STX + lane * 32 + ((warp ^ g) & 1) * 16, cs = warp < 8 ? 4096 : 1024;
        uint32_t V[4][4];
        for (int it = 0;; it++) {
            mbar_wait(bars + 8 * BAR_XB, it & 1);
            uint32_t ok = 1;
            if (warp < nw) {
                #pragma unroll
                for (int u = 0; u < 4; u++) { uint4 t4 = lds128(ca + u * cs); V[u][0] = t4.x; V[u][1] = t4.y; V[u][2] = t4.z; V[u][3] = t4.w; ok &= t4.x; }
            }
            asm volatile("{.reg .pred p; setp.ne.u32 p, %0, 0; bar.red.and.pred p, 1, 352, p; selp.u32 %0, 1, 0, p;}" : "+r"(ok) :: "memory");
            if (ok) break;
            if (warp == 10) { load_in(); hb(); }
            if (it > SPIN_LIMIT / 64) __trap();
        }
        PROF0(7);
        if (warp < nw) {
            uint32_t zr[4][2], zi[4][2];
            #pragma unroll
            for (int x = 0; x < 4; x++) {
                uint32_t er = 0, ei = 0, or_ = 0, oi = 0;
                mma_h(er, ei, tb[0], tb[1], tb[2], tb[3], V[0][x], V[1][x]);
                mma_h(or_, oi, tb[4], tb[5], tb[6], tb[7], V[2][x], V[3][x]);
                uint32_t r0 = hadd2(er, or_), r1 = hsub2(er, or_), i0 = hadd2(ei, oi), i1 = hsub2(ei, oi);
                cmul_neg(r0, i0, tb[8], tb[9]); cmul_neg(r1, i1, tb[10], tb[11]);
                uint32_t xr0 = 0, xr1 = 0, xi0 = 0, xi1 = 0;
                mma_h(xr0, xr1, r0, r1, i0, i1, tb[12], tb[13]);
                mma_h(xi0, xi1, r0, r1, i0, i1, tb[14], tb[12]);
                cmul_pos(xr0, xi0, wre[x][0], wim[x][0]); cmul_pos(xr1, xi1, wre[x][1], wim[x][1]);
                r0 = 0; i0 = 0; r1 = 0; i1 = 0;
                mma_h(r0, i0, tb[12], tb[13], tb[14], tb[12], xr0, xi0);
                mma_h(r1, i1, tb[12], tb[13], tb[14], tb[12], xr1, xi1);
                cmul_pos(r0, i0, tb[15], tb[16]); cmul_pos(r1, i1, tb[17], tb[18]);
                zr[x][0] = hadd2(r0, r1); zr[x][1] = hsub2(r0, r1); zi[x][0] = hadd2(i0, i1); zi[x][1] = hsub2(i0, i1);
            }
            #pragma unroll
            for (int nt = 0; nt < 4; nt++) {
                uint4 o = make_uint4(0, 0, 0, 0);
                const int h = nt >> 1;
                mma_h(o.x, o.y, zr[0][h], zr[1][h], zi[0][h], zi[1][h], tb[19 + 2 * nt], tb[20 + 2 * nt]);
                mma_h(o.z, o.w, zr[2][h], zr[3][h], zi[2][h], zi[3][h], tb[19 + 2 * nt], tb[20 + 2 * nt]);
                o.x &= ~1u;
                sts128(ca + nt * cs, o);
            }
        }
        fence_async_s();
        bar_sync(1, 352);
        t_st = clk32();
        PROF0(8);
        if (warp == 10 && elect()) {
            asm volatile("cp.async.bulk.tensor.2d.global.shared::cta.bulk_group [%0, {%2, %3}], [%1];" :: "l"(&tm_t), "r"(sm + OFF_STAGE), "r"(cm), "r"(0) : "memory");
            if (nw > 8) asm volatile("cp.async.bulk.tensor.2d.global.shared::cta.bulk_group [%0, {%2, %3}], [%1];" :: "l"(&tm_tx), "r"(sm + OFF_STX), "r"(cx), "r"(0) : "memory");
            asm volatile("cp.async.bulk.commit_group;" ::: "memory");
            asm volatile("cp.async.bulk.wait_group.read 0;" ::: "memory");
        }
        __syncwarp();
    }

    if (warp >= 10) { mbar_wait(bars + 8 * BAR_ROLE, 0); role = __shfl_sync(~0u, lds32(sm + OFF_MISC), 0); fence_async_s(); }
    auto first_a = [&]() {
        if (warp >= 10 && role < 64 && elect()) {
            const int it = warp - 10, hi = it >= 3; const bool p2 = it - 3 * hi == 2;
            tma4(sm + OFF_A + it * A_BYTES, p2 ? &tm_w1b : &tm_w1a, 0, 0, p2 ? 64 * rank + 8 * hi : 4 * (it - hi),
                 9 * (role >> 3) + (p2 ? 8 : (role & 4) + 2 * rank), bars + 8 * (BAR_FULL + it));
        }
        __syncwarp();
    };
    if (!rowcta) first_a();
    else {
        uint32_t tc[20], md[28];
        mbar_wait(bars + 8 * BAR_TAB2, 0);
        load_tab<5>(tc, sm + OFF_TAB + (QA + QB) * 512 + lane * 16);
        bool md_early = warp >= 10;
        if (md_early) { mbar_wait(bars + 8 * BAR_NC, 0); load_tab<7>(md, sm + OFF_MODC + lane * 16); }
        if (warp < 10) {
            uint32_t b3[16];
            load_tab<4>(b3, sm + OFF_B3 + 2048 + lane * 16);
            uint4 V[4], o[4];
            const bool tact = warp < 9 || g == 0;
            spin_until(t_st + X2D);
            #pragma unroll
            for (int u = 0; u < 4; u++) { V[u] = make_uint4(0, 0, 0, 0); if (tact) V[u] = ldx128(tptr + u * tstr); }
            md_early = __any_sync(~0u, mbar_test(bars + 8 * BAR_NC, 0));
            if (md_early) load_tab<7>(md, sm + OFF_MODC + lane * 16);
            for (int it = 0; __any_sync(~0u, (V[0].x | V[1].x | V[2].x | V[3].x) & 1u); it++) {
                #pragma unroll
                for (int u = 0; u < 4; u++) if (V[u].x & 1u) V[u] = ldx128(tptr + u * tstr);
                hb();
                if (it > SPIN_LIMIT) __trap();
            }
            PROF0(10);
            radix16(V, b3, o);
            if (tact) {
                #pragma unroll
                for (int nt = 0; nt < 4; nt++) sts128(scol + nt * (16 * SPEC_P), o[nt]);
            }
        }
        __syncthreads();
        PROF0(11);
        first_a();
        const uint32_t srow = sm + OFF_SPEC + warp * (SPEC_P * 4);
        uint32_t re[2][3], im[2][3];
        #pragma unroll
        for (int mt = 0; mt < 3; mt++) {
            const uint32_t a = srow + (g + 72 * q + 8 * mt) * 4, a2 = srow + (288 - g - 72 * q - 8 * mt) * 4;
            const uint32_t z0 = lds32(a), z1 = lds32(a + 144), z2 = lds32(a2), z3 = lds32(a2 - 144);
            #pragma unroll
            for (int m2 = 0; m2 < 2; m2++) {
                re[m2][mt] = 0; im[m2][mt] = 0;
                const uint32_t sg = m2 ? 0x3C00BC00u : 0xBC003C00u;
                mma_h(re[m2][mt], im[m2][mt], tc[m2 * 4], tc[m2 * 4 + 1], tc[m2 * 4 + 2], tc[m2 * 4 + 3], hfma2(z2, sg, z0), hfma2(z3, sg, z1));
                cmul_pos(re[m2][mt], im[m2][mt], tc[8 + (m2 * 3 + mt) * 2], tc[9 + (m2 * 3 + mt) * 2]);
            }
        }
        float y[20];
        WG_FENCE();
        #pragma unroll
        for (int mt = 0; mt < 3; mt++)
            wgmma40_rs(y, re[0][mt], re[1][mt], im[0][mt], im[1][mt], desc_lo(sm + OFF_TAB + (QA + QB + 5) * 512 + mt * 1280, 128), mt);
        WG_COMMIT();
        if (!md_early) { mbar_wait(bars + 8 * BAR_NC, 0); load_tab<7>(md, sm + OFF_MODC + lane * 16); }
        WG_WAIT(0);
        #pragma unroll
        for (int i = 0; i < 9; i++) xw[i] = bfma2(md[i], pack_bf(y[4 * (i >> 1) + (i & 1)], y[4 * (i >> 1) + 2 + (i & 1)]), xw[i]);
        float r, mr;
        ln_stats(xw, g, q, r, mr);
        uint32_t h[9], r2 = pack_bf(r, r), m2 = pack_bf(mr, mr);
        #pragma unroll
        for (int i = 0; i < 9; i++) h[i] = bfma2(bfma2(xw[i], r2, m2), md[18 + i], md[9 + i]);
        ln_stats(h, g, q, r, mr);
        r2 = pack_bf(r, r); m2 = pack_bf(mr, mr);
        {
            const int n7 = 2 * q + (g >> 2);
            const uint32_t a = sm + OFF_STAGE + (warp >> 3) * 9216 + n7 * 128 + ((warp & 7) ^ n7) * 16 + (g & 3) * 4;
            #pragma unroll
            for (int i = 0; i < 9; i++) sts32(a + i * 1024, bfma2(h[i], r2, m2));
        }
        fence_async_s();
        __syncthreads();
        PROF0(12);
        if (tid == 0) {
            asm volatile("cp.async.bulk.tensor.4d.global.shared::cta.bulk_group [%0, {%2, %2, %2, %3}], [%1];" :: "l"(&tm_h3s), "r"(sm + OFF_STAGE), "r"(0), "r"(b) : "memory");
            asm volatile("cp.async.bulk.commit_group;" ::: "memory");
        }
        #pragma unroll
        for (int i = 0; i < 9; i++) sts32(sm + OFF_X1 + warp * 1152 + (32 * i + 8 * q + g) * 4, xw[i]);
    }
    __syncthreads();
    if (rowcta) {
        if (tid == 0) { asm volatile("cp.async.bulk.wait_group 0;" ::: "memory"); fence_async_g(); red_release(g_cnt + CNT_H3 * 32); }
        PROF0(13);
        if (warp == 15) {
            __nanosleep(X1DELAY);
            #pragma unroll 1
            for (int r = 0; r < 16; r++) {
                uint4* dst = (uint4*)(p.out + (size_t)(b + 128 * r) * D_) + lane;
                const uint32_t src = sm + OFF_X1 + r * 1152 + lane * 16;
                dst[0] = lds128(src); dst[32] = lds128(src + 512); if (lane < 8) dst[64] = lds128(src + 1024);
                const uint32_t t1 = clk32(); while ((int)(clk32() - t1) < X1PACE) __nanosleep(50);
            }
            __syncwarp();
            if (lane == 0) { fence_async_g(); red_release(g_cnt + CNT_X1 * 32); }
        }
    }
    role = __shfl_sync(~0u, lds32(sm + OFF_MISC), 0);
    if (role >= 64) { if (warp == 0) PROFDUMP(); return; }

    const int gi = role >> 3, dt = role & 3, c2 = (role >> 2) & 1;
    const int wg = warp >> 2, wi = warp & 3;
    if (wg == 3) {
        uint32_t so = 0, eph = 1;
        #define RING_STEP(BYTES, OFF, ISSUE) do { \
            mbar_wait(bars + 8 * BAR_EMPTY + so, eph); \
            if (elect()) { const uint32_t fb = bars + 8 * BAR_FULL + so, dst = sm + (OFF) + so * ((BYTES) / 8); mbar_expect(fb, BYTES); ISSUE; } \
            so += 8; if (so == 8 * NST) { so = 0; eph ^= 1; } } while (0)
        const uint32_t kbt = g2_kb(lane, rank, gi, c2) | (g2_kb(32 + (lane & 3), rank, gi, c2) << 8);
        #define KB(n_) ((__shfl_sync(~0u, kbt, (n_) & 31) >> (((n_) >> 2) & 8)) & 255)
        if (warp == 12) {
            eph = 0;
            const int fb1 = 9 * gi + 4 * c2 + 2 * rank, sb2 = 4 * gi + 2 * c2;
            int pft = dt, pfj = 4 * (PF0 + PFS * dt);
            #pragma unroll 1
            for (int j = 16; j < 128; j += 4) {
                RING_STEP(A_BYTES, OFF_A, tma4(dst, &tm_w1a, 0, 0, j, fb1, fb));
                if (j < 64) { if (j & 4) RING_STEP(A_BYTES, OFF_A, tma4(dst, &tm_w1b, 0, 0, 64 * rank + j - 4, 9 * gi + 8, fb)); }
                if (j == pfj && pft < PFN) {
                    const int kb = KB(pft); pft += 4; pfj += 16 * PFS;
                    if (elect()) asm volatile("cp.async.bulk.prefetch.tensor.3d.L2.global [%0, {%1, %2, %3}];" :: "l"(&tm_w2), "r"(0), "r"(64 * kb), "r"(sb2) : "memory");
                }
            }
            #pragma unroll 1
            for (int n = 0; n < 36; n++) {
                const int kb = KB(n);
                RING_STEP(A_BYTES, OFF_A, tma3(dst, &tm_w2, 0, 64 * kb, sb2, fb));
            }
        } else if (warp == 13) {
            const uint32_t e1 = __shfl_sync(~0u, epoch + 1, 0);
            fence_async_s();
            wait_count<0>(g_cnt + CNT_H3 * 32, e1 * 128);
            fence_async_g();
            if (lane == 0) PROFT(14);
            #pragma unroll 1
            for (int j = 0; j < 128; j += 4) {
                RING_STEP(B_BYTES, OFF_B, tma3(dst, &tm_h3a, 0, 18 * dt, j, fb));
                if (j < 64 && (j & 4)) RING_STEP(B_BYTES, OFF_B, tma3(dst, &tm_h3b, 0, 18 * dt + 9 * c2, 64 * rank + j - 4, fb));
            }
            int n = 0;
            #pragma unroll 1
            for (int cls = 0; cls < 3; cls++) {
                mbar_wait(bars + 8 * (BAR_UOK + cls), 0);
                fence_async_g();
                if (cls == 1 && lane == 0) PROFT(19);
                if (cls == 0 && lane == 0) PROFT(22);
                static_assert((IT_G2 + 4) % NST != NST - 1, "no wrap at the skipped stage");
                if (cls == 1) { n++; so += 8; }
                #pragma unroll 1
                for (; n < (cls == 0 ? 4 : cls == 1 ? 21 : 36); n++) {
                    const int kb = KB(n);
                    RING_STEP(B_BYTES, OFF_B, bulk_load(dst, g_U + (kb * 4 + dt) * 1152, B_BYTES, fb));
                }
            }
            if (role == 0 && rank == 0 && lane == 0) st_relaxed(g_cnt + CNT_EPOCH * 32, e1);
        } else if (warp == 15) {
            if (elect()) mbar_arrive_remote(mapa(bars + 8 * BAR_HOLD, rank ^ 1));
            __syncwarp();
            bar_sync(6, 160);
            if (elect()) mbar_arrive(bars + 8 * (BAR_FULL + (IT_G2 + 4) % NST));
            __syncwarp();
            mbar_wait(bars + 8 * BAR_W1GO, 0);
            if (elect()) {
                char* dst = (char*)(g_U + ((9 * gi + 4 * c2 + 2 * rank + 1) * 4 + dt) * 1152);
                #pragma unroll 1
                for (int i = 0; i < W1N; i++) {
                    asm volatile("cp.async.bulk.global.shared::cta.bulk_group [%0], [%1], %2;" :: "l"(dst + i * (18432 / W1N)), "r"(sm + OFF_X1 + i * (18432 / W1N)), "n"(18432 / W1N) : "memory");
                    const uint32_t t1 = clk32(); while ((int)(clk32() - t1) < W1P) {}
                }
                asm volatile("cp.async.bulk.commit_group;" ::: "memory");
                asm volatile("cp.async.bulk.wait_group 0;" ::: "memory");
                fence_async_g(); red_release(g_cnt + (CNT_U + 16) * 32);
                #pragma unroll 1
                for (int n = 0; n < 4; n++) { __nanosleep(300); tma2(sm + OFF_X1 + n * 4608, &tm_o, 144 * dt, 256 * gi + 128 * c2 + 64 * (rank ^ 1) + 16 * n, bars + 8 * BAR_XT); }
            }
        } else {
            const uint32_t e1 = epoch + 1;
            if (lane == 0) {
                __nanosleep(4000);
                wait_count<200>(g_cnt + CNT_NC * 32, e1 * 4); wait_count<200>(g_cnt + (CNT_NC + 1) * 32, e1 * 2);
                fence_async_g();
                mbar_expect(bars + 8 * BAR_GB, 1152);
                bulk_load(sm + OFF_GB, p.scr->modc + 896, 1152, bars + 8 * BAR_GB);
                wait_count<200>(g_cnt + CNT_X1 * 32, e1 * 128);
                if (role * 2 + rank < 108) {
                    uint4* z = (uint4*)p.scr->modc + (role * 2 + rank) * 2; z[0] = z[1] = make_uint4(0, 0, 0, 0);
                }
                wait_count<50>(g_cnt + (CNT_U + dt * 2 + rank) * 32, e1 * 16);
                mbar_arrive(bars + 8 * BAR_UOK);
            }
            __syncwarp();
            bar_sync(4, 160);
            if (lane == 0) {
                fence_async_g(); red_release(g_cnt + (CNT_U + 8) * 32);
                PROFT(17);
                wait_count<0>(g_cnt + (CNT_U + 8) * 32, e1 * 128);
                mbar_arrive(bars + 8 * (BAR_UOK + 1));
                __nanosleep(1000);
                wait_count<100>(g_cnt + (CNT_U + 16) * 32, e1 * 128);
                mbar_arrive(bars + 8 * (BAR_UOK + 2));
            }
        }
    } else if (wg == 2) {
        float d0[36];
        const float bias = bf_lo(ldg_nc16(p.b1 + 576 * gi + 512 + 16 * wi + g + 8 * rank));
        for (int it = 0; it < 200 && !__any_sync(~0u, mbar_test(bars + 8 * BAR_FULL, 0)); it++) { hb(); __nanosleep(100); }
        const bool lead = wi == 0 && elect();
        #pragma unroll 1
        for (int i = 0; i < 8; i++) {
            const uint32_t s = P2S + 3 * (i & 1);
            mbar_wait(bars + 8 * BAR_FULL + 8 * s, (i >> 1) & 1);
            const uint32_t da = desc_lo(sm + OFF_A, 8192) + s * (A_BYTES / 16), db = desc_lo(sm + OFF_B, 128) + s * (B_BYTES / 16);
            WG_FENCE();
            wgmma72(d0, da, db, i);
            #pragma unroll
            for (int k = 1; k < 8; k++) wgmma72(d0, da + k * 128, db + k * 144, 1);
            WG_COMMIT();
            WG_WAIT(0);
            if (lead) mbar_arrive_n(bars + 8 * BAR_EMPTY + 8 * s, 2);
        }
        if (lead) PROFT(18);
        const uint32_t slot = sm + OFF_P2R + (tid & 127) * 16, ra = mapa(slot, rank ^ 1), rb = mapa(bars + 8 * BAR_P2R, rank ^ 1);
        float sv[18];
        #pragma unroll
        for (int i = 0; i < 18; i++) { const float lo = d0[4 * (i >> 1) + (i & 1)], hi = d0[4 * (i >> 1) + 2 + (i & 1)];
            sv[i] = rank ? lo : hi; d0[4 * (i >> 1) + (i & 1)] = (rank ? hi : lo) + bias; }
        mbar_wait(bars + 8 * BAR_HOLD, 0);
        #pragma unroll
        for (int i = 0; i < 4; i++)
            asm volatile("st.async.weak.shared::cluster.mbarrier::complete_tx::bytes.v4.f32 [%0], {%1,%2,%3,%4}, [%5];"
                :: "r"(ra + i * 2048), "f"(sv[4 * i]), "f"(sv[4 * i + 1]), "f"(sv[4 * i + 2]), "f"(sv[4 * i + 3]), "r"(rb) : "memory");
        asm volatile("st.async.weak.shared::cluster.mbarrier::complete_tx::bytes.v2.f32 [%0], {%1,%2}, [%3];" :: "r"(ra + 8192), "f"(sv[16]), "f"(sv[17]), "r"(rb) : "memory");
        mbar_wait(bars + 8 * BAR_P2R, 0);
        #pragma unroll
        for (int i = 0; i < 5; i++) {
            const uint4 v = lds128(slot + i * 2048);
            d0[8 * i] += __uint_as_float(v.x); d0[8 * i + 1] += __uint_as_float(v.y);
            if (i < 4) { d0[8 * i + 4] += __uint_as_float(v.z); d0[8 * i + 5] += __uint_as_float(v.w); }
        }
        asm volatile("bar.arrive 5, 256;" ::: "memory");
        gelu_store<0>(d0, (char*)(g_U + ((9 * gi + 8) * 4 + dt) * 1152) + wi * 4608 + rank * 2304 + c2 * 1152 + g * 16, q);
        bar_sync(8, 128);
        if (lead) { fence_async_g(); red_release(g_cnt + (CNT_U + dt * 2 + (gi >> 2)) * 32); PROFT(26); }
    } else {
        float d[72];
        const bool lead = wi == 0 && elect();
        const uint32_t da0 = desc_lo(sm + OFF_A + wg * 8192, 8192);
        const bool owner = (uint32_t)wg == rank;
        const int srow = 256 * gi + 128 * c2 + 64 * wg + 16 * wi;
        const uint32_t b2w0 = ldg_nc16(p.b2 + srow + g), b2w1 = ldg_nc16(p.b2 + srow + g + 8);
        {
            const int fr = 576 * gi + 256 * c2 + 128 * rank + 64 * wg + 16 * wi + g;
            const float bias0 = bf_lo(ldg_nc16(p.b1 + fr)), bias1 = bf_lo(ldg_nc16(p.b1 + fr + 8));
            #pragma unroll
            for (int i = 0; i < 72; i++) d[i] = (i & 2) ? bias1 : bias0;
            const uint32_t db1 = desc_lo(sm + OFF_B, 128);
            mainloop<DHI_H3, 0, IT_P1, true>(d, bars, da0, db1, lead, [&](int) {});
            mainloop<DHI_H3, IT_P1, IT_G2 - LEAD1, false>(d, bars, da0, db1, lead, [&](int) {});
            constexpr uint32_t EB = 8 * (BAR_EMPTY + (IT_G2 - LEAD1 - 1) % NST);
            if (wg == 1) { WG_WAIT(0); if (lead) mbar_arrive(bars + EB); bar_sync(9, 256); }
            #pragma unroll
            for (int i = IT_G2 - LEAD1; i < IT_G2; i++) {
                mbar_wait(bars + 8 * (BAR_FULL + i % NST), (i / NST) & 1);
                WG_FENCE();
                #pragma unroll
                for (int k = 0; k < 4; k++) {
                    if (i == IT_G2 - 1 && k == HOK1) WG_COMMIT();
                    wgmma144<DHI_H3>(d, da0 + (i % NST) * (A_BYTES / 16) + k * 128, db1 + (i % NST) * (B_BYTES / 16) + k * 288, 1);
                }
                WG_COMMIT();
                if (i == IT_G2 - 1 && HOK1 < 4) WG_WAIT(2); else WG_WAIT(1);
                if (lead && (i > IT_G2 - LEAD1 || wg == 0)) mbar_arrive(bars + 8 * (BAR_EMPTY + (i - 1) % NST));
            }
            if (wg == 0) { WG_WAIT(1); asm volatile("bar.arrive 9, 256;" ::: "memory"); }
            WG_WAIT(0);
            if (lead) mbar_arrive(bars + 8 * (BAR_EMPTY + (IT_G2 - 1) % NST));
            PROF0(16);
            if (wg == 1) bar_sync(5, 256);
            char* const ub = (wg == 0 ? (char*)(g_U + ((9 * gi + 4 * c2 + 2 * rank) * 4 + dt) * 1152) : (char*)__cvta_shared_to_generic(sm + OFF_X1)) + wi * 4608 + g * 16;
            gelu_store<0>(d, ub, q); gelu_store<2>(d, ub + 2304, q); gelu_store<36>(d, ub + 1152, q); gelu_store<38>(d, ub + 3456, q);
            PROF0(27);
            if (wg == 0) asm volatile("bar.arrive 4, 160;" ::: "memory");
            else { fence_async_s(); asm volatile("bar.arrive 6, 160;" ::: "memory"); }
        }
        const uint32_t db0 = desc_lo(sm + OFF_B, 2304);
        const bool keep = role > 64;
        constexpr int IT_L = IT_END - NST, IT_X = IT_L - 4;
        #pragma unroll
        for (int i = IT_G2; i <= IT_G2 + W1S; i++) {
            const uint32_t db = db0 + (i == IT_G2 + 4 ? OFF_X1 - OFF_B : (i % NST) * B_BYTES) / 16;
            mbar_wait(bars + 8 * (BAR_FULL + i % NST), (i / NST) & 1);
            WG_FENCE();
            #pragma unroll
            for (int k = 0; k < 4; k++) wgmma144<DHI_U>(d, da0 + (i % NST) * (A_BYTES / 16) + k * 128, db + k * 288, i > IT_G2 || k > 0 || keep);
            WG_COMMIT();
            if (i > IT_G2) { WG_WAIT(1); if (lead) mbar_arrive(bars + 8 * (BAR_EMPTY + (i - 1) % NST)); }
        }
        if (lead) mbar_arrive(bars + 8 * BAR_W1GO);
        mainloop<DHI_U, IT_G2 + W1S + 1, IT_X, false>(d, bars, da0, db0, lead, [&](int) {});
        const uint32_t ga0 = sm + OFF_GB + (144 * dt + 8 * q) * 2, tile = sm + OFF_X1 + wi * 4608, to = g * 288 + q * 16;
        #define QOFF(i_) (((i_) >> 2) * 2304 + 144 * (((i_) >> 1) & 1) + 64 * ((i_) & 1))
        #define SOFF(k_) (((k_) >> 1) * 2304 + 144 * ((k_) & 1) + 128 - 12 * q)
        #define DIDX(i_, k_) ((i_) < 8 ? 36 * (((i_) >> 1) & 1) + 16 * ((i_) & 1) + 4 * (k_) + 2 * ((i_) >> 2) : 36 * ((k_) & 1) + 32 + 2 * ((k_) >> 1))
        #define FIN(k_, f_) bfma2(g4.f_, pack_bf(d[DIDX(i, k_)], d[DIDX(i, k_) + 1]), xq[i].f_)
        uint4 xq[9];
        auto load_g = [&](int i) { uint4 r; if (i < 4) r = lds128(ga0 + QOFF(i)); else { r.x = r.z = lds32(ga0 + SOFF(0)); r.y = r.w = lds32(ga0 + SOFF(1)); } return r; };
        mainloop<DHI_U, IT_X, IT_L, false>(d, bars, da0, db0, lead, [&](int i) {
            if (!owner) {
                const uint32_t xa = tile + to;
                if (i == IT_X) { mbar_wait(bars + 8 * BAR_XT, 0); xq[0] = lds128(xa + QOFF(0)); xq[4] = lds128(xa + QOFF(4)); xq[1] = lds128(xa + QOFF(1)); }
                else if (i == IT_X + 1) { xq[5] = lds128(xa + QOFF(5)); xq[2] = lds128(xa + QOFF(2)); xq[6] = lds128(xa + QOFF(6)); }
                else if (i == IT_X + 2) { xq[3] = lds128(xa + QOFF(3)); xq[7] = lds128(xa + QOFF(7));
                    xq[8] = make_uint4(lds32(xa + SOFF(0)), lds32(xa + SOFF(1)), lds32(xa + SOFF(2)), lds32(xa + SOFF(3))); }
                else if (i == IT_X + 3) { if (elect()) mbar_arrive_remote(mapa(bars + 8 * BAR_DONE, rank ^ 1)); }
            } });
        if (owner) { WG_WAIT(0); if (lead) mbar_arrive(bars + 8 * (BAR_EMPTY + (IT_L - 1) % NST)); bar_sync(7, 256); }
        #pragma unroll
        for (int i = IT_L; i < IT_END; i++) {
            mbar_wait(bars + 8 * (BAR_FULL + i % NST), (i / NST) & 1);
            WG_FENCE();
            #pragma unroll
            for (int k = 0; k < 4; k++) {
                if (i == IT_END - 1 && k == HOK) WG_COMMIT();
                wgmma144<DHI_U>(d, da0 + (i % NST) * (A_BYTES / 16) + k * 128, db0 + (i % NST) * (B_BYTES / 16) + k * 288, 1);
            }
            WG_COMMIT();
            if (i == IT_L) { WG_WAIT(1); if (lead && !owner) mbar_arrive(bars + 8 * (BAR_EMPTY + (IT_L - 1) % NST)); }
        }
        PROF0(9);
        mbar_wait(bars + 8 * BAR_GB, 0);
        if (!owner) {
            const uint32_t ra = mapa(tile + lane * 16, rank ^ 1), rb = mapa(bars + 8 * BAR_RECV, rank ^ 1);
            mbar_wait(bars + 8 * BAR_DONE, 0);
            uint4 gn = load_g(0);
            WG_WAIT(1);
            asm volatile("bar.arrive 7, 256;" ::: "memory");
            WG_WAIT(0);
            #pragma unroll
            for (int i = 0; i < 72; i++) d[i] = fmaf(bf_lo((i & 2) ? b2w1 : b2w0), 2.f, d[i]);
            #pragma unroll
            for (int j = 0; j < 5; j++) {
                const uint4 g4 = gn;
                if (j < 4) gn = load_g(j + 1);
                #pragma unroll
                for (int i = j < 4 ? j : 8; i < 9; i += 4) if (i < 8 || j == 4)
                    asm volatile("st.async.weak.shared::cluster.mbarrier::complete_tx::bytes.v4.b32 [%0], {%1,%2,%3,%4}, [%5];"
                        :: "r"(ra + i * 512), "r"(FIN(0, x)), "r"(FIN(1, y)), "r"(FIN(2, z)), "r"(FIN(3, w)), "r"(rb) : "memory");
            }
            PROF0(6);
            if (warp == 0) PROFDUMP();
            return;
        }
        PROF0(24);
        mbar_wait(bars + 8 * BAR_RECV, 0);
        #pragma unroll
        for (int i = 0; i < 9; i++) xq[i] = lds128(tile + lane * 16 + i * 512);
        uint4 gn = load_g(0);
        WG_WAIT(0);
        __syncwarp();
        PROF0(21);
        #pragma unroll
        for (int j = 0; j < 5; j++) {
            const uint4 g4 = gn;
            if (j < 4) gn = load_g(j + 1);
            #pragma unroll
            for (int i = j < 4 ? j : 8; i < 9; i += 4) if (i < 8 || j == 4) {
                const uint4 o = make_uint4(FIN(0, x), FIN(1, y), FIN(2, z), FIN(3, w));
                if (i < 8) sts128(tile + to + QOFF(i), o);
                else { sts32(tile + to + SOFF(0), o.x); sts32(tile + to + SOFF(1), o.y); sts32(tile + to + SOFF(2), o.z); sts32(tile + to + SOFF(3), o.w); }
            }
        }
        fence_async_s();
        __syncwarp();
        if (elect()) {
            asm volatile("cp.async.bulk.tensor.2d.global.shared::cta.bulk_group [%0, {%2, %3}], [%1];" :: "l"(&tm_o), "r"(tile), "r"(144 * dt), "r"(srow) : "memory");
            asm volatile("cp.async.bulk.commit_group;" ::: "memory");
            asm volatile("cp.async.bulk.wait_group.read 0;" ::: "memory");
        }
        PROF0(23);
        if (warp == 0) { __syncwarp(); PROFDUMP(); }
    }
}

typedef CUresult (*EncodeFn)(CUtensorMap*, CUtensorMapDataType, cuuint32_t, void*, const cuuint64_t*, const cuuint64_t*, const cuuint32_t*,
                             const cuuint32_t*, CUtensorMapInterleave, CUtensorMapSwizzle, CUtensorMapL2promotion, CUtensorMapFloatOOBfill);

void encode(EncodeFn fn, CUtensorMap* m, CUtensorMapDataType dt, int rank, const void* ptr, const cuuint64_t* dims, const cuuint64_t* strides,
            const cuuint32_t* box, CUtensorMapSwizzle sw, CUtensorMapL2promotion promo = CU_TENSOR_MAP_L2_PROMOTION_L2_128B) {
    const cuuint32_t es[5] = {1, 1, 1, 1, 1};
    fn(m, dt, rank, (void*)ptr, dims, strides, box, es, CU_TENSOR_MAP_INTERLEAVE_NONE, sw, promo, CU_TENSOR_MAP_FLOAT_OOB_FILL_NONE);
}

}

extern "C" void kernel_launch(void* const* d_in, const int* in_sizes, int n_in, void* d_out, int out_size) {
    (void)in_sizes; (void)n_in; (void)out_size;
    Params p;
    p.x = (const uint16_t*)d_in[0]; p.wr = (const uint16_t*)d_in[1]; p.wi = (const uint16_t*)d_in[2];
    p.w1 = (const uint16_t*)d_in[4]; p.b1 = (const uint16_t*)d_in[5]; p.w2 = (const uint16_t*)d_in[6]; p.b2 = (const uint16_t*)d_in[7];
    p.c = (const uint16_t*)d_in[8]; p.wmod = (const uint16_t*)d_in[9]; p.out = (uint16_t*)d_out;

    void* fnp = nullptr; cudaDriverEntryPointQueryResult qr;
    cudaGetDriverEntryPoint("cuTensorMapEncodeTiled", &fnp, cudaEnableDefault, &qr);
    EncodeFn fn = (EncodeFn)fnp;
    cudaGetSymbolAddress((void**)&p.scr, g_scr); cudaGetSymbolAddress((void**)&p.tab, g_tab);
    void* h3p = p.scr->h3;
    CUtensorMap tw1a, tw1b, tw2, th3a, th3b, twr, twi, twm, tt, ttx, to, th3s, tws;
    {
        const cuuint64_t dims[4] = {64, 16, 128, 72}, st[3] = {128ull * F_ * 2, (cuuint64_t)F_ * 2, 128};
        const cuuint32_t ba[4] = {64, 16, 4, 2}, bb[4] = {64, 16, 8, 1};
        encode(fn, &tw1a, CU_TENSOR_MAP_DATA_TYPE_BFLOAT16, 4, p.w1, dims, st, ba, CU_TENSOR_MAP_SWIZZLE_128B);
        encode(fn, &tw1b, CU_TENSOR_MAP_DATA_TYPE_BFLOAT16, 4, p.w1, dims, st, bb, CU_TENSOR_MAP_SWIZZLE_128B);
    }
    {
        const cuuint64_t dims[3] = {64, F_, 32}, st[2] = {(cuuint64_t)S_ * 2, 128};
        const cuuint32_t bx[3] = {64, 64, 2};
        encode(fn, &tw2, CU_TENSOR_MAP_DATA_TYPE_BFLOAT16, 3, p.w2, dims, st, bx, CU_TENSOR_MAP_SWIZZLE_128B);
    }
    {
        const cuuint64_t dims[3] = {64, 72, 128}, st[2] = {256, 18432};
        const cuuint32_t ba[3] = {64, 18, 4}, bb[3] = {64, 9, 8};
        encode(fn, &th3a, CU_TENSOR_MAP_DATA_TYPE_UINT32, 3, h3p, dims, st, ba, CU_TENSOR_MAP_SWIZZLE_NONE);
        encode(fn, &th3b, CU_TENSOR_MAP_DATA_TYPE_UINT32, 3, h3p, dims, st, bb, CU_TENSOR_MAP_SWIZZLE_NONE);
    }
    {
        const cuuint64_t dims[4] = {32, 72, 2, 128}, st[3] = {256, 128, 18432};
        const cuuint32_t bx[4] = {32, 72, 2, 1};
        encode(fn, &th3s, CU_TENSOR_MAP_DATA_TYPE_UINT32, 4, h3p, dims, st, bx, CU_TENSOR_MAP_SWIZZLE_128B, CU_TENSOR_MAP_L2_PROMOTION_NONE);
    }
    {
        const cuuint64_t dims[3] = {4624, 4, 32}, st[2] = {9248 * 32, 9248};
        const cuuint32_t bx[3] = {56, 4, 32};
        encode(fn, &twr, CU_TENSOR_MAP_DATA_TYPE_BFLOAT16, 3, p.wr, dims, st, bx, CU_TENSOR_MAP_SWIZZLE_NONE);
        encode(fn, &twi, CU_TENSOR_MAP_DATA_TYPE_BFLOAT16, 3, p.wi, dims, st, bx, CU_TENSOR_MAP_SWIZZLE_NONE);
    }
    {
        const cuuint64_t dims[2] = {3456, 576}, st[1] = {6912};
        const cuuint32_t bx[2] = {32, 144};
        encode(fn, &tws, CU_TENSOR_MAP_DATA_TYPE_BFLOAT16, 2, p.wmod, dims, st, bx, CU_TENSOR_MAP_SWIZZLE_64B);
    }
    {
        const cuuint64_t dims[3] = {64, 576, 54}, st[2] = {6912, 128};
        const cuuint32_t bx[3] = {64, 32, 7};
        encode(fn, &twm, CU_TENSOR_MAP_DATA_TYPE_BFLOAT16, 3, p.wmod, dims, st, bx, CU_TENSOR_MAP_SWIZZLE_128B);
    }
    {
        const cuuint64_t dims[2] = {TP, 128}, st[1] = {TP * 4};
        const cuuint32_t ba[2] = {32, 128}, bb[2] = {8, 128};
        encode(fn, &tt, CU_TENSOR_MAP_DATA_TYPE_UINT32, 2, p.scr->T, dims, st, ba, CU_TENSOR_MAP_SWIZZLE_128B, CU_TENSOR_MAP_L2_PROMOTION_NONE);
        encode(fn, &ttx, CU_TENSOR_MAP_DATA_TYPE_UINT32, 2, p.scr->T, dims, st, bb, CU_TENSOR_MAP_SWIZZLE_32B, CU_TENSOR_MAP_L2_PROMOTION_NONE);
    }
    {
        const cuuint64_t dims[2] = {D_, S_}, st[1] = {D_ * 2};
        const cuuint32_t bx[2] = {144, 16};
        encode(fn, &to, CU_TENSOR_MAP_DATA_TYPE_BFLOAT16, 2, p.out, dims, st, bx, CU_TENSOR_MAP_SWIZZLE_NONE, CU_TENSOR_MAP_L2_PROMOTION_NONE);
    }
    cudaFuncSetAttribute(fused_kernel, cudaFuncAttributeMaxDynamicSharedMemorySize, SMEM_BYTES);
    cudaLaunchConfig_t cfg = {};
    cfg.gridDim = dim3(NCTA); cfg.blockDim = dim3(NTHR); cfg.dynamicSmemBytes = SMEM_BYTES; cfg.stream = cudaStreamPerThread;
    cudaLaunchAttribute at[1];
    at[0].id = cudaLaunchAttributeCooperative; at[0].val.cooperative = 1;
    cfg.attrs = at; cfg.numAttrs = 1;
    cudaLaunchKernelEx(&cfg, fused_kernel, p, tw1a, tw1b, tw2, th3a, th3b, twr, twi, twm, tt, ttx, to, th3s, tws);
}
```

```cpp
#include <cuda_runtime.h>
#include <cuda_bf16.h>
#include <cuda_fp16.h>
#include <cuda.h>
#include <stdint.h>

namespace {

constexpr int S_ = 2048, D_ = 576, F_ = 4608;
constexpr int NCTA = 132, NTHR = 512;
constexpr int TP = 4736;
constexpr int SPEC_P = 296;
constexpr int NST = 6;
constexpr int A_BYTES = 16384, B_BYTES = 18432;
constexpr int IT_P1 = 24, IT_G2 = 40, IT_END = 76;
constexpr int SPIN_LIMIT = 1 << 22;
#define X2D 1350
constexpr int P2S = 2;
#define LEAD1 4
#define W1N 8
#define W1P 100
#define W1S 5
#define XDELAY 900
#define HOK 2
#define HOK1 2
#define NCP 10800
#define SLP 64
#define FAP 0
#define CRITPF 1
#define NCD 0
#define X1D 2100
#define PF0 4
#define PFS 3
#define PFN 9
#define X1DELAY 2000
#define X1PACE 400

constexpr int OFF_A = 0;
constexpr int OFF_B = NST * A_BYTES;
constexpr int OFF_P = OFF_B + NST * B_BYTES;
constexpr int OFF_BAR = OFF_P;
constexpr int OFF_MISC = OFF_P + 504;
constexpr int OFF_GB = OFF_P + 512;
constexpr int OFF_P2R = OFF_P + 1664;
constexpr int OFF_X1 = OFF_P2R;
constexpr int OFF_PROF = OFF_X1 + 18432;
constexpr int SMEM_BYTES = OFF_PROF + 512 + 1024;
constexpr int QA = 13, QB = 7, QC = 13;
constexpr int TAB_BYTES = (QA + QB + QC) * 512;
constexpr int OFF_STAGE = OFF_B;
constexpr int OFF_STX = OFF_STAGE + 16384;
constexpr int OFF_TAB = OFF_STAGE + 20480;
constexpr int OFF_SPEC = OFF_TAB + TAB_BYTES;
constexpr int OFF_WRAW = OFF_SPEC + 19072;
constexpr int OFF_B3 = OFF_WRAW + 28672;
constexpr int OFF_MODA = OFF_B3 + 4096;
constexpr int OFF_MODC = OFF_MODA + 2560;
constexpr int OFF_RED = OFF_MODC + 3584;
constexpr int OFF_SILU = OFF_RED + 1536;
static_assert(OFF_SILU + 1152 <= OFF_P && 6 * 28672 <= OFF_B3, "scratch overflow");
constexpr int OFF_STRIP = OFF_A;
static_assert(OFF_WRAW % 128 == 0 && OFF_STAGE % 128 == 0 && OFF_STX % 128 == 0, "align");
constexpr int BAR_FULL = 0, BAR_EMPTY = 6, BAR_TAB = 12, BAR_W = 13, BAR_P2R = 16,
              BAR_XT = 17, BAR_RECV = 18, BAR_ROLE = 19, BAR_NC = 20, BAR_TAB2 = 21, BAR_XB = 22, BAR_GB = 23, BAR_HOLD = 24, BAR_W1GO = 25, BAR_UOK = 26, BAR_DONE = 30, BAR_X = 31, BAR_ST = 47;

struct Cos1152 { double c[1152]; };
constexpr double cx_cos(double x) { double t = 1, s = 1; for (int i = 1; i < 14; i++) { t *= -x * x / ((2 * i - 1) * (2 * i)); s += t; } return s; }
constexpr Cos1152 make_cos() {
    Cos1152 r{};
    for (int i = 0; i <= 288; i++) {
        double v = (i == 288) ? 0.0 : cx_cos(3.14159265358979323846 * 2.0 * i / 1152.0);
        r.c[i] = v; r.c[576 - i] = -v; r.c[576 + i] = -v; r.c[(1152 - i) % 1152] = v;
    }
    return r;
}
constexpr uint32_t cx_f2h(double v) {
    uint32_t s = v < 0 ? 0x8000u : 0u; double a = v < 0 ? -v : v;
    if (a < 1e-9) return 0;
    int e = 0;
    while (a >= 2.0) { a *= 0.5; e++; }
    while (a < 1.0 && e > -14) { a *= 2.0; e--; }
    double m = a * 1024.0; uint32_t mi = (uint32_t)m; double fr = m - mi;
    if (fr > 0.5 || (fr == 0.5 && (mi & 1))) mi++;
    return s | (uint32_t)(((e + 14) << 10) + mi);
}
struct Tab { uint32_t w[(QA + QB + QC) * 128]; };
constexpr Tab make_tab() {
    Tab t{};
    Cos1152 ct = make_cos();
    auto C = [&](int num, int den) { return ct.c[(num % den) * (1152 / den)]; };
    auto Sn = [&](int num, int den) { return ct.c[((num % den) * (1152 / den) + 864) % 1152]; };
    auto put = [&](int q0, int idx, int lane, double lo, double hi) { t.w[((q0 + idx / 4) * 32 + lane) * 4 + idx % 4] = cx_f2h(lo) | (cx_f2h(hi) << 16); };
    for (int lane = 0; lane < 32; lane++) {
        const int g = lane >> 2, q = lane & 3;
        for (int mt = 0; mt < 3; mt++) {
            const int ka = 8 * mt + g;
            for (int r = 0; r < 10; r++) {
                const int im = r & 1, i0 = (r >> 1) * 2;
                double v[2] = {0, 0};
                for (int e = 0; e < 2; e++) { int i = i0 + e, d1 = 4 * i + q; if (i < 9 && ka <= 18) v[e] = (im ? -Sn(ka * d1, 36) : C(ka * d1, 36)) / 8; }
                put(0, r < 8 ? mt * 8 + r : 16 + 2 * mt + r, lane, v[0], v[1]);
            }
            for (int v = 0; v < 2; v++) {
                const int d2 = 4 * q + v;
                put(0, 30 + (mt * 2 + v) * 2, lane, C(ka * d2, 576) * 4 / 3, C(ka * (d2 + 2), 576) * 4 / 3);
                put(0, 31 + (mt * 2 + v) * 2, lane, Sn(ka * d2, 576) * 4 / 3, Sn(ka * (d2 + 2), 576) * 4 / 3);
            }
        }
        for (int v = 0; v < 2; v++) for (int nt = 0; nt < 2; nt++) {
            const int kb = 2 * (g >> 1) + nt, part = g & 1;
            double b0[2] = {0, 0}, b1[2] = {0, 0};
            for (int e = 0; e < 2; e++) { int d2 = 4 * q + 2 * e + v; double c = C(kb * d2, 16) / 4, s = Sn(kb * d2, 16) / 4;
                b0[e] = part ? -s : c; b1[e] = part ? c : s; }
            put(0, 42 + (v * 2 + nt) * 2, lane, b0[0], b0[1]); put(0, 43 + (v * 2 + nt) * 2, lane, b1[0], b1[1]);
        }
        t.w[((QA - 1) * 32 + lane) * 4 + 2] = 0x3F803F80u;
        for (int par = 0; par < 2; par++) for (int a = 0; a < 4; a++) {
            const int ja = 2 * (q + 4 * (a >> 1)) + par; const double c = C(g * ja, 16) / 4, s = Sn(g * ja, 16) / 4;
            put(QA, par * 4 + a, lane, (a & 1) ? -s : c, (a & 1) ? c : s);
        }
        for (int h = 0; h < 2; h++) {
            put(QA, 8 + 2 * h, lane, C((g + 8 * h) * (2 * q), 128) / 2, C((g + 8 * h) * (2 * q + 1), 128) / 2);
            put(QA, 9 + 2 * h, lane, Sn((g + 8 * h) * (2 * q), 128) / 2, Sn((g + 8 * h) * (2 * q + 1), 128) / 2);
            put(QA, 16 + 2 * h, lane, C(g * (8 * h + 2 * q), 128), C(g * (8 * h + 2 * q + 1), 128));
            put(QA, 17 + 2 * h, lane, Sn(g * (8 * h + 2 * q), 128), Sn(g * (8 * h + 2 * q + 1), 128));
        }
        put(QA, 12, lane, C(g * 2 * q, 8) / 2, C(g * (2 * q + 1), 8) / 2);
        put(QA, 15, lane, C(g * 2 * q, 8) / 2, C(g * (2 * q + 1), 8) / 2);
        put(QA, 13, lane, Sn(g * 2 * q, 8) / 2, Sn(g * (2 * q + 1), 8) / 2);
        put(QA, 14, lane, -Sn(g * 2 * q, 8) / 2, -Sn(g * (2 * q + 1), 8) / 2);
        for (int u = 0; u < 4; u++) {
            const int ja = 2 * ((g >> 1) + 4 * (u & 1)) + (u >> 1), part = g & 1; double b0[2] = {0, 0}, b1[2] = {0, 0};
            for (int e = 0; e < 2; e++) { int ka = 2 * q + e; double c = C(ja * ka, 16) / 4, s = Sn(ja * ka, 16) / 4;
                b0[e] = part ? s : c; b1[e] = part ? c : -s; }
            put(QA, 20 + u * 2, lane, b0[0], b0[1]); put(QA, 21 + u * 2, lane, b1[0], b1[1]);
        }
        for (int m2 = 0; m2 < 2; m2++) {
            const int d2 = 2 * g + m2;
            for (int a = 0; a < 4; a++) {
                const int kb = 2 * q + (a >> 1); const double c = C(d2 * kb, 16) / 4, s = Sn(d2 * kb, 16) / 4;
                put(QA + QB, m2 * 4 + a, lane, (a & 1) ? s : c, (a & 1) ? c : -s);
            }
            for (int mt = 0; mt < 3; mt++) {
                const int ka = 8 * mt + 2 * q;
                put(QA + QB, 8 + (m2 * 3 + mt) * 2, lane, C(ka * d2, 576) * 4 / 3, C((ka + 1) * d2, 576) * 4 / 3);
                put(QA + QB, 9 + (m2 * 3 + mt) * 2, lane, Sn(ka * d2, 576) * 4 / 3, Sn((ka + 1) * d2, 576) * 4 / 3);
            }
        }
        for (int mt = 0; mt < 3; mt++) for (int nt = 0; nt < 5; nt++) {
            const int i = 2 * nt + (g & 1), d1 = 4 * i + (g >> 1); double b0[2] = {0, 0}, b1[2] = {0, 0};
            for (int e = 0; e < 2; e++) { int ka = 8 * mt + 2 * q + e;
                if (ka <= 18 && i < 9) { double wt = (ka == 0 || ka == 18) ? 0.125 : 0.25; b0[e] = wt * C(ka * d1, 36); b1[e] = -wt * Sn(ka * d1, 36); } }
            const int o = (QA + QB + 5) * 128 + (mt * 5 + nt) * 64 + lane;
            t.w[o] = cx_f2h(b0[0]) | (cx_f2h(b0[1]) << 16); t.w[o + 32] = cx_f2h(b1[0]) | (cx_f2h(b1[1]) << 16);
        }
    }
    return t;
}
__device__ __align__(128) const Tab g_tab = make_tab();

struct Scratch {
    uint32_t cnt[30 * 32];
    uint32_t slot[96];
    uint32_t mod[2304];
    uint32_t modc[896 + 288];
    uint32_t T[128 * TP];
    uint4 h3[128 * 1152];
    uint4 U[72 * 4 * 1152];
};
__device__ __align__(1024) Scratch g_scr;
#define g_cnt (p.scr->cnt)
#define g_slot (p.scr->slot)
#define g_mod (p.scr->mod)
#define g_T (p.scr->T)
#define g_h3 (p.scr->h3)
#define g_U (p.scr->U)
constexpr int CNT_EPOCH = 0, CNT_H3 = 1, CNT_X1 = 26, CNT_NC = 27, CNT_U = 2;
#define PROFT(i) do {} while (0)
#define PROFDUMP() do {} while (0)
#define PROF0(i) do {} while (0)

__device__ __forceinline__ void mbar_init(uint32_t bar, uint32_t cnt) { asm volatile("mbarrier.init.shared::cta.b64 [%0], %1;" :: "r"(bar), "r"(cnt) : "memory"); }
__device__ __forceinline__ void mbar_expect(uint32_t bar, uint32_t bytes) { asm volatile("mbarrier.arrive.expect_tx.shared::cta.b64 _, [%0], %1;" :: "r"(bar), "r"(bytes) : "memory"); }
__device__ __forceinline__ void mbar_arrive(uint32_t bar) { asm volatile("mbarrier.arrive.shared::cta.b64 _, [%0];" :: "r"(bar) : "memory"); }
__device__ __forceinline__ void mbar_arrive_n(uint32_t bar, uint32_t n) { asm volatile("mbarrier.arrive.shared::cta.b64 _, [%0], %1;" :: "r"(bar), "r"(n) : "memory"); }
__device__ __forceinline__ void mbar_arrive_remote(uint32_t rbar) { asm volatile("mbarrier.arrive.relaxed.cluster.shared::cluster.b64 _, [%0];" :: "r"(rbar) : "memory"); }
__device__ __forceinline__ void mbar_wait(uint32_t bar, uint32_t parity) {
    asm volatile("{.reg .pred p; .reg .u32 c;\n"
        "mbarrier.try_wait.parity.shared::cta.b64 p, [%0], %1;\n@p bra.uni DONE;\nmov.u32 c, 0;\n"
        "LOOP: mbarrier.try_wait.parity.shared::cta.b64 p, [%0], %1;\n@p bra.uni DONE;\n"
        "add.u32 c, c, 1;\nsetp.lt.u32 p, c, %2;\n@p bra.uni LOOP;\ntrap;\nDONE:}" :: "r"(bar), "r"(parity), "n"(SPIN_LIMIT) : "memory");
}
__device__ __forceinline__ bool mbar_test(uint32_t bar, uint32_t parity) {
    uint32_t ok; asm volatile("{.reg .pred p; mbarrier.test_wait.parity.shared::cta.b64 p, [%1], %2; selp.u32 %0, 1, 0, p;}" : "=r"(ok) : "r"(bar), "r"(parity) : "memory"); return ok; }
__device__ __forceinline__ uint32_t mapa(uint32_t a, uint32_t rank) { uint32_t r; asm("mapa.shared::cluster.u32 %0, %1, %2;" : "=r"(r) : "r"(a), "r"(rank)); return r; }
__device__ __forceinline__ uint32_t clk32() { uint32_t r; asm volatile("mov.u32 %0, %%clock;" : "=r"(r)); return r; }
__device__ __forceinline__ void hb() {
    asm volatile("{.reg .b32 a, b; .reg .pred p; mma.sync.aligned.m16n8k8.row.col.f16.f16.f16.f16 {a, b}, {%0,%0}, {%0}, {%0,%0};\n"
                 "setp.ne.u32 p, a, 0; @p trap;}" :: "r"(0));
}
__device__ __forceinline__ void spin_until(uint32_t t) {
    while (__any_sync(~0u, (int)(clk32() - t) < -SLP * 4)) { __nanosleep(SLP); hb(); }
    while (__any_sync(~0u, (int)(clk32() - t) < 0)) {}
}
__device__ __forceinline__ bool elect() { uint32_t r; asm volatile("{.reg .pred p; elect.sync _|p, 0xffffffff; selp.u32 %0, 1, 0, p;}" : "=r"(r)); return r; }
__device__ __forceinline__ void bar_sync(int id, int n) { asm volatile("bar.sync %0, %1;" :: "r"(id), "r"(n) : "memory"); }
__device__ __forceinline__ void bulk_load(uint32_t dst, const void* src, uint32_t bytes, uint32_t bar) {
    asm volatile("cp.async.bulk.shared::cluster.global.mbarrier::complete_tx::bytes [%0], [%1], %2, [%3];" :: "r"(dst), "l"(src), "r"(bytes), "r"(bar) : "memory"); }
__device__ __forceinline__ void tma2(uint32_t dst, const CUtensorMap* m, int c0, int c1, uint32_t bar) {
    asm volatile("cp.async.bulk.tensor.2d.shared::cluster.global.mbarrier::complete_tx::bytes [%0], [%1, {%3, %4}], [%2];" :: "r"(dst), "l"(m), "r"(bar), "r"(c0), "r"(c1) : "memory"); }
__device__ __forceinline__ void tma3(uint32_t dst, const CUtensorMap* m, int c0, int c1, int c2, uint32_t bar) {
    asm volatile("cp.async.bulk.tensor.3d.shared::cluster.global.mbarrier::complete_tx::bytes [%0], [%1, {%3, %4, %5}], [%2];" :: "r"(dst), "l"(m), "r"(bar), "r"(c0), "r"(c1), "r"(c2) : "memory"); }
__device__ __forceinline__ void tma4(uint32_t dst, const CUtensorMap* m, int c0, int c1, int c2, int c3, uint32_t bar) {
    asm volatile("cp.async.bulk.tensor.4d.shared::cluster.global.mbarrier::complete_tx::bytes [%0], [%1, {%3, %4, %5, %6}], [%2];" :: "r"(dst), "l"(m), "r"(bar), "r"(c0), "r"(c1), "r"(c2), "r"(c3) : "memory"); }
__device__ __forceinline__ void fence_async_g() { asm volatile("fence.proxy.async.global;" ::: "memory"); }
__device__ __forceinline__ void fence_async_s() { asm volatile("fence.proxy.async.shared::cta;" ::: "memory"); }
__device__ __forceinline__ uint4 lds128(uint32_t a) { uint4 v; asm volatile("ld.shared.v4.u32 {%0,%1,%2,%3}, [%4];" : "=r"(v.x), "=r"(v.y), "=r"(v.z), "=r"(v.w) : "r"(a) : "memory"); return v; }
__device__ __forceinline__ uint32_t lds32(uint32_t a) { uint32_t v; asm volatile("ld.shared.u32 %0, [%1];" : "=r"(v) : "r"(a) : "memory"); return v; }
__device__ __forceinline__ void sts128(uint32_t a, uint4 v) { asm volatile("st.shared.v4.u32 [%0], {%1,%2,%3,%4};" :: "r"(a), "r"(v.x), "r"(v.y), "r"(v.z), "r"(v.w) : "memory"); }
__device__ __forceinline__ void sts32(uint32_t a, uint32_t v) { asm volatile("st.shared.u32 [%0], %1;" :: "r"(a), "r"(v) : "memory"); }
__device__ __forceinline__ void sts16(uint32_t a, uint32_t v) { asm volatile("st.shared.u16 [%0], %1;" :: "r"(a), "h"((uint16_t)v) : "memory"); }
__device__ __forceinline__ uint4 ldx128(const void* p) {
    uint4 v; asm volatile("{.reg .b128 t; .reg .b64 a, b; ld.relaxed.gpu.global.b128 t, [%4]; mov.b128 {a, b}, t; mov.b64 {%0,%1}, a; mov.b64 {%2,%3}, b;}"
        : "=r"(v.x), "=r"(v.y), "=r"(v.z), "=r"(v.w) : "l"(p) : "memory"); return v; }
__device__ __forceinline__ void stx128(void* p, uint4 v) {
    asm volatile("{.reg .b128 t; .reg .b64 a, b; mov.b64 a, {%1,%2}; mov.b64 b, {%3,%4}; mov.b128 t, {a, b}; st.relaxed.gpu.global.b128 [%0], t;}"
        :: "l"(p), "r"(v.x), "r"(v.y), "r"(v.z), "r"(v.w) : "memory"); }
__device__ __forceinline__ uint32_t ld_relaxed(const uint32_t* p) { uint32_t v; asm volatile("ld.relaxed.gpu.global.u32 %0, [%1];" : "=r"(v) : "l"(p) : "memory"); return v; }
__device__ __forceinline__ uint32_t ld_acquire(const uint32_t* p) { uint32_t v; asm volatile("ld.acquire.gpu.global.u32 %0, [%1];" : "=r"(v) : "l"(p) : "memory"); return v; }
__device__ __forceinline__ void st_relaxed(uint32_t* p, uint32_t v) { asm volatile("st.relaxed.gpu.global.u32 [%0], %1;" :: "l"(p), "r"(v) : "memory"); }
__device__ __forceinline__ void red_release(uint32_t* p) { asm volatile("red.release.gpu.global.add.u32 [%0], 1;" :: "l"(p) : "memory"); }
template <int SLEEP> __device__ __forceinline__ void wait_count(const uint32_t* p, uint32_t target) {
    int it = 0; while ((int)(ld_acquire(p) - target) < 0) { if (SLEEP) __nanosleep(SLEEP); if (++it > SPIN_LIMIT) __trap(); }
}
__device__ __forceinline__ uint32_t ldg_nc32(const void* p) { uint32_t v; asm volatile("ld.global.nc.L1::no_allocate.u32 %0, [%1];" : "=r"(v) : "l"(p)); return v; }
__device__ __forceinline__ uint32_t ldg_nc16(const void* p) { uint16_t v; asm volatile("ld.global.nc.u16 %0, [%1];" : "=h"(v) : "l"(p)); return v; }
__device__ __forceinline__ float bf_lo(uint32_t w) { return __uint_as_float(w << 16); }
__device__ __forceinline__ float bf_hi(uint32_t w) { return __uint_as_float(w & 0xFFFF0000u); }
__device__ __forceinline__ uint32_t pack_bf(float lo, float hi) { uint32_t r; asm("cvt.rn.bf16x2.f32 %0, %1, %2;" : "=r"(r) : "f"(hi), "f"(lo)); return r; }
__device__ __forceinline__ uint32_t pack_h(float lo, float hi) { uint32_t r; asm("cvt.rn.f16x2.f32 %0, %1, %2;" : "=r"(r) : "f"(hi), "f"(lo)); return r; }
__device__ __forceinline__ float bf_round(float v) { return bf_lo(pack_bf(v, 0.f)); }
__device__ __forceinline__ uint32_t hmul2(uint32_t a, uint32_t b) { uint32_t r; asm("mul.rn.f16x2 %0, %1, %2;" : "=r"(r) : "r"(a), "r"(b)); return r; }
__device__ __forceinline__ uint32_t hfma2(uint32_t a, uint32_t b, uint32_t c) { uint32_t r; asm("fma.rn.f16x2 %0, %1, %2, %3;" : "=r"(r) : "r"(a), "r"(b), "r"(c)); return r; }
__device__ __forceinline__ uint32_t hfms2(uint32_t a, uint32_t b, uint32_t c) { uint32_t r; asm("{.reg .b32 t; neg.f16x2 t, %3; fma.rn.f16x2 %0, %1, %2, t;}" : "=r"(r) : "r"(a), "r"(b), "r"(c)); return r; }
__device__ __forceinline__ uint32_t hadd2(uint32_t a, uint32_t b) { uint32_t r; asm("add.rn.f16x2 %0, %1, %2;" : "=r"(r) : "r"(a), "r"(b)); return r; }
__device__ __forceinline__ uint32_t hsub2(uint32_t a, uint32_t b) { uint32_t r; asm("sub.rn.f16x2 %0, %1, %2;" : "=r"(r) : "r"(a), "r"(b)); return r; }
__device__ __forceinline__ void cmul_neg(uint32_t& re, uint32_t& im, uint32_t c, uint32_t s) { uint32_t a = hfma2(re, c, hmul2(im, s)), b = hfms2(im, c, hmul2(re, s)); re = a; im = b; }
__device__ __forceinline__ void cmul_pos(uint32_t& re, uint32_t& im, uint32_t c, uint32_t s) { uint32_t a = hfms2(re, c, hmul2(im, s)), b = hfma2(im, c, hmul2(re, s)); re = a; im = b; }
__device__ __forceinline__ void mma_h(uint32_t& d0, uint32_t& d1, uint32_t a0, uint32_t a1, uint32_t a2, uint32_t a3, uint32_t b0, uint32_t b1) {
    asm("mma.sync.aligned.m16n8k16.row.col.f16.f16.f16.f16 {%0,%1}, {%2,%3,%4,%5}, {%6,%7}, {%0,%1};" : "+r"(d0), "+r"(d1) : "r"(a0), "r"(a1), "r"(a2), "r"(a3), "r"(b0), "r"(b1)); }
__device__ __forceinline__ void mma_h8(uint32_t& d0, uint32_t& d1, uint32_t a0, uint32_t a1, uint32_t b0) {
    asm("mma.sync.aligned.m16n8k8.row.col.f16.f16.f16.f16 {%0,%1}, {%2,%3}, {%4}, {%0,%1};" : "+r"(d0), "+r"(d1) : "r"(a0), "r"(a1), "r"(b0)); }
template <int NQ> __device__ __forceinline__ void load_tab(uint32_t (&r)[NQ * 4], uint32_t addr) {
    #pragma unroll
    for (int i = 0; i < NQ; i++) { uint4 v = lds128(addr + i * 512); r[4 * i] = v.x; r[4 * i + 1] = v.y; r[4 * i + 2] = v.z; r[4 * i + 3] = v.w; }
}
__device__ __forceinline__ float gelu2(float x) {
    float t = x * fmaf(x * x, 0.044715f * 0.7978845608028654f, 0.7978845608028654f), th;
    asm volatile("tanh.approx.f32 %0, %1;" : "=f"(th) : "f"(t));
    return fmaf(x, th, x);
}
__device__ __forceinline__ uint32_t desc_lo(uint32_t addr, uint32_t lbo) { return ((addr & 0x3FFFF) >> 4) | ((lbo >> 4) << 16); }
constexpr uint32_t DHI_A = (1024 >> 4) | (1u << 30), DHI_H3 = 256 >> 4, DHI_U = 128 >> 4;
#define WG_FENCE() asm volatile("wgmma.fence.sync.aligned;" ::: "memory")
#define WG_COMMIT() asm volatile("wgmma.commit_group.sync.aligned;" ::: "memory")
#define WG_WAIT(n) asm volatile("wgmma.wait_group.sync.aligned %0;" :: "n"(n) : "memory")
#define R4(b) "+f"(d[b]), "+f"(d[b + 1]), "+f"(d[b + 2]), "+f"(d[b + 3])
#define R12(b) R4(b), R4(b + 4), R4(b + 8)
#define R36(b) R12(b), R12(b + 12), R12(b + 24)
template <uint32_t BHI> __device__ __forceinline__ void wgmma144(float (&d)[72], uint32_t da, uint32_t db, int acc) {
    asm volatile("{.reg .pred p; .reg .b64 a, b; setp.ne.b32 p, %74, 0; mov.b64 a, {%72, %75}; mov.b64 b, {%73, %76};\n"
        "wgmma.mma_async.sync.aligned.m64n144k16.f32.bf16.bf16 {%0,%1,%2,%3,%4,%5,%6,%7,%8,%9,%10,%11,%12,%13,%14,%15,%16,%17,%18,%19,%20,%21,%22,%23,"
        "%24,%25,%26,%27,%28,%29,%30,%31,%32,%33,%34,%35,%36,%37,%38,%39,%40,%41,%42,%43,%44,%45,%46,%47,"
        "%48,%49,%50,%51,%52,%53,%54,%55,%56,%57,%58,%59,%60,%61,%62,%63,%64,%65,%66,%67,%68,%69,%70,%71}, a, b, p, 1, 1, 1, 1;}\n"
        : R36(0), R36(36) : "r"(da), "r"(db), "r"(acc), "n"(DHI_A), "n"(BHI));
}
__device__ __forceinline__ void wgmma144x4(float (&d)[72], const uint64_t (&a)[4], const uint64_t (&b)[4]) {
    #define WG144 "wgmma.mma_async.sync.aligned.m64n144k16.f32.bf16.bf16 {%0,%1,%2,%3,%4,%5,%6,%7,%8,%9,%10,%11,%12,%13,%14,%15,%16,%17,%18,%19,%20,%21,%22,%23,%24,%25,%26,%27,%28,%29,%30,%31,%32,%33,%34,%35,%36,%37,%38,%39,%40,%41,%42,%43,%44,%45,%46,%47,%48,%49,%50,%51,%52,%53,%54,%55,%56,%57,%58,%59,%60,%61,%62,%63,%64,%65,%66,%67,%68,%69,%70,%71}, "
    asm volatile("{"
        WG144 "%72, %76, 1, 1, 1, 1, 1;\n" WG144 "%73, %77, 1, 1, 1, 1, 1;\n" WG144 "%74, %78, 1, 1, 1, 1, 1;\n" WG144 "%75, %79, 1, 1, 1, 1, 1;}\n"
        : R36(0), R36(36) : "l"(a[0]), "l"(a[1]), "l"(a[2]), "l"(a[3]), "l"(b[0]), "l"(b[1]), "l"(b[2]), "l"(b[3]));
}
__device__ __forceinline__ void wgmma40_rs(float (&d)[20], uint32_t a0, uint32_t a1, uint32_t a2, uint32_t a3, uint32_t db, int acc) {
    asm volatile("{.reg .pred p; .reg .b64 b; setp.ne.b32 p, %25, 0; mov.b64 b, {%24, %26};\n"
        "wgmma.mma_async.sync.aligned.m64n40k16.f32.f16.f16 {%0,%1,%2,%3,%4,%5,%6,%7,%8,%9,%10,%11,%12,%13,%14,%15,%16,%17,%18,%19}, {%20,%21,%22,%23}, b, p, 1, 1, 0;}\n"
        : R12(0), R4(12), R4(16) : "r"(a0), "r"(a1), "r"(a2), "r"(a3), "r"(db), "r"(acc), "n"(DHI_H3));
}
__device__ __forceinline__ void wgmma72(float (&d)[36], uint32_t da, uint32_t db, int acc) {
    asm volatile("{.reg .pred p; .reg .b64 a, b; setp.ne.b32 p, %38, 0; mov.b64 a, {%36, %39}; mov.b64 b, {%37, %40};\n"
        "wgmma.mma_async.sync.aligned.m64n72k16.f32.bf16.bf16 {%0,%1,%2,%3,%4,%5,%6,%7,%8,%9,%10,%11,%12,%13,%14,%15,%16,%17,%18,%19,%20,%21,%22,%23,"
        "%24,%25,%26,%27,%28,%29,%30,%31,%32,%33,%34,%35}, a, b, p, 1, 1, 1, 1;}\n"
        : R36(0) : "r"(da), "r"(db), "r"(acc), "n"(DHI_A), "n"(DHI_H3));
}

__device__ __forceinline__ int g2_kb(int n, int kh, int gi, int c2) {
    if (n < 4) return 36 * kh + 9 * n + 8;
    if (n == 4) return 9 * gi + 4 * c2 + 2 * kh + 1;
    const int w = n > 20, m = n - (w ? 19 : 5);
    return 9 * ((gi * w + (m >> 1)) & 7) + 4 * (n == 35 ? 1 - c2 : m & 1) + 2 * kh + w;
}

__device__ __forceinline__ void add_lo(uint64_t& d, uint32_t a) { asm("{.reg .b32 l, h; mov.b64 {l, h}, %0; add.u32 l, l, %1; mov.b64 %0, {l, h};}" : "+l"(d) : "r"(a)); }
template <uint32_t BHI, int I0, int I1, bool FIRST, class Hook>
__device__ __forceinline__ void mainloop(float (&d)[72], uint32_t bars, uint32_t da0, uint32_t db0, bool lead, Hook hook) {
    uint32_t s = I0 % NST, ph = (I0 / NST) & 1, prev = (I0 + NST - (I0 == IT_P1 ? 2 : 1)) % NST;
    uint32_t ready = 0;
    uint64_t da[4], db[4];
    #pragma unroll
    for (int k = 0; k < 4; k++) { da[k] = ((uint64_t)DHI_A << 32) + da0 + s * (A_BYTES / 16) + k * 128; db[k] = ((uint64_t)BHI << 32) + db0 + s * (B_BYTES / 16) + k * 288; }
    #pragma unroll 1
    for (int i = I0; i < I1; i++) {
        if (!ready) mbar_wait(bars + 8 * BAR_FULL + 8 * s, ph);
        const uint32_t rel = bars + 8 * BAR_EMPTY + 8 * prev, ph0 = ph; const int i0 = i;
        const bool skip = I1 == IT_P1 && (s == P2S - 1 || s == P2S + 2);
        prev = s; s += skip ? 2 : 1; if (s >= NST) { s -= NST; ph ^= 1; }
        const uint32_t adva = (s - prev) * (A_BYTES / 16), advb = (s - prev) * (B_BYTES / 16);
        WG_FENCE();
        wgmma144x4(d, da, db);
        WG_COMMIT();
        #pragma unroll
        for (int k = 0; k < 4; k++) { add_lo(da[k], adva); add_lo(db[k], advb); }
        if (skip) { mbar_wait(bars + 8 * BAR_FULL + 8 * prev + 8, ph0); i++; }
        ready = __shfl_sync(~0u, (uint32_t)mbar_test(bars + 8 * BAR_FULL + 8 * s, ph), 0);
        WG_WAIT(1);
        if (lead && (!FIRST || i0 > I0)) mbar_arrive(rel);
        hook(i0);
    }
}

struct Params {
    const uint16_t *x, *wr, *wi, *w1, *b1, *w2, *b2, *c, *wmod;
    uint16_t* out;
    Scratch* scr;
    const Tab* tab;
};

__device__ __forceinline__ void mma_bf(float (&d)[4], const uint32_t (&a)[4], uint32_t b0, uint32_t b1) {
    asm("mma.sync.aligned.m16n8k16.row.col.f32.bf16.bf16.f32 {%0,%1,%2,%3}, {%4,%5,%6,%7}, {%8,%9}, {%0,%1,%2,%3};"
        : "+f"(d[0]), "+f"(d[1]), "+f"(d[2]), "+f"(d[3]) : "r"(a[0]), "r"(a[1]), "r"(a[2]), "r"(a[3]), "r"(b0), "r"(b1)); }
__device__ __forceinline__ void ldsm4t(uint32_t (&a)[4], uint32_t addr) {
    asm volatile("ldmatrix.sync.aligned.m8n8.x4.trans.shared.b16 {%0,%1,%2,%3}, [%4];" : "=r"(a[0]), "=r"(a[1]), "=r"(a[2]), "=r"(a[3]) : "r"(addr) : "memory"); }
__device__ __forceinline__ void ln_stats(const uint32_t (&w)[9], const uint32_t (&one)[9], int g, int q, float& r, float& mr) {
    float c[2][4] = {};
    #pragma unroll
    for (int p = 0; p < 9; p++)
        asm("mma.sync.aligned.m16n8k8.row.col.f32.bf16.bf16.f32 {%0,%1,%2,%3}, {%4,%5}, {%4}, {%0,%1,%2,%3};"
            : "+f"(c[p & 1][0]), "+f"(c[p & 1][1]), "+f"(c[p & 1][2]), "+f"(c[p & 1][3]) : "r"(w[p]), "r"(one[p]));
    const float t = (g & 1) ? c[0][1] + c[1][1] : c[0][0] + c[1][0];
    float s1 = (c[0][2] + c[1][2]) + (c[0][3] + c[1][3]), s2 = __shfl_sync(~0u, t, 9 * q) + __shfl_sync(~0u, t, 9 * q + 4);
    #pragma unroll
    for (int o = 1; o < 4; o <<= 1) { s1 += __shfl_xor_sync(~0u, s1, o); s2 += __shfl_xor_sync(~0u, s2, o); }
    const float m = s1 * (1.f / D_);
    asm("rsqrt.approx.ftz.f32 %0, %1;" : "=f"(r) : "f"(fmaxf(fmaf(s2, 1.f / D_, -m * m), 0.f) + 1e-5f));
    mr = -m * r;
}
__device__ __forceinline__ float silu(float v) { return __fdividef(v, 1.f + __expf(-v)); }
__device__ __forceinline__ uint32_t bfma2(uint32_t a, uint32_t b, uint32_t c) { uint32_t r; asm("fma.rn.bf16x2 %0, %1, %2, %3;" : "=r"(r) : "r"(a), "r"(b), "r"(c)); return r; }
__device__ __forceinline__ void radix16(const uint4 (&V)[4], const uint32_t (&B)[16], uint4 (&o)[4]) {
    #pragma unroll
    for (int nt = 0; nt < 4; nt++) o[nt] = make_uint4(0, 0, 0, 0);
    #pragma unroll
    for (int u = 0; u < 4; u++)
        #pragma unroll
        for (int nt = 0; nt < 4; nt++) {
            const uint32_t b = B[((u >> 1) * 4 + nt) * 2 + (u & 1)];
            mma_h8(o[nt].x, o[nt].y, V[u].x, V[u].y, b); mma_h8(o[nt].z, o[nt].w, V[u].z, V[u].w, b);
        }
}
template <int OFF, int N> __device__ __forceinline__ void gelu_store(const float (&d)[N], char* p, int q) {
    uint32_t w[9];
    #pragma unroll
    for (int blk = 0; blk < 9; blk++) w[blk] = pack_bf(gelu2(d[OFF + 4 * blk]), gelu2(d[OFF + 4 * blk + 1]));
    asm volatile("st.v4.u32 [%0], {%1,%2,%3,%4};" :: "l"(p + q * 128), "r"(w[0]), "r"(w[1]), "r"(w[2]), "r"(w[3]) : "memory");
    asm volatile("st.v4.u32 [%0+512], {%1,%2,%3,%4};" :: "l"(p + q * 128), "r"(w[4]), "r"(w[5]), "r"(w[6]), "r"(w[7]) : "memory");
    asm volatile("st.u32 [%0+1024], %1;" :: "l"(p + q * 4), "r"(w[8]) : "memory");
}

__global__ void __cluster_dims__(2, 1, 1) __launch_bounds__(NTHR, 1)
fused_kernel(const Params p,
             const __grid_constant__ CUtensorMap tm_w1a, const __grid_constant__ CUtensorMap tm_w1b, const __grid_constant__ CUtensorMap tm_w2,
             const __grid_constant__ CUtensorMap tm_h3a, const __grid_constant__ CUtensorMap tm_h3b,
             const __grid_constant__ CUtensorMap tm_wr, const __grid_constant__ CUtensorMap tm_wi, const __grid_constant__ CUtensorMap tm_wm,
             const __grid_constant__ CUtensorMap tm_t, const __grid_constant__ CUtensorMap tm_tx, const __grid_constant__ CUtensorMap tm_o,
             const __grid_constant__ CUtensorMap tm_h3s, const __grid_constant__ CUtensorMap tm_ws)
{
    extern __shared__ char smem_raw[];
    const uint32_t t0 = clk32();
    const uint32_t sm = __shfl_sync(~0u, ((uint32_t)__cvta_generic_to_shared(smem_raw) + 1023u) & ~1023u, 0);
    const int tid = threadIdx.x, warp = __shfl_sync(~0u, tid >> 5, 0), lane = tid & 31, g = lane >> 2, q = lane & 3;
    const int b = blockIdx.x;
    const uint32_t rank = b & 1;
    const uint32_t bars = sm + OFF_BAR;
    const bool rowcta = b < 128;

    auto nc_issue = [&](int st, uint32_t sl) {
        const int pass = st >= 18;
        mbar_expect(bars + 8 * (BAR_X + sl), 28672);
        tma3(sm + sl * 28672, &tm_wm, 0, 32 * (st - 18 * pass), 18 + 28 * pass + 7 * (b - 128), bars + 8 * (BAR_X + sl));
    };
    uint32_t epoch;
    const bool strip = b < 72 && !(b & 1);
    if (warp < 12) {
        epoch = ld_relaxed(g_cnt + CNT_EPOCH * 32);
        if (warp >= 8 && lane < 24 && (strip || !rowcta)) {
            uint32_t cw[3];
            #pragma unroll
            for (int u = 0; u < 3; u++) cw[u] = ldg_nc32(p.c + 144 * (warp - 8) + 48 * u + 2 * lane);
            #pragma unroll
            for (int u = 0; u < 3; u++) sts32(sm + OFF_SILU + (72 * (warp - 8) + 24 * u + lane) * 4, pack_bf(silu(bf_lo(cw[u])), silu(bf_hi(cw[u]))));
        }
        __syncwarp();
        hb();
        bar_sync(2, 512);
    } else {
        const int w4 = 4 * (warp - 12);
        if (elect()) {
            if (warp == 14 && b < 13) asm volatile("cp.async.bulk.prefetch.L2.global [%0], 512;" :: "l"(p.tab->w + b * 128) : "memory");
            if (strip && warp == 15) asm volatile("prefetch.tensormap [%0];" :: "l"(&tm_ws) : "memory");
            if (CRITPF) {
                asm volatile("cp.async.bulk.prefetch.L2.global [%0], 2304;" :: "l"(p.wmod + (b + 33 * w4) * 3456) : "memory");
                if (warp == 12 && b < 48) asm volatile("cp.async.bulk.prefetch.L2.global [%0], 2304;" :: "l"(p.wmod + (b + 528) * 3456) : "memory");
            }
        }
        if (warp == 13) hb();
        if (elect()) {
            if (rowcta) {
                for (int i = 0; i < 4; i++) mbar_init(bars + 8 * (BAR_X + w4 + i), 1);
                const uint32_t sb = bars + 8 * (BAR_ST + warp - 12);
                mbar_init(sb, 1);
                if (warp == 15) mbar_init(bars + 8 * BAR_TAB, 1);
                fence_async_s();
                if (warp == 15) { mbar_expect(bars + 8 * BAR_TAB, QA * 512); bulk_load(sm + OFF_TAB, p.tab, QA * 512, bars + 8 * BAR_TAB); }
                if (strip) { mbar_expect(sb, 9216); tma2(sm + OFF_STRIP + (warp - 12) * 9216, &tm_ws, 16 * b, 36 * w4, sb); }
            } else if (warp == 12) {
                for (int i = 0; i < 12; i++) mbar_init(bars + 8 * (BAR_X + i), i < 6 ? 1 : 14);
                fence_async_s();
                if (NCD) while ((int)(clk32() - t0) < NCD) {}
                for (int st = 0; st < 6; st++) nc_issue(st, st);
            }
            if (warp == 12) {
                asm volatile("prefetch.tensormap [%0];" :: "l"(&tm_wr) : "memory"); asm volatile("prefetch.tensormap [%0];" :: "l"(&tm_wi) : "memory");
                asm volatile("prefetch.tensormap [%0];" :: "l"(&tm_t) : "memory"); asm volatile("prefetch.tensormap [%0];" :: "l"(&tm_tx) : "memory");
            } else if (warp == 14) {
                for (int i = BAR_W; i < BAR_X; i++) mbar_init(bars + 8 * i, i == BAR_DONE || i == BAR_NC ? 4 : i == BAR_W1GO ? 2 : 1);
                mbar_expect(bars + 8 * BAR_W, 28672); mbar_expect(bars + 8 * BAR_TAB2, (QB + QC) * 512);
                mbar_expect(bars + 8 * BAR_ROLE, 4); mbar_expect(bars + 8 * BAR_P2R, 9216); mbar_expect(bars + 8 * BAR_RECV, 18432); mbar_expect(bars + 8 * BAR_XT, 18432);
            } else if (warp == 13) {
                for (int i = 0; i < 2 * NST; i++) mbar_init(bars + 8 * i, 2);
                for (int i = 0; i < NST; i++) mbar_expect(bars + 8 * (BAR_FULL + i), A_BYTES);
            }
            asm volatile("fence.mbarrier_init.release.cluster;" ::: "memory");
        }
        __syncwarp();
        asm volatile("bar.arrive 2, 512;" ::: "memory");
        if (rowcta && elect()) {
            if (XDELAY) while ((int)(clk32() - t0) < XDELAY) {}
            for (int r = w4; r < w4 + 4; r++) {
                mbar_expect(bars + 8 * (BAR_X + r), 1152);
                bulk_load(sm + OFF_STAGE + r * 1152, p.x + (size_t)(b + 128 * r) * D_, 1152, bars + 8 * (BAR_X + r));
            }
        }
        __syncwarp();
        epoch = ld_relaxed(g_cnt + CNT_EPOCH * 32);
        sts16(sm + OFF_MODA + ((warp - 11) * 32 + lane) * 16 + w4 + 2, 0);
        #pragma unroll 1
        for (int s1 = (tid >> 4) & 7; s1 < 16; s1 += 8) {
            const int k1 = tid & 15;
            float s, c;
            __sincosf((float)(((k1 * (128 * s1 + b) + 1024) & 2047) - 1024) * (3.14159265358979f / 1024.f), &s, &c); s *= 0.25f; c *= 0.25f;
            const int rf = ((s1 >> 3) * 4 + (k1 >> 2)) * 2 + ((s1 >> 2) & 1), ri = ((k1 >> 3) * 4 + (s1 >> 2)) * 2 + ((k1 >> 2) & 1);
            const uint32_t af = sm + OFF_B3 + ((rf >> 2) * 32 + (k1 & 3) * 8 + (s1 & 3)) * 16 + (rf & 3) * 4;
            const uint32_t ai = sm + OFF_B3 + 2048 + ((ri >> 2) * 32 + (s1 & 3) * 8 + (k1 & 3)) * 16 + (ri & 3) * 4;
            sts32(af, pack_h(c, s)); sts32(af + 64, pack_h(-s, c)); sts32(ai, pack_h(c, -s)); sts32(ai + 64, pack_h(s, c));
        }
        hb();
        bar_sync(3, 128);
    }
    asm volatile("barrier.cluster.arrive.relaxed.aligned;" ::: "memory");
    const uint32_t tag = (epoch + 1) & 0xFFFFu;

    const int trow = 4 * (b & 7) + ((b >> 4) & 3) + 64 * ((b >> 3) & 1) + 32 * (b >> 6);
    uint32_t* const tptr = g_T + (size_t)trow * TP + (warp < 9 ? q * 288 + 32 * warp : 4608 + 8 * q) + 4 * g;
    const int tstr = warp < 9 ? 1152 : 32;
    const uint32_t scol = sm + OFF_SPEC + (q * SPEC_P + (warp < 8 ? 72 * (warp >> 1) + 40 * (warp & 1) + 4 * g : warp == 8 ? 72 * (g >> 1) + 32 + 4 * (g & 1) : 288 + 4 * g)) * 4;
    const int wc0 = (b >> 3) * 289 + 72 * ((b & 7) >> 1) + 40 * (b & 1);

    uint32_t xw[9], one[9], t_st = t0;
    if (!rowcta) {
        const int nst = b < 130 ? 36 : 18;
        __syncthreads();
        if (warp == 14) {
            uint32_t sl = 0, ph = 0;
            #pragma unroll 1
            for (int st = 6; st < nst; st++) {
                mbar_wait(bars + 8 * (BAR_X + 6 + sl), ph);
                if (elect()) nc_issue(st, sl);
                if (++sl == 6) { sl = 0; ph ^= 1; }
            }
        } else if (warp < 14) {
            uint32_t sl = 0, ph = 0;
            const uint32_t ad0 = sm + (warp >> 1) * 4096 + ((lane & 7) + 8 * (lane >> 4)) * 128, ch = (warp & 1) * 4 + ((lane >> 3) & 1);
            #pragma unroll 1
            for (int pass = 0; pass * 18 < nst; pass++) {
                float acc[2][4] = {};
                #pragma unroll 1
                for (int st = 0; st < 18; st++) {
                    const uint32_t sa = sm + OFF_SILU + (16 * st + q) * 4;
                    const uint32_t b0 = lds32(sa), b1 = lds32(sa + 16), b2 = lds32(sa + 32), b3 = lds32(sa + 48);
                    mbar_wait(bars + 8 * (BAR_X + sl), ph);
                    #pragma unroll
                    for (int m = 0; m < 2; m++) {
                        uint32_t a[4], a2[4];
                        const uint32_t ad = ad0 + sl * 28672 + ((ch + 2 * m) ^ (lane & 7)) * 16;
                        ldsm4t(a, ad); ldsm4t(a2, ad + 2048);
                        mma_bf(acc[m], a, b0, b1); mma_bf(acc[m], a2, b2, b3);
                    }
                    if (elect()) mbar_arrive(bars + 8 * (BAR_X + 6 + sl));
                    if (++sl == 6) { sl = 0; ph ^= 1; }
                }
                const int cb = 28 * pass + 7 * (b - 128) + (warp >> 1), gg = (g >> 1) + 4 * q;
                uint32_t w[2];
                #pragma unroll
                for (int m = 0; m < 2; m++) {
                    float v = bf_round(q ? acc[m][2] : acc[m][0]); if (cb >= 27) v *= 0.5f; else if (cb >= 18) v += 1.f;
                    w[m] = max(pack_bf(v, __shfl_xor_sync(~0u, v, 4)), 1u);
                }
                if (q < 2 && !(g & 1)) {
                    const int qq = (warp & 1) * 2;
                    if (cb < 27) asm volatile("st.relaxed.gpu.global.v2.u32 [%0], {%1, %2};" :: "l"(p.scr->modc + 32 * cb + 4 * gg + qq), "r"(w[0]), "r"(w[1]) : "memory");
                    else if (cb < 36) { uint32_t* o = p.scr->modc + 896 + 32 * (cb - 27) + 8 * qq + gg; o[0] = w[0]; o[8] = w[1]; }
                }
                if (tid == 0 && pass == 0) PROFT(25);
                bar_sync(1, 448);
                if (tid == 0) { fence_async_g(); red_release(g_cnt + (CNT_NC + pass) * 32); }
                __syncwarp();
            }
            fence_async_s();
        }
        __syncthreads();
    } else {
        uint32_t ta[QA * 4];
        if (strip && (warp >> 2) == 2) {
            const int w = warp - 8;
            uint32_t sb[18];
            #pragma unroll
            for (int u = 0; u < 18; u++) sb[u] = lds32(sm + OFF_SILU + (72 * w + 4 * u + q) * 4);
            const uint32_t ra = sm + OFF_STRIP + (144 * w + (lane & 7) + 8 * (lane >> 4)) * 64, sw = (lane >> 1) & 3, ch = (lane >> 3) & 1;
            float acc[2][2][4] = {};
            mbar_wait(bars + 8 * (BAR_ST + w), 0);
            #pragma unroll
            for (int u = 0; u < 9; u++)
                #pragma unroll
                for (int m = 0; m < 2; m++) { uint32_t a[4]; ldsm4t(a, ra + u * 1024 + ((ch + 2 * m) ^ sw) * 16); mma_bf(acc[u & 1][m], a, sb[2 * u], sb[2 * u + 1]); }
            #define PICK(a_) ((q & 2) ? ((q & 1) ? a_[1][2] : a_[1][0]) : ((q & 1) ? a_[0][2] : a_[0][0]))
            sts32(sm + OFF_RED + ((8 * q + g) * 4 + w) * 4, __float_as_uint(PICK(acc[0]) + PICK(acc[1])));
            if (tid == 256) PROFT(0);
            bar_sync(10, 128);
            if (warp == 8) {
                const uint4 v = lds128(sm + OFF_RED + lane * 16);
                float sum = bf_round((__uint_as_float(v.x) + __uint_as_float(v.y)) + (__uint_as_float(v.z) + __uint_as_float(v.w)));
                if (b >= 36) sum = bf_round(1.f + sum);
                st_relaxed(g_mod + b * 16 + (lane & 16) + (lane & 1) * 8 + ((lane & 15) >> 1), (pack_h(0.f, sum) & 0xFFFF0000u) | tag);
                if (tid == 256) PROFT(1);
            }
        }
        mbar_wait(bars + 8 * BAR_TAB, 0);
        load_tab<QA>(ta, sm + OFF_TAB + lane * 16);
        auto w_prefetch = [&]() {
            if (warp >= 14 && elect()) asm volatile("cp.async.bulk.prefetch.L2.global [%0], 9248;" :: "l"((warp == 14 ? p.wr : p.wi) + b * 4624) : "memory");
            __syncwarp();
        };
        uint32_t nb[2][5];
        uint4 mv = make_uint4(tag, tag, tag, tag);
        const bool poller = warp < 8 || warp == 12;
        const int mc = warp < 8 ? tid : tid - 128, mst = (mc >> 2) % 36, midx = (mc < 144 ? 10 : 0) + 5 * ((mc >> 1) & 1) + (mst >> 3);
        const uint32_t* mp = g_mod + mc * 4;
        const uint32_t ma = sm + OFF_MODA + ((midx >> 2) * 32 + (mc & 1) * 16 + (mst & 3)) * 16 + (midx & 3) * 4 + ((mst >> 2) & 1) * 2;
        #define MOD_MISSING ((((mv.x ^ tag) | (mv.y ^ tag) | (mv.z ^ tag) | (mv.w ^ tag)) & 0xFFFFu) != 0)
        #pragma unroll
        for (int i = 0; i < 9; i++) one[i] = lds32(sm + OFF_TAB + (QA - 1) * 512 + i * 16 + 8);
        hb();
        mbar_wait(bars + 8 * (BAR_X + warp), 0);
        if (poller) mv = ldx128(mp);
        PROF0(28);
        #pragma unroll
        for (int i = 0; i < 9; i++) xw[i] = lds32(sm + OFF_STAGE + warp * 1152 + (32 * i + 8 * q + g) * 4);
        {
            float r, mr;
            ln_stats(xw, one, g, q, r, mr);
            #pragma unroll
            for (int pp = 0; pp < 5; pp++) {
                nb[0][pp] = pack_h(fmaf(bf_lo(xw[2 * pp]), r, mr), pp < 4 ? fmaf(bf_lo(xw[pp < 4 ? 2 * pp + 1 : 0]), r, mr) : 0.f);
                nb[1][pp] = pack_h(fmaf(bf_hi(xw[2 * pp]), r, mr), pp < 4 ? fmaf(bf_hi(xw[pp < 4 ? 2 * pp + 1 : 0]), r, mr) : 0.f);
            }
        }
        PROF0(2);
        w_prefetch();
        if (poller) {
            for (int it = 0; __any_sync(~0u, MOD_MISSING); it++) { if (MOD_MISSING) mv = ldx128(mp); hb(); if (it > SPIN_LIMIT) __trap(); }
            sts16(ma, mv.x >> 16); sts16(ma + 64, mv.y >> 16); sts16(ma + 128, mv.z >> 16); sts16(ma + 192, mv.w >> 16);
        }
        __syncthreads();
        PROF0(3);
        if (warp >= 13 && elect()) {
            if (warp == 15) bulk_load(sm + OFF_TAB + QA * 512, p.tab->w + QA * 128, (QB + QC) * 512, bars + 8 * BAR_TAB2);
            else tma3(sm + OFF_WRAW + (warp - 13) * 14336, warp == 13 ? &tm_wr : &tm_wi, wc0 & ~7, 0, 0, bars + 8 * BAR_W);
        }
        __syncwarp();
        {
            uint32_t md[20];
            load_tab<5>(md, sm + OFF_MODA + lane * 16);
            #pragma unroll
            for (int v = 0; v < 2; v++)
                #pragma unroll
                for (int pp = 0; pp < 5; pp++) nb[v][pp] = hfma2(nb[v][pp], md[v * 5 + pp], md[10 + v * 5 + pp]);
        }
        uint32_t re[3][2], im[3][2];
        #pragma unroll
        for (int mt = 0; mt < 3; mt++)
            #pragma unroll
            for (int v = 0; v < 2; v++) {
                re[mt][v] = 0; im[mt][v] = 0;
                mma_h8(re[mt][v], im[mt][v], ta[24 + 2 * mt], ta[25 + 2 * mt], nb[v][4]);
                mma_h(re[mt][v], im[mt][v], ta[mt * 8], ta[mt * 8 + 1], ta[mt * 8 + 2], ta[mt * 8 + 3], nb[v][0], nb[v][1]);
                mma_h(re[mt][v], im[mt][v], ta[mt * 8 + 4], ta[mt * 8 + 5], ta[mt * 8 + 6], ta[mt * 8 + 7], nb[v][2], nb[v][3]);
                cmul_neg(re[mt][v], im[mt][v], ta[30 + (mt * 2 + v) * 2], ta[31 + (mt * 2 + v) * 2]);
            }
        const uint32_t srow = sm + OFF_SPEC + warp * (SPEC_P * 4);
        #pragma unroll
        for (int nt = 0; nt < 2; nt++) {
            uint32_t o[2][4];
            #pragma unroll
            for (int v = 0; v < 2; v++) {
                const uint32_t b0 = ta[42 + (v * 2 + nt) * 2], b1 = ta[43 + (v * 2 + nt) * 2];
                o[v][0] = o[v][1] = o[v][2] = o[v][3] = 0;
                mma_h(o[v][0], o[v][1], re[0][v], re[1][v], im[0][v], im[1][v], b0, b1);
                mma_h(o[v][2], o[v][3], re[2][0], re[2][1], im[2][0], im[2][1], b0, b1);
            }
            const uint32_t a = srow + (g + 72 * q + 36 * nt) * 4, a2 = srow + (288 - g - 72 * q - 36 * nt) * 4;
            sts32(a, hadd2(o[0][0], o[1][0])); sts32(a + 32, hadd2(o[0][1], o[1][1])); if (g < 3) sts32(a + 64, hadd2(o[0][2], o[1][3]));
            if (g > 0 || (q == 0 && nt == 0)) sts32(a2, hsub2(o[0][0], o[1][0]) ^ 0x80000000u);
            sts32(a2 - 32, hsub2(o[0][1], o[1][1]) ^ 0x80000000u); if (g < 2) sts32(a2 - 64, hsub2(o[0][2], o[1][3]) ^ 0x80000000u);
        }
        uint32_t b3[16];
        if (warp < 10) load_tab<4>(b3, sm + OFF_B3 + lane * 16);
        __syncthreads();
        t_st = clk32();
        PROF0(4);
        if (warp < 10) {
            uint4 V[4], o[4];
            #pragma unroll
            for (int u = 0; u < 4; u++) V[u] = lds128(scol + u * (16 * SPEC_P));
            radix16(V, b3, o);
            #pragma unroll
            for (int nt = 0; nt < 4; nt++) { o[nt].x |= 1u; if (warp < 9 || g < 2) stx128(tptr + nt * tstr, o[nt]); }
        }
        PROF0(5);
    }

    int role = 0;
    asm volatile("barrier.cluster.wait.aligned;" ::: "memory");
    if (warp >= 12) {
        const int t = tid - 384;
        if (tid == 448 && rank == 0) {
            uint32_t smid; asm volatile("mov.u32 %0, %%smid;" : "=r"(smid));
            const uint32_t tp = smid >> 1;
            uint32_t pr = tp < 32 ? (tp & 7) * 8 + (tp >> 3) : tp < 60 ? (1 + (tp - 32) % 7) * 8 + 4 + (tp - 32) / 7 : tp < 62 ? 4 + tp : tp < 66 ? tp - 58 : 0;
            while (atomicExch(g_slot + pr, epoch + 1) == epoch + 1) pr = pr == 65 ? 0 : pr + 1;
            #pragma unroll
            for (int r = 0; r < 2; r++)
                asm volatile("st.async.weak.shared::cluster.mbarrier::complete_tx::bytes.u32 [%0], %1, [%2];" :: "r"(mapa(sm + OFF_MISC, r)), "r"(pr), "r"(mapa(bars + 8 * BAR_ROLE, r)) : "memory");
        }
        __syncwarp();
        if (t == 0) {
            asm volatile("prefetch.tensormap [%0];" :: "l"(&tm_w1a) : "memory");
            asm volatile("prefetch.tensormap [%0];" :: "l"(&tm_h3a) : "memory"); asm volatile("prefetch.tensormap [%0];" :: "l"(&tm_w1b) : "memory");
            asm volatile("prefetch.tensormap [%0];" :: "l"(&tm_h3b) : "memory"); asm volatile("prefetch.tensormap [%0];" :: "l"(&tm_w2) : "memory");
            asm volatile("prefetch.tensormap [%0];" :: "l"(&tm_o) : "memory"); asm volatile("prefetch.tensormap [%0];" :: "l"(&tm_h3s) : "memory");
        }
        __syncwarp();
        if (rowcta) {
            spin_until(t0 + NCP);
            uint4 v[2];
            v[1] = make_uint4(1, 1, 1, 1);
            for (int it = 0;; it++) {
                v[0] = ldx128(p.scr->modc + 4 * t); if (t < 88) v[1] = ldx128(p.scr->modc + 512 + 4 * t);
                if (__all_sync(~0u, min(min(min(v[0].x, v[0].y), min(v[0].z, v[0].w)), min(min(v[1].x, v[1].y), min(v[1].z, v[1].w))) != 0)) break;
                __nanosleep(100); if (it > SPIN_LIMIT) __trap();
            }
            #pragma unroll
            for (int u = 0; u < 2; u++) if (u == 0 || t < 88) {
                const uint32_t a = sm + OFF_MODC + (((t >> 5) + 4 * u) * 32 + 4 * (t & 7)) * 16 + ((t >> 3) & 3) * 4;
                sts32(a, v[u].x); sts32(a + 16, v[u].y); sts32(a + 32, v[u].z); sts32(a + 48, v[u].w);
            }
            __syncwarp();
            if (elect()) mbar_arrive(bars + 8 * BAR_NC);
            if (t == 0) PROFT(29);
        }
    } else if (rowcta && warp < 11) {
        const int nw = !(b & 1) ? 10 : (b & 7) == 7 ? 9 : 8;
        const int cm = (b >> 3) * 288 + (b & 7) * 32, cx = (b & 1) ? 4608 + 8 * (b >> 3) : (b >> 3) * 288 + 256 + 4 * (b & 7);
        auto load_in = [&]() {
            if (elect()) {
                mbar_expect(bars + 8 * BAR_XB, nw > 8 ? 20480 : 16384);
                tma2(sm + OFF_STAGE, &tm_t, cm, 0, bars + 8 * BAR_XB);
                if (nw > 8) tma2(sm + OFF_STX, &tm_tx, cx, 0, bars + 8 * BAR_XB);
            }
            __syncwarp();
        };
        if (warp == 10) { fence_async_s(); spin_until(t_st + X1D); load_in(); }
        uint32_t tb[QB * 4], wre[4][2], wim[4][2];
        if (warp < nw) {
            mbar_wait(bars + 8 * BAR_TAB2, 0);
            load_tab<QB>(tb, sm + OFF_TAB + QA * 512 + lane * 16);
            mbar_wait(bars + 8 * BAR_W, 0);
            const int off = wc0 & 7;
            const uint32_t wa = sm + OFF_WRAW + lane * 112 + ((off >> 1) + 2 * warp) * 4, sh = (off & 1) * 16;
            #pragma unroll
            for (int c = 0; c < 2; c++)
                #pragma unroll
                for (int h = 0; h < 2; h++) {
                    uint32_t y[2][2];
                    #pragma unroll
                    for (int e = 0; e < 2; e++) {
                        const uint32_t a = wa + c * 14336 + (h + 2 * e) * 3584, x0 = lds32(a), x1 = lds32(a + 4), x2 = lds32(a + 8);
                        y[e][0] = __funnelshift_r(x0, x1, sh); y[e][1] = __funnelshift_r(x1, x2, sh);
                    }
                    #pragma unroll
                    for (int x = 0; x < 4; x++) {
                        const uint32_t v = (x & 1) ? pack_h(bf_hi(y[0][x >> 1]), bf_hi(y[1][x >> 1])) : pack_h(bf_lo(y[0][x >> 1]), bf_lo(y[1][x >> 1]));
                        if (c) wim[x][h] = v; else wre[x][h] = v;
                    }
                }
        }
        const uint32_t ca = warp < 8 ? sm + OFF_STAGE + lane * 128 + (warp ^ (lane & 7)) * 16 : sm + OFF_STX + lane * 32 + ((warp ^ g) & 1) * 16, cs = warp < 8 ? 4096 : 1024;
        uint32_t V[4][4];
        for (int it = 0;; it++) {
            mbar_wait(bars + 8 * BAR_XB, it & 1);
            uint32_t ok = 1;
            if (warp < nw) {
                #pragma unroll
                for (int u = 0; u < 4; u++) { uint4 t4 = lds128(ca + u * cs); V[u][0] = t4.x; V[u][1] = t4.y; V[u][2] = t4.z; V[u][3] = t4.w; ok &= t4.x; }
            }
            asm volatile("{.reg .pred p; setp.ne.u32 p, %0, 0; bar.red.and.pred p, 1, 352, p; selp.u32 %0, 1, 0, p;}" : "+r"(ok) :: "memory");
            if (ok) break;
            if (warp == 10) { load_in(); hb(); }
            if (it > SPIN_LIMIT / 64) __trap();
        }
        PROF0(7);
        if (warp < nw) {
            uint32_t zr[4][2], zi[4][2];
            #pragma unroll
            for (int x = 0; x < 4; x++) {
                uint32_t er = 0, ei = 0, or_ = 0, oi = 0;
                mma_h(er, ei, tb[0], tb[1], tb[2], tb[3], V[0][x], V[1][x]);
                mma_h(or_, oi, tb[4], tb[5], tb[6], tb[7], V[2][x], V[3][x]);
                uint32_t r0 = hadd2(er, or_), r1 = hsub2(er, or_), i0 = hadd2(ei, oi), i1 = hsub2(ei, oi);
                cmul_neg(r0, i0, tb[8], tb[9]); cmul_neg(r1, i1, tb[10], tb[11]);
                uint32_t xr0 = 0, xr1 = 0, xi0 = 0, xi1 = 0;
                mma_h(xr0, xr1, r0, r1, i0, i1, tb[12], tb[13]);
                mma_h(xi0, xi1, r0, r1, i0, i1, tb[14], tb[15]);
                cmul_pos(xr0, xi0, wre[x][0], wim[x][0]); cmul_pos(xr1, xi1, wre[x][1], wim[x][1]);
                r0 = 0; i0 = 0; r1 = 0; i1 = 0;
                mma_h(r0, i0, tb[12], tb[13], tb[14], tb[15], xr0, xi0);
                mma_h(r1, i1, tb[12], tb[13], tb[14], tb[15], xr1, xi1);
                cmul_pos(r0, i0, tb[16], tb[17]); cmul_pos(r1, i1, tb[18], tb[19]);
                zr[x][0] = hadd2(r0, r1); zr[x][1] = hsub2(r0, r1); zi[x][0] = hadd2(i0, i1); zi[x][1] = hsub2(i0, i1);
            }
            #pragma unroll
            for (int nt = 0; nt < 4; nt++) {
                uint4 o = make_uint4(0, 0, 0, 0);
                const int h = nt >> 1;
                mma_h(o.x, o.y, zr[0][h], zr[1][h], zi[0][h], zi[1][h], tb[20 + 2 * nt], tb[21 + 2 * nt]);
                mma_h(o.z, o.w, zr[2][h], zr[3][h], zi[2][h], zi[3][h], tb[20 + 2 * nt], tb[21 + 2 * nt]);
                o.x &= ~1u;
                sts128(ca + nt * cs, o);
            }
        }
        fence_async_s();
        bar_sync(1, 352);
        t_st = clk32();
        PROF0(8);
        if (warp == 10 && elect()) {
            asm volatile("cp.async.bulk.tensor.2d.global.shared::cta.bulk_group [%0, {%2, %3}], [%1];" :: "l"(&tm_t), "r"(sm + OFF_STAGE), "r"(cm), "r"(0) : "memory");
            if (nw > 8) asm volatile("cp.async.bulk.tensor.2d.global.shared::cta.bulk_group [%0, {%2, %3}], [%1];" :: "l"(&tm_tx), "r"(sm + OFF_STX), "r"(cx), "r"(0) : "memory");
            asm volatile("cp.async.bulk.commit_group;" ::: "memory");
            asm volatile("cp.async.bulk.wait_group.read 0;" ::: "memory");
        }
        __syncwarp();
    }

    if (warp >= 10) { mbar_wait(bars + 8 * BAR_ROLE, 0); role = __shfl_sync(~0u, lds32(sm + OFF_MISC), 0); fence_async_s(); }
    auto first_a = [&]() {
        if (warp >= 10 && role < 64 && elect()) {
            const int it = warp - 10, hi = it >= 3; const bool p2 = it - 3 * hi == 2;
            tma4(sm + OFF_A + it * A_BYTES, p2 ? &tm_w1b : &tm_w1a, 0, 0, p2 ? 64 * rank + 8 * hi : 4 * (it - hi),
                 9 * (role >> 3) + (p2 ? 8 : (role & 4) + 2 * rank), bars + 8 * (BAR_FULL + it));
        }
        __syncwarp();
    };
    if (!rowcta) first_a();
    else {
        uint32_t tc[20], md[28];
        mbar_wait(bars + 8 * BAR_TAB2, 0);
        load_tab<5>(tc, sm + OFF_TAB + (QA + QB) * 512 + lane * 16);
        bool md_early = warp >= 10;
        if (md_early) { mbar_wait(bars + 8 * BAR_NC, 0); load_tab<7>(md, sm + OFF_MODC + lane * 16); }
        if (FAP > 1 && warp >= 10) { spin_until(t0 + FAP); first_a(); }
        if (warp < 10) {
            uint32_t b3[16];
            load_tab<4>(b3, sm + OFF_B3 + 2048 + lane * 16);
            uint4 V[4], o[4];
            const bool tact = warp < 9 || g == 0;
            spin_until(t_st + X2D);
            #pragma unroll
            for (int u = 0; u < 4; u++) { V[u] = make_uint4(0, 0, 0, 0); if (tact) V[u] = ldx128(tptr + u * tstr); }
            md_early = __any_sync(~0u, mbar_test(bars + 8 * BAR_NC, 0));
            if (md_early) load_tab<7>(md, sm + OFF_MODC + lane * 16);
            for (int it = 0; __any_sync(~0u, (V[0].x | V[1].x | V[2].x | V[3].x) & 1u); it++) {
                #pragma unroll
                for (int u = 0; u < 4; u++) if (V[u].x & 1u) V[u] = ldx128(tptr + u * tstr);
                hb();
                if (it > SPIN_LIMIT) __trap();
            }
            PROF0(10);
            radix16(V, b3, o);
            if (tact) {
                #pragma unroll
                for (int nt = 0; nt < 4; nt++) sts128(scol + nt * (16 * SPEC_P), o[nt]);
            }
        }
        __syncthreads();
        PROF0(11);
        if (FAP == 0) first_a();
        const uint32_t srow = sm + OFF_SPEC + warp * (SPEC_P * 4);
        uint32_t re[2][3], im[2][3];
        #pragma unroll
        for (int mt = 0; mt < 3; mt++) {
            const uint32_t a = srow + (g + 72 * q + 8 * mt) * 4, a2 = srow + (288 - g - 72 * q - 8 * mt) * 4;
            const uint32_t z0 = lds32(a), z1 = lds32(a + 144), z2 = lds32(a2), z3 = lds32(a2 - 144);
            #pragma unroll
            for (int m2 = 0; m2 < 2; m2++) {
                re[m2][mt] = 0; im[m2][mt] = 0;
                const uint32_t sg = m2 ? 0x3C00BC00u : 0xBC003C00u;
                mma_h(re[m2][mt], im[m2][mt], tc[m2 * 4], tc[m2 * 4 + 1], tc[m2 * 4 + 2], tc[m2 * 4 + 3], hfma2(z2, sg, z0), hfma2(z3, sg, z1));
                cmul_pos(re[m2][mt], im[m2][mt], tc[8 + (m2 * 3 + mt) * 2], tc[9 + (m2 * 3 + mt) * 2]);
            }
        }
        float y[20];
        WG_FENCE();
        #pragma unroll
        for (int mt = 0; mt < 3; mt++)
            wgmma40_rs(y, re[0][mt], re[1][mt], im[0][mt], im[1][mt], desc_lo(sm + OFF_TAB + (QA + QB + 5) * 512 + mt * 1280, 128), mt);
        WG_COMMIT();
        if (FAP == 1) first_a();
        if (!md_early) { mbar_wait(bars + 8 * BAR_NC, 0); load_tab<7>(md, sm + OFF_MODC + lane * 16); }
        WG_WAIT(0);
        #pragma unroll
        for (int i = 0; i < 9; i++) xw[i] = bfma2(md[i], pack_bf(y[4 * (i >> 1) + (i & 1)], y[4 * (i >> 1) + 2 + (i & 1)]), xw[i]);
        float r, mr;
        ln_stats(xw, one, g, q, r, mr);
        uint32_t r2 = pack_bf(r, r), m2 = pack_bf(mr, mr);
        #pragma unroll
        for (int i = 0; i < 9; i++) {
            sts32(sm + OFF_X1 + warp * 1152 + (32 * i + 8 * q + g) * 4, xw[i]);
            xw[i] = bfma2(bfma2(xw[i], r2, m2), md[18 + i], md[9 + i]);
        }
        ln_stats(xw, one, g, q, r, mr);
        r2 = pack_bf(r, r); m2 = pack_bf(mr, mr);
        {
            const int n7 = 2 * q + (g >> 2);
            const uint32_t a = sm + OFF_STAGE + (warp >> 3) * 9216 + n7 * 128 + ((warp & 7) ^ n7) * 16 + (g & 3) * 4;
            #pragma unroll
            for (int i = 0; i < 9; i++) sts32(a + i * 1024, bfma2(xw[i], r2, m2));
        }
        fence_async_s();
        __syncthreads();
        PROF0(12);
        if (tid == 0) {
            asm volatile("cp.async.bulk.tensor.4d.global.shared::cta.bulk_group [%0, {%2, %2, %2, %3}], [%1];" :: "l"(&tm_h3s), "r"(sm + OFF_STAGE), "r"(0), "r"(b) : "memory");
            asm volatile("cp.async.bulk.commit_group;" ::: "memory");
        }
    }
    if (!rowcta) __syncthreads();
    else {
        if (tid == 0) { asm volatile("cp.async.bulk.wait_group 0;" ::: "memory"); fence_async_g(); red_release(g_cnt + CNT_H3 * 32); }
        PROF0(13);
        if (warp == 15) {
            __nanosleep(X1DELAY);
            #pragma unroll 1
            for (int r = 0; r < 16; r++) {
                uint4* dst = (uint4*)(p.out + (size_t)(b + 128 * r) * D_) + lane;
                const uint32_t src = sm + OFF_X1 + r * 1152 + lane * 16;
                dst[0] = lds128(src); dst[32] = lds128(src + 512); if (lane < 8) dst[64] = lds128(src + 1024);
                const uint32_t t1 = clk32(); while ((int)(clk32() - t1) < X1PACE) __nanosleep(50);
            }
            __syncwarp();
            if (lane == 0) { fence_async_g(); red_release(g_cnt + CNT_X1 * 32); }
        }
    }
    role = __shfl_sync(~0u, lds32(sm + OFF_MISC), 0);
    if (role >= 64) { if (warp == 0) PROFDUMP(); return; }

    const int gi = role >> 3, dt = role & 3, c2 = (role >> 2) & 1;
    const int wg = warp >> 2, wi = warp & 3;
    if (wg == 3) {
        uint32_t so = 0, eph = 1;
        #define RING_STEP(BYTES, OFF, ISSUE) do { \
            mbar_wait(bars + 8 * BAR_EMPTY + so, eph); \
            if (elect()) { const uint32_t fb = bars + 8 * BAR_FULL + so, dst = sm + (OFF) + so * ((BYTES) / 8); mbar_expect(fb, BYTES); ISSUE; } \
            so += 8; if (so == 8 * NST) { so = 0; eph ^= 1; } } while (0)
        const uint32_t kbt = g2_kb(lane, rank, gi, c2) | (g2_kb(32 + (lane & 3), rank, gi, c2) << 8);
        #define KB(n_) ((__shfl_sync(~0u, kbt, (n_) & 31) >> (((n_) >> 2) & 8)) & 255)
        if (warp == 12) {
            eph = 0;
            const int fb1 = 9 * gi + 4 * c2 + 2 * rank, sb2 = 4 * gi + 2 * c2;
            int pft = dt, pfj = 4 * (PF0 + PFS * dt);
            #pragma unroll 1
            for (int j = 16; j < 128; j += 4) {
                RING_STEP(A_BYTES, OFF_A, tma4(dst, &tm_w1a, 0, 0, j, fb1, fb));
                if (j < 64) { if (j & 4) RING_STEP(A_BYTES, OFF_A, tma4(dst, &tm_w1b, 0, 0, 64 * rank + j - 4, 9 * gi + 8, fb)); }
                if (j == pfj && pft < PFN) {
                    const int kb = KB(pft); pft += 4; pfj += 16 * PFS;
                    if (elect()) asm volatile("cp.async.bulk.prefetch.tensor.3d.L2.global [%0, {%1, %2, %3}];" :: "l"(&tm_w2), "r"(0), "r"(64 * kb), "r"(sb2) : "memory");
                }
            }
            #pragma unroll 1
            for (int n = 0; n < 36; n++) {
                const int kb = KB(n);
                RING_STEP(A_BYTES, OFF_A, tma3(dst, &tm_w2, 0, 64 * kb, sb2, fb));
            }
        } else if (warp == 13) {
            const uint32_t e1 = __shfl_sync(~0u, epoch + 1, 0);
            fence_async_s();
            wait_count<0>(g_cnt + CNT_H3 * 32, e1 * 128);
            fence_async_g();
            if (lane == 0) PROFT(14);
            #pragma unroll 1
            for (int j = 0; j < 128; j += 4) {
                RING_STEP(B_BYTES, OFF_B, tma3(dst, &tm_h3a, 0, 18 * dt, j, fb));
                if (j < 64 && (j & 4)) RING_STEP(B_BYTES, OFF_B, tma3(dst, &tm_h3b, 0, 18 * dt + 9 * c2, 64 * rank + j - 4, fb));
            }
            int n = 0;
            #pragma unroll 1
            for (int cls = 0; cls < 3; cls++) {
                mbar_wait(bars + 8 * (BAR_UOK + cls), 0);
                fence_async_g();
                if (cls == 1 && lane == 0) PROFT(19);
                if (cls == 0 && lane == 0) PROFT(22);
                static_assert((IT_G2 + 4) % NST != NST - 1, "no wrap at the skipped stage");
                if (cls == 1) { n++; so += 8; }
                #pragma unroll 1
                for (; n < (cls == 0 ? 4 : cls == 1 ? 21 : 36); n++) {
                    const int kb = KB(n);
                    RING_STEP(B_BYTES, OFF_B, bulk_load(dst, g_U + (kb * 4 + dt) * 1152, B_BYTES, fb));
                }
            }
            if (role == 0 && rank == 0 && lane == 0) st_relaxed(g_cnt + CNT_EPOCH * 32, e1);
        } else if (warp == 15) {
            if (elect()) mbar_arrive_remote(mapa(bars + 8 * BAR_HOLD, rank ^ 1));
            __syncwarp();
            bar_sync(6, 160);
            if (elect()) mbar_arrive(bars + 8 * (BAR_FULL + (IT_G2 + 4) % NST));
            __syncwarp();
            mbar_wait(bars + 8 * BAR_W1GO, 0);
            if (elect()) {
                char* dst = (char*)(g_U + ((9 * gi + 4 * c2 + 2 * rank + 1) * 4 + dt) * 1152);
                #pragma unroll 1
                for (int i = 0; i < W1N; i++) {
                    asm volatile("cp.async.bulk.global.shared::cta.bulk_group [%0], [%1], %2;" :: "l"(dst + i * (18432 / W1N)), "r"(sm + OFF_X1 + i * (18432 / W1N)), "n"(18432 / W1N) : "memory");
                    const uint32_t t1 = clk32(); while ((int)(clk32() - t1) < W1P) {}
                }
                asm volatile("cp.async.bulk.commit_group;" ::: "memory");
                asm volatile("cp.async.bulk.wait_group 0;" ::: "memory");
                fence_async_g(); red_release(g_cnt + (CNT_U + 16) * 32);
                #pragma unroll 1
                for (int n = 0; n < 4; n++) { __nanosleep(300); tma2(sm + OFF_X1 + n * 4608, &tm_o, 144 * dt, 256 * gi + 128 * c2 + 64 * (rank ^ 1) + 16 * n, bars + 8 * BAR_XT); }
            }
        } else {
            const uint32_t e1 = epoch + 1;
            if (lane == 0) {
                __nanosleep(4000);
                wait_count<200>(g_cnt + CNT_NC * 32, e1 * 4); wait_count<200>(g_cnt + (CNT_NC + 1) * 32, e1 * 2);
                fence_async_g();
                mbar_expect(bars + 8 * BAR_GB, 1152);
                bulk_load(sm + OFF_GB, p.scr->modc + 896, 1152, bars + 8 * BAR_GB);
                wait_count<200>(g_cnt + CNT_X1 * 32, e1 * 128);
                if (role * 2 + rank < 108) {
                    uint4* z = (uint4*)p.scr->modc + (role * 2 + rank) * 2; z[0] = z[1] = make_uint4(0, 0, 0, 0);
                }
                wait_count<50>(g_cnt + (CNT_U + dt * 2 + rank) * 32, e1 * 16);
                mbar_arrive(bars + 8 * BAR_UOK);
            }
            __syncwarp();
            bar_sync(4, 160);
            if (lane == 0) {
                fence_async_g(); red_release(g_cnt + (CNT_U + 8) * 32);
                PROFT(17);
                wait_count<0>(g_cnt + (CNT_U + 8) * 32, e1 * 128);
                mbar_arrive(bars + 8 * (BAR_UOK + 1));
                __nanosleep(1000);
                wait_count<100>(g_cnt + (CNT_U + 16) * 32, e1 * 128);
                mbar_arrive(bars + 8 * (BAR_UOK + 2));
            }
        }
    } else if (wg == 2) {
        float d0[36];
        const float bias = bf_lo(ldg_nc16(p.b1 + 576 * gi + 512 + 16 * wi + g + 8 * rank));
        for (int it = 0; it < 200 && !__any_sync(~0u, mbar_test(bars + 8 * BAR_FULL, 0)); it++) { hb(); __nanosleep(100); }
        const bool lead = wi == 0 && elect();
        #pragma unroll 1
        for (int i = 0; i < 8; i++) {
            const uint32_t s = P2S + 3 * (i & 1);
            mbar_wait(bars + 8 * BAR_FULL + 8 * s, (i >> 1) & 1);
            const uint32_t da = desc_lo(sm + OFF_A, 8192) + s * (A_BYTES / 16), db = desc_lo(sm + OFF_B, 128) + s * (B_BYTES / 16);
            WG_FENCE();
            wgmma72(d0, da, db, i);
            #pragma unroll
            for (int k = 1; k < 8; k++) wgmma72(d0, da + k * 128, db + k * 144, 1);
            WG_COMMIT();
            WG_WAIT(0);
            if (lead) mbar_arrive_n(bars + 8 * BAR_EMPTY + 8 * s, 2);
        }
        if (lead) PROFT(18);
        const uint32_t slot = sm + OFF_P2R + (tid & 127) * 16, ra = mapa(slot, rank ^ 1), rb = mapa(bars + 8 * BAR_P2R, rank ^ 1);
        float sv[18];
        #pragma unroll
        for (int i = 0; i < 18; i++) { const float lo = d0[4 * (i >> 1) + (i & 1)], hi = d0[4 * (i >> 1) + 2 + (i & 1)];
            sv[i] = rank ? lo : hi; d0[4 * (i >> 1) + (i & 1)] = (rank ? hi : lo) + bias; }
        mbar_wait(bars + 8 * BAR_HOLD, 0);
        #pragma unroll
        for (int i = 0; i < 4; i++)
            asm volatile("st.async.weak.shared::cluster.mbarrier::complete_tx::bytes.v4.f32 [%0], {%1,%2,%3,%4}, [%5];"
                :: "r"(ra + i * 2048), "f"(sv[4 * i]), "f"(sv[4 * i + 1]), "f"(sv[4 * i + 2]), "f"(sv[4 * i + 3]), "r"(rb) : "memory");
        asm volatile("st.async.weak.shared::cluster.mbarrier::complete_tx::bytes.v2.f32 [%0], {%1,%2}, [%3];" :: "r"(ra + 8192), "f"(sv[16]), "f"(sv[17]), "r"(rb) : "memory");
        mbar_wait(bars + 8 * BAR_P2R, 0);
        #pragma unroll
        for (int i = 0; i < 5; i++) {
            const uint4 v = lds128(slot + i * 2048);
            d0[8 * i] += __uint_as_float(v.x); d0[8 * i + 1] += __uint_as_float(v.y);
            if (i < 4) { d0[8 * i + 4] += __uint_as_float(v.z); d0[8 * i + 5] += __uint_as_float(v.w); }
        }
        asm volatile("bar.arrive 5, 256;" ::: "memory");
        gelu_store<0>(d0, (char*)(g_U + ((9 * gi + 8) * 4 + dt) * 1152) + wi * 4608 + rank * 2304 + c2 * 1152 + g * 16, q);
        bar_sync(8, 128);
        if (lead) { fence_async_g(); red_release(g_cnt + (CNT_U + dt * 2 + (gi >> 2)) * 32); PROFT(26); }
    } else {
        float d[72];
        const bool lead = wi == 0 && elect();
        const uint32_t da0 = desc_lo(sm + OFF_A + wg * 8192, 8192);
        const bool owner = (uint32_t)wg == rank;
        const int srow = 256 * gi + 128 * c2 + 64 * wg + 16 * wi;
        const uint32_t b2w0 = ldg_nc16(p.b2 + srow + g), b2w1 = ldg_nc16(p.b2 + srow + g + 8);
        {
            const int fr = 576 * gi + 256 * c2 + 128 * rank + 64 * wg + 16 * wi + g;
            const float bias0 = bf_lo(ldg_nc16(p.b1 + fr)), bias1 = bf_lo(ldg_nc16(p.b1 + fr + 8));
            #pragma unroll
            for (int i = 0; i < 72; i++) d[i] = (i & 2) ? bias1 : bias0;
            const uint32_t db1 = desc_lo(sm + OFF_B, 128);
            mainloop<DHI_H3, 0, IT_P1, true>(d, bars, da0, db1, lead, [&](int) {});
            mainloop<DHI_H3, IT_P1, IT_G2 - LEAD1, false>(d, bars, da0, db1, lead, [&](int) {});
            constexpr uint32_t EB = 8 * (BAR_EMPTY + (IT_G2 - LEAD1 - 1) % NST);
            if (wg == 1) { WG_WAIT(0); if (lead) mbar_arrive(bars + EB); bar_sync(9, 256); }
            #pragma unroll
            for (int i = IT_G2 - LEAD1; i < IT_G2; i++) {
                mbar_wait(bars + 8 * (BAR_FULL + i % NST), (i / NST) & 1);
                WG_FENCE();
                #pragma unroll
                for (int k = 0; k < 4; k++) {
                    if (i == IT_G2 - 1 && k == HOK1) WG_COMMIT();
                    wgmma144<DHI_H3>(d, da0 + (i % NST) * (A_BYTES / 16) + k * 128, db1 + (i % NST) * (B_BYTES / 16) + k * 288, 1);
                }
                WG_COMMIT();
                if (i == IT_G2 - 1 && HOK1 < 4) WG_WAIT(2); else WG_WAIT(1);
                if (lead && (i > IT_G2 - LEAD1 || wg == 0)) mbar_arrive(bars + 8 * (BAR_EMPTY + (i - 1) % NST));
            }
            if (wg == 0) { WG_WAIT(1); asm volatile("bar.arrive 9, 256;" ::: "memory"); }
            WG_WAIT(0);
            if (lead) mbar_arrive(bars + 8 * (BAR_EMPTY + (IT_G2 - 1) % NST));
            PROF0(16);
            if (wg == 1) bar_sync(5, 256);
            char* const ub = (wg == 0 ? (char*)(g_U + ((9 * gi + 4 * c2 + 2 * rank) * 4 + dt) * 1152) : (char*)__cvta_shared_to_generic(sm + OFF_X1)) + wi * 4608 + g * 16;
            gelu_store<0>(d, ub, q); gelu_store<2>(d, ub + 2304, q); gelu_store<36>(d, ub + 1152, q); gelu_store<38>(d, ub + 3456, q);
            PROF0(27);
            if (wg == 0) asm volatile("bar.arrive 4, 160;" ::: "memory");
            else { fence_async_s(); asm volatile("bar.arrive 6, 160;" ::: "memory"); }
        }
        const uint32_t db0 = desc_lo(sm + OFF_B, 2304);
        const bool keep = role > 64;
        constexpr int IT_L = IT_END - NST, IT_X = IT_L - 4;
        #pragma unroll
        for (int i = IT_G2; i <= IT_G2 + W1S; i++) {
            const uint32_t db = db0 + (i == IT_G2 + 4 ? OFF_X1 - OFF_B : (i % NST) * B_BYTES) / 16;
            mbar_wait(bars + 8 * (BAR_FULL + i % NST), (i / NST) & 1);
            WG_FENCE();
            #pragma unroll
            for (int k = 0; k < 4; k++) wgmma144<DHI_U>(d, da0 + (i % NST) * (A_BYTES / 16) + k * 128, db + k * 288, i > IT_G2 || k > 0 || keep);
            WG_COMMIT();
            if (i > IT_G2) { WG_WAIT(1); if (lead) mbar_arrive(bars + 8 * (BAR_EMPTY + (i - 1) % NST)); }
        }
        if (lead) mbar_arrive(bars + 8 * BAR_W1GO);
        mainloop<DHI_U, IT_G2 + W1S + 1, IT_X, false>(d, bars, da0, db0, lead, [&](int) {});
        const uint32_t ga0 = sm + OFF_GB + (144 * dt + 8 * q) * 2, tile = sm + OFF_X1 + wi * 4608, to = g * 288 + q * 16;
        #define QOFF(i_) (((i_) >> 2) * 2304 + 144 * (((i_) >> 1) & 1) + 64 * ((i_) & 1))
        #define SOFF(k_) (((k_) >> 1) * 2304 + 144 * ((k_) & 1) + 128 - 12 * q)
        #define DIDX(i_, k_) ((i_) < 8 ? 36 * (((i_) >> 1) & 1) + 16 * ((i_) & 1) + 4 * (k_) + 2 * ((i_) >> 2) : 36 * ((k_) & 1) + 32 + 2 * ((k_) >> 1))
        #define FIN(k_, f_) bfma2(g4.f_, pack_bf(d[DIDX(i, k_)], d[DIDX(i, k_) + 1]), xq[i].f_)
        uint4 xq[9];
        auto load_g = [&](int i) { uint4 r; if (i < 4) r = lds128(ga0 + QOFF(i)); else { r.x = r.z = lds32(ga0 + SOFF(0)); r.y = r.w = lds32(ga0 + SOFF(1)); } return r; };
        mainloop<DHI_U, IT_X, IT_L, false>(d, bars, da0, db0, lead, [&](int i) {
            if (!owner) {
                const uint32_t xa = tile + to;
                if (i == IT_X) { mbar_wait(bars + 8 * BAR_XT, 0); xq[0] = lds128(xa + QOFF(0)); xq[4] = lds128(xa + QOFF(4)); xq[1] = lds128(xa + QOFF(1)); }
                else if (i == IT_X + 1) { xq[5] = lds128(xa + QOFF(5)); xq[2] = lds128(xa + QOFF(2)); xq[6] = lds128(xa + QOFF(6)); }
                else if (i == IT_X + 2) { xq[3] = lds128(xa + QOFF(3)); xq[7] = lds128(xa + QOFF(7));
                    xq[8] = make_uint4(lds32(xa + SOFF(0)), lds32(xa + SOFF(1)), lds32(xa + SOFF(2)), lds32(xa + SOFF(3))); }
                else if (i == IT_X + 3) { if (elect()) mbar_arrive_remote(mapa(bars + 8 * BAR_DONE, rank ^ 1)); }
            } });
        if (owner) { WG_WAIT(0); if (lead) mbar_arrive(bars + 8 * (BAR_EMPTY + (IT_L - 1) % NST)); bar_sync(7, 256); }
        #pragma unroll
        for (int i = IT_L; i < IT_END; i++) {
            mbar_wait(bars + 8 * (BAR_FULL + i % NST), (i / NST) & 1);
            WG_FENCE();
            #pragma unroll
            for (int k = 0; k < 4; k++) {
                if (i == IT_END - 1 && k == HOK) WG_COMMIT();
                wgmma144<DHI_U>(d, da0 + (i % NST) * (A_BYTES / 16) + k * 128, db0 + (i % NST) * (B_BYTES / 16) + k * 288, 1);
            }
            WG_COMMIT();
            if (i == IT_L) { WG_WAIT(1); if (lead && !owner) mbar_arrive(bars + 8 * (BAR_EMPTY + (IT_L - 1) % NST)); }
        }
        PROF0(9);
        mbar_wait(bars + 8 * BAR_GB, 0);
        if (!owner) {
            const uint32_t ra = mapa(tile + lane * 16, rank ^ 1), rb = mapa(bars + 8 * BAR_RECV, rank ^ 1);
            mbar_wait(bars + 8 * BAR_DONE, 0);
            uint4 gn = load_g(0);
            WG_WAIT(1);
            asm volatile("bar.arrive 7, 256;" ::: "memory");
            WG_WAIT(0);
            #pragma unroll
            for (int i = 0; i < 72; i++) d[i] = fmaf(bf_lo((i & 2) ? b2w1 : b2w0), 2.f, d[i]);
            #pragma unroll
            for (int j = 0; j < 5; j++) {
                const uint4 g4 = gn;
                if (j < 4) gn = load_g(j + 1);
                #pragma unroll
                for (int i = j < 4 ? j : 8; i < 9; i += 4) if (i < 8 || j == 4)
                    asm volatile("st.async.weak.shared::cluster.mbarrier::complete_tx::bytes.v4.b32 [%0], {%1,%2,%3,%4}, [%5];"
                        :: "r"(ra + i * 512), "r"(FIN(0, x)), "r"(FIN(1, y)), "r"(FIN(2, z)), "r"(FIN(3, w)), "r"(rb) : "memory");
            }
            PROF0(6);
            if (warp == 0) PROFDUMP();
            return;
        }
        PROF0(24);
        mbar_wait(bars + 8 * BAR_RECV, 0);
        #pragma unroll
        for (int i = 0; i < 9; i++) xq[i] = lds128(tile + lane * 16 + i * 512);
        uint4 gn = load_g(0);
        WG_WAIT(0);
        __syncwarp();
        PROF0(21);
        #pragma unroll
        for (int j = 0; j < 5; j++) {
            const uint4 g4 = gn;
            if (j < 4) gn = load_g(j + 1);
            #pragma unroll
            for (int i = j < 4 ? j : 8; i < 9; i += 4) if (i < 8 || j == 4) {
                const uint4 o = make_uint4(FIN(0, x), FIN(1, y), FIN(2, z), FIN(3, w));
                if (i < 8) sts128(tile + to + QOFF(i), o);
                else { sts32(tile + to + SOFF(0), o.x); sts32(tile + to + SOFF(1), o.y); sts32(tile + to + SOFF(2), o.z); sts32(tile + to + SOFF(3), o.w); }
            }
        }
        fence_async_s();
        __syncwarp();
        if (elect()) {
            asm volatile("cp.async.bulk.tensor.2d.global.shared::cta.bulk_group [%0, {%2, %3}], [%1];" :: "l"(&tm_o), "r"(tile), "r"(144 * dt), "r"(srow) : "memory");
            asm volatile("cp.async.bulk.commit_group;" ::: "memory");
            asm volatile("cp.async.bulk.wait_group.read 0;" ::: "memory");
        }
        PROF0(23);
        if (warp == 0) { __syncwarp(); PROFDUMP(); }
    }
}

typedef CUresult (*EncodeFn)(CUtensorMap*, CUtensorMapDataType, cuuint32_t, void*, const cuuint64_t*, const cuuint64_t*, const cuuint32_t*,
                             const cuuint32_t*, CUtensorMapInterleave, CUtensorMapSwizzle, CUtensorMapL2promotion, CUtensorMapFloatOOBfill);

void encode(EncodeFn fn, CUtensorMap* m, CUtensorMapDataType dt, int rank, const void* ptr, const cuuint64_t* dims, const cuuint64_t* strides,
            const cuuint32_t* box, CUtensorMapSwizzle sw, CUtensorMapL2promotion promo = CU_TENSOR_MAP_L2_PROMOTION_L2_128B) {
    const cuuint32_t es[5] = {1, 1, 1, 1, 1};
    fn(m, dt, rank, (void*)ptr, dims, strides, box, es, CU_TENSOR_MAP_INTERLEAVE_NONE, sw, promo, CU_TENSOR_MAP_FLOAT_OOB_FILL_NONE);
}

}

extern "C" void kernel_launch(void* const* d_in, const int* in_sizes, int n_in, void* d_out, int out_size) {
    (void)in_sizes; (void)n_in; (void)out_size;
    Params p;
    p.x = (const uint16_t*)d_in[0]; p.wr = (const uint16_t*)d_in[1]; p.wi = (const uint16_t*)d_in[2];
    p.w1 = (const uint16_t*)d_in[4]; p.b1 = (const uint16_t*)d_in[5]; p.w2 = (const uint16_t*)d_in[6]; p.b2 = (const uint16_t*)d_in[7];
    p.c = (const uint16_t*)d_in[8]; p.wmod = (const uint16_t*)d_in[9]; p.out = (uint16_t*)d_out;

    void* fnp = nullptr; cudaDriverEntryPointQueryResult qr;
    cudaGetDriverEntryPoint("cuTensorMapEncodeTiled", &fnp, cudaEnableDefault, &qr);
    EncodeFn fn = (EncodeFn)fnp;
    cudaGetSymbolAddress((void**)&p.scr, g_scr); cudaGetSymbolAddress((void**)&p.tab, g_tab);
    void* h3p = p.scr->h3;
    CUtensorMap tw1a, tw1b, tw2, th3a, th3b, twr, twi, twm, tt, ttx, to, th3s, tws;
    {
        const cuuint64_t dims[4] = {64, 16, 128, 72}, st[3] = {128ull * F_ * 2, (cuuint64_t)F_ * 2, 128};
        const cuuint32_t ba[4] = {64, 16, 4, 2}, bb[4] = {64, 16, 8, 1};
        encode(fn, &tw1a, CU_TENSOR_MAP_DATA_TYPE_BFLOAT16, 4, p.w1, dims, st, ba, CU_TENSOR_MAP_SWIZZLE_128B);
        encode(fn, &tw1b, CU_TENSOR_MAP_DATA_TYPE_BFLOAT16, 4, p.w1, dims, st, bb, CU_TENSOR_MAP_SWIZZLE_128B);
    }
    {
        const cuuint64_t dims[3] = {64, F_, 32}, st[2] = {(cuuint64_t)S_ * 2, 128};
        const cuuint32_t bx[3] = {64, 64, 2};
        encode(fn, &tw2, CU_TENSOR_MAP_DATA_TYPE_BFLOAT16, 3, p.w2, dims, st, bx, CU_TENSOR_MAP_SWIZZLE_128B);
    }
    {
        const cuuint64_t dims[3] = {64, 72, 128}, st[2] = {256, 18432};
        const cuuint32_t ba[3] = {64, 18, 4}, bb[3] = {64, 9, 8};
        encode(fn, &th3a, CU_TENSOR_MAP_DATA_TYPE_UINT32, 3, h3p, dims, st, ba, CU_TENSOR_MAP_SWIZZLE_NONE);
        encode(fn, &th3b, CU_TENSOR_MAP_DATA_TYPE_UINT32, 3, h3p, dims, st, bb, CU_TENSOR_MAP_SWIZZLE_NONE);
    }
    {
        const cuuint64_t dims[4] = {32, 72, 2, 128}, st[3] = {256, 128, 18432};
        const cuuint32_t bx[4] = {32, 72, 2, 1};
        encode(fn, &th3s, CU_TENSOR_MAP_DATA_TYPE_UINT32, 4, h3p, dims, st, bx, CU_TENSOR_MAP_SWIZZLE_128B, CU_TENSOR_MAP_L2_PROMOTION_NONE);
    }
    {
        const cuuint64_t dims[3] = {4624, 4, 32}, st[2] = {9248 * 32, 9248};
        const cuuint32_t bx[3] = {56, 4, 32};
        encode(fn, &twr, CU_TENSOR_MAP_DATA_TYPE_BFLOAT16, 3, p.wr, dims, st, bx, CU_TENSOR_MAP_SWIZZLE_NONE);
        encode(fn, &twi, CU_TENSOR_MAP_DATA_TYPE_BFLOAT16, 3, p.wi, dims, st, bx, CU_TENSOR_MAP_SWIZZLE_NONE);
    }
    {
        const cuuint64_t dims[2] = {3456, 576}, st[1] = {6912};
        const cuuint32_t bx[2] = {32, 144};
        encode(fn, &tws, CU_TENSOR_MAP_DATA_TYPE_BFLOAT16, 2, p.wmod, dims, st, bx, CU_TENSOR_MAP_SWIZZLE_64B);
    }
    {
        const cuuint64_t dims[3] = {64, 576, 54}, st[2] = {6912, 128};
        const cuuint32_t bx[3] = {64, 32, 7};
        encode(fn, &twm, CU_TENSOR_MAP_DATA_TYPE_BFLOAT16, 3, p.wmod, dims, st, bx, CU_TENSOR_MAP_SWIZZLE_128B);
    }
    {
        const cuuint64_t dims[2] = {TP, 128}, st[1] = {TP * 4};
        const cuuint32_t ba[2] = {32, 128}, bb[2] = {8, 128};
        encode(fn, &tt, CU_TENSOR_MAP_DATA_TYPE_UINT32, 2, p.scr->T, dims, st, ba, CU_TENSOR_MAP_SWIZZLE_128B, CU_TENSOR_MAP_L2_PROMOTION_NONE);
        encode(fn, &ttx, CU_TENSOR_MAP_DATA_TYPE_UINT32, 2, p.scr->T, dims, st, bb, CU_TENSOR_MAP_SWIZZLE_32B, CU_TENSOR_MAP_L2_PROMOTION_NONE);
    }
    {
        const cuuint64_t dims[2] = {D_, S_}, st[1] = {D_ * 2};
        const cuuint32_t bx[2] = {144, 16};
        encode(fn, &to, CU_TENSOR_MAP_DATA_TYPE_BFLOAT16, 2, p.out, dims, st, bx, CU_TENSOR_MAP_SWIZZLE_NONE, CU_TENSOR_MAP_L2_PROMOTION_NONE);
    }
    cudaFuncSetAttribute(fused_kernel, cudaFuncAttributeMaxDynamicSharedMemorySize, SMEM_BYTES);
    cudaLaunchConfig_t cfg = {};
    cfg.gridDim = dim3(NCTA); cfg.blockDim = dim3(NTHR); cfg.dynamicSmemBytes = SMEM_BYTES; cfg.stream = cudaStreamPerThread;
    cudaLaunchAttribute at[1];
    at[0].id = cudaLaunchAttributeCooperative; at[0].val.cooperative = 1;
    cfg.attrs = at; cfg.numAttrs = 1;
    cudaLaunchKernelEx(&cfg, fused_kernel, p, tw1a, tw1b, tw2, th3a, th3b, twr, twi, twm, tt, ttx, to, th3s, tws);
}
```

```cpp
#include <cuda_runtime.h>
#include <cuda_bf16.h>
#include <cuda_fp16.h>
#include <cuda.h>
#include <stdint.h>

namespace {

constexpr int S_ = 2048, D_ = 576, F_ = 4608;
constexpr int NCTA = 132, NTHR = 512;
constexpr int TP = 4736;
constexpr int SPEC_P = 296;
constexpr int NST = 6;
constexpr int A_BYTES = 16384, B_BYTES = 18432;
constexpr int IT_P1 = 24, IT_G2 = 40, IT_END = 76;
constexpr int SPIN_LIMIT = 1 << 22;
#define X2D 1350
constexpr int P2S = 2;
#define LEAD1 4
#define W1N 8
#define W1P 100
#define W1S 5
#define XDELAY 1100
#define HOK 2
#define HOK1 2
#define NCP 10800
#define SLP 64
#define HOLD 1
#define PFD 0
#define FAP 0
#define X1D 2100
#define PF0 4
#define PFS 3
#define PFN 9
#define X1DELAY 2000
#define X1PACE 400

constexpr int OFF_A = 0;
constexpr int OFF_B = NST * A_BYTES;
constexpr int OFF_P = OFF_B + NST * B_BYTES;
constexpr int OFF_BAR = OFF_P;
constexpr int OFF_EPOCH = OFF_P + 480;
constexpr int OFF_MISC = OFF_P + 496;
constexpr int OFF_GB = OFF_P + 512;
constexpr int OFF_P2R = OFF_P + 1664;
constexpr int OFF_X1 = OFF_P2R;
constexpr int OFF_PROF = OFF_X1 + 18432;
constexpr int SMEM_BYTES = OFF_PROF + 512 + 1024;
constexpr int QA = 13, QB = 7, QC = 13;
constexpr int TAB_BYTES = (QA + QB + QC) * 512;
constexpr int OFF_STAGE = OFF_B;
constexpr int OFF_STX = OFF_STAGE + 16384;
constexpr int OFF_TAB = OFF_STAGE + 20480;
constexpr int OFF_SPEC = OFF_TAB + TAB_BYTES;
constexpr int OFF_WRAW = OFF_SPEC + 19072;
constexpr int OFF_B3 = OFF_WRAW + 28672;
constexpr int OFF_MODA = OFF_B3 + 4096;
constexpr int OFF_MODC = OFF_MODA + 2560;
constexpr int OFF_RED = OFF_MODC + 3584;
constexpr int OFF_SILU = OFF_RED + 1536;
static_assert(OFF_SILU + 1152 <= OFF_P && 6 * 28672 <= OFF_B3, "scratch overflow");
constexpr int OFF_STRIP = OFF_A;
static_assert(OFF_WRAW % 128 == 0 && OFF_STAGE % 128 == 0 && OFF_STX % 128 == 0, "align");
constexpr int BAR_FULL = 0, BAR_EMPTY = 6, BAR_TAB = 12, BAR_W = 13, BAR_P2R = 16,
              BAR_XT = 17, BAR_RECV = 18, BAR_ROLE = 19, BAR_NC = 20, BAR_TAB2 = 21, BAR_XB = 22, BAR_GB = 23, BAR_HOLD = 24, BAR_W1GO = 25, BAR_UOK = 26, BAR_DONE = 30, BAR_X = 31, BAR_ST = 47;

struct Cos1152 { double c[1152]; };
constexpr double cx_cos(double x) { double t = 1, s = 1; for (int i = 1; i < 14; i++) { t *= -x * x / ((2 * i - 1) * (2 * i)); s += t; } return s; }
constexpr Cos1152 make_cos() {
    Cos1152 r{};
    for (int i = 0; i <= 288; i++) {
        double v = (i == 288) ? 0.0 : cx_cos(3.14159265358979323846 * 2.0 * i / 1152.0);
        r.c[i] = v; r.c[576 - i] = -v; r.c[576 + i] = -v; r.c[(1152 - i) % 1152] = v;
    }
    return r;
}
constexpr uint32_t cx_f2h(double v) {
    uint32_t s = v < 0 ? 0x8000u : 0u; double a = v < 0 ? -v : v;
    if (a < 1e-9) return 0;
    int e = 0;
    while (a >= 2.0) { a *= 0.5; e++; }
    while (a < 1.0 && e > -14) { a *= 2.0; e--; }
    double m = a * 1024.0; uint32_t mi = (uint32_t)m; double fr = m - mi;
    if (fr > 0.5 || (fr == 0.5 && (mi & 1))) mi++;
    return s | (uint32_t)(((e + 14) << 10) + mi);
}
struct Tab { uint32_t w[(QA + QB + QC) * 128]; };
constexpr Tab make_tab() {
    Tab t{};
    Cos1152 ct = make_cos();
    auto C = [&](int num, int den) { return ct.c[(num % den) * (1152 / den)]; };
    auto Sn = [&](int num, int den) { return ct.c[((num % den) * (1152 / den) + 864) % 1152]; };
    auto put = [&](int q0, int idx, int lane, double lo, double hi) { t.w[((q0 + idx / 4) * 32 + lane) * 4 + idx % 4] = cx_f2h(lo) | (cx_f2h(hi) << 16); };
    for (int lane = 0; lane < 32; lane++) {
        const int g = lane >> 2, q = lane & 3;
        for (int mt = 0; mt < 3; mt++) {
            const int ka = 8 * mt + g;
            for (int r = 0; r < 10; r++) {
                const int im = r & 1, i0 = (r >> 1) * 2;
                double v[2] = {0, 0};
                for (int e = 0; e < 2; e++) { int i = i0 + e, d1 = 4 * i + q; if (i < 9 && ka <= 18) v[e] = (im ? -Sn(ka * d1, 36) : C(ka * d1, 36)) / 8; }
                put(0, r < 8 ? mt * 8 + r : 16 + 2 * mt + r, lane, v[0], v[1]);
            }
            for (int v = 0; v < 2; v++) {
                const int d2 = 4 * q + v;
                put(0, 30 + (mt * 2 + v) * 2, lane, C(ka * d2, 576) * 4 / 3, C(ka * (d2 + 2), 576) * 4 / 3);
                put(0, 31 + (mt * 2 + v) * 2, lane, Sn(ka * d2, 576) * 4 / 3, Sn(ka * (d2 + 2), 576) * 4 / 3);
            }
        }
        for (int v = 0; v < 2; v++) for (int nt = 0; nt < 2; nt++) {
            const int kb = 2 * (g >> 1) + nt, part = g & 1;
            double b0[2] = {0, 0}, b1[2] = {0, 0};
            for (int e = 0; e < 2; e++) { int d2 = 4 * q + 2 * e + v; double c = C(kb * d2, 16) / 4, s = Sn(kb * d2, 16) / 4;
                b0[e] = part ? -s : c; b1[e] = part ? c : s; }
            put(0, 42 + (v * 2 + nt) * 2, lane, b0[0], b0[1]); put(0, 43 + (v * 2 + nt) * 2, lane, b1[0], b1[1]);
        }
        t.w[((QA - 1) * 32 + lane) * 4 + 2] = 0x3F803F80u;
        for (int par = 0; par < 2; par++) for (int a = 0; a < 4; a++) {
            const int ja = 2 * (q + 4 * (a >> 1)) + par; const double c = C(g * ja, 16) / 4, s = Sn(g * ja, 16) / 4;
            put(QA, par * 4 + a, lane, (a & 1) ? -s : c, (a & 1) ? c : s);
        }
        for (int h = 0; h < 2; h++) {
            put(QA, 8 + 2 * h, lane, C((g + 8 * h) * (2 * q), 128) / 2, C((g + 8 * h) * (2 * q + 1), 128) / 2);
            put(QA, 9 + 2 * h, lane, Sn((g + 8 * h) * (2 * q), 128) / 2, Sn((g + 8 * h) * (2 * q + 1), 128) / 2);
            put(QA, 16 + 2 * h, lane, C(g * (8 * h + 2 * q), 128), C(g * (8 * h + 2 * q + 1), 128));
            put(QA, 17 + 2 * h, lane, Sn(g * (8 * h + 2 * q), 128), Sn(g * (8 * h + 2 * q + 1), 128));
        }
        put(QA, 12, lane, C(g * 2 * q, 8) / 2, C(g * (2 * q + 1), 8) / 2);
        put(QA, 15, lane, C(g * 2 * q, 8) / 2, C(g * (2 * q + 1), 8) / 2);
        put(QA, 13, lane, Sn(g * 2 * q, 8) / 2, Sn(g * (2 * q + 1), 8) / 2);
        put(QA, 14, lane, -Sn(g * 2 * q, 8) / 2, -Sn(g * (2 * q + 1), 8) / 2);
        for (int u = 0; u < 4; u++) {
            const int ja = 2 * ((g >> 1) + 4 * (u & 1)) + (u >> 1), part = g & 1; double b0[2] = {0, 0}, b1[2] = {0, 0};
            for (int e = 0; e < 2; e++) { int ka = 2 * q + e; double c = C(ja * ka, 16) / 4, s = Sn(ja * ka, 16) / 4;
                b0[e] = part ? s : c; b1[e] = part ? c : -s; }
            put(QA, 20 + u * 2, lane, b0[0], b0[1]); put(QA, 21 + u * 2, lane, b1[0], b1[1]);
        }
        for (int m2 = 0; m2 < 2; m2++) {
            const int d2 = 2 * g + m2;
            for (int a = 0; a < 4; a++) {
                const int kb = 2 * q + (a >> 1); const double c = C(d2 * kb, 16) / 4, s = Sn(d2 * kb, 16) / 4;
                put(QA + QB, m2 * 4 + a, lane, (a & 1) ? s : c, (a & 1) ? c : -s);
            }
            for (int mt = 0; mt < 3; mt++) {
                const int ka = 8 * mt + 2 * q;
                put(QA + QB, 8 + (m2 * 3 + mt) * 2, lane, C(ka * d2, 576) * 4 / 3, C((ka + 1) * d2, 576) * 4 / 3);
                put(QA + QB, 9 + (m2 * 3 + mt) * 2, lane, Sn(ka * d2, 576) * 4 / 3, Sn((ka + 1) * d2, 576) * 4 / 3);
            }
        }
        for (int mt = 0; mt < 3; mt++) for (int nt = 0; nt < 5; nt++) {
            const int i = 2 * nt + (g & 1), d1 = 4 * i + (g >> 1); double b0[2] = {0, 0}, b1[2] = {0, 0};
            for (int e = 0; e < 2; e++) { int ka = 8 * mt + 2 * q + e;
                if (ka <= 18 && i < 9) { double wt = (ka == 0 || ka == 18) ? 0.125 : 0.25; b0[e] = wt * C(ka * d1, 36); b1[e] = -wt * Sn(ka * d1, 36); } }
            const int o = (QA + QB + 5) * 128 + (mt * 5 + nt) * 64 + lane;
            t.w[o] = cx_f2h(b0[0]) | (cx_f2h(b0[1]) << 16); t.w[o + 32] = cx_f2h(b1[0]) | (cx_f2h(b1[1]) << 16);
        }
    }
    return t;
}
__device__ __align__(128) const Tab g_tab = make_tab();

struct Scratch {
    uint32_t cnt[30 * 32];
    uint32_t slot[96];
    uint32_t mod[2304];
    uint32_t modc[896 + 288];
    uint32_t T[128 * TP];
    uint4 h3[128 * 1152];
    uint4 U[72 * 4 * 1152];
};
__device__ __align__(1024) Scratch g_scr;
#define g_cnt (p.scr->cnt)
#define g_slot (p.scr->slot)
#define g_mod (p.scr->mod)
#define g_T (p.scr->T)
#define g_h3 (p.scr->h3)
#define g_U (p.scr->U)
constexpr int CNT_EPOCH = 0, CNT_H3 = 1, CNT_X1 = 26, CNT_NC = 27, CNT_U = 2;
#define PROFT(i) do {} while (0)
#define PROFDUMP() do {} while (0)
#define PROF0(i) do {} while (0)

__device__ __forceinline__ void mbar_init(uint32_t bar, uint32_t cnt) { asm volatile("mbarrier.init.shared::cta.b64 [%0], %1;" :: "r"(bar), "r"(cnt) : "memory"); }
__device__ __forceinline__ void mbar_expect(uint32_t bar, uint32_t bytes) { asm volatile("mbarrier.arrive.expect_tx.shared::cta.b64 _, [%0], %1;" :: "r"(bar), "r"(bytes) : "memory"); }
__device__ __forceinline__ void mbar_arrive(uint32_t bar) { asm volatile("mbarrier.arrive.shared::cta.b64 _, [%0];" :: "r"(bar) : "memory"); }
__device__ __forceinline__ void mbar_arrive_n(uint32_t bar, uint32_t n) { asm volatile("mbarrier.arrive.shared::cta.b64 _, [%0], %1;" :: "r"(bar), "r"(n) : "memory"); }
__device__ __forceinline__ void mbar_arrive_remote(uint32_t rbar) { asm volatile("mbarrier.arrive.relaxed.cluster.shared::cluster.b64 _, [%0];" :: "r"(rbar) : "memory"); }
__device__ __forceinline__ void mbar_wait(uint32_t bar, uint32_t parity) {
    asm volatile("{.reg .pred p; .reg .u32 c;\n"
        "mbarrier.try_wait.parity.shared::cta.b64 p, [%0], %1;\n@p bra.uni DONE;\nmov.u32 c, 0;\n"
        "LOOP: mbarrier.try_wait.parity.shared::cta.b64 p, [%0], %1;\n@p bra.uni DONE;\n"
        "add.u32 c, c, 1;\nsetp.lt.u32 p, c, %2;\n@p bra.uni LOOP;\ntrap;\nDONE:}" :: "r"(bar), "r"(parity), "n"(SPIN_LIMIT) : "memory");
}
__device__ __forceinline__ bool mbar_test(uint32_t bar, uint32_t parity) {
    uint32_t ok; asm volatile("{.reg .pred p; mbarrier.test_wait.parity.shared::cta.b64 p, [%1], %2; selp.u32 %0, 1, 0, p;}" : "=r"(ok) : "r"(bar), "r"(parity) : "memory"); return ok; }
__device__ __forceinline__ uint32_t mapa(uint32_t a, uint32_t rank) { uint32_t r; asm("mapa.shared::cluster.u32 %0, %1, %2;" : "=r"(r) : "r"(a), "r"(rank)); return r; }
__device__ __forceinline__ uint32_t clk32() { uint32_t r; asm volatile("mov.u32 %0, %%clock;" : "=r"(r)); return r; }
__device__ __forceinline__ void hb() {
    asm volatile("{.reg .b32 a, b; .reg .pred p; mma.sync.aligned.m16n8k8.row.col.f16.f16.f16.f16 {a, b}, {%0,%0}, {%0}, {%0,%0};\n"
                 "setp.ne.u32 p, a, 0; @p trap;}" :: "r"(0));
}
__device__ __forceinline__ void spin_until(uint32_t t) {
    while (__any_sync(~0u, (int)(clk32() - t) < -SLP * 4)) { __nanosleep(SLP); hb(); }
    while (__any_sync(~0u, (int)(clk32() - t) < 0)) {}
}
__device__ __forceinline__ bool elect() { uint32_t r; asm volatile("{.reg .pred p; elect.sync _|p, 0xffffffff; selp.u32 %0, 1, 0, p;}" : "=r"(r)); return r; }
__device__ __forceinline__ void bar_sync(int id, int n) { asm volatile("bar.sync %0, %1;" :: "r"(id), "r"(n) : "memory"); }
__device__ __forceinline__ void bulk_load(uint32_t dst, const void* src, uint32_t bytes, uint32_t bar) {
    asm volatile("cp.async.bulk.shared::cluster.global.mbarrier::complete_tx::bytes [%0], [%1], %2, [%3];" :: "r"(dst), "l"(src), "r"(bytes), "r"(bar) : "memory"); }
__device__ __forceinline__ void tma2(uint32_t dst, const CUtensorMap* m, int c0, int c1, uint32_t bar) {
    asm volatile("cp.async.bulk.tensor.2d.shared::cluster.global.mbarrier::complete_tx::bytes [%0], [%1, {%3, %4}], [%2];" :: "r"(dst), "l"(m), "r"(bar), "r"(c0), "r"(c1) : "memory"); }
__device__ __forceinline__ void tma3(uint32_t dst, const CUtensorMap* m, int c0, int c1, int c2, uint32_t bar) {
    asm volatile("cp.async.bulk.tensor.3d.shared::cluster.global.mbarrier::complete_tx::bytes [%0], [%1, {%3, %4, %5}], [%2];" :: "r"(dst), "l"(m), "r"(bar), "r"(c0), "r"(c1), "r"(c2) : "memory"); }
__device__ __forceinline__ void tma4(uint32_t dst, const CUtensorMap* m, int c0, int c1, int c2, int c3, uint32_t bar) {
    asm volatile("cp.async.bulk.tensor.4d.shared::cluster.global.mbarrier::complete_tx::bytes [%0], [%1, {%3, %4, %5, %6}], [%2];" :: "r"(dst), "l"(m), "r"(bar), "r"(c0), "r"(c1), "r"(c2), "r"(c3) : "memory"); }
__device__ __forceinline__ void fence_async_g() { asm volatile("fence.proxy.async.global;" ::: "memory"); }
__device__ __forceinline__ void fence_async_s() { asm volatile("fence.proxy.async.shared::cta;" ::: "memory"); }
__device__ __forceinline__ uint4 lds128(uint32_t a) { uint4 v; asm volatile("ld.shared.v4.u32 {%0,%1,%2,%3}, [%4];" : "=r"(v.x), "=r"(v.y), "=r"(v.z), "=r"(v.w) : "r"(a) : "memory"); return v; }
__device__ __forceinline__ uint32_t lds32(uint32_t a) { uint32_t v; asm volatile("ld.shared.u32 %0, [%1];" : "=r"(v) : "r"(a) : "memory"); return v; }
__device__ __forceinline__ void sts128(uint32_t a, uint4 v) { asm volatile("st.shared.v4.u32 [%0], {%1,%2,%3,%4};" :: "r"(a), "r"(v.x), "r"(v.y), "r"(v.z), "r"(v.w) : "memory"); }
__device__ __forceinline__ void sts32(uint32_t a, uint32_t v) { asm volatile("st.shared.u32 [%0], %1;" :: "r"(a), "r"(v) : "memory"); }
__device__ __forceinline__ void sts16(uint32_t a, uint32_t v) { asm volatile("st.shared.u16 [%0], %1;" :: "r"(a), "h"((uint16_t)v) : "memory"); }
__device__ __forceinline__ uint4 ldx128(const void* p) {
    uint4 v; asm volatile("{.reg .b128 t; .reg .b64 a, b; ld.relaxed.gpu.global.b128 t, [%4]; mov.b128 {a, b}, t; mov.b64 {%0,%1}, a; mov.b64 {%2,%3}, b;}"
        : "=r"(v.x), "=r"(v.y), "=r"(v.z), "=r"(v.w) : "l"(p) : "memory"); return v; }
__device__ __forceinline__ void stx128(void* p, uint4 v) {
    asm volatile("{.reg .b128 t; .reg .b64 a, b; mov.b64 a, {%1,%2}; mov.b64 b, {%3,%4}; mov.b128 t, {a, b}; st.relaxed.gpu.global.b128 [%0], t;}"
        :: "l"(p), "r"(v.x), "r"(v.y), "r"(v.z), "r"(v.w) : "memory"); }
__device__ __forceinline__ uint32_t ld_acquire(const uint32_t* p) { uint32_t v; asm volatile("ld.acquire.gpu.global.u32 %0, [%1];" : "=r"(v) : "l"(p) : "memory"); return v; }
__device__ __forceinline__ void st_relaxed(uint32_t* p, uint32_t v) { asm volatile("st.relaxed.gpu.global.u32 [%0], %1;" :: "l"(p), "r"(v) : "memory"); }
__device__ __forceinline__ void red_release(uint32_t* p) { asm volatile("red.release.gpu.global.add.u32 [%0], 1;" :: "l"(p) : "memory"); }
template <int SLEEP> __device__ __forceinline__ void wait_count(const uint32_t* p, uint32_t target) {
    int it = 0; while ((int)(ld_acquire(p) - target) < 0) { if (SLEEP) __nanosleep(SLEEP); if (++it > SPIN_LIMIT) __trap(); }
}
__device__ __forceinline__ uint32_t ldg_nc32(const void* p) { uint32_t v; asm volatile("ld.global.nc.L1::no_allocate.u32 %0, [%1];" : "=r"(v) : "l"(p)); return v; }
__device__ __forceinline__ uint32_t ldg_nc16(const void* p) { uint16_t v; asm volatile("ld.global.nc.u16 %0, [%1];" : "=h"(v) : "l"(p)); return v; }
__device__ __forceinline__ float bf_lo(uint32_t w) { return __uint_as_float(w << 16); }
__device__ __forceinline__ float bf_hi(uint32_t w) { return __uint_as_float(w & 0xFFFF0000u); }
__device__ __forceinline__ uint32_t pack_bf(float lo, float hi) { uint32_t r; asm("cvt.rn.bf16x2.f32 %0, %1, %2;" : "=r"(r) : "f"(hi), "f"(lo)); return r; }
__device__ __forceinline__ uint32_t pack_h(float lo, float hi) { uint32_t r; asm("cvt.rn.f16x2.f32 %0, %1, %2;" : "=r"(r) : "f"(hi), "f"(lo)); return r; }
__device__ __forceinline__ float bf_round(float v) { return bf_lo(pack_bf(v, 0.f)); }
__device__ __forceinline__ uint32_t hmul2(uint32_t a, uint32_t b) { uint32_t r; asm("mul.rn.f16x2 %0, %1, %2;" : "=r"(r) : "r"(a), "r"(b)); return r; }
__device__ __forceinline__ uint32_t hfma2(uint32_t a, uint32_t b, uint32_t c) { uint32_t r; asm("fma.rn.f16x2 %0, %1, %2, %3;" : "=r"(r) : "r"(a), "r"(b), "r"(c)); return r; }
__device__ __forceinline__ uint32_t hfms2(uint32_t a, uint32_t b, uint32_t c) { uint32_t r; asm("{.reg .b32 t; neg.f16x2 t, %3; fma.rn.f16x2 %0, %1, %2, t;}" : "=r"(r) : "r"(a), "r"(b), "r"(c)); return r; }
__device__ __forceinline__ uint32_t hadd2(uint32_t a, uint32_t b) { uint32_t r; asm("add.rn.f16x2 %0, %1, %2;" : "=r"(r) : "r"(a), "r"(b)); return r; }
__device__ __forceinline__ uint32_t hsub2(uint32_t a, uint32_t b) { uint32_t r; asm("sub.rn.f16x2 %0, %1, %2;" : "=r"(r) : "r"(a), "r"(b)); return r; }
__device__ __forceinline__ void cmul_neg(uint32_t& re, uint32_t& im, uint32_t c, uint32_t s) { uint32_t a = hfma2(re, c, hmul2(im, s)), b = hfms2(im, c, hmul2(re, s)); re = a; im = b; }
__device__ __forceinline__ void cmul_pos(uint32_t& re, uint32_t& im, uint32_t c, uint32_t s) { uint32_t a = hfms2(re, c, hmul2(im, s)), b = hfma2(im, c, hmul2(re, s)); re = a; im = b; }
__device__ __forceinline__ void mma_h(uint32_t& d0, uint32_t& d1, uint32_t a0, uint32_t a1, uint32_t a2, uint32_t a3, uint32_t b0, uint32_t b1) {
    asm("mma.sync.aligned.m16n8k16.row.col.f16.f16.f16.f16 {%0,%1}, {%2,%3,%4,%5}, {%6,%7}, {%0,%1};" : "+r"(d0), "+r"(d1) : "r"(a0), "r"(a1), "r"(a2), "r"(a3), "r"(b0), "r"(b1)); }
__device__ __forceinline__ void mma_h8(uint32_t& d0, uint32_t& d1, uint32_t a0, uint32_t a1, uint32_t b0) {
    asm("mma.sync.aligned.m16n8k8.row.col.f16.f16.f16.f16 {%0,%1}, {%2,%3}, {%4}, {%0,%1};" : "+r"(d0), "+r"(d1) : "r"(a0), "r"(a1), "r"(b0)); }
template <int NQ> __device__ __forceinline__ void load_tab(uint32_t (&r)[NQ * 4], uint32_t addr) {
    #pragma unroll
    for (int i = 0; i < NQ; i++) { uint4 v = lds128(addr + i * 512); r[4 * i] = v.x; r[4 * i + 1] = v.y; r[4 * i + 2] = v.z; r[4 * i + 3] = v.w; }
}
__device__ __forceinline__ float gelu2(float x) {
    float t = x * fmaf(x * x, 0.044715f * 0.7978845608028654f, 0.7978845608028654f), th;
    asm volatile("tanh.approx.f32 %0, %1;" : "=f"(th) : "f"(t));
    return fmaf(x, th, x);
}
__device__ __forceinline__ uint32_t desc_lo(uint32_t addr, uint32_t lbo) { return ((addr & 0x3FFFF) >> 4) | ((lbo >> 4) << 16); }
constexpr uint32_t DHI_A = (1024 >> 4) | (1u << 30), DHI_H3 = 256 >> 4, DHI_U = 128 >> 4;
#define WG_FENCE() asm volatile("wgmma.fence.sync.aligned;" ::: "memory")
#define WG_COMMIT() asm volatile("wgmma.commit_group.sync.aligned;" ::: "memory")
#define WG_WAIT(n) asm volatile("wgmma.wait_group.sync.aligned %0;" :: "n"(n) : "memory")
#define R4(b) "+f"(d[b]), "+f"(d[b + 1]), "+f"(d[b + 2]), "+f"(d[b + 3])
#define R12(b) R4(b), R4(b + 4), R4(b + 8)
#define R36(b) R12(b), R12(b + 12), R12(b + 24)
template <uint32_t BHI> __device__ __forceinline__ void wgmma144(float (&d)[72], uint32_t da, uint32_t db, int acc) {
    asm volatile("{.reg .pred p; .reg .b64 a, b; setp.ne.b32 p, %74, 0; mov.b64 a, {%72, %75}; mov.b64 b, {%73, %76};\n"
        "wgmma.mma_async.sync.aligned.m64n144k16.f32.bf16.bf16 {%0,%1,%2,%3,%4,%5,%6,%7,%8,%9,%10,%11,%12,%13,%14,%15,%16,%17,%18,%19,%20,%21,%22,%23,"
        "%24,%25,%26,%27,%28,%29,%30,%31,%32,%33,%34,%35,%36,%37,%38,%39,%40,%41,%42,%43,%44,%45,%46,%47,"
        "%48,%49,%50,%51,%52,%53,%54,%55,%56,%57,%58,%59,%60,%61,%62,%63,%64,%65,%66,%67,%68,%69,%70,%71}, a, b, p, 1, 1, 1, 1;}\n"
        : R36(0), R36(36) : "r"(da), "r"(db), "r"(acc), "n"(DHI_A), "n"(BHI));
}
__device__ __forceinline__ void wgmma144x4(float (&d)[72], const uint64_t (&a)[4], const uint64_t (&b)[4]) {
    #define WG144 "wgmma.mma_async.sync.aligned.m64n144k16.f32.bf16.bf16 {%0,%1,%2,%3,%4,%5,%6,%7,%8,%9,%10,%11,%12,%13,%14,%15,%16,%17,%18,%19,%20,%21,%22,%23,%24,%25,%26,%27,%28,%29,%30,%31,%32,%33,%34,%35,%36,%37,%38,%39,%40,%41,%42,%43,%44,%45,%46,%47,%48,%49,%50,%51,%52,%53,%54,%55,%56,%57,%58,%59,%60,%61,%62,%63,%64,%65,%66,%67,%68,%69,%70,%71}, "
    asm volatile("{"
        WG144 "%72, %76, 1, 1, 1, 1, 1;\n" WG144 "%73, %77, 1, 1, 1, 1, 1;\n" WG144 "%74, %78, 1, 1, 1, 1, 1;\n" WG144 "%75, %79, 1, 1, 1, 1, 1;}\n"
        : R36(0), R36(36) : "l"(a[0]), "l"(a[1]), "l"(a[2]), "l"(a[3]), "l"(b[0]), "l"(b[1]), "l"(b[2]), "l"(b[3]));
}
__device__ __forceinline__ void wgmma40_rs(float (&d)[20], uint32_t a0, uint32_t a1, uint32_t a2, uint32_t a3, uint32_t db, int acc) {
    asm volatile("{.reg .pred p; .reg .b64 b; setp.ne.b32 p, %25, 0; mov.b64 b, {%24, %26};\n"
        "wgmma.mma_async.sync.aligned.m64n40k16.f32.f16.f16 {%0,%1,%2,%3,%4,%5,%6,%7,%8,%9,%10,%11,%12,%13,%14,%15,%16,%17,%18,%19}, {%20,%21,%22,%23}, b, p, 1, 1, 0;}\n"
        : R12(0), R4(12), R4(16) : "r"(a0), "r"(a1), "r"(a2), "r"(a3), "r"(db), "r"(acc), "n"(DHI_H3));
}
__device__ __forceinline__ void wgmma72(float (&d)[36], uint32_t da, uint32_t db, int acc) {
    asm volatile("{.reg .pred p; .reg .b64 a, b; setp.ne.b32 p, %38, 0; mov.b64 a, {%36, %39}; mov.b64 b, {%37, %40};\n"
        "wgmma.mma_async.sync.aligned.m64n72k16.f32.bf16.bf16 {%0,%1,%2,%3,%4,%5,%6,%7,%8,%9,%10,%11,%12,%13,%14,%15,%16,%17,%18,%19,%20,%21,%22,%23,"
        "%24,%25,%26,%27,%28,%29,%30,%31,%32,%33,%34,%35}, a, b, p, 1, 1, 1, 1;}\n"
        : R36(0) : "r"(da), "r"(db), "r"(acc), "n"(DHI_A), "n"(DHI_H3));
}

__device__ __forceinline__ int g2_kb(int n, int kh, int gi, int c2) {
    if (n < 4) return 36 * kh + 9 * n + 8;
    if (n == 4) return 9 * gi + 4 * c2 + 2 * kh + 1;
    const int w = n > 20, m = n - (w ? 19 : 5);
    return 9 * ((gi * w + (m >> 1)) & 7) + 4 * (n == 35 ? 1 - c2 : m & 1) + 2 * kh + w;
}

__device__ __forceinline__ void add_lo(uint64_t& d, uint32_t a) { asm("{.reg .b32 l, h; mov.b64 {l, h}, %0; add.u32 l, l, %1; mov.b64 %0, {l, h};}" : "+l"(d) : "r"(a)); }
template <uint32_t BHI, int I0, int I1, bool FIRST, class Hook>
__device__ __forceinline__ void mainloop(float (&d)[72], uint32_t bars, uint32_t da0, uint32_t db0, bool lead, Hook hook) {
    uint32_t s = I0 % NST, ph = (I0 / NST) & 1, prev = (I0 + NST - (I0 == IT_P1 ? 2 : 1)) % NST;
    uint32_t ready = 0;
    uint64_t da[4], db[4];
    #pragma unroll
    for (int k = 0; k < 4; k++) { da[k] = ((uint64_t)DHI_A << 32) + da0 + s * (A_BYTES / 16) + k * 128; db[k] = ((uint64_t)BHI << 32) + db0 + s * (B_BYTES / 16) + k * 288; }
    #pragma unroll 1
    for (int i = I0; i < I1; i++) {
        if (!ready) mbar_wait(bars + 8 * BAR_FULL + 8 * s, ph);
        const uint32_t rel = bars + 8 * BAR_EMPTY + 8 * prev, ph0 = ph; const int i0 = i;
        const bool skip = I1 == IT_P1 && (s == P2S - 1 || s == P2S + 2);
        prev = s; s += skip ? 2 : 1; if (s >= NST) { s -= NST; ph ^= 1; }
        const uint32_t adva = (s - prev) * (A_BYTES / 16), advb = (s - prev) * (B_BYTES / 16);
        WG_FENCE();
        wgmma144x4(d, da, db);
        WG_COMMIT();
        #pragma unroll
        for (int k = 0; k < 4; k++) { add_lo(da[k], adva); add_lo(db[k], advb); }
        if (skip) { mbar_wait(bars + 8 * BAR_FULL + 8 * prev + 8, ph0); i++; }
        ready = __shfl_sync(~0u, (uint32_t)mbar_test(bars + 8 * BAR_FULL + 8 * s, ph), 0);
        WG_WAIT(1);
        if (lead && (!FIRST || i0 > I0)) mbar_arrive(rel);
        hook(i0);
    }
}

struct Params {
    const uint16_t *wmod, *c, *x;
    Scratch* scr;
    const Tab* tab;
    const uint16_t *wr, *wi, *w1, *b1, *w2, *b2;
    uint16_t* out;
};

__device__ __forceinline__ void mma_bf(float (&d)[4], const uint32_t (&a)[4], uint32_t b0, uint32_t b1) {
    asm("mma.sync.aligned.m16n8k16.row.col.f32.bf16.bf16.f32 {%0,%1,%2,%3}, {%4,%5,%6,%7}, {%8,%9}, {%0,%1,%2,%3};"
        : "+f"(d[0]), "+f"(d[1]), "+f"(d[2]), "+f"(d[3]) : "r"(a[0]), "r"(a[1]), "r"(a[2]), "r"(a[3]), "r"(b0), "r"(b1)); }
__device__ __forceinline__ void ldsm4t(uint32_t (&a)[4], uint32_t addr) {
    asm volatile("ldmatrix.sync.aligned.m8n8.x4.trans.shared.b16 {%0,%1,%2,%3}, [%4];" : "=r"(a[0]), "=r"(a[1]), "=r"(a[2]), "=r"(a[3]) : "r"(addr) : "memory"); }
__device__ __forceinline__ void ln_stats(const uint32_t (&w)[9], const uint32_t (&one)[9], int g, int q, float& r, float& mr) {
    float c[2][4] = {};
    #pragma unroll
    for (int p = 0; p < 9; p++)
        asm("mma.sync.aligned.m16n8k8.row.col.f32.bf16.bf16.f32 {%0,%1,%2,%3}, {%4,%5}, {%4}, {%0,%1,%2,%3};"
            : "+f"(c[p & 1][0]), "+f"(c[p & 1][1]), "+f"(c[p & 1][2]), "+f"(c[p & 1][3]) : "r"(w[p]), "r"(one[p]));
    const float t = (g & 1) ? c[0][1] + c[1][1] : c[0][0] + c[1][0];
    float s1 = (c[0][2] + c[1][2]) + (c[0][3] + c[1][3]), s2 = __shfl_sync(~0u, t, 9 * q) + __shfl_sync(~0u, t, 9 * q + 4);
    #pragma unroll
    for (int o = 1; o < 4; o <<= 1) { s1 += __shfl_xor_sync(~0u, s1, o); s2 += __shfl_xor_sync(~0u, s2, o); }
    const float m = s1 * (1.f / D_);
    asm("rsqrt.approx.ftz.f32 %0, %1;" : "=f"(r) : "f"(fmaxf(fmaf(s2, 1.f / D_, -m * m), 0.f) + 1e-5f));
    mr = -m * r;
}
__device__ __forceinline__ float silu(float v) { return __fdividef(v, 1.f + __expf(-v)); }
__device__ __forceinline__ uint32_t bfma2(uint32_t a, uint32_t b, uint32_t c) { uint32_t r; asm("fma.rn.bf16x2 %0, %1, %2, %3;" : "=r"(r) : "r"(a), "r"(b), "r"(c)); return r; }
__device__ __forceinline__ void radix16(const uint4 (&V)[4], const uint32_t (&B)[16], uint4 (&o)[4]) {
    #pragma unroll
    for (int nt = 0; nt < 4; nt++) o[nt] = make_uint4(0, 0, 0, 0);
    #pragma unroll
    for (int u = 0; u < 4; u++)
        #pragma unroll
        for (int nt = 0; nt < 4; nt++) {
            const uint32_t b = B[((u >> 1) * 4 + nt) * 2 + (u & 1)];
            mma_h8(o[nt].x, o[nt].y, V[u].x, V[u].y, b); mma_h8(o[nt].z, o[nt].w, V[u].z, V[u].w, b);
        }
}
template <int OFF, int N> __device__ __forceinline__ void gelu_store(const float (&d)[N], char* p, int q) {
    uint32_t w[9];
    #pragma unroll
    for (int blk = 0; blk < 9; blk++) w[blk] = pack_bf(gelu2(d[OFF + 4 * blk]), gelu2(d[OFF + 4 * blk + 1]));
    asm volatile("st.v4.u32 [%0], {%1,%2,%3,%4};" :: "l"(p + q * 128), "r"(w[0]), "r"(w[1]), "r"(w[2]), "r"(w[3]) : "memory");
    asm volatile("st.v4.u32 [%0+512], {%1,%2,%3,%4};" :: "l"(p + q * 128), "r"(w[4]), "r"(w[5]), "r"(w[6]), "r"(w[7]) : "memory");
    asm volatile("st.u32 [%0+1024], %1;" :: "l"(p + q * 4), "r"(w[8]) : "memory");
}

__global__ void __cluster_dims__(2, 1, 1) __launch_bounds__(NTHR, 1)
fused_kernel(const Params p,
             const __grid_constant__ CUtensorMap tm_w1a, const __grid_constant__ CUtensorMap tm_w1b, const __grid_constant__ CUtensorMap tm_w2,
             const __grid_constant__ CUtensorMap tm_h3a, const __grid_constant__ CUtensorMap tm_h3b,
             const __grid_constant__ CUtensorMap tm_wr, const __grid_constant__ CUtensorMap tm_wi, const __grid_constant__ CUtensorMap tm_wm,
             const __grid_constant__ CUtensorMap tm_t, const __grid_constant__ CUtensorMap tm_tx, const __grid_constant__ CUtensorMap tm_o,
             const __grid_constant__ CUtensorMap tm_h3s, const __grid_constant__ CUtensorMap tm_ws)
{
    extern __shared__ char smem_raw[];
    const uint32_t t0 = clk32();
    const uint32_t sm = __shfl_sync(~0u, ((uint32_t)__cvta_generic_to_shared(smem_raw) + 1023u) & ~1023u, 0);
    const int tid = threadIdx.x, warp = __shfl_sync(~0u, tid >> 5, 0), lane = tid & 31, g = lane >> 2, q = lane & 3;
    const int b = blockIdx.x;
    const uint32_t rank = b & 1;
    const uint32_t bars = sm + OFF_BAR;
    const bool rowcta = b < 128;

    auto nc_issue = [&](int st, uint32_t sl) {
        const int pass = st >= 18;
        mbar_expect(bars + 8 * (BAR_X + sl), 28672);
        tma3(sm + sl * 28672, &tm_wm, 0, 32 * (st - 18 * pass), 18 + 28 * pass + 7 * (b - 128), bars + 8 * (BAR_X + sl));
    };
    uint32_t epoch;
    const bool strip = b < 72 && !(b & 1);
    const bool sil = (warp >> 2) == 2 && lane < 24 && (strip || !rowcta);
    uint32_t cw[3];
    if (elect()) {
        mbar_init(bars + 8 * (BAR_X + warp), rowcta || warp < 6 ? 1 : 14);
        if (warp >= 12) {
            if (strip) { const uint32_t sb = bars + 8 * (BAR_ST + warp - 12);
                mbar_init(sb, 1); mbar_expect(sb, 9216); tma2(sm + OFF_STRIP + (warp - 12) * 9216, &tm_ws, 16 * b, 144 * (warp - 12), sb); }
        } else if (warp == 7) {
            mbar_init(bars + 8 * BAR_TAB, 1); mbar_expect(bars + 8 * BAR_TAB, rowcta ? QA * 512 + 16 : 16);
            bulk_load(sm + OFF_EPOCH, g_cnt + CNT_EPOCH * 32, 16, bars + 8 * BAR_TAB);
            if (rowcta) bulk_load(sm + OFF_TAB, p.tab, QA * 512, bars + 8 * BAR_TAB);
        } else if (b + 132 * warp < 576) {
            if (PFD) while ((int)(clk32() - t0) < PFD) {}
            asm volatile("cp.async.bulk.prefetch.L2.global [%0], 2304;" :: "l"(p.wmod + (b + 132 * warp) * 3456) : "memory");
        }
    }
    if (sil) {
        #pragma unroll
        for (int u = 0; u < 3; u++) cw[u] = ldg_nc32(p.c + 144 * (warp - 8) + 48 * u + 2 * lane);
    }
    if (warp == 6) hb();
    __syncthreads();
    if (!rowcta) { if (warp < 6 && elect()) nc_issue(warp, warp); }
    if (warp == 5 || warp == 6) {
        if (elect()) {
            if (warp == 5) {
                for (int i = BAR_W; i < BAR_X; i++) mbar_init(bars + 8 * i, i == BAR_DONE || i == BAR_NC ? 4 : i == BAR_W1GO ? 2 : 1);
                mbar_expect(bars + 8 * BAR_W, 28672); mbar_expect(bars + 8 * BAR_TAB2, (QB + QC) * 512);
                mbar_expect(bars + 8 * BAR_ROLE, 4); mbar_expect(bars + 8 * BAR_P2R, 9216); mbar_expect(bars + 8 * BAR_RECV, 18432); mbar_expect(bars + 8 * BAR_XT, 18432);
            } else {
                for (int i = 0; i < 2 * NST; i++) mbar_init(bars + 8 * i, 2);
                for (int i = 0; i < NST; i++) mbar_expect(bars + 8 * (BAR_FULL + i), A_BYTES);
            }
            asm volatile("fence.mbarrier_init.release.cluster;" ::: "memory");
        }
    } else if (warp >= 12 && elect())
        asm volatile("prefetch.tensormap [%0];" :: "l"(warp == 12 ? &tm_wr : warp == 13 ? &tm_wi : warp == 14 ? &tm_t : &tm_tx) : "memory");
    if (rowcta && elect()) {
        if (XDELAY) while ((int)(clk32() - t0) < XDELAY) {}
        mbar_expect(bars + 8 * (BAR_X + warp), 1152);
        bulk_load(sm + OFF_STAGE + warp * 1152, p.x + (size_t)(b + 128 * warp) * D_, 1152, bars + 8 * (BAR_X + warp));
    }
    if ((warp >> 2) == 2) {
        if (sil) {
            #pragma unroll
            for (int u = 0; u < 3; u++) sts32(sm + OFF_SILU + (72 * (warp - 8) + 24 * u + lane) * 4, pack_bf(silu(bf_lo(cw[u])), silu(bf_hi(cw[u]))));
        }
    }
    __syncwarp();
    hb();

    const int trow = 4 * (b & 7) + ((b >> 4) & 3) + 64 * ((b >> 3) & 1) + 32 * (b >> 6);
    uint32_t* const tptr = g_T + (size_t)trow * TP + (warp < 9 ? q * 288 + 32 * warp : 4608 + 8 * q) + 4 * g;
    const int tstr = warp < 9 ? 1152 : 32;
    const uint32_t scol = sm + OFF_SPEC + (q * SPEC_P + (warp < 8 ? 72 * (warp >> 1) + 40 * (warp & 1) + 4 * g : warp == 8 ? 72 * (g >> 1) + 32 + 4 * (g & 1) : 288 + 4 * g)) * 4;
    const int wc0 = (b >> 3) * 289 + 72 * ((b & 7) >> 1) + 40 * (b & 1);

    uint32_t xw[9], one[9], t_st = t0;
    if (!rowcta) {
        const int nst = b < 130 ? 36 : 18;
        __syncthreads();
        asm volatile("barrier.cluster.arrive.relaxed.aligned;" ::: "memory");
        mbar_wait(bars + 8 * BAR_TAB, 0);
        epoch = lds32(sm + OFF_EPOCH);
        if (warp == 14) {
            uint32_t sl = 0, ph = 0;
            #pragma unroll 1
            for (int st = 6; st < nst; st++) {
                mbar_wait(bars + 8 * (BAR_X + 6 + sl), ph);
                if (elect()) nc_issue(st, sl);
                if (++sl == 6) { sl = 0; ph ^= 1; }
            }
        } else if (warp < 14) {
            uint32_t sl = 0, ph = 0;
            const uint32_t ad0 = sm + (warp >> 1) * 4096 + ((lane & 7) + 8 * (lane >> 4)) * 128, ch = (warp & 1) * 4 + ((lane >> 3) & 1);
            #pragma unroll 1
            for (int pass = 0; pass * 18 < nst; pass++) {
                float acc[2][4] = {};
                #pragma unroll 1
                for (int st = 0; st < 18; st++) {
                    const uint32_t sa = sm + OFF_SILU + (16 * st + q) * 4;
                    const uint32_t b0 = lds32(sa), b1 = lds32(sa + 16), b2 = lds32(sa + 32), b3 = lds32(sa + 48);
                    mbar_wait(bars + 8 * (BAR_X + sl), ph);
                    #pragma unroll
                    for (int m = 0; m < 2; m++) {
                        uint32_t a[4], a2[4];
                        const uint32_t ad = ad0 + sl * 28672 + ((ch + 2 * m) ^ (lane & 7)) * 16;
                        ldsm4t(a, ad); ldsm4t(a2, ad + 2048);
                        mma_bf(acc[m], a, b0, b1); mma_bf(acc[m], a2, b2, b3);
                    }
                    if (elect()) mbar_arrive(bars + 8 * (BAR_X + 6 + sl));
                    if (++sl == 6) { sl = 0; ph ^= 1; }
                }
                const int cb = 28 * pass + 7 * (b - 128) + (warp >> 1), gg = (g >> 1) + 4 * q;
                uint32_t w[2];
                #pragma unroll
                for (int m = 0; m < 2; m++) {
                    float v = bf_round(q ? acc[m][2] : acc[m][0]); if (cb >= 27) v *= 0.5f; else if (cb >= 18) v += 1.f;
                    w[m] = max(pack_bf(v, __shfl_xor_sync(~0u, v, 4)), 1u);
                }
                if (q < 2 && !(g & 1)) {
                    const int qq = (warp & 1) * 2;
                    if (cb < 27) asm volatile("st.relaxed.gpu.global.v2.u32 [%0], {%1, %2};" :: "l"(p.scr->modc + 32 * cb + 4 * gg + qq), "r"(w[0]), "r"(w[1]) : "memory");
                    else if (cb < 36) { uint32_t* o = p.scr->modc + 896 + 32 * (cb - 27) + 8 * qq + gg; o[0] = w[0]; o[8] = w[1]; }
                }
                if (tid == 0 && pass == 0) PROFT(25);
                bar_sync(1, 448);
                if (tid == 0) { fence_async_g(); red_release(g_cnt + (CNT_NC + pass) * 32); }
                __syncwarp();
            }
            fence_async_s();
        }
        __syncthreads();
    } else {
        uint32_t ta[QA * 4];
        if (strip && (warp >> 2) == 2) {
            const int w = warp - 8;
            uint32_t sb[18];
            #pragma unroll
            for (int u = 0; u < 18; u++) sb[u] = lds32(sm + OFF_SILU + (72 * w + 4 * u + q) * 4);
            const uint32_t ra = sm + OFF_STRIP + (144 * w + (lane & 7) + 8 * (lane >> 4)) * 64, sw = (lane >> 1) & 3, ch = (lane >> 3) & 1;
            float acc[2][2][4] = {};
            mbar_wait(bars + 8 * (BAR_ST + w), 0);
            #pragma unroll
            for (int u = 0; u < 9; u++)
                #pragma unroll
                for (int m = 0; m < 2; m++) { uint32_t a[4]; ldsm4t(a, ra + u * 1024 + ((ch + 2 * m) ^ sw) * 16); mma_bf(acc[u & 1][m], a, sb[2 * u], sb[2 * u + 1]); }
            #define PICK(a_) ((q & 2) ? ((q & 1) ? a_[1][2] : a_[1][0]) : ((q & 1) ? a_[0][2] : a_[0][0]))
            sts32(sm + OFF_RED + ((8 * q + g) * 4 + w) * 4, __float_as_uint(PICK(acc[0]) + PICK(acc[1])));
            if (tid == 256) PROFT(0);
            bar_sync(10, 128);
            if (warp == 8) {
                mbar_wait(bars + 8 * BAR_TAB, 0);
                const uint4 v = lds128(sm + OFF_RED + lane * 16);
                float sum = bf_round((__uint_as_float(v.x) + __uint_as_float(v.y)) + (__uint_as_float(v.z) + __uint_as_float(v.w)));
                if (b >= 36) sum = bf_round(1.f + sum);
                st_relaxed(g_mod + b * 16 + (lane & 16) + (lane & 1) * 8 + ((lane & 15) >> 1), (pack_h(0.f, sum) & 0xFFFF0000u) | ((lds32(sm + OFF_EPOCH) + 1) & 0xFFFFu));
                if (HOLD) asm volatile("bar.arrive 11, 416;" ::: "memory");
                if (tid == 256) PROFT(1);
            }
        }
        mbar_wait(bars + 8 * BAR_TAB, 0);
        load_tab<QA>(ta, sm + OFF_TAB + lane * 16);
        epoch = lds32(sm + OFF_EPOCH);
        const uint32_t tag = (epoch + 1) & 0xFFFFu;
        auto w_prefetch = [&]() {
            if (warp >= 14 && elect()) asm volatile("cp.async.bulk.prefetch.L2.global [%0], 9248;" :: "l"((warp == 14 ? p.wr : p.wi) + b * 4624) : "memory");
            __syncwarp();
        };
        uint32_t nb[2][5];
        uint4 mv = make_uint4(tag, tag, tag, tag);
        const bool poller = warp < 8 || warp == 12;
        const int mc = warp < 8 ? tid : tid - 128, mst = (mc >> 2) % 36, midx = (mc < 144 ? 10 : 0) + 5 * ((mc >> 1) & 1) + (mst >> 3);
        const uint32_t* mp = g_mod + mc * 4;
        const uint32_t ma = sm + OFF_MODA + ((midx >> 2) * 32 + (mc & 1) * 16 + (mst & 3)) * 16 + (midx & 3) * 4 + ((mst >> 2) & 1) * 2;
        #define MOD_MISSING ((((mv.x ^ tag) | (mv.y ^ tag) | (mv.z ^ tag) | (mv.w ^ tag)) & 0xFFFFu) != 0)
        if (HOLD && strip && (warp >> 2) != 2) bar_sync(11, 416);
        #pragma unroll
        for (int i = 0; i < 9; i++) one[i] = lds32(sm + OFF_TAB + (QA - 1) * 512 + i * 16 + 8);
        hb();
        mbar_wait(bars + 8 * (BAR_X + warp), 0);
        if (poller) mv = ldx128(mp);
        PROF0(28);
        #pragma unroll
        for (int i = 0; i < 9; i++) xw[i] = lds32(sm + OFF_STAGE + warp * 1152 + (32 * i + 8 * q + g) * 4);
        {
            float r, mr;
            ln_stats(xw, one, g, q, r, mr);
            #pragma unroll
            for (int pp = 0; pp < 5; pp++) {
                nb[0][pp] = pack_h(fmaf(bf_lo(xw[2 * pp]), r, mr), pp < 4 ? fmaf(bf_lo(xw[pp < 4 ? 2 * pp + 1 : 0]), r, mr) : 0.f);
                nb[1][pp] = pack_h(fmaf(bf_hi(xw[2 * pp]), r, mr), pp < 4 ? fmaf(bf_hi(xw[pp < 4 ? 2 * pp + 1 : 0]), r, mr) : 0.f);
            }
        }
        PROF0(2);
        w_prefetch();
        if (poller && MOD_MISSING) mv = ldx128(mp);
        if (warp < 8) {
            if (warp >= 4) sts16(sm + OFF_MODA + ((warp - 3) * 32 + lane) * 16 + (warp - 4) * 4 + 2, 0);
            const int k1 = tid & 15, s1 = tid >> 4;
            float s, c;
            __sincosf((float)(((k1 * (128 * s1 + b) + 1024) & 2047) - 1024) * (3.14159265358979f / 1024.f), &s, &c); s *= 0.25f; c *= 0.25f;
            const int rf = ((s1 >> 3) * 4 + (k1 >> 2)) * 2 + ((s1 >> 2) & 1), ri = ((k1 >> 3) * 4 + (s1 >> 2)) * 2 + ((k1 >> 2) & 1);
            const uint32_t af = sm + OFF_B3 + ((rf >> 2) * 32 + (k1 & 3) * 8 + (s1 & 3)) * 16 + (rf & 3) * 4;
            const uint32_t ai = sm + OFF_B3 + 2048 + ((ri >> 2) * 32 + (s1 & 3) * 8 + (k1 & 3)) * 16 + (ri & 3) * 4;
            sts32(af, pack_h(c, s)); sts32(af + 64, pack_h(-s, c)); sts32(ai, pack_h(c, -s)); sts32(ai + 64, pack_h(s, c));
        }
        if (poller) {
            for (int it = 0; __any_sync(~0u, MOD_MISSING); it++) { if (MOD_MISSING) mv = ldx128(mp); hb(); if (it > SPIN_LIMIT) __trap(); }
            sts16(ma, mv.x >> 16); sts16(ma + 64, mv.y >> 16); sts16(ma + 128, mv.z >> 16); sts16(ma + 192, mv.w >> 16);
        }
        __syncthreads();
        PROF0(3);
        asm volatile("barrier.cluster.arrive.relaxed.aligned;" ::: "memory");
        if (warp >= 13 && elect()) {
            if (warp == 15) bulk_load(sm + OFF_TAB + QA * 512, p.tab->w + QA * 128, (QB + QC) * 512, bars + 8 * BAR_TAB2);
            else tma3(sm + OFF_WRAW + (warp - 13) * 14336, warp == 13 ? &tm_wr : &tm_wi, wc0 & ~7, 0, 0, bars + 8 * BAR_W);
        }
        __syncwarp();
        {
            uint32_t md[20];
            load_tab<5>(md, sm + OFF_MODA + lane * 16);
            #pragma unroll
            for (int v = 0; v < 2; v++)
                #pragma unroll
                for (int pp = 0; pp < 5; pp++) nb[v][pp] = hfma2(nb[v][pp], md[v * 5 + pp], md[10 + v * 5 + pp]);
        }
        uint32_t re[3][2], im[3][2];
        #pragma unroll
        for (int mt = 0; mt < 3; mt++)
            #pragma unroll
            for (int v = 0; v < 2; v++) {
                re[mt][v] = 0; im[mt][v] = 0;
                mma_h8(re[mt][v], im[mt][v], ta[24 + 2 * mt], ta[25 + 2 * mt], nb[v][4]);
                mma_h(re[mt][v], im[mt][v], ta[mt * 8], ta[mt * 8 + 1], ta[mt * 8 + 2], ta[mt * 8 + 3], nb[v][0], nb[v][1]);
                mma_h(re[mt][v], im[mt][v], ta[mt * 8 + 4], ta[mt * 8 + 5], ta[mt * 8 + 6], ta[mt * 8 + 7], nb[v][2], nb[v][3]);
                cmul_neg(re[mt][v], im[mt][v], ta[30 + (mt * 2 + v) * 2], ta[31 + (mt * 2 + v) * 2]);
            }
        const uint32_t srow = sm + OFF_SPEC + warp * (SPEC_P * 4);
        #pragma unroll
        for (int nt = 0; nt < 2; nt++) {
            uint32_t o[2][4];
            #pragma unroll
            for (int v = 0; v < 2; v++) {
                const uint32_t b0 = ta[42 + (v * 2 + nt) * 2], b1 = ta[43 + (v * 2 + nt) * 2];
                o[v][0] = o[v][1] = o[v][2] = o[v][3] = 0;
                mma_h(o[v][0], o[v][1], re[0][v], re[1][v], im[0][v], im[1][v], b0, b1);
                mma_h(o[v][2], o[v][3], re[2][0], re[2][1], im[2][0], im[2][1], b0, b1);
            }
            const uint32_t a = srow + (g + 72 * q + 36 * nt) * 4, a2 = srow + (288 - g - 72 * q - 36 * nt) * 4;
            sts32(a, hadd2(o[0][0], o[1][0])); sts32(a + 32, hadd2(o[0][1], o[1][1])); if (g < 3) sts32(a + 64, hadd2(o[0][2], o[1][3]));
            if (g > 0 || (q == 0 && nt == 0)) sts32(a2, hsub2(o[0][0], o[1][0]) ^ 0x80000000u);
            sts32(a2 - 32, hsub2(o[0][1], o[1][1]) ^ 0x80000000u); if (g < 2) sts32(a2 - 64, hsub2(o[0][2], o[1][3]) ^ 0x80000000u);
        }
        uint32_t b3[16];
        if (warp < 10) load_tab<4>(b3, sm + OFF_B3 + lane * 16);
        __syncthreads();
        t_st = clk32();
        PROF0(4);
        if (warp < 10) {
            uint4 V[4], o[4];
            #pragma unroll
            for (int u = 0; u < 4; u++) V[u] = lds128(scol + u * (16 * SPEC_P));
            radix16(V, b3, o);
            #pragma unroll
            for (int nt = 0; nt < 4; nt++) { o[nt].x |= 1u; if (warp < 9 || g < 2) stx128(tptr + nt * tstr, o[nt]); }
        }
        PROF0(5);
    }

    int role = 0;
    asm volatile("barrier.cluster.wait.aligned;" ::: "memory");
    if (warp >= 12) {
        const int t = tid - 384;
        if (tid == 448 && rank == 0) {
            uint32_t smid; asm volatile("mov.u32 %0, %%smid;" : "=r"(smid));
            const uint32_t tp = smid >> 1;
            uint32_t pr = tp < 32 ? (tp & 7) * 8 + (tp >> 3) : tp < 60 ? (1 + (tp - 32) % 7) * 8 + 4 + (tp - 32) / 7 : tp < 62 ? 4 + tp : tp < 66 ? tp - 58 : 0;
            while (atomicExch(g_slot + pr, epoch + 1) == epoch + 1) pr = pr == 65 ? 0 : pr + 1;
            #pragma unroll
            for (int r = 0; r < 2; r++)
                asm volatile("st.async.weak.shared::cluster.mbarrier::complete_tx::bytes.u32 [%0], %1, [%2];" :: "r"(mapa(sm + OFF_MISC, r)), "r"(pr), "r"(mapa(bars + 8 * BAR_ROLE, r)) : "memory");
        }
        __syncwarp();
        if (t == 0) {
            asm volatile("prefetch.tensormap [%0];" :: "l"(&tm_w1a) : "memory");
            asm volatile("prefetch.tensormap [%0];" :: "l"(&tm_h3a) : "memory"); asm volatile("prefetch.tensormap [%0];" :: "l"(&tm_w1b) : "memory");
            asm volatile("prefetch.tensormap [%0];" :: "l"(&tm_h3b) : "memory"); asm volatile("prefetch.tensormap [%0];" :: "l"(&tm_w2) : "memory");
            asm volatile("prefetch.tensormap [%0];" :: "l"(&tm_o) : "memory"); asm volatile("prefetch.tensormap [%0];" :: "l"(&tm_h3s) : "memory");
        }
        __syncwarp();
        if (rowcta) {
            spin_until(t0 + NCP);
            uint4 v[2];
            v[1] = make_uint4(1, 1, 1, 1);
            for (int it = 0;; it++) {
                v[0] = ldx128(p.scr->modc + 4 * t); if (t < 88) v[1] = ldx128(p.scr->modc + 512 + 4 * t);
                if (__all_sync(~0u, min(min(min(v[0].x, v[0].y), min(v[0].z, v[0].w)), min(min(v[1].x, v[1].y), min(v[1].z, v[1].w))) != 0)) break;
                __nanosleep(100); if (it > SPIN_LIMIT) __trap();
            }
            #pragma unroll
            for (int u = 0; u < 2; u++) if (u == 0 || t < 88) {
                const uint32_t a = sm + OFF_MODC + (((t >> 5) + 4 * u) * 32 + 4 * (t & 7)) * 16 + ((t >> 3) & 3) * 4;
                sts32(a, v[u].x); sts32(a + 16, v[u].y); sts32(a + 32, v[u].z); sts32(a + 48, v[u].w);
            }
            __syncwarp();
            if (elect()) mbar_arrive(bars + 8 * BAR_NC);
            if (t == 0) PROFT(29);
        }
    } else if (rowcta && warp < 11) {
        const int nw = !(b & 1) ? 10 : (b & 7) == 7 ? 9 : 8;
        const int cm = (b >> 3) * 288 + (b & 7) * 32, cx = (b & 1) ? 4608 + 8 * (b >> 3) : (b >> 3) * 288 + 256 + 4 * (b & 7);
        auto load_in = [&]() {
            if (elect()) {
                mbar_expect(bars + 8 * BAR_XB, nw > 8 ? 20480 : 16384);
                tma2(sm + OFF_STAGE, &tm_t, cm, 0, bars + 8 * BAR_XB);
                if (nw > 8) tma2(sm + OFF_STX, &tm_tx, cx, 0, bars + 8 * BAR_XB);
            }
            __syncwarp();
        };
        if (warp == 10) { fence_async_s(); spin_until(t_st + X1D); load_in(); }
        uint32_t tb[QB * 4], wre[4][2], wim[4][2];
        if (warp < nw) {
            mbar_wait(bars + 8 * BAR_TAB2, 0);
            load_tab<QB>(tb, sm + OFF_TAB + QA * 512 + lane * 16);
            mbar_wait(bars + 8 * BAR_W, 0);
            const int off = wc0 & 7;
            const uint32_t wa = sm + OFF_WRAW + lane * 112 + ((off >> 1) + 2 * warp) * 4, sh = (off & 1) * 16;
            #pragma unroll
            for (int c = 0; c < 2; c++)
                #pragma unroll
                for (int h = 0; h < 2; h++) {
                    uint32_t y[2][2];
                    #pragma unroll
                    for (int e = 0; e < 2; e++) {
                        const uint32_t a = wa + c * 14336 + (h + 2 * e) * 3584, x0 = lds32(a), x1 = lds32(a + 4), x2 = lds32(a + 8);
                        y[e][0] = __funnelshift_r(x0, x1, sh); y[e][1] = __funnelshift_r(x1, x2, sh);
                    }
                    #pragma unroll
                    for (int x = 0; x < 4; x++) {
                        const uint32_t v = (x & 1) ? pack_h(bf_hi(y[0][x >> 1]), bf_hi(y[1][x >> 1])) : pack_h(bf_lo(y[0][x >> 1]), bf_lo(y[1][x >> 1]));
                        if (c) wim[x][h] = v; else wre[x][h] = v;
                    }
                }
        }
        const uint32_t ca = warp < 8 ? sm + OFF_STAGE + lane * 128 + (warp ^ (lane & 7)) * 16 : sm + OFF_STX + lane * 32 + ((warp ^ g) & 1) * 16, cs = warp < 8 ? 4096 : 1024;
        uint32_t V[4][4];
        for (int it = 0;; it++) {
            mbar_wait(bars + 8 * BAR_XB, it & 1);
            uint32_t ok = 1;
            if (warp < nw) {
                #pragma unroll
                for (int u = 0; u < 4; u++) { uint4 t4 = lds128(ca + u * cs); V[u][0] = t4.x; V[u][1] = t4.y; V[u][2] = t4.z; V[u][3] = t4.w; ok &= t4.x; }
            }
            asm volatile("{.reg .pred p; setp.ne.u32 p, %0, 0; bar.red.and.pred p, 1, 352, p; selp.u32 %0, 1, 0, p;}" : "+r"(ok) :: "memory");
            if (ok) break;
            if (warp == 10) { load_in(); hb(); }
            if (it > SPIN_LIMIT / 64) __trap();
        }
        PROF0(7);
        if (warp < nw) {
            uint32_t zr[4][2], zi[4][2];
            #pragma unroll
            for (int x = 0; x < 4; x++) {
                uint32_t er = 0, ei = 0, or_ = 0, oi = 0;
                mma_h(er, ei, tb[0], tb[1], tb[2], tb[3], V[0][x], V[1][x]);
                mma_h(or_, oi, tb[4], tb[5], tb[6], tb[7], V[2][x], V[3][x]);
                uint32_t r0 = hadd2(er, or_), r1 = hsub2(er, or_), i0 = hadd2(ei, oi), i1 = hsub2(ei, oi);
                cmul_neg(r0, i0, tb[8], tb[9]); cmul_neg(r1, i1, tb[10], tb[11]);
                uint32_t xr0 = 0, xr1 = 0, xi0 = 0, xi1 = 0;
                mma_h(xr0, xr1, r0, r1, i0, i1, tb[12], tb[13]);
                mma_h(xi0, xi1, r0, r1, i0, i1, tb[14], tb[15]);
                cmul_pos(xr0, xi0, wre[x][0], wim[x][0]); cmul_pos(xr1, xi1, wre[x][1], wim[x][1]);
                r0 = 0; i0 = 0; r1 = 0; i1 = 0;
                mma_h(r0, i0, tb[12], tb[13], tb[14], tb[15], xr0, xi0);
                mma_h(r1, i1, tb[12], tb[13], tb[14], tb[15], xr1, xi1);
                cmul_pos(r0, i0, tb[16], tb[17]); cmul_pos(r1, i1, tb[18], tb[19]);
                zr[x][0] = hadd2(r0, r1); zr[x][1] = hsub2(r0, r1); zi[x][0] = hadd2(i0, i1); zi[x][1] = hsub2(i0, i1);
            }
            #pragma unroll
            for (int nt = 0; nt < 4; nt++) {
                uint4 o = make_uint4(0, 0, 0, 0);
                const int h = nt >> 1;
                mma_h(o.x, o.y, zr[0][h], zr[1][h], zi[0][h], zi[1][h], tb[20 + 2 * nt], tb[21 + 2 * nt]);
                mma_h(o.z, o.w, zr[2][h], zr[3][h], zi[2][h], zi[3][h], tb[20 + 2 * nt], tb[21 + 2 * nt]);
                o.x &= ~1u;
                sts128(ca + nt * cs, o);
            }
        }
        fence_async_s();
        bar_sync(1, 352);
        t_st = clk32();
        PROF0(8);
        if (warp == 10 && elect()) {
            asm volatile("cp.async.bulk.tensor.2d.global.shared::cta.bulk_group [%0, {%2, %3}], [%1];" :: "l"(&tm_t), "r"(sm + OFF_STAGE), "r"(cm), "r"(0) : "memory");
            if (nw > 8) asm volatile("cp.async.bulk.tensor.2d.global.shared::cta.bulk_group [%0, {%2, %3}], [%1];" :: "l"(&tm_tx), "r"(sm + OFF_STX), "r"(cx), "r"(0) : "memory");
            asm volatile("cp.async.bulk.commit_group;" ::: "memory");
            asm volatile("cp.async.bulk.wait_group.read 0;" ::: "memory");
        }
        __syncwarp();
    }

    if (warp >= 10) { mbar_wait(bars + 8 * BAR_ROLE, 0); role = __shfl_sync(~0u, lds32(sm + OFF_MISC), 0); fence_async_s(); }
    auto first_a = [&]() {
        if (warp >= 10 && role < 64 && elect()) {
            const int it = warp - 10, hi = it >= 3; const bool p2 = it - 3 * hi == 2;
            tma4(sm + OFF_A + it * A_BYTES, p2 ? &tm_w1b : &tm_w1a, 0, 0, p2 ? 64 * rank + 8 * hi : 4 * (it - hi),
                 9 * (role >> 3) + (p2 ? 8 : (role & 4) + 2 * rank), bars + 8 * (BAR_FULL + it));
        }
        __syncwarp();
    };
    if (!rowcta) first_a();
    else {
        uint32_t tc[20], md[28];
        mbar_wait(bars + 8 * BAR_TAB2, 0);
        load_tab<5>(tc, sm + OFF_TAB + (QA + QB) * 512 + lane * 16);
        bool md_early = warp >= 10;
        if (md_early) { mbar_wait(bars + 8 * BAR_NC, 0); load_tab<7>(md, sm + OFF_MODC + lane * 16); }
        if (FAP > 1 && warp >= 10) { spin_until(t0 + FAP); first_a(); }
        if (warp < 10) {
            uint32_t b3[16];
            load_tab<4>(b3, sm + OFF_B3 + 2048 + lane * 16);
            uint4 V[4], o[4];
            const bool tact = warp < 9 || g == 0;
            spin_until(t_st + X2D);
            #pragma unroll
            for (int u = 0; u < 4; u++) { V[u] = make_uint4(0, 0, 0, 0); if (tact) V[u] = ldx128(tptr + u * tstr); }
            md_early = __any_sync(~0u, mbar_test(bars + 8 * BAR_NC, 0));
            if (md_early) load_tab<7>(md, sm + OFF_MODC + lane * 16);
            for (int it = 0; __any_sync(~0u, (V[0].x | V[1].x | V[2].x | V[3].x) & 1u); it++) {
                #pragma unroll
                for (int u = 0; u < 4; u++) if (V[u].x & 1u) V[u] = ldx128(tptr + u * tstr);
                hb();
                if (it > SPIN_LIMIT) __trap();
            }
            PROF0(10);
            radix16(V, b3, o);
            if (tact) {
                #pragma unroll
                for (int nt = 0; nt < 4; nt++) sts128(scol + nt * (16 * SPEC_P), o[nt]);
            }
        }
        __syncthreads();
        PROF0(11);
        if (FAP == 0) first_a();
        const uint32_t srow = sm + OFF_SPEC + warp * (SPEC_P * 4);
        uint32_t re[2][3], im[2][3];
        #pragma unroll
        for (int mt = 0; mt < 3; mt++) {
            const uint32_t a = srow + (g + 72 * q + 8 * mt) * 4, a2 = srow + (288 - g - 72 * q - 8 * mt) * 4;
            const uint32_t z0 = lds32(a), z1 = lds32(a + 144), z2 = lds32(a2), z3 = lds32(a2 - 144);
            #pragma unroll
            for (int m2 = 0; m2 < 2; m2++) {
                re[m2][mt] = 0; im[m2][mt] = 0;
                const uint32_t sg = m2 ? 0x3C00BC00u : 0xBC003C00u;
                mma_h(re[m2][mt], im[m2][mt], tc[m2 * 4], tc[m2 * 4 + 1], tc[m2 * 4 + 2], tc[m2 * 4 + 3], hfma2(z2, sg, z0), hfma2(z3, sg, z1));
                cmul_pos(re[m2][mt], im[m2][mt], tc[8 + (m2 * 3 + mt) * 2], tc[9 + (m2 * 3 + mt) * 2]);
            }
        }
        float y[20];
        WG_FENCE();
        #pragma unroll
        for (int mt = 0; mt < 3; mt++)
            wgmma40_rs(y, re[0][mt], re[1][mt], im[0][mt], im[1][mt], desc_lo(sm + OFF_TAB + (QA + QB + 5) * 512 + mt * 1280, 128), mt);
        WG_COMMIT();
        if (FAP == 1) first_a();
        if (!md_early) { mbar_wait(bars + 8 * BAR_NC, 0); load_tab<7>(md, sm + OFF_MODC + lane * 16); }
        WG_WAIT(0);
        #pragma unroll
        for (int i = 0; i < 9; i++) xw[i] = bfma2(md[i], pack_bf(y[4 * (i >> 1) + (i & 1)], y[4 * (i >> 1) + 2 + (i & 1)]), xw[i]);
        float r, mr;
        ln_stats(xw, one, g, q, r, mr);
        uint32_t r2 = pack_bf(r, r), m2 = pack_bf(mr, mr);
        #pragma unroll
        for (int i = 0; i < 9; i++) {
            sts32(sm + OFF_X1 + warp * 1152 + (32 * i + 8 * q + g) * 4, xw[i]);
            xw[i] = bfma2(bfma2(xw[i], r2, m2), md[18 + i], md[9 + i]);
        }
        ln_stats(xw, one, g, q, r, mr);
        r2 = pack_bf(r, r); m2 = pack_bf(mr, mr);
        {
            const int n7 = 2 * q + (g >> 2);
            const uint32_t a = sm + OFF_STAGE + (warp >> 3) * 9216 + n7 * 128 + ((warp & 7) ^ n7) * 16 + (g & 3) * 4;
            #pragma unroll
            for (int i = 0; i < 9; i++) sts32(a + i * 1024, bfma2(xw[i], r2, m2));
        }
        fence_async_s();
        __syncthreads();
        PROF0(12);
        if (tid == 0) {
            asm volatile("cp.async.bulk.tensor.4d.global.shared::cta.bulk_group [%0, {%2, %2, %2, %3}], [%1];" :: "l"(&tm_h3s), "r"(sm + OFF_STAGE), "r"(0), "r"(b) : "memory");
            asm volatile("cp.async.bulk.commit_group;" ::: "memory");
        }
    }
    if (!rowcta) __syncthreads();
    else {
        if (tid == 0) { asm volatile("cp.async.bulk.wait_group 0;" ::: "memory"); fence_async_g(); red_release(g_cnt + CNT_H3 * 32); }
        PROF0(13);
        if (warp == 15) {
            __nanosleep(X1DELAY);
            #pragma unroll 1
            for (int r = 0; r < 16; r++) {
                uint4* dst = (uint4*)(p.out + (size_t)(b + 128 * r) * D_) + lane;
                const uint32_t src = sm + OFF_X1 + r * 1152 + lane * 16;
                dst[0] = lds128(src); dst[32] = lds128(src + 512); if (lane < 8) dst[64] = lds128(src + 1024);
                const uint32_t t1 = clk32(); while ((int)(clk32() - t1) < X1PACE) __nanosleep(50);
            }
            __syncwarp();
            if (lane == 0) { fence_async_g(); red_release(g_cnt + CNT_X1 * 32); }
        }
    }
    role = __shfl_sync(~0u, lds32(sm + OFF_MISC), 0);
    if (role >= 64) { if (warp == 0) PROFDUMP(); return; }

    const int gi = role >> 3, dt = role & 3, c2 = (role >> 2) & 1;
    const int wg = warp >> 2, wi = warp & 3;
    if (wg == 3) {
        uint32_t so = 0, eph = 1;
        #define RING_STEP(BYTES, OFF, ISSUE) do { \
            mbar_wait(bars + 8 * BAR_EMPTY + so, eph); \
            if (elect()) { const uint32_t fb = bars + 8 * BAR_FULL + so, dst = sm + (OFF) + so * ((BYTES) / 8); mbar_expect(fb, BYTES); ISSUE; } \
            so += 8; if (so == 8 * NST) { so = 0; eph ^= 1; } } while (0)
        const uint32_t kbt = g2_kb(lane, rank, gi, c2) | (g2_kb(32 + (lane & 3), rank, gi, c2) << 8);
        #define KB(n_) ((__shfl_sync(~0u, kbt, (n_) & 31) >> (((n_) >> 2) & 8)) & 255)
        if (warp == 12) {
            eph = 0;
            const int fb1 = 9 * gi + 4 * c2 + 2 * rank, sb2 = 4 * gi + 2 * c2;
            int pft = dt, pfj = 4 * (PF0 + PFS * dt);
            #pragma unroll 1
            for (int j = 16; j < 128; j += 4) {
                RING_STEP(A_BYTES, OFF_A, tma4(dst, &tm_w1a, 0, 0, j, fb1, fb));
                if (j < 64) { if (j & 4) RING_STEP(A_BYTES, OFF_A, tma4(dst, &tm_w1b, 0, 0, 64 * rank + j - 4, 9 * gi + 8, fb)); }
                if (j == pfj && pft < PFN) {
                    const int kb = KB(pft); pft += 4; pfj += 16 * PFS;
                    if (elect()) asm volatile("cp.async.bulk.prefetch.tensor.3d.L2.global [%0, {%1, %2, %3}];" :: "l"(&tm_w2), "r"(0), "r"(64 * kb), "r"(sb2) : "memory");
                }
            }
            #pragma unroll 1
            for (int n = 0; n < 36; n++) {
                const int kb = KB(n);
                RING_STEP(A_BYTES, OFF_A, tma3(dst, &tm_w2, 0, 64 * kb, sb2, fb));
            }
        } else if (warp == 13) {
            const uint32_t e1 = __shfl_sync(~0u, epoch + 1, 0);
            fence_async_s();
            wait_count<0>(g_cnt + CNT_H3 * 32, e1 * 128);
            fence_async_g();
            if (lane == 0) PROFT(14);
            #pragma unroll 1
            for (int j = 0; j < 128; j += 4) {
                RING_STEP(B_BYTES, OFF_B, tma3(dst, &tm_h3a, 0, 18 * dt, j, fb));
                if (j < 64 && (j & 4)) RING_STEP(B_BYTES, OFF_B, tma3(dst, &tm_h3b, 0, 18 * dt + 9 * c2, 64 * rank + j - 4, fb));
            }
            int n = 0;
            #pragma unroll 1
            for (int cls = 0; cls < 3; cls++) {
                mbar_wait(bars + 8 * (BAR_UOK + cls), 0);
                fence_async_g();
                if (cls == 1 && lane == 0) PROFT(19);
                if (cls == 0 && lane == 0) PROFT(22);
                static_assert((IT_G2 + 4) % NST != NST - 1, "no wrap at the skipped stage");
                if (cls == 1) { n++; so += 8; }
                #pragma unroll 1
                for (; n < (cls == 0 ? 4 : cls == 1 ? 21 : 36); n++) {
                    const int kb = KB(n);
                    RING_STEP(B_BYTES, OFF_B, bulk_load(dst, g_U + (kb * 4 + dt) * 1152, B_BYTES, fb));
                }
            }
            if (role == 0 && rank == 0 && lane == 0) st_relaxed(g_cnt + CNT_EPOCH * 32, e1);
        } else if (warp == 15) {
            if (elect()) mbar_arrive_remote(mapa(bars + 8 * BAR_HOLD, rank ^ 1));
            __syncwarp();
            bar_sync(6, 160);
            if (elect()) mbar_arrive(bars + 8 * (BAR_FULL + (IT_G2 + 4) % NST));
            __syncwarp();
            mbar_wait(bars + 8 * BAR_W1GO, 0);
            if (elect()) {
                char* dst = (char*)(g_U + ((9 * gi + 4 * c2 + 2 * rank + 1) * 4 + dt) * 1152);
                #pragma unroll 1
                for (int i = 0; i < W1N; i++) {
                    asm volatile("cp.async.bulk.global.shared::cta.bulk_group [%0], [%1], %2;" :: "l"(dst + i * (18432 / W1N)), "r"(sm + OFF_X1 + i * (18432 / W1N)), "n"(18432 / W1N) : "memory");
                    const uint32_t t1 = clk32(); while ((int)(clk32() - t1) < W1P) {}
                }
                asm volatile("cp.async.bulk.commit_group;" ::: "memory");
                asm volatile("cp.async.bulk.wait_group 0;" ::: "memory");
                fence_async_g(); red_release(g_cnt + (CNT_U + 16) * 32);
                #pragma unroll 1
                for (int n = 0; n < 4; n++) { __nanosleep(300); tma2(sm + OFF_X1 + n * 4608, &tm_o, 144 * dt, 256 * gi + 128 * c2 + 64 * (rank ^ 1) + 16 * n, bars + 8 * BAR_XT); }
            }
        } else {
            const uint32_t e1 = epoch + 1;
            if (lane == 0) {
                __nanosleep(4000);
                wait_count<200>(g_cnt + CNT_NC * 32, e1 * 4); wait_count<200>(g_cnt + (CNT_NC + 1) * 32, e1 * 2);
                fence_async_g();
                mbar_expect(bars + 8 * BAR_GB, 1152);
                bulk_load(sm + OFF_GB, p.scr->modc + 896, 1152, bars + 8 * BAR_GB);
                wait_count<200>(g_cnt + CNT_X1 * 32, e1 * 128);
                if (role * 2 + rank < 108) {
                    uint4* z = (uint4*)p.scr->modc + (role * 2 + rank) * 2; z[0] = z[1] = make_uint4(0, 0, 0, 0);
                }
                wait_count<50>(g_cnt + (CNT_U + dt * 2 + rank) * 32, e1 * 16);
                mbar_arrive(bars + 8 * BAR_UOK);
            }
            __syncwarp();
            bar_sync(4, 160);
            if (lane == 0) {
                fence_async_g(); red_release(g_cnt + (CNT_U + 8) * 32);
                PROFT(17);
                wait_count<0>(g_cnt + (CNT_U + 8) * 32, e1 * 128);
                mbar_arrive(bars + 8 * (BAR_UOK + 1));
                __nanosleep(1000);
                wait_count<100>(g_cnt + (CNT_U + 16) * 32, e1 * 128);
                mbar_arrive(bars + 8 * (BAR_UOK + 2));
            }
        }
    } else if (wg == 2) {
        float d0[36];
        const float bias = bf_lo(ldg_nc16(p.b1 + 576 * gi + 512 + 16 * wi + g + 8 * rank));
        for (int it = 0; it < 200 && !__any_sync(~0u, mbar_test(bars + 8 * BAR_FULL, 0)); it++) { hb(); __nanosleep(100); }
        const bool lead = wi == 0 && elect();
        #pragma unroll 1
        for (int i = 0; i < 8; i++) {
            const uint32_t s = P2S + 3 * (i & 1);
            mbar_wait(bars + 8 * BAR_FULL + 8 * s, (i >> 1) & 1);
            const uint32_t da = desc_lo(sm + OFF_A, 8192) + s * (A_BYTES / 16), db = desc_lo(sm + OFF_B, 128) + s * (B_BYTES / 16);
            WG_FENCE();
            wgmma72(d0, da, db, i);
            #pragma unroll
            for (int k = 1; k < 8; k++) wgmma72(d0, da + k * 128, db + k * 144, 1);
            WG_COMMIT();
            WG_WAIT(0);
            if (lead) mbar_arrive_n(bars + 8 * BAR_EMPTY + 8 * s, 2);
        }
        if (lead) PROFT(18);
        const uint32_t slot = sm + OFF_P2R + (tid & 127) * 16, ra = mapa(slot, rank ^ 1), rb = mapa(bars + 8 * BAR_P2R, rank ^ 1);
        float sv[18];
        #pragma unroll
        for (int i = 0; i < 18; i++) { const float lo = d0[4 * (i >> 1) + (i & 1)], hi = d0[4 * (i >> 1) + 2 + (i & 1)];
            sv[i] = rank ? lo : hi; d0[4 * (i >> 1) + (i & 1)] = (rank ? hi : lo) + bias; }
        mbar_wait(bars + 8 * BAR_HOLD, 0);
        #pragma unroll
        for (int i = 0; i < 4; i++)
            asm volatile("st.async.weak.shared::cluster.mbarrier::complete_tx::bytes.v4.f32 [%0], {%1,%2,%3,%4}, [%5];"
                :: "r"(ra + i * 2048), "f"(sv[4 * i]), "f"(sv[4 * i + 1]), "f"(sv[4 * i + 2]), "f"(sv[4 * i + 3]), "r"(rb) : "memory");
        asm volatile("st.async.weak.shared::cluster.mbarrier::complete_tx::bytes.v2.f32 [%0], {%1,%2}, [%3];" :: "r"(ra + 8192), "f"(sv[16]), "f"(sv[17]), "r"(rb) : "memory");
        mbar_wait(bars + 8 * BAR_P2R, 0);
        #pragma unroll
        for (int i = 0; i < 5; i++) {
            const uint4 v = lds128(slot + i * 2048);
            d0[8 * i] += __uint_as_float(v.x); d0[8 * i + 1] += __uint_as_float(v.y);
            if (i < 4) { d0[8 * i + 4] += __uint_as_float(v.z); d0[8 * i + 5] += __uint_as_float(v.w); }
        }
        asm volatile("bar.arrive 5, 256;" ::: "memory");
        gelu_store<0>(d0, (char*)(g_U + ((9 * gi + 8) * 4 + dt) * 1152) + wi * 4608 + rank * 2304 + c2 * 1152 + g * 16, q);
        bar_sync(8, 128);
        if (lead) { fence_async_g(); red_release(g_cnt + (CNT_U + dt * 2 + (gi >> 2)) * 32); PROFT(26); }
    } else {
        float d[72];
        const bool lead = wi == 0 && elect();
        const uint32_t da0 = desc_lo(sm + OFF_A + wg * 8192, 8192);
        const bool owner = (uint32_t)wg == rank;
        const int srow = 256 * gi + 128 * c2 + 64 * wg + 16 * wi;
        const uint32_t b2w0 = ldg_nc16(p.b2 + srow + g), b2w1 = ldg_nc16(p.b2 + srow + g + 8);
        {
            const int fr = 576 * gi + 256 * c2 + 128 * rank + 64 * wg + 16 * wi + g;
            const float bias0 = bf_lo(ldg_nc16(p.b1 + fr)), bias1 = bf_lo(ldg_nc16(p.b1 + fr + 8));
            #pragma unroll
            for (int i = 0; i < 72; i++) d[i] = (i & 2) ? bias1 : bias0;
            const uint32_t db1 = desc_lo(sm + OFF_B, 128);
            mainloop<DHI_H3, 0, IT_P1, true>(d, bars, da0, db1, lead, [&](int) {});
            mainloop<DHI_H3, IT_P1, IT_G2 - LEAD1, false>(d, bars, da0, db1, lead, [&](int) {});
            constexpr uint32_t EB = 8 * (BAR_EMPTY + (IT_G2 - LEAD1 - 1) % NST);
            if (wg == 1) { WG_WAIT(0); if (lead) mbar_arrive(bars + EB); bar_sync(9, 256); }
            #pragma unroll
            for (int i = IT_G2 - LEAD1; i < IT_G2; i++) {
                mbar_wait(bars + 8 * (BAR_FULL + i % NST), (i / NST) & 1);
                WG_FENCE();
                #pragma unroll
                for (int k = 0; k < 4; k++) {
                    if (i == IT_G2 - 1 && k == HOK1) WG_COMMIT();
                    wgmma144<DHI_H3>(d, da0 + (i % NST) * (A_BYTES / 16) + k * 128, db1 + (i % NST) * (B_BYTES / 16) + k * 288, 1);
                }
                WG_COMMIT();
                if (i == IT_G2 - 1 && HOK1 < 4) WG_WAIT(2); else WG_WAIT(1);
                if (lead && (i > IT_G2 - LEAD1 || wg == 0)) mbar_arrive(bars + 8 * (BAR_EMPTY + (i - 1) % NST));
            }
            if (wg == 0) { WG_WAIT(1); asm volatile("bar.arrive 9, 256;" ::: "memory"); }
            WG_WAIT(0);
            if (lead) mbar_arrive(bars + 8 * (BAR_EMPTY + (IT_G2 - 1) % NST));
            PROF0(16);
            if (wg == 1) bar_sync(5, 256);
            char* const ub = (wg == 0 ? (char*)(g_U + ((9 * gi + 4 * c2 + 2 * rank) * 4 + dt) * 1152) : (char*)__cvta_shared_to_generic(sm + OFF_X1)) + wi * 4608 + g * 16;
            gelu_store<0>(d, ub, q); gelu_store<2>(d, ub + 2304, q); gelu_store<36>(d, ub + 1152, q); gelu_store<38>(d, ub + 3456, q);
            PROF0(27);
            if (wg == 0) asm volatile("bar.arrive 4, 160;" ::: "memory");
            else { fence_async_s(); asm volatile("bar.arrive 6, 160;" ::: "memory"); }
        }
        const uint32_t db0 = desc_lo(sm + OFF_B, 2304);
        const bool keep = role > 64;
        constexpr int IT_L = IT_END - NST, IT_X = IT_L - 4;
        #pragma unroll
        for (int i = IT_G2; i <= IT_G2 + W1S; i++) {
            const uint32_t db = db0 + (i == IT_G2 + 4 ? OFF_X1 - OFF_B : (i % NST) * B_BYTES) / 16;
            mbar_wait(bars + 8 * (BAR_FULL + i % NST), (i / NST) & 1);
            WG_FENCE();
            #pragma unroll
            for (int k = 0; k < 4; k++) wgmma144<DHI_U>(d, da0 + (i % NST) * (A_BYTES / 16) + k * 128, db + k * 288, i > IT_G2 || k > 0 || keep);
            WG_COMMIT();
            if (i > IT_G2) { WG_WAIT(1); if (lead) mbar_arrive(bars + 8 * (BAR_EMPTY + (i - 1) % NST)); }
        }
        if (lead) mbar_arrive(bars + 8 * BAR_W1GO);
        mainloop<DHI_U, IT_G2 + W1S + 1, IT_X, false>(d, bars, da0, db0, lead, [&](int) {});
        const uint32_t ga0 = sm + OFF_GB + (144 * dt + 8 * q) * 2, tile = sm + OFF_X1 + wi * 4608, to = g * 288 + q * 16;
        #define QOFF(i_) (((i_) >> 2) * 2304 + 144 * (((i_) >> 1) & 1) + 64 * ((i_) & 1))
        #define SOFF(k_) (((k_) >> 1) * 2304 + 144 * ((k_) & 1) + 128 - 12 * q)
        #define DIDX(i_, k_) ((i_) < 8 ? 36 * (((i_) >> 1) & 1) + 16 * ((i_) & 1) + 4 * (k_) + 2 * ((i_) >> 2) : 36 * ((k_) & 1) + 32 + 2 * ((k_) >> 1))
        #define FIN(k_, f_) bfma2(g4.f_, pack_bf(d[DIDX(i, k_)], d[DIDX(i, k_) + 1]), xq[i].f_)
        uint4 xq[9];
        auto load_g = [&](int i) { uint4 r; if (i < 4) r = lds128(ga0 + QOFF(i)); else { r.x = r.z = lds32(ga0 + SOFF(0)); r.y = r.w = lds32(ga0 + SOFF(1)); } return r; };
        mainloop<DHI_U, IT_X, IT_L, false>(d, bars, da0, db0, lead, [&](int i) {
            if (!owner) {
                const uint32_t xa = tile + to;
                if (i == IT_X) { mbar_wait(bars + 8 * BAR_XT, 0); xq[0] = lds128(xa + QOFF(0)); xq[4] = lds128(xa + QOFF(4)); xq[1] = lds128(xa + QOFF(1)); }
                else if (i == IT_X + 1) { xq[5] = lds128(xa + QOFF(5)); xq[2] = lds128(xa + QOFF(2)); xq[6] = lds128(xa + QOFF(6)); }
                else if (i == IT_X + 2) { xq[3] = lds128(xa + QOFF(3)); xq[7] = lds128(xa + QOFF(7));
                    xq[8] = make_uint4(lds32(xa + SOFF(0)), lds32(xa + SOFF(1)), lds32(xa + SOFF(2)), lds32(xa + SOFF(3))); }
                else if (i == IT_X + 3) { if (elect()) mbar_arrive_remote(mapa(bars + 8 * BAR_DONE, rank ^ 1)); }
            } });
        if (owner) { WG_WAIT(0); if (lead) mbar_arrive(bars + 8 * (BAR_EMPTY + (IT_L - 1) % NST)); bar_sync(7, 256); }
        #pragma unroll
        for (int i = IT_L; i < IT_END; i++) {
            mbar_wait(bars + 8 * (BAR_FULL + i % NST), (i / NST) & 1);
            WG_FENCE();
            #pragma unroll
            for (int k = 0; k < 4; k++) {
                if (i == IT_END - 1 && k == HOK) WG_COMMIT();
                wgmma144<DHI_U>(d, da0 + (i % NST) * (A_BYTES / 16) + k * 128, db0 + (i % NST) * (B_BYTES / 16) + k * 288, 1);
            }
            WG_COMMIT();
            if (i == IT_L) { WG_WAIT(1); if (lead && !owner) mbar_arrive(bars + 8 * (BAR_EMPTY + (IT_L - 1) % NST)); }
        }
        PROF0(9);
        mbar_wait(bars + 8 * BAR_GB, 0);
        if (!owner) {
            const uint32_t ra = mapa(tile + lane * 16, rank ^ 1), rb = mapa(bars + 8 * BAR_RECV, rank ^ 1);
            mbar_wait(bars + 8 * BAR_DONE, 0);
            uint4 gn = load_g(0);
            WG_WAIT(1);
            asm volatile("bar.arrive 7, 256;" ::: "memory");
            WG_WAIT(0);
            #pragma unroll
            for (int i = 0; i < 72; i++) d[i] = fmaf(bf_lo((i & 2) ? b2w1 : b2w0), 2.f, d[i]);
            #pragma unroll
            for (int j = 0; j < 5; j++) {
                const uint4 g4 = gn;
                if (j < 4) gn = load_g(j + 1);
                #pragma unroll
                for (int i = j < 4 ? j : 8; i < 9; i += 4) if (i < 8 || j == 4)
                    asm volatile("st.async.weak.shared::cluster.mbarrier::complete_tx::bytes.v4.b32 [%0], {%1,%2,%3,%4}, [%5];"
                        :: "r"(ra + i * 512), "r"(FIN(0, x)), "r"(FIN(1, y)), "r"(FIN(2, z)), "r"(FIN(3, w)), "r"(rb) : "memory");
            }
            PROF0(6);
            if (warp == 0) PROFDUMP();
            return;
        }
        PROF0(24);
        mbar_wait(bars + 8 * BAR_RECV, 0);
        #pragma unroll
        for (int i = 0; i < 9; i++) xq[i] = lds128(tile + lane * 16 + i * 512);
        uint4 gn = load_g(0);
        WG_WAIT(0);
        __syncwarp();
        PROF0(21);
        #pragma unroll
        for (int j = 0; j < 5; j++) {
            const uint4 g4 = gn;
            if (j < 4) gn = load_g(j + 1);
            #pragma unroll
            for (int i = j < 4 ? j : 8; i < 9; i += 4) if (i < 8 || j == 4) {
                const uint4 o = make_uint4(FIN(0, x), FIN(1, y), FIN(2, z), FIN(3, w));
                if (i < 8) sts128(tile + to + QOFF(i), o);
                else { sts32(tile + to + SOFF(0), o.x); sts32(tile + to + SOFF(1), o.y); sts32(tile + to + SOFF(2), o.z); sts32(tile + to + SOFF(3), o.w); }
            }
        }
        fence_async_s();
        __syncwarp();
        if (elect()) {
            asm volatile("cp.async.bulk.tensor.2d.global.shared::cta.bulk_group [%0, {%2, %3}], [%1];" :: "l"(&tm_o), "r"(tile), "r"(144 * dt), "r"(srow) : "memory");
            asm volatile("cp.async.bulk.commit_group;" ::: "memory");
            asm volatile("cp.async.bulk.wait_group.read 0;" ::: "memory");
        }
        PROF0(23);
        if (warp == 0) { __syncwarp(); PROFDUMP(); }
    }
}

typedef CUresult (*EncodeFn)(CUtensorMap*, CUtensorMapDataType, cuuint32_t, void*, const cuuint64_t*, const cuuint64_t*, const cuuint32_t*,
                             const cuuint32_t*, CUtensorMapInterleave, CUtensorMapSwizzle, CUtensorMapL2promotion, CUtensorMapFloatOOBfill);

void encode(EncodeFn fn, CUtensorMap* m, CUtensorMapDataType dt, int rank, const void* ptr, const cuuint64_t* dims, const cuuint64_t* strides,
            const cuuint32_t* box, CUtensorMapSwizzle sw, CUtensorMapL2promotion promo = CU_TENSOR_MAP_L2_PROMOTION_L2_128B) {
    const cuuint32_t es[5] = {1, 1, 1, 1, 1};
    fn(m, dt, rank, (void*)ptr, dims, strides, box, es, CU_TENSOR_MAP_INTERLEAVE_NONE, sw, promo, CU_TENSOR_MAP_FLOAT_OOB_FILL_NONE);
}

}

extern "C" void kernel_launch(void* const* d_in, const int* in_sizes, int n_in, void* d_out, int out_size) {
    (void)in_sizes; (void)n_in; (void)out_size;
    Params p;
    p.x = (const uint16_t*)d_in[0]; p.wr = (const uint16_t*)d_in[1]; p.wi = (const uint16_t*)d_in[2];
    p.w1 = (const uint16_t*)d_in[4]; p.b1 = (const uint16_t*)d_in[5]; p.w2 = (const uint16_t*)d_in[6]; p.b2 = (const uint16_t*)d_in[7];
    p.c = (const uint16_t*)d_in[8]; p.wmod = (const uint16_t*)d_in[9]; p.out = (uint16_t*)d_out;

    void* fnp = nullptr; cudaDriverEntryPointQueryResult qr;
    cudaGetDriverEntryPoint("cuTensorMapEncodeTiled", &fnp, cudaEnableDefault, &qr);
    EncodeFn fn = (EncodeFn)fnp;
    cudaGetSymbolAddress((void**)&p.scr, g_scr); cudaGetSymbolAddress((void**)&p.tab, g_tab);
    void* h3p = p.scr->h3;
    CUtensorMap tw1a, tw1b, tw2, th3a, th3b, twr, twi, twm, tt, ttx, to, th3s, tws;
    {
        const cuuint64_t dims[4] = {64, 16, 128, 72}, st[3] = {128ull * F_ * 2, (cuuint64_t)F_ * 2, 128};
        const cuuint32_t ba[4] = {64, 16, 4, 2}, bb[4] = {64, 16, 8, 1};
        encode(fn, &tw1a, CU_TENSOR_MAP_DATA_TYPE_BFLOAT16, 4, p.w1, dims, st, ba, CU_TENSOR_MAP_SWIZZLE_128B);
        encode(fn, &tw1b, CU_TENSOR_MAP_DATA_TYPE_BFLOAT16, 4, p.w1, dims, st, bb, CU_TENSOR_MAP_SWIZZLE_128B);
    }
    {
        const cuuint64_t dims[3] = {64, F_, 32}, st[2] = {(cuuint64_t)S_ * 2, 128};
        const cuuint32_t bx[3] = {64, 64, 2};
        encode(fn, &tw2, CU_TENSOR_MAP_DATA_TYPE_BFLOAT16, 3, p.w2, dims, st, bx, CU_TENSOR_MAP_SWIZZLE_128B);
    }
    {
        const cuuint64_t dims[3] = {64, 72, 128}, st[2] = {256, 18432};
        const cuuint32_t ba[3] = {64, 18, 4}, bb[3] = {64, 9, 8};
        encode(fn, &th3a, CU_TENSOR_MAP_DATA_TYPE_UINT32, 3, h3p, dims, st, ba, CU_TENSOR_MAP_SWIZZLE_NONE);
        encode(fn, &th3b, CU_TENSOR_MAP_DATA_TYPE_UINT32, 3, h3p, dims, st, bb, CU_TENSOR_MAP_SWIZZLE_NONE);
    }
    {
        const cuuint64_t dims[4] = {32, 72, 2, 128}, st[3] = {256, 128, 18432};
        const cuuint32_t bx[4] = {32, 72, 2, 1};
        encode(fn, &th3s, CU_TENSOR_MAP_DATA_TYPE_UINT32, 4, h3p, dims, st, bx, CU_TENSOR_MAP_SWIZZLE_128B, CU_TENSOR_MAP_L2_PROMOTION_NONE);
    }
    {
        const cuuint64_t dims[3] = {4624, 4, 32}, st[2] = {9248 * 32, 9248};
        const cuuint32_t bx[3] = {56, 4, 32};
        encode(fn, &twr, CU_TENSOR_MAP_DATA_TYPE_BFLOAT16, 3, p.wr, dims, st, bx, CU_TENSOR_MAP_SWIZZLE_NONE);
        encode(fn, &twi, CU_TENSOR_MAP_DATA_TYPE_BFLOAT16, 3, p.wi, dims, st, bx, CU_TENSOR_MAP_SWIZZLE_NONE);
    }
    {
        const cuuint64_t dims[2] = {3456, 576}, st[1] = {6912};
        const cuuint32_t bx[2] = {32, 144};
        encode(fn, &tws, CU_TENSOR_MAP_DATA_TYPE_BFLOAT16, 2, p.wmod, dims, st, bx, CU_TENSOR_MAP_SWIZZLE_64B);
    }
    {
        const cuuint64_t dims[3] = {64, 576, 54}, st[2] = {6912, 128};
        const cuuint32_t bx[3] = {64, 32, 7};
        encode(fn, &twm, CU_TENSOR_MAP_DATA_TYPE_BFLOAT16, 3, p.wmod, dims, st, bx, CU_TENSOR_MAP_SWIZZLE_128B);
    }
    {
        const cuuint64_t dims[2] = {TP, 128}, st[1] = {TP * 4};
        const cuuint32_t ba[2] = {32, 128}, bb[2] = {8, 128};
        encode(fn, &tt, CU_TENSOR_MAP_DATA_TYPE_UINT32, 2, p.scr->T, dims, st, ba, CU_TENSOR_MAP_SWIZZLE_128B, CU_TENSOR_MAP_L2_PROMOTION_NONE);
        encode(fn, &ttx, CU_TENSOR_MAP_DATA_TYPE_UINT32, 2, p.scr->T, dims, st, bb, CU_TENSOR_MAP_SWIZZLE_32B, CU_TENSOR_MAP_L2_PROMOTION_NONE);
    }
    {
        const cuuint64_t dims[2] = {D_, S_}, st[1] = {D_ * 2};
        const cuuint32_t bx[2] = {144, 16};
        encode(fn, &to, CU_TENSOR_MAP_DATA_TYPE_BFLOAT16, 2, p.out, dims, st, bx, CU_TENSOR_MAP_SWIZZLE_NONE, CU_TENSOR_MAP_L2_PROMOTION_NONE);
    }
    cudaFuncSetAttribute(fused_kernel, cudaFuncAttributeMaxDynamicSharedMemorySize, SMEM_BYTES);
    cudaLaunchConfig_t cfg = {};
    cfg.gridDim = dim3(NCTA); cfg.blockDim = dim3(NTHR); cfg.dynamicSmemBytes = SMEM_BYTES; cfg.stream = cudaStreamPerThread;
    cudaLaunchAttribute at[1];
    at[0].id = cudaLaunchAttributeCooperative; at[0].val.cooperative = 1;
    cfg.attrs = at; cfg.numAttrs = 1;
    cudaLaunchKernelEx(&cfg, fused_kernel, p, tw1a, tw1b, tw2, th3a, th3b, twr, twi, twm, tt, ttx, to, th3s, tws);
}
```

```cpp
#include <cuda_runtime.h>
#include <cuda_bf16.h>
#include <cuda_fp16.h>
#include <cuda.h>
#include <stdint.h>

namespace {

constexpr int S_ = 2048, D_ = 576, F_ = 4608;
constexpr int NCTA = 132, NTHR = 512;
constexpr int TP = 4736;
constexpr int SPEC_P = 296;
constexpr int NST = 6;
constexpr int A_BYTES = 16384, B_BYTES = 18432;
constexpr int IT_P1 = 24, IT_G2 = 40, IT_END = 76;
constexpr int SPIN_LIMIT = 1 << 22;
#define X2D 1350
constexpr int P2S = 2;
#define LEAD1 4
#define W1N 8
#define W1P 100
#define W1S 5
#define XDELAY 1100
#define HOK 2
#define HOK1 2
#define NCP 10800
#define SLP 64
#define X1D 2100
#define PF0 4
#define PFS 3
#define PFN 9
#define X1DELAY 2000
#define X1PACE 400

constexpr int OFF_A = 0;
constexpr int OFF_B = NST * A_BYTES;
constexpr int OFF_P = OFF_B + NST * B_BYTES;
constexpr int OFF_BAR = OFF_P;
constexpr int OFF_EPOCH = OFF_P + 480;
constexpr int OFF_MISC = OFF_P + 496;
constexpr int OFF_GB = OFF_P + 512;
constexpr int OFF_P2R = OFF_P + 1664;
constexpr int OFF_X1 = OFF_P2R;
constexpr int OFF_PROF = OFF_X1 + 18432;
constexpr int SMEM_BYTES = OFF_PROF + 512 + 1024;
constexpr int QA = 13, QB = 7, QC = 13;
constexpr int TAB_BYTES = (QA + QB + QC) * 512;
constexpr int OFF_STAGE = OFF_B;
constexpr int OFF_STX = OFF_STAGE + 16384;
constexpr int OFF_TAB = OFF_STAGE + 20480;
constexpr int OFF_SPEC = OFF_TAB + TAB_BYTES;
constexpr int OFF_WRAW = OFF_SPEC + 19072;
constexpr int OFF_B3 = OFF_WRAW + 28672;
constexpr int OFF_MODA = OFF_B3 + 4096;
constexpr int OFF_MODC = OFF_MODA + 2560;
constexpr int OFF_RED = OFF_MODC + 3584;
constexpr int OFF_HEXP = OFF_RED + 512;
constexpr int OFF_SILU = OFF_RED + 1536;
static_assert(OFF_SILU + 1152 <= OFF_P && 6 * 28672 <= OFF_B3, "scratch overflow");
constexpr int OFF_STRIP = OFF_A;
static_assert(OFF_WRAW % 128 == 0 && OFF_STAGE % 128 == 0 && OFF_STX % 128 == 0, "align");
constexpr int BAR_FULL = 0, BAR_EMPTY = 6, BAR_TAB = 12, BAR_W = 13, BAR_P2R = 16,
              BAR_XT = 17, BAR_RECV = 18, BAR_ROLE = 19, BAR_NC = 20, BAR_TAB2 = 21, BAR_XB = 22, BAR_GB = 23, BAR_HOLD = 24, BAR_W1GO = 25, BAR_UOK = 26, BAR_DONE = 30, BAR_X = 31, BAR_ST = 47;

struct Cos1152 { double c[1152]; };
constexpr double cx_cos(double x) { double t = 1, s = 1; for (int i = 1; i < 14; i++) { t *= -x * x / ((2 * i - 1) * (2 * i)); s += t; } return s; }
constexpr Cos1152 make_cos() {
    Cos1152 r{};
    for (int i = 0; i <= 288; i++) {
        double v = (i == 288) ? 0.0 : cx_cos(3.14159265358979323846 * 2.0 * i / 1152.0);
        r.c[i] = v; r.c[576 - i] = -v; r.c[576 + i] = -v; r.c[(1152 - i) % 1152] = v;
    }
    return r;
}
constexpr uint32_t cx_f2h(double v) {
    uint32_t s = v < 0 ? 0x8000u : 0u; double a = v < 0 ? -v : v;
    if (a < 1e-9) return 0;
    int e = 0;
    while (a >= 2.0) { a *= 0.5; e++; }
    while (a < 1.0 && e > -14) { a *= 2.0; e--; }
    double m = a * 1024.0; uint32_t mi = (uint32_t)m; double fr = m - mi;
    if (fr > 0.5 || (fr == 0.5 && (mi & 1))) mi++;
    return s | (uint32_t)(((e + 14) << 10) + mi);
}
struct Tab { uint32_t w[(QA + QB + QC) * 128]; };
constexpr Tab make_tab() {
    Tab t{};
    Cos1152 ct = make_cos();
    auto C = [&](int num, int den) { return ct.c[(num % den) * (1152 / den)]; };
    auto Sn = [&](int num, int den) { return ct.c[((num % den) * (1152 / den) + 864) % 1152]; };
    auto put = [&](int q0, int idx, int lane, double lo, double hi) { t.w[((q0 + idx / 4) * 32 + lane) * 4 + idx % 4] = cx_f2h(lo) | (cx_f2h(hi) << 16); };
    for (int lane = 0; lane < 32; lane++) {
        const int g = lane >> 2, q = lane & 3;
        for (int mt = 0; mt < 3; mt++) {
            const int ka = 8 * mt + g;
            for (int r = 0; r < 10; r++) {
                const int im = r & 1, i0 = (r >> 1) * 2;
                double v[2] = {0, 0};
                for (int e = 0; e < 2; e++) { int i = i0 + e, d1 = 4 * i + q; if (i < 9 && ka <= 18) v[e] = (im ? -Sn(ka * d1, 36) : C(ka * d1, 36)) / 8; }
                put(0, r < 8 ? mt * 8 + r : 16 + 2 * mt + r, lane, v[0], v[1]);
            }
            for (int v = 0; v < 2; v++) {
                const int d2 = 4 * q + v;
                put(0, 30 + (mt * 2 + v) * 2, lane, C(ka * d2, 576) * 4 / 3, C(ka * (d2 + 2), 576) * 4 / 3);
                put(0, 31 + (mt * 2 + v) * 2, lane, Sn(ka * d2, 576) * 4 / 3, Sn(ka * (d2 + 2), 576) * 4 / 3);
            }
        }
        for (int v = 0; v < 2; v++) for (int nt = 0; nt < 2; nt++) {
            const int kb = 2 * (g >> 1) + nt, part = g & 1;
            double b0[2] = {0, 0}, b1[2] = {0, 0};
            for (int e = 0; e < 2; e++) { int d2 = 4 * q + 2 * e + v; double c = C(kb * d2, 16) / 4, s = Sn(kb * d2, 16) / 4;
                b0[e] = part ? -s : c; b1[e] = part ? c : s; }
            put(0, 42 + (v * 2 + nt) * 2, lane, b0[0], b0[1]); put(0, 43 + (v * 2 + nt) * 2, lane, b1[0], b1[1]);
        }
        t.w[((QA - 1) * 32 + lane) * 4 + 2] = 0x3F803F80u;
        for (int par = 0; par < 2; par++) for (int a = 0; a < 4; a++) {
            const int ja = 2 * (q + 4 * (a >> 1)) + par; const double c = C(g * ja, 16) / 4, s = Sn(g * ja, 16) / 4;
            put(QA, par * 4 + a, lane, (a & 1) ? -s : c, (a & 1) ? c : s);
        }
        for (int h = 0; h < 2; h++) {
            put(QA, 8 + 2 * h, lane, C((g + 8 * h) * (2 * q), 128) / 2, C((g + 8 * h) * (2 * q + 1), 128) / 2);
            put(QA, 9 + 2 * h, lane, Sn((g + 8 * h) * (2 * q), 128) / 2, Sn((g + 8 * h) * (2 * q + 1), 128) / 2);
            put(QA, 16 + 2 * h, lane, C(g * (8 * h + 2 * q), 128), C(g * (8 * h + 2 * q + 1), 128));
            put(QA, 17 + 2 * h, lane, Sn(g * (8 * h + 2 * q), 128), Sn(g * (8 * h + 2 * q + 1), 128));
        }
        put(QA, 12, lane, C(g * 2 * q, 8) / 2, C(g * (2 * q + 1), 8) / 2);
        put(QA, 15, lane, C(g * 2 * q, 8) / 2, C(g * (2 * q + 1), 8) / 2);
        put(QA, 13, lane, Sn(g * 2 * q, 8) / 2, Sn(g * (2 * q + 1), 8) / 2);
        put(QA, 14, lane, -Sn(g * 2 * q, 8) / 2, -Sn(g * (2 * q + 1), 8) / 2);
        for (int u = 0; u < 4; u++) {
            const int ja = 2 * ((g >> 1) + 4 * (u & 1)) + (u >> 1), part = g & 1; double b0[2] = {0, 0}, b1[2] = {0, 0};
            for (int e = 0; e < 2; e++) { int ka = 2 * q + e; double c = C(ja * ka, 16) / 4, s = Sn(ja * ka, 16) / 4;
                b0[e] = part ? s : c; b1[e] = part ? c : -s; }
            put(QA, 20 + u * 2, lane, b0[0], b0[1]); put(QA, 21 + u * 2, lane, b1[0], b1[1]);
        }
        for (int m2 = 0; m2 < 2; m2++) {
            const int d2 = 2 * g + m2;
            for (int a = 0; a < 4; a++) {
                const int kb = 2 * q + (a >> 1); const double c = C(d2 * kb, 16) / 4, s = Sn(d2 * kb, 16) / 4;
                put(QA + QB, m2 * 4 + a, lane, (a & 1) ? s : c, (a & 1) ? c : -s);
            }
            for (int mt = 0; mt < 3; mt++) {
                const int ka = 8 * mt + 2 * q;
                put(QA + QB, 8 + (m2 * 3 + mt) * 2, lane, C(ka * d2, 576) * 4 / 3, C((ka + 1) * d2, 576) * 4 / 3);
                put(QA + QB, 9 + (m2 * 3 + mt) * 2, lane, Sn(ka * d2, 576) * 4 / 3, Sn((ka + 1) * d2, 576) * 4 / 3);
            }
        }
        for (int mt = 0; mt < 3; mt++) for (int nt = 0; nt < 5; nt++) {
            const int i = 2 * nt + (g & 1), d1 = 4 * i + (g >> 1); double b0[2] = {0, 0}, b1[2] = {0, 0};
            for (int e = 0; e < 2; e++) { int ka = 8 * mt + 2 * q + e;
                if (ka <= 18 && i < 9) { double wt = (ka == 0 || ka == 18) ? 0.125 : 0.25; b0[e] = wt * C(ka * d1, 36); b1[e] = -wt * Sn(ka * d1, 36); } }
            const int o = (QA + QB + 5) * 128 + (mt * 5 + nt) * 64 + lane;
            t.w[o] = cx_f2h(b0[0]) | (cx_f2h(b0[1]) << 16); t.w[o + 32] = cx_f2h(b1[0]) | (cx_f2h(b1[1]) << 16);
        }
    }
    return t;
}
__device__ __align__(128) const Tab g_tab = make_tab();

struct Scratch {
    uint32_t cnt[30 * 32];
    uint32_t slot[96];
    uint32_t mod[2304];
    uint32_t modc[896 + 288];
    uint32_t T[128 * TP];
    uint4 h3[128 * 1152];
    uint4 U[72 * 4 * 1152];
};
__device__ __align__(1024) Scratch g_scr;
#define g_cnt (p.scr->cnt)
#define g_slot (p.scr->slot)
#define g_mod (p.scr->mod)
#define g_T (p.scr->T)
#define g_h3 (p.scr->h3)
#define g_U (p.scr->U)
constexpr int CNT_EPOCH = 0, CNT_H3 = 1, CNT_X1 = 26, CNT_NC = 27, CNT_U = 2;
#define PROFT(i) do {} while (0)
#define PROFDUMP() do {} while (0)
#define PROF0(i) do {} while (0)

__device__ __forceinline__ void mbar_init(uint32_t bar, uint32_t cnt) { asm volatile("mbarrier.init.shared::cta.b64 [%0], %1;" :: "r"(bar), "r"(cnt) : "memory"); }
__device__ __forceinline__ void mbar_expect(uint32_t bar, uint32_t bytes) { asm volatile("mbarrier.arrive.expect_tx.shared::cta.b64 _, [%0], %1;" :: "r"(bar), "r"(bytes) : "memory"); }
__device__ __forceinline__ void mbar_arrive(uint32_t bar) { asm volatile("mbarrier.arrive.shared::cta.b64 _, [%0];" :: "r"(bar) : "memory"); }
__device__ __forceinline__ void mbar_arrive_n(uint32_t bar, uint32_t n) { asm volatile("mbarrier.arrive.shared::cta.b64 _, [%0], %1;" :: "r"(bar), "r"(n) : "memory"); }
__device__ __forceinline__ void mbar_arrive_remote(uint32_t rbar) { asm volatile("mbarrier.arrive.relaxed.cluster.shared::cluster.b64 _, [%0];" :: "r"(rbar) : "memory"); }
__device__ __forceinline__ void mbar_wait(uint32_t bar, uint32_t parity) {
    asm volatile("{.reg .pred p; .reg .u32 c;\n"
        "mbarrier.try_wait.parity.shared::cta.b64 p, [%0], %1;\n@p bra.uni DONE;\nmov.u32 c, 0;\n"
        "LOOP: mbarrier.try_wait.parity.shared::cta.b64 p, [%0], %1;\n@p bra.uni DONE;\n"
        "add.u32 c, c, 1;\nsetp.lt.u32 p, c, %2;\n@p bra.uni LOOP;\ntrap;\nDONE:}" :: "r"(bar), "r"(parity), "n"(SPIN_LIMIT) : "memory");
}
__device__ __forceinline__ bool mbar_test(uint32_t bar, uint32_t parity) {
    uint32_t ok; asm volatile("{.reg .pred p; mbarrier.test_wait.parity.shared::cta.b64 p, [%1], %2; selp.u32 %0, 1, 0, p;}" : "=r"(ok) : "r"(bar), "r"(parity) : "memory"); return ok; }
__device__ __forceinline__ uint32_t mapa(uint32_t a, uint32_t rank) { uint32_t r; asm("mapa.shared::cluster.u32 %0, %1, %2;" : "=r"(r) : "r"(a), "r"(rank)); return r; }
__device__ __forceinline__ uint32_t clk32() { uint32_t r; asm volatile("mov.u32 %0, %%clock;" : "=r"(r)); return r; }
__device__ __forceinline__ void hb() {
    asm volatile("{.reg .b32 a, b; .reg .pred p; mma.sync.aligned.m16n8k8.row.col.f16.f16.f16.f16 {a, b}, {%0,%0}, {%0}, {%0,%0};\n"
                 "setp.ne.u32 p, a, 0; @p trap;}" :: "r"(0));
}
__device__ __forceinline__ void spin_until(uint32_t t) {
    while (__any_sync(~0u, (int)(clk32() - t) < -SLP * 4)) { __nanosleep(SLP); hb(); }
    while (__any_sync(~0u, (int)(clk32() - t) < 0)) {}
}
__device__ __forceinline__ bool elect() { uint32_t r; asm volatile("{.reg .pred p; elect.sync _|p, 0xffffffff; selp.u32 %0, 1, 0, p;}" : "=r"(r)); return r; }
__device__ __forceinline__ void bar_sync(int id, int n) { asm volatile("bar.sync %0, %1;" :: "r"(id), "r"(n) : "memory"); }
__device__ __forceinline__ void bulk_load(uint32_t dst, const void* src, uint32_t bytes, uint32_t bar) {
    asm volatile("cp.async.bulk.shared::cluster.global.mbarrier::complete_tx::bytes [%0], [%1], %2, [%3];" :: "r"(dst), "l"(src), "r"(bytes), "r"(bar) : "memory"); }
__device__ __forceinline__ void tma2(uint32_t dst, const CUtensorMap* m, int c0, int c1, uint32_t bar) {
    asm volatile("cp.async.bulk.tensor.2d.shared::cluster.global.mbarrier::complete_tx::bytes [%0], [%1, {%3, %4}], [%2];" :: "r"(dst), "l"(m), "r"(bar), "r"(c0), "r"(c1) : "memory"); }
__device__ __forceinline__ void tma3(uint32_t dst, const CUtensorMap* m, int c0, int c1, int c2, uint32_t bar) {
    asm volatile("cp.async.bulk.tensor.3d.shared::cluster.global.mbarrier::complete_tx::bytes [%0], [%1, {%3, %4, %5}], [%2];" :: "r"(dst), "l"(m), "r"(bar), "r"(c0), "r"(c1), "r"(c2) : "memory"); }
__device__ __forceinline__ void tma4(uint32_t dst, const CUtensorMap* m, int c0, int c1, int c2, int c3, uint32_t bar) {
    asm volatile("cp.async.bulk.tensor.4d.shared::cluster.global.mbarrier::complete_tx::bytes [%0], [%1, {%3, %4, %5, %6}], [%2];" :: "r"(dst), "l"(m), "r"(bar), "r"(c0), "r"(c1), "r"(c2), "r"(c3) : "memory"); }
__device__ __forceinline__ void fence_async_g() { asm volatile("fence.proxy.async.global;" ::: "memory"); }
__device__ __forceinline__ void fence_async_s() { asm volatile("fence.proxy.async.shared::cta;" ::: "memory"); }
__device__ __forceinline__ uint4 lds128(uint32_t a) { uint4 v; asm volatile("ld.shared.v4.u32 {%0,%1,%2,%3}, [%4];" : "=r"(v.x), "=r"(v.y), "=r"(v.z), "=r"(v.w) : "r"(a) : "memory"); return v; }
__device__ __forceinline__ uint32_t lds32(uint32_t a) { uint32_t v; asm volatile("ld.shared.u32 %0, [%1];" : "=r"(v) : "r"(a) : "memory"); return v; }
__device__ __forceinline__ void sts128(uint32_t a, uint4 v) { asm volatile("st.shared.v4.u32 [%0], {%1,%2,%3,%4};" :: "r"(a), "r"(v.x), "r"(v.y), "r"(v.z), "r"(v.w) : "memory"); }
__device__ __forceinline__ void sts32(uint32_t a, uint32_t v) { asm volatile("st.shared.u32 [%0], %1;" :: "r"(a), "r"(v) : "memory"); }
__device__ __forceinline__ void sts16(uint32_t a, uint32_t v) { asm volatile("st.shared.u16 [%0], %1;" :: "r"(a), "h"((uint16_t)v) : "memory"); }
__device__ __forceinline__ uint4 ldx128(const void* p) {
    uint4 v; asm volatile("{.reg .b128 t; .reg .b64 a, b; ld.relaxed.gpu.global.b128 t, [%4]; mov.b128 {a, b}, t; mov.b64 {%0,%1}, a; mov.b64 {%2,%3}, b;}"
        : "=r"(v.x), "=r"(v.y), "=r"(v.z), "=r"(v.w) : "l"(p) : "memory"); return v; }
__device__ __forceinline__ void stx128(void* p, uint4 v) {
    asm volatile("{.reg .b128 t; .reg .b64 a, b; mov.b64 a, {%1,%2}; mov.b64 b, {%3,%4}; mov.b128 t, {a, b}; st.relaxed.gpu.global.b128 [%0], t;}"
        :: "l"(p), "r"(v.x), "r"(v.y), "r"(v.z), "r"(v.w) : "memory"); }
__device__ __forceinline__ uint32_t ld_acquire(const uint32_t* p) { uint32_t v; asm volatile("ld.acquire.gpu.global.u32 %0, [%1];" : "=r"(v) : "l"(p) : "memory"); return v; }
__device__ __forceinline__ void st_relaxed(uint32_t* p, uint32_t v) { asm volatile("st.relaxed.gpu.global.u32 [%0], %1;" :: "l"(p), "r"(v) : "memory"); }
__device__ __forceinline__ void red_release(uint32_t* p) { asm volatile("red.release.gpu.global.add.u32 [%0], 1;" :: "l"(p) : "memory"); }
template <int SLEEP> __device__ __forceinline__ void wait_count(const uint32_t* p, uint32_t target) {
    int it = 0; while ((int)(ld_acquire(p) - target) < 0) { if (SLEEP) __nanosleep(SLEEP); if (++it > SPIN_LIMIT) __trap(); }
}
__device__ __forceinline__ uint32_t ldg_nc32(const void* p) { uint32_t v; asm volatile("ld.global.nc.L1::no_allocate.u32 %0, [%1];" : "=r"(v) : "l"(p)); return v; }
__device__ __forceinline__ uint32_t ldg_nc16(const void* p) { uint16_t v; asm volatile("ld.global.nc.u16 %0, [%1];" : "=h"(v) : "l"(p)); return v; }
__device__ __forceinline__ float bf_lo(uint32_t w) { return __uint_as_float(w << 16); }
__device__ __forceinline__ float bf_hi(uint32_t w) { return __uint_as_float(w & 0xFFFF0000u); }
__device__ __forceinline__ uint32_t pack_bf(float lo, float hi) { uint32_t r; asm("cvt.rn.bf16x2.f32 %0, %1, %2;" : "=r"(r) : "f"(hi), "f"(lo)); return r; }
__device__ __forceinline__ uint32_t pack_h(float lo, float hi) { uint32_t r; asm("cvt.rn.f16x2.f32 %0, %1, %2;" : "=r"(r) : "f"(hi), "f"(lo)); return r; }
__device__ __forceinline__ float bf_round(float v) { return bf_lo(pack_bf(v, 0.f)); }
__device__ __forceinline__ uint32_t hmul2(uint32_t a, uint32_t b) { uint32_t r; asm("mul.rn.f16x2 %0, %1, %2;" : "=r"(r) : "r"(a), "r"(b)); return r; }
__device__ __forceinline__ uint32_t hfma2(uint32_t a, uint32_t b, uint32_t c) { uint32_t r; asm("fma.rn.f16x2 %0, %1, %2, %3;" : "=r"(r) : "r"(a), "r"(b), "r"(c)); return r; }
__device__ __forceinline__ uint32_t hfms2(uint32_t a, uint32_t b, uint32_t c) { uint32_t r; asm("{.reg .b32 t; neg.f16x2 t, %3; fma.rn.f16x2 %0, %1, %2, t;}" : "=r"(r) : "r"(a), "r"(b), "r"(c)); return r; }
__device__ __forceinline__ uint32_t hadd2(uint32_t a, uint32_t b) { uint32_t r; asm("add.rn.f16x2 %0, %1, %2;" : "=r"(r) : "r"(a), "r"(b)); return r; }
__device__ __forceinline__ uint32_t hsub2(uint32_t a, uint32_t b) { uint32_t r; asm("sub.rn.f16x2 %0, %1, %2;" : "=r"(r) : "r"(a), "r"(b)); return r; }
__device__ __forceinline__ void cmul_neg(uint32_t& re, uint32_t& im, uint32_t c, uint32_t s) { uint32_t a = hfma2(re, c, hmul2(im, s)), b = hfms2(im, c, hmul2(re, s)); re = a; im = b; }
__device__ __forceinline__ void cmul_pos(uint32_t& re, uint32_t& im, uint32_t c, uint32_t s) { uint32_t a = hfms2(re, c, hmul2(im, s)), b = hfma2(im, c, hmul2(re, s)); re = a; im = b; }
__device__ __forceinline__ void mma_h(uint32_t& d0, uint32_t& d1, uint32_t a0, uint32_t a1, uint32_t a2, uint32_t a3, uint32_t b0, uint32_t b1) {
    asm("mma.sync.aligned.m16n8k16.row.col.f16.f16.f16.f16 {%0,%1}, {%2,%3,%4,%5}, {%6,%7}, {%0,%1};" : "+r"(d0), "+r"(d1) : "r"(a0), "r"(a1), "r"(a2), "r"(a3), "r"(b0), "r"(b1)); }
__device__ __forceinline__ void mma_h8(uint32_t& d0, uint32_t& d1, uint32_t a0, uint32_t a1, uint32_t b0) {
    asm("mma.sync.aligned.m16n8k8.row.col.f16.f16.f16.f16 {%0,%1}, {%2,%3}, {%4}, {%0,%1};" : "+r"(d0), "+r"(d1) : "r"(a0), "r"(a1), "r"(b0)); }
template <int NQ> __device__ __forceinline__ void load_tab(uint32_t (&r)[NQ * 4], uint32_t addr) {
    #pragma unroll
    for (int i = 0; i < NQ; i++) { uint4 v = lds128(addr + i * 512); r[4 * i] = v.x; r[4 * i + 1] = v.y; r[4 * i + 2] = v.z; r[4 * i + 3] = v.w; }
}
__device__ __forceinline__ float gelu2(float x) {
    float t = x * fmaf(x * x, 0.044715f * 0.7978845608028654f, 0.7978845608028654f), th;
    asm volatile("tanh.approx.f32 %0, %1;" : "=f"(th) : "f"(t));
    return fmaf(x, th, x);
}
__device__ __forceinline__ uint32_t desc_lo(uint32_t addr, uint32_t lbo) { return ((addr & 0x3FFFF) >> 4) | ((lbo >> 4) << 16); }
constexpr uint32_t DHI_A = (1024 >> 4) | (1u << 30), DHI_H3 = 256 >> 4, DHI_U = 128 >> 4;
#define WG_FENCE() asm volatile("wgmma.fence.sync.aligned;" ::: "memory")
#define WG_COMMIT() asm volatile("wgmma.commit_group.sync.aligned;" ::: "memory")
#define WG_WAIT(n) asm volatile("wgmma.wait_group.sync.aligned %0;" :: "n"(n) : "memory")
#define R4(b) "+f"(d[b]), "+f"(d[b + 1]), "+f"(d[b + 2]), "+f"(d[b + 3])
#define R12(b) R4(b), R4(b + 4), R4(b + 8)
#define R36(b) R12(b), R12(b + 12), R12(b + 24)
template <uint32_t BHI> __device__ __forceinline__ void wgmma144(float (&d)[72], uint32_t da, uint32_t db, int acc) {
    asm volatile("{.reg .pred p; .reg .b64 a, b; setp.ne.b32 p, %74, 0; mov.b64 a, {%72, %75}; mov.b64 b, {%73, %76};\n"
        "wgmma.mma_async.sync.aligned.m64n144k16.f32.bf16.bf16 {%0,%1,%2,%3,%4,%5,%6,%7,%8,%9,%10,%11,%12,%13,%14,%15,%16,%17,%18,%19,%20,%21,%22,%23,"
        "%24,%25,%26,%27,%28,%29,%30,%31,%32,%33,%34,%35,%36,%37,%38,%39,%40,%41,%42,%43,%44,%45,%46,%47,"
        "%48,%49,%50,%51,%52,%53,%54,%55,%56,%57,%58,%59,%60,%61,%62,%63,%64,%65,%66,%67,%68,%69,%70,%71}, a, b, p, 1, 1, 1, 1;}\n"
        : R36(0), R36(36) : "r"(da), "r"(db), "r"(acc), "n"(DHI_A), "n"(BHI));
}
__device__ __forceinline__ void wgmma144x4(float (&d)[72], const uint64_t (&a)[4], const uint64_t (&b)[4]) {
    #define WG144 "wgmma.mma_async.sync.aligned.m64n144k16.f32.bf16.bf16 {%0,%1,%2,%3,%4,%5,%6,%7,%8,%9,%10,%11,%12,%13,%14,%15,%16,%17,%18,%19,%20,%21,%22,%23,%24,%25,%26,%27,%28,%29,%30,%31,%32,%33,%34,%35,%36,%37,%38,%39,%40,%41,%42,%43,%44,%45,%46,%47,%48,%49,%50,%51,%52,%53,%54,%55,%56,%57,%58,%59,%60,%61,%62,%63,%64,%65,%66,%67,%68,%69,%70,%71}, "
    asm volatile("{"
        WG144 "%72, %76, 1, 1, 1, 1, 1;\n" WG144 "%73, %77, 1, 1, 1, 1, 1;\n" WG144 "%74, %78, 1, 1, 1, 1, 1;\n" WG144 "%75, %79, 1, 1, 1, 1, 1;}\n"
        : R36(0), R36(36) : "l"(a[0]), "l"(a[1]), "l"(a[2]), "l"(a[3]), "l"(b[0]), "l"(b[1]), "l"(b[2]), "l"(b[3]));
}
__device__ __forceinline__ void wgmma40_rs(float (&d)[20], uint32_t a0, uint32_t a1, uint32_t a2, uint32_t a3, uint32_t db, int acc) {
    asm volatile("{.reg .pred p; .reg .b64 b; setp.ne.b32 p, %25, 0; mov.b64 b, {%24, %26};\n"
        "wgmma.mma_async.sync.aligned.m64n40k16.f32.f16.f16 {%0,%1,%2,%3,%4,%5,%6,%7,%8,%9,%10,%11,%12,%13,%14,%15,%16,%17,%18,%19}, {%20,%21,%22,%23}, b, p, 1, 1, 0;}\n"
        : R12(0), R4(12), R4(16) : "r"(a0), "r"(a1), "r"(a2), "r"(a3), "r"(db), "r"(acc), "n"(DHI_H3));
}
__device__ __forceinline__ void wgmma72(float (&d)[36], uint32_t da, uint32_t db, int acc) {
    asm volatile("{.reg .pred p; .reg .b64 a, b; setp.ne.b32 p, %38, 0; mov.b64 a, {%36, %39}; mov.b64 b, {%37, %40};\n"
        "wgmma.mma_async.sync.aligned.m64n72k16.f32.bf16.bf16 {%0,%1,%2,%3,%4,%5,%6,%7,%8,%9,%10,%11,%12,%13,%14,%15,%16,%17,%18,%19,%20,%21,%22,%23,"
        "%24,%25,%26,%27,%28,%29,%30,%31,%32,%33,%34,%35}, a, b, p, 1, 1, 1, 1;}\n"
        : R36(0) : "r"(da), "r"(db), "r"(acc), "n"(DHI_A), "n"(DHI_H3));
}

__device__ __forceinline__ int g2_kb(int n, int kh, int gi, int c2) {
    if (n < 4) return 36 * kh + 9 * n + 8;
    if (n == 4) return 9 * gi + 4 * c2 + 2 * kh + 1;
    const int w = n > 20, m = n - (w ? 19 : 5);
    return 9 * ((gi * w + (m >> 1)) & 7) + 4 * (n == 35 ? 1 - c2 : m & 1) + 2 * kh + w;
}

__device__ __forceinline__ void add_lo(uint64_t& d, uint32_t a) { asm("{.reg .b32 l, h; mov.b64 {l, h}, %0; add.u32 l, l, %1; mov.b64 %0, {l, h};}" : "+l"(d) : "r"(a)); }
template <uint32_t BHI, int I0, int I1, bool FIRST, class Hook>
__device__ __forceinline__ void mainloop(float (&d)[72], uint32_t bars, uint32_t da0, uint32_t db0, bool lead, Hook hook) {
    uint32_t s = I0 % NST, ph = (I0 / NST) & 1, prev = (I0 + NST - (I0 == IT_P1 ? 2 : 1)) % NST;
    uint32_t ready = 0;
    uint64_t da[4], db[4];
    #pragma unroll
    for (int k = 0; k < 4; k++) { da[k] = ((uint64_t)DHI_A << 32) + da0 + s * (A_BYTES / 16) + k * 128; db[k] = ((uint64_t)BHI << 32) + db0 + s * (B_BYTES / 16) + k * 288; }
    #pragma unroll 1
    for (int i = I0; i < I1; i++) {
        if (!ready) mbar_wait(bars + 8 * BAR_FULL + 8 * s, ph);
        const uint32_t rel = bars + 8 * BAR_EMPTY + 8 * prev, ph0 = ph; const int i0 = i;
        const bool skip = I1 == IT_P1 && (s == P2S - 1 || s == P2S + 2);
        prev = s; s += skip ? 2 : 1; if (s >= NST) { s -= NST; ph ^= 1; }
        const uint32_t adva = (s - prev) * (A_BYTES / 16), advb = (s - prev) * (B_BYTES / 16);
        WG_FENCE();
        wgmma144x4(d, da, db);
        WG_COMMIT();
        #pragma unroll
        for (int k = 0; k < 4; k++) { add_lo(da[k], adva); add_lo(db[k], advb); }
        if (skip) { mbar_wait(bars + 8 * BAR_FULL + 8 * prev + 8, ph0); i++; }
        ready = __shfl_sync(~0u, (uint32_t)mbar_test(bars + 8 * BAR_FULL + 8 * s, ph), 0);
        WG_WAIT(1);
        if (lead && (!FIRST || i0 > I0)) mbar_arrive(rel);
        hook(i0);
    }
}

struct Params {
    const uint16_t *wmod, *c, *x;
    Scratch* scr;
    const Tab* tab;
    const uint16_t *wr, *wi, *w1, *b1, *w2, *b2;
    uint16_t* out;
};

__device__ __forceinline__ void mma_bf(float (&d)[4], const uint32_t (&a)[4], uint32_t b0, uint32_t b1) {
    asm("mma.sync.aligned.m16n8k16.row.col.f32.bf16.bf16.f32 {%0,%1,%2,%3}, {%4,%5,%6,%7}, {%8,%9}, {%0,%1,%2,%3};"
        : "+f"(d[0]), "+f"(d[1]), "+f"(d[2]), "+f"(d[3]) : "r"(a[0]), "r"(a[1]), "r"(a[2]), "r"(a[3]), "r"(b0), "r"(b1)); }
__device__ __forceinline__ void ldsm4t(uint32_t (&a)[4], uint32_t addr) {
    asm volatile("ldmatrix.sync.aligned.m8n8.x4.trans.shared.b16 {%0,%1,%2,%3}, [%4];" : "=r"(a[0]), "=r"(a[1]), "=r"(a[2]), "=r"(a[3]) : "r"(addr) : "memory"); }
__device__ __forceinline__ void ln_stats(const uint32_t (&w)[9], const uint32_t (&one)[9], int g, int q, float& r, float& mr) {
    float c[2][4] = {};
    #pragma unroll
    for (int p = 0; p < 9; p++)
        asm("mma.sync.aligned.m16n8k8.row.col.f32.bf16.bf16.f32 {%0,%1,%2,%3}, {%4,%5}, {%4}, {%0,%1,%2,%3};"
            : "+f"(c[p & 1][0]), "+f"(c[p & 1][1]), "+f"(c[p & 1][2]), "+f"(c[p & 1][3]) : "r"(w[p]), "r"(one[p]));
    const float t = (g & 1) ? c[0][1] + c[1][1] : c[0][0] + c[1][0];
    float s1 = (c[0][2] + c[1][2]) + (c[0][3] + c[1][3]), s2 = __shfl_sync(~0u, t, 9 * q) + __shfl_sync(~0u, t, 9 * q + 4);
    #pragma unroll
    for (int o = 1; o < 4; o <<= 1) { s1 += __shfl_xor_sync(~0u, s1, o); s2 += __shfl_xor_sync(~0u, s2, o); }
    const float m = s1 * (1.f / D_);
    asm("rsqrt.approx.ftz.f32 %0, %1;" : "=f"(r) : "f"(fmaxf(fmaf(s2, 1.f / D_, -m * m), 0.f) + 1e-5f));
    mr = -m * r;
}
__device__ __forceinline__ float silu(float v) { return __fdividef(v, 1.f + __expf(-v)); }
__device__ __forceinline__ uint32_t bfma2(uint32_t a, uint32_t b, uint32_t c) { uint32_t r; asm("fma.rn.bf16x2 %0, %1, %2, %3;" : "=r"(r) : "r"(a), "r"(b), "r"(c)); return r; }
__device__ __forceinline__ void radix16(const uint4 (&V)[4], const uint32_t (&B)[16], uint4 (&o)[4]) {
    #pragma unroll
    for (int nt = 0; nt < 4; nt++) o[nt] = make_uint4(0, 0, 0, 0);
    #pragma unroll
    for (int u = 0; u < 4; u++)
        #pragma unroll
        for (int nt = 0; nt < 4; nt++) {
            const uint32_t b = B[((u >> 1) * 4 + nt) * 2 + (u & 1)];
            mma_h8(o[nt].x, o[nt].y, V[u].x, V[u].y, b); mma_h8(o[nt].z, o[nt].w, V[u].z, V[u].w, b);
        }
}
template <int OFF, int N> __device__ __forceinline__ void gelu_store(const float (&d)[N], char* p, int q) {
    uint32_t w[9];
    #pragma unroll
    for (int blk = 0; blk < 9; blk++) w[blk] = pack_bf(gelu2(d[OFF + 4 * blk]), gelu2(d[OFF + 4 * blk + 1]));
    asm volatile("st.v4.u32 [%0], {%1,%2,%3,%4};" :: "l"(p + q * 128), "r"(w[0]), "r"(w[1]), "r"(w[2]), "r"(w[3]) : "memory");
    asm volatile("st.v4.u32 [%0+512], {%1,%2,%3,%4};" :: "l"(p + q * 128), "r"(w[4]), "r"(w[5]), "r"(w[6]), "r"(w[7]) : "memory");
    asm volatile("st.u32 [%0+1024], %1;" :: "l"(p + q * 4), "r"(w[8]) : "memory");
}

__global__ void __cluster_dims__(2, 1, 1) __launch_bounds__(NTHR, 1)
fused_kernel(const Params p,
             const __grid_constant__ CUtensorMap tm_w1a, const __grid_constant__ CUtensorMap tm_w1b, const __grid_constant__ CUtensorMap tm_w2,
             const __grid_constant__ CUtensorMap tm_h3a, const __grid_constant__ CUtensorMap tm_h3b,
             const __grid_constant__ CUtensorMap tm_wr, const __grid_constant__ CUtensorMap tm_wi, const __grid_constant__ CUtensorMap tm_wm,
             const __grid_constant__ CUtensorMap tm_t, const __grid_constant__ CUtensorMap tm_tx, const __grid_constant__ CUtensorMap tm_o,
             const __grid_constant__ CUtensorMap tm_h3s, const __grid_constant__ CUtensorMap tm_ws)
{
    extern __shared__ char smem_raw[];
    const uint32_t t0 = clk32();
    const uint32_t sm = __shfl_sync(~0u, ((uint32_t)__cvta_generic_to_shared(smem_raw) + 1023u) & ~1023u, 0);
    const int tid = threadIdx.x, warp = __shfl_sync(~0u, tid >> 5, 0), lane = tid & 31, g = lane >> 2, q = lane & 3;
    const int b = blockIdx.x;
    const uint32_t rank = b & 1;
    const uint32_t bars = sm + OFF_BAR;
    const bool rowcta = b < 128;

    auto nc_issue = [&](int st, uint32_t sl) {
        const int pass = st >= 18;
        mbar_expect(bars + 8 * (BAR_X + sl), 28672);
        tma3(sm + sl * 28672, &tm_wm, 0, 32 * (st - 18 * pass), 18 + 28 * pass + 7 * (b - 128), bars + 8 * (BAR_X + sl));
    };
    uint32_t epoch;
    const bool strip = b < 72 && !(b & 1);
    const bool sil = (warp >> 2) == 2 && lane < 24 && (strip || !rowcta);
    uint32_t cw[3];
    if (elect()) {
        mbar_init(bars + 8 * (BAR_X + warp), rowcta || warp < 6 ? 1 : 14);
        if (warp >= 12) {
            if (strip) { const uint32_t sb = bars + 8 * (BAR_ST + warp - 12);
                mbar_init(sb, 1); mbar_expect(sb, 9216); tma2(sm + OFF_STRIP + (warp - 12) * 9216, &tm_ws, 16 * b, 144 * (warp - 12), sb); }
        } else if (warp == 7) {
            mbar_init(bars + 8 * BAR_TAB, 1); mbar_expect(bars + 8 * BAR_TAB, rowcta ? QA * 512 + 16 : 16);
            bulk_load(sm + OFF_EPOCH, g_cnt + CNT_EPOCH * 32, 16, bars + 8 * BAR_TAB);
            if (rowcta) bulk_load(sm + OFF_TAB, p.tab, QA * 512, bars + 8 * BAR_TAB);
        } else if (b + 132 * warp < 576) {
            asm volatile("cp.async.bulk.prefetch.L2.global [%0], 2304;" :: "l"(p.wmod + (b + 132 * warp) * 3456) : "memory");
        }
    }
    if (sil) {
        #pragma unroll
        for (int u = 0; u < 3; u++) cw[u] = ldg_nc32(p.c + 144 * (warp - 8) + 48 * u + 2 * lane);
    }
    if (warp == 6) hb();
    __syncthreads();
    if (!rowcta) { if (warp < 6 && elect()) nc_issue(warp, warp); }
    if (warp == 5 || warp == 6) {
        if (elect()) {
            if (warp == 5) {
                for (int i = BAR_W; i < BAR_X; i++) mbar_init(bars + 8 * i, i == BAR_DONE || i == BAR_NC ? 4 : i == BAR_W1GO ? 2 : 1);
                mbar_expect(bars + 8 * BAR_W, 28672); mbar_expect(bars + 8 * BAR_TAB2, (QB + QC) * 512);
                mbar_expect(bars + 8 * BAR_ROLE, 4); mbar_expect(bars + 8 * BAR_P2R, 9216); mbar_expect(bars + 8 * BAR_RECV, 18432); mbar_expect(bars + 8 * BAR_XT, 18432);
            } else {
                for (int i = 0; i < 2 * NST; i++) mbar_init(bars + 8 * i, 2);
                for (int i = 0; i < NST; i++) mbar_expect(bars + 8 * (BAR_FULL + i), A_BYTES);
            }
            asm volatile("fence.mbarrier_init.release.cluster;" ::: "memory");
        }
    } else if (warp >= 12 && elect())
        asm volatile("prefetch.tensormap [%0];" :: "l"(warp == 12 ? &tm_wr : warp == 13 ? &tm_wi : warp == 14 ? &tm_t : &tm_tx) : "memory");
    uint32_t sb[18];
    if ((warp >> 2) == 2) {
        if (sil) {
            #pragma unroll
            for (int u = 0; u < 3; u++) sts32(sm + OFF_SILU + (72 * (warp - 8) + 24 * u + lane) * 4, pack_bf(silu(bf_lo(cw[u])), silu(bf_hi(cw[u]))));
        }
        __syncwarp();
        if (strip) {
            #pragma unroll
            for (int u = 0; u < 18; u++) sb[u] = lds32(sm + OFF_SILU + (72 * (warp - 8) + 4 * u + q) * 4);
        }
    }
    if (rowcta && elect()) {
        if (XDELAY) while ((int)(clk32() - t0) < XDELAY) {}
        mbar_expect(bars + 8 * (BAR_X + warp), 1152);
        bulk_load(sm + OFF_STAGE + warp * 1152, p.x + (size_t)(b + 128 * warp) * D_, 1152, bars + 8 * (BAR_X + warp));
    }
    __syncwarp();
    hb();

    const int trow = 4 * (b & 7) + ((b >> 4) & 3) + 64 * ((b >> 3) & 1) + 32 * (b >> 6);
    uint32_t* const tptr = g_T + (size_t)trow * TP + (warp < 9 ? q * 288 + 32 * warp : 4608 + 8 * q) + 4 * g;
    const int tstr = warp < 9 ? 1152 : 32;
    const uint32_t scol = sm + OFF_SPEC + (q * SPEC_P + (warp < 8 ? 72 * (warp >> 1) + 40 * (warp & 1) + 4 * g : warp == 8 ? 72 * (g >> 1) + 32 + 4 * (g & 1) : 288 + 4 * g)) * 4;
    const int wc0 = (b >> 3) * 289 + 72 * ((b & 7) >> 1) + 40 * (b & 1);

    uint32_t xw[9], one[9], t_st = t0, hexp = 0;
    if (!rowcta) {
        const int nst = b < 130 ? 36 : 18;
        __syncthreads();
        asm volatile("barrier.cluster.arrive.relaxed.aligned;" ::: "memory");
        mbar_wait(bars + 8 * BAR_TAB, 0);
        epoch = lds32(sm + OFF_EPOCH);
        if (warp == 14) {
            uint32_t sl = 0, ph = 0;
            #pragma unroll 1
            for (int st = 6; st < nst; st++) {
                mbar_wait(bars + 8 * (BAR_X + 6 + sl), ph);
                if (elect()) nc_issue(st, sl);
                if (++sl == 6) { sl = 0; ph ^= 1; }
            }
        } else if (warp < 14) {
            uint32_t sl = 0, ph = 0;
            const uint32_t ad0 = sm + (warp >> 1) * 4096 + ((lane & 7) + 8 * (lane >> 4)) * 128, ch = (warp & 1) * 4 + ((lane >> 3) & 1);
            #pragma unroll 1
            for (int pass = 0; pass * 18 < nst; pass++) {
                float acc[2][4] = {};
                #pragma unroll 1
                for (int st = 0; st < 18; st++) {
                    const uint32_t sa = sm + OFF_SILU + (16 * st + q) * 4;
                    const uint32_t b0 = lds32(sa), b1 = lds32(sa + 16), b2 = lds32(sa + 32), b3 = lds32(sa + 48);
                    mbar_wait(bars + 8 * (BAR_X + sl), ph);
                    #pragma unroll
                    for (int m = 0; m < 2; m++) {
                        uint32_t a[4], a2[4];
                        const uint32_t ad = ad0 + sl * 28672 + ((ch + 2 * m) ^ (lane & 7)) * 16;
                        ldsm4t(a, ad); ldsm4t(a2, ad + 2048);
                        mma_bf(acc[m], a, b0, b1); mma_bf(acc[m], a2, b2, b3);
                    }
                    if (elect()) mbar_arrive(bars + 8 * (BAR_X + 6 + sl));
                    if (++sl == 6) { sl = 0; ph ^= 1; }
                }
                const int cb = 28 * pass + 7 * (b - 128) + (warp >> 1), gg = (g >> 1) + 4 * q;
                uint32_t w[2];
                #pragma unroll
                for (int m = 0; m < 2; m++) {
                    float v = bf_round(q ? acc[m][2] : acc[m][0]); if (cb >= 27) v *= 0.5f; else if (cb >= 18) v += 1.f;
                    w[m] = max(pack_bf(v, __shfl_xor_sync(~0u, v, 4)), 1u);
                }
                if (q < 2 && !(g & 1)) {
                    const int qq = (warp & 1) * 2;
                    if (cb < 27) asm volatile("st.relaxed.gpu.global.v2.u32 [%0], {%1, %2};" :: "l"(p.scr->modc + 32 * cb + 4 * gg + qq), "r"(w[0]), "r"(w[1]) : "memory");
                    else if (cb < 36) { uint32_t* o = p.scr->modc + 896 + 32 * (cb - 27) + 8 * qq + gg; o[0] = w[0]; o[8] = w[1]; }
                }
                if (tid == 0 && pass == 0) PROFT(25);
                bar_sync(1, 448);
                if (tid == 0) { fence_async_g(); red_release(g_cnt + (CNT_NC + pass) * 32); }
                __syncwarp();
            }
            fence_async_s();
        }
        __syncthreads();
    } else {
        uint32_t ta[QA * 4];
        if (strip && (warp >> 2) == 2) {
            const int w = warp - 8;
            const uint32_t ra = sm + OFF_STRIP + (144 * w + (lane & 7) + 8 * (lane >> 4)) * 64, sw = (lane >> 1) & 3, ch = (lane >> 3) & 1;
            float acc[2][2][4] = {};
            mbar_wait(bars + 8 * (BAR_ST + w), 0);
            #pragma unroll
            for (int u = 0; u < 9; u++)
                #pragma unroll
                for (int m = 0; m < 2; m++) { uint32_t a[4]; ldsm4t(a, ra + u * 1024 + ((ch + 2 * m) ^ sw) * 16); mma_bf(acc[u & 1][m], a, sb[2 * u], sb[2 * u + 1]); }
            #define PICK(a_) ((q & 2) ? ((q & 1) ? a_[1][2] : a_[1][0]) : ((q & 1) ? a_[0][2] : a_[0][0]))
            sts32(sm + OFF_RED + ((8 * q + g) * 4 + w) * 4, __float_as_uint(PICK(acc[0]) + PICK(acc[1])));
            if (tid == 256) PROFT(0);
            bar_sync(10, 128);
            if (warp == 8) {
                mbar_wait(bars + 8 * BAR_TAB, 0);
                const uint4 v = lds128(sm + OFF_RED + lane * 16);
                float sum = bf_round((__uint_as_float(v.x) + __uint_as_float(v.y)) + (__uint_as_float(v.z) + __uint_as_float(v.w)));
                if (b >= 36) sum = bf_round(1.f + sum);
                st_relaxed(g_mod + b * 16 + (lane & 16) + (lane & 1) * 8 + ((lane & 15) >> 1), (fabsf(sum) < 8.f ? pack_h(0.f, sum) : __float_as_uint(sum) | 0x8000u) | ((lds32(sm + OFF_EPOCH) + 1) & 0x7FFFu));
                asm volatile("bar.arrive 11, 416;" ::: "memory");
                if (tid == 256) PROFT(1);
            }
        }
        mbar_wait(bars + 8 * BAR_TAB, 0);
        load_tab<QA>(ta, sm + OFF_TAB + lane * 16);
        epoch = lds32(sm + OFF_EPOCH);
        const uint32_t tag = (epoch + 1) & 0x7FFFu;
        auto w_prefetch = [&]() {
            if (warp >= 14 && elect()) asm volatile("cp.async.bulk.prefetch.L2.global [%0], 9248;" :: "l"((warp == 14 ? p.wr : p.wi) + b * 4624) : "memory");
            __syncwarp();
        };
        uint32_t nb[2][5];
        uint4 mv = make_uint4(tag, tag, tag, tag);
        const bool poller = warp < 8 || warp == 12;
        const int mc = warp < 8 ? tid : tid - 128, mst = (mc >> 2) % 36, midx = (mc < 144 ? 10 : 0) + 5 * ((mc >> 1) & 1) + (mst >> 3);
        const uint32_t* mp = g_mod + mc * 4;
        const uint32_t ma = sm + OFF_MODA + ((midx >> 2) * 32 + (mc & 1) * 16 + (mst & 3)) * 16 + (midx & 3) * 4 + ((mst >> 2) & 1) * 2;
        #define MOD_MISSING ((((mv.x ^ tag) | (mv.y ^ tag) | (mv.z ^ tag) | (mv.w ^ tag)) & 0x7FFFu) != 0)
        if (strip && (warp >> 2) != 2) bar_sync(11, 416);
        #pragma unroll
        for (int i = 0; i < 9; i++) one[i] = lds32(sm + OFF_TAB + (QA - 1) * 512 + i * 16 + 8);
        hb();
        mbar_wait(bars + 8 * (BAR_X + warp), 0);
        if (poller) mv = ldx128(mp);
        PROF0(28);
        #pragma unroll
        for (int i = 0; i < 9; i++) xw[i] = lds32(sm + OFF_STAGE + warp * 1152 + (32 * i + 8 * q + g) * 4);
        {
            float r, mr;
            ln_stats(xw, one, g, q, r, mr);
            #pragma unroll
            for (int pp = 0; pp < 5; pp++) {
                nb[0][pp] = pack_h(fmaf(bf_lo(xw[2 * pp]), r, mr), pp < 4 ? fmaf(bf_lo(xw[pp < 4 ? 2 * pp + 1 : 0]), r, mr) : 0.f);
                nb[1][pp] = pack_h(fmaf(bf_hi(xw[2 * pp]), r, mr), pp < 4 ? fmaf(bf_hi(xw[pp < 4 ? 2 * pp + 1 : 0]), r, mr) : 0.f);
            }
        }
        PROF0(2);
        w_prefetch();
        if (poller && MOD_MISSING) mv = ldx128(mp);
        if (warp < 8) {
            if (warp >= 4) sts16(sm + OFF_MODA + ((warp - 3) * 32 + lane) * 16 + (warp - 4) * 4 + 2, 0);
            const int k1 = tid & 15, s1 = tid >> 4;
            float s, c;
            __sincosf((float)(((k1 * (128 * s1 + b) + 1024) & 2047) - 1024) * (3.14159265358979f / 1024.f), &s, &c); s *= 0.25f; c *= 0.25f;
            const int rf = ((s1 >> 3) * 4 + (k1 >> 2)) * 2 + ((s1 >> 2) & 1), ri = ((k1 >> 3) * 4 + (s1 >> 2)) * 2 + ((k1 >> 2) & 1);
            const uint32_t af = sm + OFF_B3 + ((rf >> 2) * 32 + (k1 & 3) * 8 + (s1 & 3)) * 16 + (rf & 3) * 4;
            const uint32_t ai = sm + OFF_B3 + 2048 + ((ri >> 2) * 32 + (s1 & 3) * 8 + (k1 & 3)) * 16 + (ri & 3) * 4;
            sts32(af, pack_h(c, s)); sts32(af + 64, pack_h(-s, c)); sts32(ai, pack_h(c, -s)); sts32(ai + 64, pack_h(s, c));
        }
        if (poller) {
            for (int it = 0; __any_sync(~0u, MOD_MISSING); it++) { if (MOD_MISSING) mv = ldx128(mp); hb(); if (it > SPIN_LIMIT) __trap(); }
            sts16(ma, mv.x >> 16); sts16(ma + 64, mv.y >> 16); sts16(ma + 128, mv.z >> 16); sts16(ma + 192, mv.w >> 16);
        }
        uint32_t redo = 0; asm volatile("" : "+r"(redo));
        #pragma unroll 1
        do { if (redo) {
            const uint32_t w[4] = {mv.x, mv.y, mv.z, mv.w}; float f[4]; uint32_t big = 0;
            #pragma unroll
            for (int e = 0; e < 4; e++) { f[e] = (w[e] & 0x8000u) ? bf_hi(w[e]) : __half2float(__ushort_as_half(w[e] >> 16)); big = max(big, __float_as_uint(f[e]) << 1 >> 24); }
            sts32(sm + OFF_HEXP + warp * 4, __reduce_max_sync(~0u, big));
            __syncthreads();
            hexp = min(__reduce_max_sync(~0u, lds32(sm + OFF_HEXP + (lane & 15) * 4)), 253u) - 127;
            const float sc = __uint_as_float((127 - hexp) << 23);
            if (poller) {
                #pragma unroll
                for (int e = 0; e < 4; e++) sts16(ma + 64 * e, pack_h(f[e] * sc, 0.f));
            }
            mv = make_uint4(0, 0, 0, 0);
          }
          redo = __syncthreads_or((mv.x | mv.y | mv.z | mv.w) & 0x8000u);
          asm volatile("" : "+r"(redo));
        } while (redo);
        PROF0(3);
        asm volatile("barrier.cluster.arrive.relaxed.aligned;" ::: "memory");
        if (warp >= 13 && elect()) {
            if (warp == 15) bulk_load(sm + OFF_TAB + QA * 512, p.tab->w + QA * 128, (QB + QC) * 512, bars + 8 * BAR_TAB2);
            else tma3(sm + OFF_WRAW + (warp - 13) * 14336, warp == 13 ? &tm_wr : &tm_wi, wc0 & ~7, 0, 0, bars + 8 * BAR_W);
        }
        __syncwarp();
        {
            uint32_t md[20];
            load_tab<5>(md, sm + OFF_MODA + lane * 16);
            #pragma unroll
            for (int v = 0; v < 2; v++)
                #pragma unroll
                for (int pp = 0; pp < 5; pp++) nb[v][pp] = hfma2(nb[v][pp], md[v * 5 + pp], md[10 + v * 5 + pp]);
        }
        uint32_t re[3][2], im[3][2];
        #pragma unroll
        for (int mt = 0; mt < 3; mt++)
            #pragma unroll
            for (int v = 0; v < 2; v++) {
                re[mt][v] = 0; im[mt][v] = 0;
                mma_h8(re[mt][v], im[mt][v], ta[24 + 2 * mt], ta[25 + 2 * mt], nb[v][4]);
                mma_h(re[mt][v], im[mt][v], ta[mt * 8], ta[mt * 8 + 1], ta[mt * 8 + 2], ta[mt * 8 + 3], nb[v][0], nb[v][1]);
                mma_h(re[mt][v], im[mt][v], ta[mt * 8 + 4], ta[mt * 8 + 5], ta[mt * 8 + 6], ta[mt * 8 + 7], nb[v][2], nb[v][3]);
                cmul_neg(re[mt][v], im[mt][v], ta[30 + (mt * 2 + v) * 2], ta[31 + (mt * 2 + v) * 2]);
            }
        const uint32_t srow = sm + OFF_SPEC + warp * (SPEC_P * 4);
        #pragma unroll
        for (int nt = 0; nt < 2; nt++) {
            uint32_t o[2][4];
            #pragma unroll
            for (int v = 0; v < 2; v++) {
                const uint32_t b0 = ta[42 + (v * 2 + nt) * 2], b1 = ta[43 + (v * 2 + nt) * 2];
                o[v][0] = o[v][1] = o[v][2] = o[v][3] = 0;
                mma_h(o[v][0], o[v][1], re[0][v], re[1][v], im[0][v], im[1][v], b0, b1);
                mma_h(o[v][2], o[v][3], re[2][0], re[2][1], im[2][0], im[2][1], b0, b1);
            }
            const uint32_t a = srow + (g + 72 * q + 36 * nt) * 4, a2 = srow + (288 - g - 72 * q - 36 * nt) * 4;
            sts32(a, hadd2(o[0][0], o[1][0])); sts32(a + 32, hadd2(o[0][1], o[1][1])); if (g < 3) sts32(a + 64, hadd2(o[0][2], o[1][3]));
            if (g > 0 || (q == 0 && nt == 0)) sts32(a2, hsub2(o[0][0], o[1][0]) ^ 0x80000000u);
            sts32(a2 - 32, hsub2(o[0][1], o[1][1]) ^ 0x80000000u); if (g < 2) sts32(a2 - 64, hsub2(o[0][2], o[1][3]) ^ 0x80000000u);
        }
        uint32_t b3[16];
        if (warp < 10) load_tab<4>(b3, sm + OFF_B3 + lane * 16);
        __syncthreads();
        t_st = clk32();
        PROF0(4);
        if (warp < 10) {
            uint4 V[4], o[4];
            #pragma unroll
            for (int u = 0; u < 4; u++) V[u] = lds128(scol + u * (16 * SPEC_P));
            radix16(V, b3, o);
            #pragma unroll
            for (int nt = 0; nt < 4; nt++) { o[nt].x |= 1u; if (warp < 9 || g < 2) stx128(tptr + nt * tstr, o[nt]); }
        }
        PROF0(5);
    }

    int role = 0;
    asm volatile("barrier.cluster.wait.aligned;" ::: "memory");
    if (warp >= 12) {
        const int t = tid - 384;
        if (tid == 448 && rank == 0) {
            uint32_t smid; asm volatile("mov.u32 %0, %%smid;" : "=r"(smid));
            const uint32_t tp = smid >> 1;
            uint32_t pr = tp < 32 ? (tp & 7) * 8 + (tp >> 3) : tp < 60 ? (1 + (tp - 32) % 7) * 8 + 4 + (tp - 32) / 7 : tp < 62 ? 4 + tp : tp < 66 ? tp - 58 : 0;
            while (atomicExch(g_slot + pr, epoch + 1) == epoch + 1) pr = pr == 65 ? 0 : pr + 1;
            #pragma unroll
            for (int r = 0; r < 2; r++)
                asm volatile("st.async.weak.shared::cluster.mbarrier::complete_tx::bytes.u32 [%0], %1, [%2];" :: "r"(mapa(sm + OFF_MISC, r)), "r"(pr), "r"(mapa(bars + 8 * BAR_ROLE, r)) : "memory");
        }
        __syncwarp();
        if (t == 0) {
            asm volatile("prefetch.tensormap [%0];" :: "l"(&tm_w1a) : "memory");
            asm volatile("prefetch.tensormap [%0];" :: "l"(&tm_h3a) : "memory"); asm volatile("prefetch.tensormap [%0];" :: "l"(&tm_w1b) : "memory");
            asm volatile("prefetch.tensormap [%0];" :: "l"(&tm_h3b) : "memory"); asm volatile("prefetch.tensormap [%0];" :: "l"(&tm_w2) : "memory");
            asm volatile("prefetch.tensormap [%0];" :: "l"(&tm_o) : "memory"); asm volatile("prefetch.tensormap [%0];" :: "l"(&tm_h3s) : "memory");
        }
        __syncwarp();
        if (rowcta) {
            spin_until(t0 + NCP);
            uint4 v[2];
            v[1] = make_uint4(1, 1, 1, 1);
            for (int it = 0;; it++) {
                v[0] = ldx128(p.scr->modc + 4 * t); if (t < 88) v[1] = ldx128(p.scr->modc + 512 + 4 * t);
                if (__all_sync(~0u, min(min(min(v[0].x, v[0].y), min(v[0].z, v[0].w)), min(min(v[1].x, v[1].y), min(v[1].z, v[1].w))) != 0)) break;
                __nanosleep(100); if (it > SPIN_LIMIT) __trap();
            }
            if (t < 72) { const uint32_t sc = ((127 + hexp) << 7) * 0x10001u;
                v[0] = make_uint4(bfma2(v[0].x, sc, 0x80008000u), bfma2(v[0].y, sc, 0x80008000u), bfma2(v[0].z, sc, 0x80008000u), bfma2(v[0].w, sc, 0x80008000u)); }
            #pragma unroll
            for (int u = 0; u < 2; u++) if (u == 0 || t < 88) {
                const uint32_t a = sm + OFF_MODC + (((t >> 5) + 4 * u) * 32 + 4 * (t & 7)) * 16 + ((t >> 3) & 3) * 4;
                sts32(a, v[u].x); sts32(a + 16, v[u].y); sts32(a + 32, v[u].z); sts32(a + 48, v[u].w);
            }
            __syncwarp();
            if (elect()) mbar_arrive(bars + 8 * BAR_NC);
            if (t == 0) PROFT(29);
        }
    } else if (rowcta && warp < 11) {
        const int nw = !(b & 1) ? 10 : (b & 7) == 7 ? 9 : 8;
        const int cm = (b >> 3) * 288 + (b & 7) * 32, cx = (b & 1) ? 4608 + 8 * (b >> 3) : (b >> 3) * 288 + 256 + 4 * (b & 7);
        auto load_in = [&]() {
            if (elect()) {
                mbar_expect(bars + 8 * BAR_XB, nw > 8 ? 20480 : 16384);
                tma2(sm + OFF_STAGE, &tm_t, cm, 0, bars + 8 * BAR_XB);
                if (nw > 8) tma2(sm + OFF_STX, &tm_tx, cx, 0, bars + 8 * BAR_XB);
            }
            __syncwarp();
        };
        if (warp == 10) { fence_async_s(); spin_until(t_st + X1D); load_in(); }
        uint32_t tb[QB * 4], wre[4][2], wim[4][2];
        if (warp < nw) {
            mbar_wait(bars + 8 * BAR_TAB2, 0);
            load_tab<QB>(tb, sm + OFF_TAB + QA * 512 + lane * 16);
            mbar_wait(bars + 8 * BAR_W, 0);
            const int off = wc0 & 7;
            const uint32_t wa = sm + OFF_WRAW + lane * 112 + ((off >> 1) + 2 * warp) * 4, sh = (off & 1) * 16;
            #pragma unroll
            for (int c = 0; c < 2; c++)
                #pragma unroll
                for (int h = 0; h < 2; h++) {
                    uint32_t y[2][2];
                    #pragma unroll
                    for (int e = 0; e < 2; e++) {
                        const uint32_t a = wa + c * 14336 + (h + 2 * e) * 3584, x0 = lds32(a), x1 = lds32(a + 4), x2 = lds32(a + 8);
                        y[e][0] = __funnelshift_r(x0, x1, sh); y[e][1] = __funnelshift_r(x1, x2, sh);
                    }
                    #pragma unroll
                    for (int x = 0; x < 4; x++) {
                        const uint32_t v = (x & 1) ? pack_h(bf_hi(y[0][x >> 1]), bf_hi(y[1][x >> 1])) : pack_h(bf_lo(y[0][x >> 1]), bf_lo(y[1][x >> 1]));
                        if (c) wim[x][h] = v; else wre[x][h] = v;
                    }
                }
        }
        const uint32_t ca = warp < 8 ? sm + OFF_STAGE + lane * 128 + (warp ^ (lane & 7)) * 16 : sm + OFF_STX + lane * 32 + ((warp ^ g) & 1) * 16, cs = warp < 8 ? 4096 : 1024;
        uint32_t V[4][4];
        for (int it = 0;; it++) {
            mbar_wait(bars + 8 * BAR_XB, it & 1);
            uint32_t ok = 1;
            if (warp < nw) {
                #pragma unroll
                for (int u = 0; u < 4; u++) { uint4 t4 = lds128(ca + u * cs); V[u][0] = t4.x; V[u][1] = t4.y; V[u][2] = t4.z; V[u][3] = t4.w; ok &= t4.x; }
            }
            asm volatile("{.reg .pred p; setp.ne.u32 p, %0, 0; bar.red.and.pred p, 1, 352, p; selp.u32 %0, 1, 0, p;}" : "+r"(ok) :: "memory");
            if (ok) break;
            if (warp == 10) { load_in(); hb(); }
            if (it > SPIN_LIMIT / 64) __trap();
        }
        PROF0(7);
        if (warp < nw) {
            uint32_t zr[4][2], zi[4][2];
            #pragma unroll
            for (int x = 0; x < 4; x++) {
                uint32_t er = 0, ei = 0, or_ = 0, oi = 0;
                mma_h(er, ei, tb[0], tb[1], tb[2], tb[3], V[0][x], V[1][x]);
                mma_h(or_, oi, tb[4], tb[5], tb[6], tb[7], V[2][x], V[3][x]);
                uint32_t r0 = hadd2(er, or_), r1 = hsub2(er, or_), i0 = hadd2(ei, oi), i1 = hsub2(ei, oi);
                cmul_neg(r0, i0, tb[8], tb[9]); cmul_neg(r1, i1, tb[10], tb[11]);
                uint32_t xr0 = 0, xr1 = 0, xi0 = 0, xi1 = 0;
                mma_h(xr0, xr1, r0, r1, i0, i1, tb[12], tb[13]);
                mma_h(xi0, xi1, r0, r1, i0, i1, tb[14], tb[15]);
                cmul_pos(xr0, xi0, wre[x][0], wim[x][0]); cmul_pos(xr1, xi1, wre[x][1], wim[x][1]);
                r0 = 0; i0 = 0; r1 = 0; i1 = 0;
                mma_h(r0, i0, tb[12], tb[13], tb[14], tb[15], xr0, xi0);
                mma_h(r1, i1, tb[12], tb[13], tb[14], tb[15], xr1, xi1);
                cmul_pos(r0, i0, tb[16], tb[17]); cmul_pos(r1, i1, tb[18], tb[19]);
                zr[x][0] = hadd2(r0, r1); zr[x][1] = hsub2(r0, r1); zi[x][0] = hadd2(i0, i1); zi[x][1] = hsub2(i0, i1);
            }
            #pragma unroll
            for (int nt = 0; nt < 4; nt++) {
                uint4 o = make_uint4(0, 0, 0, 0);
                const int h = nt >> 1;
                mma_h(o.x, o.y, zr[0][h], zr[1][h], zi[0][h], zi[1][h], tb[20 + 2 * nt], tb[21 + 2 * nt]);
                mma_h(o.z, o.w, zr[2][h], zr[3][h], zi[2][h], zi[3][h], tb[20 + 2 * nt], tb[21 + 2 * nt]);
                o.x &= ~1u;
                sts128(ca + nt * cs, o);
            }
        }
        fence_async_s();
        bar_sync(1, 352);
        t_st = clk32();
        PROF0(8);
        if (warp == 10 && elect()) {
            asm volatile("cp.async.bulk.tensor.2d.global.shared::cta.bulk_group [%0, {%2, %3}], [%1];" :: "l"(&tm_t), "r"(sm + OFF_STAGE), "r"(cm), "r"(0) : "memory");
            if (nw > 8) asm volatile("cp.async.bulk.tensor.2d.global.shared::cta.bulk_group [%0, {%2, %3}], [%1];" :: "l"(&tm_tx), "r"(sm + OFF_STX), "r"(cx), "r"(0) : "memory");
            asm volatile("cp.async.bulk.commit_group;" ::: "memory");
            asm volatile("cp.async.bulk.wait_group.read 0;" ::: "memory");
        }
        __syncwarp();
    }

    if (warp >= 10) { mbar_wait(bars + 8 * BAR_ROLE, 0); role = __shfl_sync(~0u, lds32(sm + OFF_MISC), 0); fence_async_s(); }
    auto first_a = [&]() {
        if (warp >= 10 && role < 64 && elect()) {
            const int it = warp - 10, hi = it >= 3; const bool p2 = it - 3 * hi == 2;
            tma4(sm + OFF_A + it * A_BYTES, p2 ? &tm_w1b : &tm_w1a, 0, 0, p2 ? 64 * rank + 8 * hi : 4 * (it - hi),
                 9 * (role >> 3) + (p2 ? 8 : (role & 4) + 2 * rank), bars + 8 * (BAR_FULL + it));
        }
        __syncwarp();
    };
    if (!rowcta) first_a();
    else {
        uint32_t tc[20], md[28];
        mbar_wait(bars + 8 * BAR_TAB2, 0);
        load_tab<5>(tc, sm + OFF_TAB + (QA + QB) * 512 + lane * 16);
        bool md_early = warp >= 10;
        if (md_early) { mbar_wait(bars + 8 * BAR_NC, 0); load_tab<7>(md, sm + OFF_MODC + lane * 16); }
        if (warp < 10) {
            uint32_t b3[16];
            load_tab<4>(b3, sm + OFF_B3 + 2048 + lane * 16);
            uint4 V[4], o[4];
            const bool tact = warp < 9 || g == 0;
            spin_until(t_st + X2D);
            #pragma unroll
            for (int u = 0; u < 4; u++) { V[u] = make_uint4(0, 0, 0, 0); if (tact) V[u] = ldx128(tptr + u * tstr); }
            md_early = __any_sync(~0u, mbar_test(bars + 8 * BAR_NC, 0));
            if (md_early) load_tab<7>(md, sm + OFF_MODC + lane * 16);
            for (int it = 0; __any_sync(~0u, (V[0].x | V[1].x | V[2].x | V[3].x) & 1u); it++) {
                #pragma unroll
                for (int u = 0; u < 4; u++) if (V[u].x & 1u) V[u] = ldx128(tptr + u * tstr);
                hb();
                if (it > SPIN_LIMIT) __trap();
            }
            PROF0(10);
            radix16(V, b3, o);
            if (tact) {
                #pragma unroll
                for (int nt = 0; nt < 4; nt++) sts128(scol + nt * (16 * SPEC_P), o[nt]);
            }
        }
        __syncthreads();
        PROF0(11);
        first_a();
        const uint32_t srow = sm + OFF_SPEC + warp * (SPEC_P * 4);
        uint32_t re[2][3], im[2][3];
        #pragma unroll
        for (int mt = 0; mt < 3; mt++) {
            const uint32_t a = srow + (g + 72 * q + 8 * mt) * 4, a2 = srow + (288 - g - 72 * q - 8 * mt) * 4;
            const uint32_t z0 = lds32(a), z1 = lds32(a + 144), z2 = lds32(a2), z3 = lds32(a2 - 144);
            #pragma unroll
            for (int m2 = 0; m2 < 2; m2++) {
                re[m2][mt] = 0; im[m2][mt] = 0;
                const uint32_t sg = m2 ? 0x3C00BC00u : 0xBC003C00u;
                mma_h(re[m2][mt], im[m2][mt], tc[m2 * 4], tc[m2 * 4 + 1], tc[m2 * 4 + 2], tc[m2 * 4 + 3], hfma2(z2, sg, z0), hfma2(z3, sg, z1));
                cmul_pos(re[m2][mt], im[m2][mt], tc[8 + (m2 * 3 + mt) * 2], tc[9 + (m2 * 3 + mt) * 2]);
            }
        }
        float y[20];
        WG_FENCE();
        #pragma unroll
        for (int mt = 0; mt < 3; mt++)
            wgmma40_rs(y, re[0][mt], re[1][mt], im[0][mt], im[1][mt], desc_lo(sm + OFF_TAB + (QA + QB + 5) * 512 + mt * 1280, 128), mt);
        WG_COMMIT();
        if (!md_early) { mbar_wait(bars + 8 * BAR_NC, 0); load_tab<7>(md, sm + OFF_MODC + lane * 16); }
        WG_WAIT(0);
        #pragma unroll
        for (int i = 0; i < 9; i++) xw[i] = bfma2(md[i], pack_bf(y[4 * (i >> 1) + (i & 1)], y[4 * (i >> 1) + 2 + (i & 1)]), xw[i]);
        float r, mr;
        ln_stats(xw, one, g, q, r, mr);
        uint32_t r2 = pack_bf(r, r), m2 = pack_bf(mr, mr);
        #pragma unroll
        for (int i = 0; i < 9; i++) {
            sts32(sm + OFF_X1 + warp * 1152 + (32 * i + 8 * q + g) * 4, xw[i]);
            xw[i] = bfma2(bfma2(xw[i], r2, m2), md[18 + i], md[9 + i]);
        }
        ln_stats(xw, one, g, q, r, mr);
        r2 = pack_bf(r, r); m2 = pack_bf(mr, mr);
        {
            const int n7 = 2 * q + (g >> 2);
            const uint32_t a = sm + OFF_STAGE + (warp >> 3) * 9216 + n7 * 128 + ((warp & 7) ^ n7) * 16 + (g & 3) * 4;
            #pragma unroll
            for (int i = 0; i < 9; i++) sts32(a + i * 1024, bfma2(xw[i], r2, m2));
        }
        fence_async_s();
        __syncthreads();
        PROF0(12);
        if (tid == 0) {
            asm volatile("cp.async.bulk.tensor.4d.global.shared::cta.bulk_group [%0, {%2, %2, %2, %3}], [%1];" :: "l"(&tm_h3s), "r"(sm + OFF_STAGE), "r"(0), "r"(b) : "memory");
            asm volatile("cp.async.bulk.commit_group;" ::: "memory");
        }
    }
    if (!rowcta) __syncthreads();
    else {
        if (tid == 0) { asm volatile("cp.async.bulk.wait_group 0;" ::: "memory"); fence_async_g(); red_release(g_cnt + CNT_H3 * 32); }
        PROF0(13);
        if (warp == 15) {
            __nanosleep(X1DELAY);
            #pragma unroll 1
            for (int r = 0; r < 16; r++) {
                uint4* dst = (uint4*)(p.out + (size_t)(b + 128 * r) * D_) + lane;
                const uint32_t src = sm + OFF_X1 + r * 1152 + lane * 16;
                dst[0] = lds128(src); dst[32] = lds128(src + 512); if (lane < 8) dst[64] = lds128(src + 1024);
                const uint32_t t1 = clk32(); while ((int)(clk32() - t1) < X1PACE) __nanosleep(50);
            }
            __syncwarp();
            if (lane == 0) { fence_async_g(); red_release(g_cnt + CNT_X1 * 32); }
        }
    }
    role = __shfl_sync(~0u, lds32(sm + OFF_MISC), 0);
    if (role >= 64) { if (warp == 0) PROFDUMP(); return; }

    const int gi = role >> 3, dt = role & 3, c2 = (role >> 2) & 1;
    const int wg = warp >> 2, wi = warp & 3;
    if (wg == 3) {
        uint32_t so = 0, eph = 1;
        #define RING_STEP(BYTES, OFF, ISSUE) do { \
            mbar_wait(bars + 8 * BAR_EMPTY + so, eph); \
            if (elect()) { const uint32_t fb = bars + 8 * BAR_FULL + so, dst = sm + (OFF) + so * ((BYTES) / 8); mbar_expect(fb, BYTES); ISSUE; } \
            so += 8; if (so == 8 * NST) { so = 0; eph ^= 1; } } while (0)
        const uint32_t kbt = g2_kb(lane, rank, gi, c2) | (g2_kb(32 + (lane & 3), rank, gi, c2) << 8);
        #define KB(n_) ((__shfl_sync(~0u, kbt, (n_) & 31) >> (((n_) >> 2) & 8)) & 255)
        if (warp == 12) {
            eph = 0;
            const int fb1 = 9 * gi + 4 * c2 + 2 * rank, sb2 = 4 * gi + 2 * c2;
            int pft = dt, pfj = 4 * (PF0 + PFS * dt);
            #pragma unroll 1
            for (int j = 16; j < 128; j += 4) {
                RING_STEP(A_BYTES, OFF_A, tma4(dst, &tm_w1a, 0, 0, j, fb1, fb));
                if (j < 64) { if (j & 4) RING_STEP(A_BYTES, OFF_A, tma4(dst, &tm_w1b, 0, 0, 64 * rank + j - 4, 9 * gi + 8, fb)); }
                if (j == pfj && pft < PFN) {
                    const int kb = KB(pft); pft += 4; pfj += 16 * PFS;
                    if (elect()) asm volatile("cp.async.bulk.prefetch.tensor.3d.L2.global [%0, {%1, %2, %3}];" :: "l"(&tm_w2), "r"(0), "r"(64 * kb), "r"(sb2) : "memory");
                }
            }
            #pragma unroll 1
            for (int n = 0; n < 36; n++) {
                const int kb = KB(n);
                RING_STEP(A_BYTES, OFF_A, tma3(dst, &tm_w2, 0, 64 * kb, sb2, fb));
            }
        } else if (warp == 13) {
            const uint32_t e1 = __shfl_sync(~0u, epoch + 1, 0);
            fence_async_s();
            wait_count<0>(g_cnt + CNT_H3 * 32, e1 * 128);
            fence_async_g();
            if (lane == 0) PROFT(14);
            #pragma unroll 1
            for (int j = 0; j < 128; j += 4) {
                RING_STEP(B_BYTES, OFF_B, tma3(dst, &tm_h3a, 0, 18 * dt, j, fb));
                if (j < 64 && (j & 4)) RING_STEP(B_BYTES, OFF_B, tma3(dst, &tm_h3b, 0, 18 * dt + 9 * c2, 64 * rank + j - 4, fb));
            }
            int n = 0;
            #pragma unroll 1
            for (int cls = 0; cls < 3; cls++) {
                mbar_wait(bars + 8 * (BAR_UOK + cls), 0);
                fence_async_g();
                if (cls == 1 && lane == 0) PROFT(19);
                if (cls == 0 && lane == 0) PROFT(22);
                static_assert((IT_G2 + 4) % NST != NST - 1, "no wrap at the skipped stage");
                if (cls == 1) { n++; so += 8; }
                #pragma unroll 1
                for (; n < (cls == 0 ? 4 : cls == 1 ? 21 : 36); n++) {
                    const int kb = KB(n);
                    RING_STEP(B_BYTES, OFF_B, bulk_load(dst, g_U + (kb * 4 + dt) * 1152, B_BYTES, fb));
                }
            }
            if (role == 0 && rank == 0 && lane == 0) st_relaxed(g_cnt + CNT_EPOCH * 32, e1);
        } else if (warp == 15) {
            if (elect()) mbar_arrive_remote(mapa(bars + 8 * BAR_HOLD, rank ^ 1));
            __syncwarp();
            bar_sync(6, 160);
            if (elect()) mbar_arrive(bars + 8 * (BAR_FULL + (IT_G2 + 4) % NST));
            __syncwarp();
            mbar_wait(bars + 8 * BAR_W1GO, 0);
            if (elect()) {
                char* dst = (char*)(g_U + ((9 * gi + 4 * c2 + 2 * rank + 1) * 4 + dt) * 1152);
                #pragma unroll 1
                for (int i = 0; i < W1N; i++) {
                    asm volatile("cp.async.bulk.global.shared::cta.bulk_group [%0], [%1], %2;" :: "l"(dst + i * (18432 / W1N)), "r"(sm + OFF_X1 + i * (18432 / W1N)), "n"(18432 / W1N) : "memory");
                    const uint32_t t1 = clk32(); while ((int)(clk32() - t1) < W1P) {}
                }
                asm volatile("cp.async.bulk.commit_group;" ::: "memory");
                asm volatile("cp.async.bulk.wait_group 0;" ::: "memory");
                fence_async_g(); red_release(g_cnt + (CNT_U + 16) * 32);
                #pragma unroll 1
                for (int n = 0; n < 4; n++) { __nanosleep(300); tma2(sm + OFF_X1 + n * 4608, &tm_o, 144 * dt, 256 * gi + 128 * c2 + 64 * (rank ^ 1) + 16 * n, bars + 8 * BAR_XT); }
            }
        } else {
            const uint32_t e1 = epoch + 1;
            if (lane == 0) {
                __nanosleep(4000);
                wait_count<200>(g_cnt + CNT_NC * 32, e1 * 4); wait_count<200>(g_cnt + (CNT_NC + 1) * 32, e1 * 2);
                fence_async_g();
                mbar_expect(bars + 8 * BAR_GB, 1152);
                bulk_load(sm + OFF_GB, p.scr->modc + 896, 1152, bars + 8 * BAR_GB);
                wait_count<200>(g_cnt + CNT_X1 * 32, e1 * 128);
                if (role * 2 + rank < 108) {
                    uint4* z = (uint4*)p.scr->modc + (role * 2 + rank) * 2; z[0] = z[1] = make_uint4(0, 0, 0, 0);
                }
                wait_count<50>(g_cnt + (CNT_U + dt * 2 + rank) * 32, e1 * 16);
                mbar_arrive(bars + 8 * BAR_UOK);
            }
            __syncwarp();
            bar_sync(4, 160);
            if (lane == 0) {
                fence_async_g(); red_release(g_cnt + (CNT_U + 8) * 32);
                PROFT(17);
                wait_count<0>(g_cnt + (CNT_U + 8) * 32, e1 * 128);
                mbar_arrive(bars + 8 * (BAR_UOK + 1));
                __nanosleep(1000);
                wait_count<100>(g_cnt + (CNT_U + 16) * 32, e1 * 128);
                mbar_arrive(bars + 8 * (BAR_UOK + 2));
            }
        }
    } else if (wg == 2) {
        float d0[36];
        const float bias = bf_lo(ldg_nc16(p.b1 + 576 * gi + 512 + 16 * wi + g + 8 * rank));
        for (int it = 0; it < 200 && !__any_sync(~0u, mbar_test(bars + 8 * BAR_FULL, 0)); it++) { hb(); __nanosleep(100); }
        const bool lead = wi == 0 && elect();
        #pragma unroll 1
        for (int i = 0; i < 8; i++) {
            const uint32_t s = P2S + 3 * (i & 1);
            mbar_wait(bars + 8 * BAR_FULL + 8 * s, (i >> 1) & 1);
            const uint32_t da = desc_lo(sm + OFF_A, 8192) + s * (A_BYTES / 16), db = desc_lo(sm + OFF_B, 128) + s * (B_BYTES / 16);
            WG_FENCE();
            wgmma72(d0, da, db, i);
            #pragma unroll
            for (int k = 1; k < 8; k++) wgmma72(d0, da + k * 128, db + k * 144, 1);
            WG_COMMIT();
            WG_WAIT(0);
            if (lead) mbar_arrive_n(bars + 8 * BAR_EMPTY + 8 * s, 2);
        }
        if (lead) PROFT(18);
        const uint32_t slot = sm + OFF_P2R + (tid & 127) * 16, ra = mapa(slot, rank ^ 1), rb = mapa(bars + 8 * BAR_P2R, rank ^ 1);
        float sv[18];
        #pragma unroll
        for (int i = 0; i < 18; i++) { const float lo = d0[4 * (i >> 1) + (i & 1)], hi = d0[4 * (i >> 1) + 2 + (i & 1)];
            sv[i] = rank ? lo : hi; d0[4 * (i >> 1) + (i & 1)] = (rank ? hi : lo) + bias; }
        mbar_wait(bars + 8 * BAR_HOLD, 0);
        #pragma unroll
        for (int i = 0; i < 4; i++)
            asm volatile("st.async.weak.shared::cluster.mbarrier::complete_tx::bytes.v4.f32 [%0], {%1,%2,%3,%4}, [%5];"
                :: "r"(ra + i * 2048), "f"(sv[4 * i]), "f"(sv[4 * i + 1]), "f"(sv[4 * i + 2]), "f"(sv[4 * i + 3]), "r"(rb) : "memory");
        asm volatile("st.async.weak.shared::cluster.mbarrier::complete_tx::bytes.v2.f32 [%0], {%1,%2}, [%3];" :: "r"(ra + 8192), "f"(sv[16]), "f"(sv[17]), "r"(rb) : "memory");
        mbar_wait(bars + 8 * BAR_P2R, 0);
        #pragma unroll
        for (int i = 0; i < 5; i++) {
            const uint4 v = lds128(slot + i * 2048);
            d0[8 * i] += __uint_as_float(v.x); d0[8 * i + 1] += __uint_as_float(v.y);
            if (i < 4) { d0[8 * i + 4] += __uint_as_float(v.z); d0[8 * i + 5] += __uint_as_float(v.w); }
        }
        asm volatile("bar.arrive 5, 256;" ::: "memory");
        gelu_store<0>(d0, (char*)(g_U + ((9 * gi + 8) * 4 + dt) * 1152) + wi * 4608 + rank * 2304 + c2 * 1152 + g * 16, q);
        bar_sync(8, 128);
        if (lead) { fence_async_g(); red_release(g_cnt + (CNT_U + dt * 2 + (gi >> 2)) * 32); PROFT(26); }
    } else {
        float d[72];
        const bool lead = wi == 0 && elect();
        const uint32_t da0 = desc_lo(sm + OFF_A + wg * 8192, 8192);
        const bool owner = (uint32_t)wg == rank;
        const int srow = 256 * gi + 128 * c2 + 64 * wg + 16 * wi;
        const uint32_t b2w0 = ldg_nc16(p.b2 + srow + g), b2w1 = ldg_nc16(p.b2 + srow + g + 8);
        {
            const int fr = 576 * gi + 256 * c2 + 128 * rank + 64 * wg + 16 * wi + g;
            const float bias0 = bf_lo(ldg_nc16(p.b1 + fr)), bias1 = bf_lo(ldg_nc16(p.b1 + fr + 8));
            #pragma unroll
            for (int i = 0; i < 72; i++) d[i] = (i & 2) ? bias1 : bias0;
            const uint32_t db1 = desc_lo(sm + OFF_B, 128);
            mainloop<DHI_H3, 0, IT_P1, true>(d, bars, da0, db1, lead, [&](int) {});
            mainloop<DHI_H3, IT_P1, IT_G2 - LEAD1, false>(d, bars, da0, db1, lead, [&](int) {});
            constexpr uint32_t EB = 8 * (BAR_EMPTY + (IT_G2 - LEAD1 - 1) % NST);
            if (wg == 1) { WG_WAIT(0); if (lead) mbar_arrive(bars + EB); bar_sync(9, 256); }
            #pragma unroll
            for (int i = IT_G2 - LEAD1; i < IT_G2; i++) {
                mbar_wait(bars + 8 * (BAR_FULL + i % NST), (i / NST) & 1);
                WG_FENCE();
                #pragma unroll
                for (int k = 0; k < 4; k++) {
                    if (i == IT_G2 - 1 && k == HOK1) WG_COMMIT();
                    wgmma144<DHI_H3>(d, da0 + (i % NST) * (A_BYTES / 16) + k * 128, db1 + (i % NST) * (B_BYTES / 16) + k * 288, 1);
                }
                WG_COMMIT();
                if (i == IT_G2 - 1 && HOK1 < 4) WG_WAIT(2); else WG_WAIT(1);
                if (lead && (i > IT_G2 - LEAD1 || wg == 0)) mbar_arrive(bars + 8 * (BAR_EMPTY + (i - 1) % NST));
            }
            if (wg == 0) { WG_WAIT(1); asm volatile("bar.arrive 9, 256;" ::: "memory"); }
            WG_WAIT(0);
            if (lead) mbar_arrive(bars + 8 * (BAR_EMPTY + (IT_G2 - 1) % NST));
            PROF0(16);
            if (wg == 1) bar_sync(5, 256);
            char* const ub = (wg == 0 ? (char*)(g_U + ((9 * gi + 4 * c2 + 2 * rank) * 4 + dt) * 1152) : (char*)__cvta_shared_to_generic(sm + OFF_X1)) + wi * 4608 + g * 16;
            gelu_store<0>(d, ub, q); gelu_store<2>(d, ub + 2304, q); gelu_store<36>(d, ub + 1152, q); gelu_store<38>(d, ub + 3456, q);
            PROF0(27);
            if (wg == 0) asm volatile("bar.arrive 4, 160;" ::: "memory");
            else { fence_async_s(); asm volatile("bar.arrive 6, 160;" ::: "memory"); }
        }
        const uint32_t db0 = desc_lo(sm + OFF_B, 2304);
        const bool keep = role > 64;
        constexpr int IT_L = IT_END - NST, IT_X = IT_L - 4;
        #pragma unroll
        for (int i = IT_G2; i <= IT_G2 + W1S; i++) {
            const uint32_t db = db0 + (i == IT_G2 + 4 ? OFF_X1 - OFF_B : (i % NST) * B_BYTES) / 16;
            mbar_wait(bars + 8 * (BAR_FULL + i % NST), (i / NST) & 1);
            WG_FENCE();
            #pragma unroll
            for (int k = 0; k < 4; k++) wgmma144<DHI_U>(d, da0 + (i % NST) * (A_BYTES / 16) + k * 128, db + k * 288, i > IT_G2 || k > 0 || keep);
            WG_COMMIT();
            if (i > IT_G2) { WG_WAIT(1); if (lead) mbar_arrive(bars + 8 * (BAR_EMPTY + (i - 1) % NST)); }
        }
        if (lead) mbar_arrive(bars + 8 * BAR_W1GO);
        mainloop<DHI_U, IT_G2 + W1S + 1, IT_X, false>(d, bars, da0, db0, lead, [&](int) {});
        const uint32_t ga0 = sm + OFF_GB + (144 * dt + 8 * q) * 2, tile = sm + OFF_X1 + wi * 4608, to = g * 288 + q * 16;
        #define QOFF(i_) (((i_) >> 2) * 2304 + 144 * (((i_) >> 1) & 1) + 64 * ((i_) & 1))
        #define SOFF(k_) (((k_) >> 1) * 2304 + 144 * ((k_) & 1) + 128 - 12 * q)
        #define DIDX(i_, k_) ((i_) < 8 ? 36 * (((i_) >> 1) & 1) + 16 * ((i_) & 1) + 4 * (k_) + 2 * ((i_) >> 2) : 36 * ((k_) & 1) + 32 + 2 * ((k_) >> 1))
        #define FIN(k_, f_) bfma2(g4.f_, pack_bf(d[DIDX(i, k_)], d[DIDX(i, k_) + 1]), xq[i].f_)
        uint4 xq[9];
        auto load_g = [&](int i) { uint4 r; if (i < 4) r = lds128(ga0 + QOFF(i)); else { r.x = r.z = lds32(ga0 + SOFF(0)); r.y = r.w = lds32(ga0 + SOFF(1)); } return r; };
        mainloop<DHI_U, IT_X, IT_L, false>(d, bars, da0, db0, lead, [&](int i) {
            if (!owner) {
                const uint32_t xa = tile + to;
                if (i == IT_X) { mbar_wait(bars + 8 * BAR_XT, 0); xq[0] = lds128(xa + QOFF(0)); xq[4] = lds128(xa + QOFF(4)); xq[1] = lds128(xa + QOFF(1)); }
                else if (i == IT_X + 1) { xq[5] = lds128(xa + QOFF(5)); xq[2] = lds128(xa + QOFF(2)); xq[6] = lds128(xa + QOFF(6)); }
                else if (i == IT_X + 2) { xq[3] = lds128(xa + QOFF(3)); xq[7] = lds128(xa + QOFF(7));
                    xq[8] = make_uint4(lds32(xa + SOFF(0)), lds32(xa + SOFF(1)), lds32(xa + SOFF(2)), lds32(xa + SOFF(3))); }
                else if (i == IT_X + 3) { if (elect()) mbar_arrive_remote(mapa(bars + 8 * BAR_DONE, rank ^ 1)); }
            } });
        if (owner) { WG_WAIT(0); if (lead) mbar_arrive(bars + 8 * (BAR_EMPTY + (IT_L - 1) % NST)); bar_sync(7, 256); }
        #pragma unroll
        for (int i = IT_L; i < IT_END; i++) {
            mbar_wait(bars + 8 * (BAR_FULL + i % NST), (i / NST) & 1);
            WG_FENCE();
            #pragma unroll
            for (int k = 0; k < 4; k++) {
                if (i == IT_END - 1 && k == HOK) WG_COMMIT();
                wgmma144<DHI_U>(d, da0 + (i % NST) * (A_BYTES / 16) + k * 128, db0 + (i % NST) * (B_BYTES / 16) + k * 288, 1);
            }
            WG_COMMIT();
            if (i == IT_L) { WG_WAIT(1); if (lead && !owner) mbar_arrive(bars + 8 * (BAR_EMPTY + (IT_L - 1) % NST)); }
        }
        PROF0(9);
        mbar_wait(bars + 8 * BAR_GB, 0);
        if (!owner) {
            const uint32_t ra = mapa(tile + lane * 16, rank ^ 1), rb = mapa(bars + 8 * BAR_RECV, rank ^ 1);
            mbar_wait(bars + 8 * BAR_DONE, 0);
            uint4 gn = load_g(0);
            WG_WAIT(1);
            asm volatile("bar.arrive 7, 256;" ::: "memory");
            WG_WAIT(0);
            #pragma unroll
            for (int i = 0; i < 72; i++) d[i] = fmaf(bf_lo((i & 2) ? b2w1 : b2w0), 2.f, d[i]);
            #pragma unroll
            for (int j = 0; j < 5; j++) {
                const uint4 g4 = gn;
                if (j < 4) gn = load_g(j + 1);
                #pragma unroll
                for (int i = j < 4 ? j : 8; i < 9; i += 4) if (i < 8 || j == 4)
                    asm volatile("st.async.weak.shared::cluster.mbarrier::complete_tx::bytes.v4.b32 [%0], {%1,%2,%3,%4}, [%5];"
                        :: "r"(ra + i * 512), "r"(FIN(0, x)), "r"(FIN(1, y)), "r"(FIN(2, z)), "r"(FIN(3, w)), "r"(rb) : "memory");
            }
            PROF0(6);
            if (warp == 0) PROFDUMP();
            return;
        }
        PROF0(24);
        mbar_wait(bars + 8 * BAR_RECV, 0);
        #pragma unroll
        for (int i = 0; i < 9; i++) xq[i] = lds128(tile + lane * 16 + i * 512);
        uint4 gn = load_g(0);
        WG_WAIT(0);
        __syncwarp();
        PROF0(21);
        #pragma unroll
        for (int j = 0; j < 5; j++) {
            const uint4 g4 = gn;
            if (j < 4) gn = load_g(j + 1);
            #pragma unroll
            for (int i = j < 4 ? j : 8; i < 9; i += 4) if (i < 8 || j == 4) {
                const uint4 o = make_uint4(FIN(0, x), FIN(1, y), FIN(2, z), FIN(3, w));
                if (i < 8) sts128(tile + to + QOFF(i), o);
                else { sts32(tile + to + SOFF(0), o.x); sts32(tile + to + SOFF(1), o.y); sts32(tile + to + SOFF(2), o.z); sts32(tile + to + SOFF(3), o.w); }
            }
        }
        fence_async_s();
        __syncwarp();
        if (elect()) {
            asm volatile("cp.async.bulk.tensor.2d.global.shared::cta.bulk_group [%0, {%2, %3}], [%1];" :: "l"(&tm_o), "r"(tile), "r"(144 * dt), "r"(srow) : "memory");
            asm volatile("cp.async.bulk.commit_group;" ::: "memory");
            asm volatile("cp.async.bulk.wait_group.read 0;" ::: "memory");
        }
        PROF0(23);
        if (warp == 0) { __syncwarp(); PROFDUMP(); }
    }
}

typedef CUresult (*EncodeFn)(CUtensorMap*, CUtensorMapDataType, cuuint32_t, void*, const cuuint64_t*, const cuuint64_t*, const cuuint32_t*,
                             const cuuint32_t*, CUtensorMapInterleave, CUtensorMapSwizzle, CUtensorMapL2promotion, CUtensorMapFloatOOBfill);

void encode(EncodeFn fn, CUtensorMap* m, CUtensorMapDataType dt, int rank, const void* ptr, const cuuint64_t* dims, const cuuint64_t* strides,
            const cuuint32_t* box, CUtensorMapSwizzle sw, CUtensorMapL2promotion promo = CU_TENSOR_MAP_L2_PROMOTION_L2_128B) {
    const cuuint32_t es[5] = {1, 1, 1, 1, 1};
    fn(m, dt, rank, (void*)ptr, dims, strides, box, es, CU_TENSOR_MAP_INTERLEAVE_NONE, sw, promo, CU_TENSOR_MAP_FLOAT_OOB_FILL_NONE);
}

}

extern "C" void kernel_launch(void* const* d_in, const int* in_sizes, int n_in, void* d_out, int out_size) {
    (void)in_sizes; (void)n_in; (void)out_size;
    Params p;
    p.x = (const uint16_t*)d_in[0]; p.wr = (const uint16_t*)d_in[1]; p.wi = (const uint16_t*)d_in[2];
    p.w1 = (const uint16_t*)d_in[4]; p.b1 = (const uint16_t*)d_in[5]; p.w2 = (const uint16_t*)d_in[6]; p.b2 = (const uint16_t*)d_in[7];
    p.c = (const uint16_t*)d_in[8]; p.wmod = (const uint16_t*)d_in[9]; p.out = (uint16_t*)d_out;

    void* fnp = nullptr; cudaDriverEntryPointQueryResult qr;
    cudaGetDriverEntryPoint("cuTensorMapEncodeTiled", &fnp, cudaEnableDefault, &qr);
    EncodeFn fn = (EncodeFn)fnp;
    cudaGetSymbolAddress((void**)&p.scr, g_scr); cudaGetSymbolAddress((void**)&p.tab, g_tab);
    void* h3p = p.scr->h3;
    CUtensorMap tw1a, tw1b, tw2, th3a, th3b, twr, twi, twm, tt, ttx, to, th3s, tws;
    {
        const cuuint64_t dims[4] = {64, 16, 128, 72}, st[3] = {128ull * F_ * 2, (cuuint64_t)F_ * 2, 128};
        const cuuint32_t ba[4] = {64, 16, 4, 2}, bb[4] = {64, 16, 8, 1};
        encode(fn, &tw1a, CU_TENSOR_MAP_DATA_TYPE_BFLOAT16, 4, p.w1, dims, st, ba, CU_TENSOR_MAP_SWIZZLE_128B);
        encode(fn, &tw1b, CU_TENSOR_MAP_DATA_TYPE_BFLOAT16, 4, p.w1, dims, st, bb, CU_TENSOR_MAP_SWIZZLE_128B);
    }
    {
        const cuuint64_t dims[3] = {64, F_, 32}, st[2] = {(cuuint64_t)S_ * 2, 128};
        const cuuint32_t bx[3] = {64, 64, 2};
        encode(fn, &tw2, CU_TENSOR_MAP_DATA_TYPE_BFLOAT16, 3, p.w2, dims, st, bx, CU_TENSOR_MAP_SWIZZLE_128B);
    }
    {
        const cuuint64_t dims[3] = {64, 72, 128}, st[2] = {256, 18432};
        const cuuint32_t ba[3] = {64, 18, 4}, bb[3] = {64, 9, 8};
        encode(fn, &th3a, CU_TENSOR_MAP_DATA_TYPE_UINT32, 3, h3p, dims, st, ba, CU_TENSOR_MAP_SWIZZLE_NONE);
        encode(fn, &th3b, CU_TENSOR_MAP_DATA_TYPE_UINT32, 3, h3p, dims, st, bb, CU_TENSOR_MAP_SWIZZLE_NONE);
    }
    {
        const cuuint64_t dims[4] = {32, 72, 2, 128}, st[3] = {256, 128, 18432};
        const cuuint32_t bx[4] = {32, 72, 2, 1};
        encode(fn, &th3s, CU_TENSOR_MAP_DATA_TYPE_UINT32, 4, h3p, dims, st, bx, CU_TENSOR_MAP_SWIZZLE_128B, CU_TENSOR_MAP_L2_PROMOTION_NONE);
    }
    {
        const cuuint64_t dims[3] = {4624, 4, 32}, st[2] = {9248 * 32, 9248};
        const cuuint32_t bx[3] = {56, 4, 32};
        encode(fn, &twr, CU_TENSOR_MAP_DATA_TYPE_BFLOAT16, 3, p.wr, dims, st, bx, CU_TENSOR_MAP_SWIZZLE_NONE);
        encode(fn, &twi, CU_TENSOR_MAP_DATA_TYPE_BFLOAT16, 3, p.wi, dims, st, bx, CU_TENSOR_MAP_SWIZZLE_NONE);
    }
    {
        const cuuint64_t dims[2] = {3456, 576}, st[1] = {6912};
        const cuuint32_t bx[2] = {32, 144};
        encode(fn, &tws, CU_TENSOR_MAP_DATA_TYPE_BFLOAT16, 2, p.wmod, dims, st, bx, CU_TENSOR_MAP_SWIZZLE_64B);
    }
    {
        const cuuint64_t dims[3] = {64, 576, 54}, st[2] = {6912, 128};
        const cuuint32_t bx[3] = {64, 32, 7};
        encode(fn, &twm, CU_TENSOR_MAP_DATA_TYPE_BFLOAT16, 3, p.wmod, dims, st, bx, CU_TENSOR_MAP_SWIZZLE_128B);
    }
    {
        const cuuint64_t dims[2] = {TP, 128}, st[1] = {TP * 4};
        const cuuint32_t ba[2] = {32, 128}, bb[2] = {8, 128};
        encode(fn, &tt, CU_TENSOR_MAP_DATA_TYPE_UINT32, 2, p.scr->T, dims, st, ba, CU_TENSOR_MAP_SWIZZLE_128B, CU_TENSOR_MAP_L2_PROMOTION_NONE);
        encode(fn, &ttx, CU_TENSOR_MAP_DATA_TYPE_UINT32, 2, p.scr->T, dims, st, bb, CU_TENSOR_MAP_SWIZZLE_32B, CU_TENSOR_MAP_L2_PROMOTION_NONE);
    }
    {
        const cuuint64_t dims[2] = {D_, S_}, st[1] = {D_ * 2};
        const cuuint32_t bx[2] = {144, 16};
        encode(fn, &to, CU_TENSOR_MAP_DATA_TYPE_BFLOAT16, 2, p.out, dims, st, bx, CU_TENSOR_MAP_SWIZZLE_NONE, CU_TENSOR_MAP_L2_PROMOTION_NONE);
    }
    cudaFuncSetAttribute(fused_kernel, cudaFuncAttributeMaxDynamicSharedMemorySize, SMEM_BYTES);
    cudaLaunchConfig_t cfg = {};
    cfg.gridDim = dim3(NCTA); cfg.blockDim = dim3(NTHR); cfg.dynamicSmemBytes = SMEM_BYTES; cfg.stream = cudaStreamPerThread;
    cudaLaunchAttribute at[1];
    at[0].id = cudaLaunchAttributeCooperative; at[0].val.cooperative = 1;
    cfg.attrs = at; cfg.numAttrs = 1;
    cudaLaunchKernelEx(&cfg, fused_kernel, p, tw1a, tw1b, tw2, th3a, th3b, twr, twi, twm, tt, ttx, to, th3s, tws);
}
```

```cpp
#include <cuda_runtime.h>
#include <cuda_bf16.h>
#include <cuda_fp16.h>
#include <cuda.h>
#include <stdint.h>

namespace {

constexpr int S_ = 2048, D_ = 576, F_ = 4608;
constexpr int NCTA = 132, NTHR = 512;
constexpr int TP = 4736;
constexpr int SPEC_P = 296;
constexpr int NST = 6;
constexpr int A_BYTES = 16384, B_BYTES = 18432;
constexpr int IT_P1 = 24, IT_G2 = 40, IT_END = 76;
constexpr int SPIN_LIMIT = 1 << 22;
#define X2D 1350
constexpr int P2S = 2;
#define LEAD1 4
#define W1N 8
#define W1P 100
#define W1S 5
#define XDELAY 1100
#define HOK 2
#define HOK1 2
#define NCP 10800
#define PEEK 0
#define SLP 64
#define X1D 2100
#define PF0 4
#define PFS 3
#define PFN 9
#define X1DELAY 2000
#define X1PACE 400

constexpr int OFF_A = 0;
constexpr int OFF_B = NST * A_BYTES;
constexpr int OFF_P = OFF_B + NST * B_BYTES;
constexpr int OFF_BAR = OFF_P;
constexpr int OFF_EPOCH = OFF_P + 480;
constexpr int OFF_MISC = OFF_P + 496;
constexpr int OFF_GB = OFF_P + 512;
constexpr int OFF_P2R = OFF_P + 1664;
constexpr int OFF_X1 = OFF_P2R;
constexpr int OFF_PROF = OFF_X1 + 18432;
constexpr int SMEM_BYTES = OFF_PROF + 512;
constexpr int QA = 13, QB = 7, QC = 13;
constexpr int TAB_BYTES = (QA + QB + QC) * 512;
constexpr int OFF_STAGE = OFF_B;
constexpr int OFF_STX = OFF_STAGE + 16384;
constexpr int OFF_TAB = OFF_STAGE + 20480;
constexpr int OFF_SPEC = OFF_TAB + TAB_BYTES;
constexpr int OFF_WRAW = OFF_SPEC + 19072;
constexpr int OFF_B3 = OFF_WRAW + 28672;
constexpr int OFF_MODA = OFF_B3 + 4096;
constexpr int OFF_MODC = OFF_MODA + 2560;
constexpr int OFF_RED = OFF_MODC + 3584;
constexpr int OFF_HEXP = OFF_RED + 512;
constexpr int OFF_SILU = OFF_RED + 1536;
static_assert(OFF_SILU + 1152 <= OFF_P && 6 * 28672 <= OFF_B3, "scratch overflow");
constexpr int OFF_STRIP = OFF_A;
static_assert(OFF_WRAW % 128 == 0 && OFF_STAGE % 128 == 0 && OFF_STX % 128 == 0, "align");
constexpr int BAR_FULL = 0, BAR_EMPTY = 6, BAR_TAB = 12, BAR_W = 13, BAR_P2R = 16,
              BAR_XT = 17, BAR_RECV = 18, BAR_ROLE = 19, BAR_NC = 20, BAR_TAB2 = 21, BAR_XB = 22, BAR_GB = 23, BAR_HOLD = 24, BAR_W1GO = 25, BAR_UOK = 26, BAR_DONE = 30, BAR_X = 31, BAR_ST = 47;

struct Cos1152 { double c[1152]; };
constexpr double cx_cos(double x) { double t = 1, s = 1; for (int i = 1; i < 14; i++) { t *= -x * x / ((2 * i - 1) * (2 * i)); s += t; } return s; }
constexpr Cos1152 make_cos() {
    Cos1152 r{};
    for (int i = 0; i <= 288; i++) {
        double v = (i == 288) ? 0.0 : cx_cos(3.14159265358979323846 * 2.0 * i / 1152.0);
        r.c[i] = v; r.c[576 - i] = -v; r.c[576 + i] = -v; r.c[(1152 - i) % 1152] = v;
    }
    return r;
}
constexpr uint32_t cx_f2h(double v) {
    uint32_t s = v < 0 ? 0x8000u : 0u; double a = v < 0 ? -v : v;
    if (a < 1e-9) return 0;
    int e = 0;
    while (a >= 2.0) { a *= 0.5; e++; }
    while (a < 1.0 && e > -14) { a *= 2.0; e--; }
    double m = a * 1024.0; uint32_t mi = (uint32_t)m; double fr = m - mi;
    if (fr > 0.5 || (fr == 0.5 && (mi & 1))) mi++;
    return s | (uint32_t)(((e + 14) << 10) + mi);
}
struct Tab { uint32_t w[(QA + QB + QC) * 128]; };
constexpr Tab make_tab() {
    Tab t{};
    Cos1152 ct = make_cos();
    auto C = [&](int num, int den) { return ct.c[(num % den) * (1152 / den)]; };
    auto Sn = [&](int num, int den) { return ct.c[((num % den) * (1152 / den) + 864) % 1152]; };
    auto put = [&](int q0, int idx, int lane, double lo, double hi) { t.w[((q0 + idx / 4) * 32 + lane) * 4 + idx % 4] = cx_f2h(lo) | (cx_f2h(hi) << 16); };
    for (int lane = 0; lane < 32; lane++) {
        const int g = lane >> 2, q = lane & 3;
        for (int mt = 0; mt < 3; mt++) {
            const int ka = 8 * mt + g;
            for (int r = 0; r < 10; r++) {
                const int im = r & 1, i0 = (r >> 1) * 2;
                double v[2] = {0, 0};
                for (int e = 0; e < 2; e++) { int i = i0 + e, d1 = 4 * i + q; if (i < 9 && ka <= 18) v[e] = (im ? -Sn(ka * d1, 36) : C(ka * d1, 36)) / 8; }
                put(0, r < 8 ? mt * 8 + r : 16 + 2 * mt + r, lane, v[0], v[1]);
            }
            for (int v = 0; v < 2; v++) {
                const int d2 = 4 * q + v;
                put(0, 30 + (mt * 2 + v) * 2, lane, C(ka * d2, 576) * 4 / 3, C(ka * (d2 + 2), 576) * 4 / 3);
                put(0, 31 + (mt * 2 + v) * 2, lane, Sn(ka * d2, 576) * 4 / 3, Sn(ka * (d2 + 2), 576) * 4 / 3);
            }
        }
        for (int v = 0; v < 2; v++) for (int nt = 0; nt < 2; nt++) {
            const int kb = 2 * (g >> 1) + nt, part = g & 1;
            double b0[2] = {0, 0}, b1[2] = {0, 0};
            for (int e = 0; e < 2; e++) { int d2 = 4 * q + 2 * e + v; double c = C(kb * d2, 16) / 4, s = Sn(kb * d2, 16) / 4;
                b0[e] = part ? -s : c; b1[e] = part ? c : s; }
            put(0, 42 + (v * 2 + nt) * 2, lane, b0[0], b0[1]); put(0, 43 + (v * 2 + nt) * 2, lane, b1[0], b1[1]);
        }
        t.w[((QA - 1) * 32 + lane) * 4 + 2] = 0x3F803F80u;
        for (int par = 0; par < 2; par++) for (int a = 0; a < 4; a++) {
            const int ja = 2 * (q + 4 * (a >> 1)) + par; const double c = C(g * ja, 16) / 4, s = Sn(g * ja, 16) / 4;
            put(QA, par * 4 + a, lane, (a & 1) ? -s : c, (a & 1) ? c : s);
        }
        for (int h = 0; h < 2; h++) {
            put(QA, 8 + 2 * h, lane, C((g + 8 * h) * (2 * q), 128) / 2, C((g + 8 * h) * (2 * q + 1), 128) / 2);
            put(QA, 9 + 2 * h, lane, Sn((g + 8 * h) * (2 * q), 128) / 2, Sn((g + 8 * h) * (2 * q + 1), 128) / 2);
            put(QA, 16 + 2 * h, lane, C(g * (8 * h + 2 * q), 128), C(g * (8 * h + 2 * q + 1), 128));
            put(QA, 17 + 2 * h, lane, Sn(g * (8 * h + 2 * q), 128), Sn(g * (8 * h + 2 * q + 1), 128));
        }
        put(QA, 12, lane, C(g * 2 * q, 8) / 2, C(g * (2 * q + 1), 8) / 2);
        put(QA, 15, lane, C(g * 2 * q, 8) / 2, C(g * (2 * q + 1), 8) / 2);
        put(QA, 13, lane, Sn(g * 2 * q, 8) / 2, Sn(g * (2 * q + 1), 8) / 2);
        put(QA, 14, lane, -Sn(g * 2 * q, 8) / 2, -Sn(g * (2 * q + 1), 8) / 2);
        for (int u = 0; u < 4; u++) {
            const int ja = 2 * ((g >> 1) + 4 * (u & 1)) + (u >> 1), part = g & 1; double b0[2] = {0, 0}, b1[2] = {0, 0};
            for (int e = 0; e < 2; e++) { int ka = 2 * q + e; double c = C(ja * ka, 16) / 4, s = Sn(ja * ka, 16) / 4;
                b0[e] = part ? s : c; b1[e] = part ? c : -s; }
            put(QA, 20 + u * 2, lane, b0[0], b0[1]); put(QA, 21 + u * 2, lane, b1[0], b1[1]);
        }
        for (int m2 = 0; m2 < 2; m2++) {
            const int d2 = 2 * g + m2;
            for (int a = 0; a < 4; a++) {
                const int kb = 2 * q + (a >> 1); const double c = C(d2 * kb, 16) / 4, s = Sn(d2 * kb, 16) / 4;
                put(QA + QB, m2 * 4 + a, lane, (a & 1) ? s : c, (a & 1) ? c : -s);
            }
            for (int mt = 0; mt < 3; mt++) {
                const int ka = 8 * mt + 2 * q;
                put(QA + QB, 8 + (m2 * 3 + mt) * 2, lane, C(ka * d2, 576) * 4 / 3, C((ka + 1) * d2, 576) * 4 / 3);
                put(QA + QB, 9 + (m2 * 3 + mt) * 2, lane, Sn(ka * d2, 576) * 4 / 3, Sn((ka + 1) * d2, 576) * 4 / 3);
            }
        }
        for (int mt = 0; mt < 3; mt++) for (int nt = 0; nt < 5; nt++) {
            const int i = 2 * nt + (g & 1), d1 = 4 * i + (g >> 1); double b0[2] = {0, 0}, b1[2] = {0, 0};
            for (int e = 0; e < 2; e++) { int ka = 8 * mt + 2 * q + e;
                if (ka <= 18 && i < 9) { double wt = (ka == 0 || ka == 18) ? 0.125 : 0.25; b0[e] = wt * C(ka * d1, 36); b1[e] = -wt * Sn(ka * d1, 36); } }
            const int o = (QA + QB + 5) * 128 + (mt * 5 + nt) * 64 + lane;
            t.w[o] = cx_f2h(b0[0]) | (cx_f2h(b0[1]) << 16); t.w[o + 32] = cx_f2h(b1[0]) | (cx_f2h(b1[1]) << 16);
        }
    }
    return t;
}
__device__ __align__(128) const Tab g_tab = make_tab();

struct Scratch {
    uint32_t cnt[30 * 32];
    uint32_t slot[96];
    uint32_t mod[2304];
    uint32_t modc[896 + 288];
    uint32_t T[128 * TP];
    uint4 h3[128 * 1152];
    uint4 U[72 * 4 * 1152];
};
__device__ __align__(1024) Scratch g_scr;
#define g_cnt (p.scr->cnt)
#define g_slot (p.scr->slot)
#define g_mod (p.scr->mod)
#define g_T (p.scr->T)
#define g_h3 (p.scr->h3)
#define g_U (p.scr->U)
constexpr int CNT_EPOCH = 0, CNT_H3 = 1, CNT_X1 = 26, CNT_NC = 27, CNT_U = 2;
#define PROFT(i) do {} while (0)
#define PROFDUMP() do {} while (0)
#define PROF0(i) do {} while (0)

__device__ __forceinline__ void mbar_init(uint32_t bar, uint32_t cnt) { asm volatile("mbarrier.init.shared::cta.b64 [%0], %1;" :: "r"(bar), "r"(cnt) : "memory"); }
__device__ __forceinline__ void mbar_expect(uint32_t bar, uint32_t bytes) { asm volatile("mbarrier.arrive.expect_tx.shared::cta.b64 _, [%0], %1;" :: "r"(bar), "r"(bytes) : "memory"); }
__device__ __forceinline__ void mbar_arrive(uint32_t bar) { asm volatile("mbarrier.arrive.shared::cta.b64 _, [%0];" :: "r"(bar) : "memory"); }
__device__ __forceinline__ void mbar_arrive_n(uint32_t bar, uint32_t n) { asm volatile("mbarrier.arrive.shared::cta.b64 _, [%0], %1;" :: "r"(bar), "r"(n) : "memory"); }
__device__ __forceinline__ void mbar_arrive_remote(uint32_t rbar) { asm volatile("mbarrier.arrive.relaxed.cluster.shared::cluster.b64 _, [%0];" :: "r"(rbar) : "memory"); }
template <bool FAST = true> __device__ __forceinline__ void mbar_wait(uint32_t bar, uint32_t parity) {
    if (FAST || !PEEK) asm volatile("{.reg .pred p; .reg .u32 c;\n"
        "mbarrier.try_wait.parity.shared::cta.b64 p, [%0], %1;\n@p bra.uni DONE;\nmov.u32 c, 0;\n"
        "LOOP: mbarrier.try_wait.parity.shared::cta.b64 p, [%0], %1;\n@p bra.uni DONE;\n"
        "add.u32 c, c, 1;\nsetp.lt.u32 p, c, %2;\n@p bra.uni LOOP;\ntrap;\nDONE:}" :: "r"(bar), "r"(parity), "n"(SPIN_LIMIT) : "memory");
    else asm volatile("{.reg .pred p; .reg .u32 c;\nmov.u32 c, 0;\n"
        "LOOP: mbarrier.try_wait.parity.shared::cta.b64 p, [%0], %1;\n@p bra.uni DONE;\n"
        "add.u32 c, c, 1;\nsetp.lt.u32 p, c, %2;\n@p bra.uni LOOP;\ntrap;\nDONE:}" :: "r"(bar), "r"(parity), "n"(SPIN_LIMIT) : "memory");
}
__device__ __forceinline__ bool mbar_test(uint32_t bar, uint32_t parity) {
    uint32_t ok; asm volatile("{.reg .pred p; mbarrier.test_wait.parity.shared::cta.b64 p, [%1], %2; selp.u32 %0, 1, 0, p;}" : "=r"(ok) : "r"(bar), "r"(parity) : "memory"); return ok; }
__device__ __forceinline__ uint32_t mapa(uint32_t a, uint32_t rank) { uint32_t r; asm("mapa.shared::cluster.u32 %0, %1, %2;" : "=r"(r) : "r"(a), "r"(rank)); return r; }
__device__ __forceinline__ uint32_t clk32() { uint32_t r; asm volatile("mov.u32 %0, %%clock;" : "=r"(r)); return r; }
__device__ __forceinline__ void hb() {
    asm volatile("{.reg .b32 a, b; .reg .pred p; mma.sync.aligned.m16n8k8.row.col.f16.f16.f16.f16 {a, b}, {%0,%0}, {%0}, {%0,%0};\n"
                 "setp.ne.u32 p, a, 0; @p trap;}" :: "r"(0));
}
__device__ __forceinline__ void spin_until(uint32_t t) {
    while (__any_sync(~0u, (int)(clk32() - t) < -SLP * 4)) { __nanosleep(SLP); hb(); }
    while (__any_sync(~0u, (int)(clk32() - t) < 0)) {}
}
__device__ __forceinline__ bool elect() { uint32_t r; asm volatile("{.reg .pred p; elect.sync _|p, 0xffffffff; selp.u32 %0, 1, 0, p;}" : "=r"(r)); return r; }
__device__ __forceinline__ void bar_sync(int id, int n) { asm volatile("bar.sync %0, %1;" :: "r"(id), "r"(n) : "memory"); }
__device__ __forceinline__ void bulk_load(uint32_t dst, const void* src, uint32_t bytes, uint32_t bar) {
    asm volatile("cp.async.bulk.shared::cluster.global.mbarrier::complete_tx::bytes [%0], [%1], %2, [%3];" :: "r"(dst), "l"(src), "r"(bytes), "r"(bar) : "memory"); }
__device__ __forceinline__ void tma2(uint32_t dst, const CUtensorMap* m, int c0, int c1, uint32_t bar) {
    asm volatile("cp.async.bulk.tensor.2d.shared::cluster.global.mbarrier::complete_tx::bytes [%0], [%1, {%3, %4}], [%2];" :: "r"(dst), "l"(m), "r"(bar), "r"(c0), "r"(c1) : "memory"); }
__device__ __forceinline__ void tma3(uint32_t dst, const CUtensorMap* m, int c0, int c1, int c2, uint32_t bar) {
    asm volatile("cp.async.bulk.tensor.3d.shared::cluster.global.mbarrier::complete_tx::bytes [%0], [%1, {%3, %4, %5}], [%2];" :: "r"(dst), "l"(m), "r"(bar), "r"(c0), "r"(c1), "r"(c2) : "memory"); }
__device__ __forceinline__ void tma4(uint32_t dst, const CUtensorMap* m, int c0, int c1, int c2, int c3, uint32_t bar) {
    asm volatile("cp.async.bulk.tensor.4d.shared::cluster.global.mbarrier::complete_tx::bytes [%0], [%1, {%3, %4, %5, %6}], [%2];" :: "r"(dst), "l"(m), "r"(bar), "r"(c0), "r"(c1), "r"(c2), "r"(c3) : "memory"); }
__device__ __forceinline__ void fence_async_g() { asm volatile("fence.proxy.async.global;" ::: "memory"); }
__device__ __forceinline__ void fence_async_s() { asm volatile("fence.proxy.async.shared::cta;" ::: "memory"); }
__device__ __forceinline__ uint4 lds128(uint32_t a) { uint4 v; asm volatile("ld.shared.v4.u32 {%0,%1,%2,%3}, [%4];" : "=r"(v.x), "=r"(v.y), "=r"(v.z), "=r"(v.w) : "r"(a) : "memory"); return v; }
__device__ __forceinline__ uint32_t lds32(uint32_t a) { uint32_t v; asm volatile("ld.shared.u32 %0, [%1];" : "=r"(v) : "r"(a) : "memory"); return v; }
__device__ __forceinline__ void sts128(uint32_t a, uint4 v) { asm volatile("st.shared.v4.u32 [%0], {%1,%2,%3,%4};" :: "r"(a), "r"(v.x), "r"(v.y), "r"(v.z), "r"(v.w) : "memory"); }
__device__ __forceinline__ void sts32(uint32_t a, uint32_t v) { asm volatile("st.shared.u32 [%0], %1;" :: "r"(a), "r"(v) : "memory"); }
__device__ __forceinline__ void sts16(uint32_t a, uint32_t v) { asm volatile("st.shared.u16 [%0], %1;" :: "r"(a), "h"((uint16_t)v) : "memory"); }
__device__ __forceinline__ uint4 ldx128(const void* p) {
    uint4 v; asm volatile("{.reg .b128 t; .reg .b64 a, b; ld.relaxed.gpu.global.b128 t, [%4]; mov.b128 {a, b}, t; mov.b64 {%0,%1}, a; mov.b64 {%2,%3}, b;}"
        : "=r"(v.x), "=r"(v.y), "=r"(v.z), "=r"(v.w) : "l"(p) : "memory"); return v; }
__device__ __forceinline__ void stx128(void* p, uint4 v) {
    asm volatile("{.reg .b128 t; .reg .b64 a, b; mov.b64 a, {%1,%2}; mov.b64 b, {%3,%4}; mov.b128 t, {a, b}; st.relaxed.gpu.global.b128 [%0], t;}"
        :: "l"(p), "r"(v.x), "r"(v.y), "r"(v.z), "r"(v.w) : "memory"); }
__device__ __forceinline__ uint32_t ld_acquire(const uint32_t* p) { uint32_t v; asm volatile("ld.acquire.gpu.global.u32 %0, [%1];" : "=r"(v) : "l"(p) : "memory"); return v; }
__device__ __forceinline__ void st_relaxed(uint32_t* p, uint32_t v) { asm volatile("st.relaxed.gpu.global.u32 [%0], %1;" :: "l"(p), "r"(v) : "memory"); }
__device__ __forceinline__ void red_release(uint32_t* p) { asm volatile("red.release.gpu.global.add.u32 [%0], 1;" :: "l"(p) : "memory"); }
template <int SLEEP> __device__ __forceinline__ void wait_count(const uint32_t* p, uint32_t target) {
    int it = 0; while ((int)(ld_acquire(p) - target) < 0) { if (SLEEP) __nanosleep(SLEEP); if (++it > SPIN_LIMIT) __trap(); }
}
__device__ __forceinline__ uint32_t ldg_nc32(const void* p) { uint32_t v; asm volatile("ld.global.nc.L1::no_allocate.u32 %0, [%1];" : "=r"(v) : "l"(p)); return v; }
__device__ __forceinline__ uint32_t ldg_nc16(const void* p) { uint16_t v; asm volatile("ld.global.nc.u16 %0, [%1];" : "=h"(v) : "l"(p)); return v; }
__device__ __forceinline__ float bf_lo(uint32_t w) { return __uint_as_float(w << 16); }
__device__ __forceinline__ float bf_hi(uint32_t w) { return __uint_as_float(w & 0xFFFF0000u); }
__device__ __forceinline__ uint32_t pack_bf(float lo, float hi) { uint32_t r; asm("cvt.rn.bf16x2.f32 %0, %1, %2;" : "=r"(r) : "f"(hi), "f"(lo)); return r; }
__device__ __forceinline__ uint32_t pack_h(float lo, float hi) { uint32_t r; asm("cvt.rn.f16x2.f32 %0, %1, %2;" : "=r"(r) : "f"(hi), "f"(lo)); return r; }
__device__ __forceinline__ float bf_round(float v) { return bf_lo(pack_bf(v, 0.f)); }
__device__ __forceinline__ uint32_t hmul2(uint32_t a, uint32_t b) { uint32_t r; asm("mul.rn.f16x2 %0, %1, %2;" : "=r"(r) : "r"(a), "r"(b)); return r; }
__device__ __forceinline__ uint32_t hfma2(uint32_t a, uint32_t b, uint32_t c) { uint32_t r; asm("fma.rn.f16x2 %0, %1, %2, %3;" : "=r"(r) : "r"(a), "r"(b), "r"(c)); return r; }
__device__ __forceinline__ uint32_t hfms2(uint32_t a, uint32_t b, uint32_t c) { uint32_t r; asm("{.reg .b32 t; neg.f16x2 t, %3; fma.rn.f16x2 %0, %1, %2, t;}" : "=r"(r) : "r"(a), "r"(b), "r"(c)); return r; }
__device__ __forceinline__ uint32_t hadd2(uint32_t a, uint32_t b) { uint32_t r; asm("add.rn.f16x2 %0, %1, %2;" : "=r"(r) : "r"(a), "r"(b)); return r; }
__device__ __forceinline__ uint32_t hsub2(uint32_t a, uint32_t b) { uint32_t r; asm("sub.rn.f16x2 %0, %1, %2;" : "=r"(r) : "r"(a), "r"(b)); return r; }
__device__ __forceinline__ void cmul_neg(uint32_t& re, uint32_t& im, uint32_t c, uint32_t s) { uint32_t a = hfma2(re, c, hmul2(im, s)), b = hfms2(im, c, hmul2(re, s)); re = a; im = b; }
__device__ __forceinline__ void cmul_pos(uint32_t& re, uint32_t& im, uint32_t c, uint32_t s) { uint32_t a = hfms2(re, c, hmul2(im, s)), b = hfma2(im, c, hmul2(re, s)); re = a; im = b; }
__device__ __forceinline__ void mma_h(uint32_t& d0, uint32_t& d1, uint32_t a0, uint32_t a1, uint32_t a2, uint32_t a3, uint32_t b0, uint32_t b1) {
    asm("mma.sync.aligned.m16n8k16.row.col.f16.f16.f16.f16 {%0,%1}, {%2,%3,%4,%5}, {%6,%7}, {%0,%1};" : "+r"(d0), "+r"(d1) : "r"(a0), "r"(a1), "r"(a2), "r"(a3), "r"(b0), "r"(b1)); }
__device__ __forceinline__ void mma_h8(uint32_t& d0, uint32_t& d1, uint32_t a0, uint32_t a1, uint32_t b0) {
    asm("mma.sync.aligned.m16n8k8.row.col.f16.f16.f16.f16 {%0,%1}, {%2,%3}, {%4}, {%0,%1};" : "+r"(d0), "+r"(d1) : "r"(a0), "r"(a1), "r"(b0)); }
template <int NQ> __device__ __forceinline__ void load_tab(uint32_t (&r)[NQ * 4], uint32_t addr) {
    #pragma unroll
    for (int i = 0; i < NQ; i++) { uint4 v = lds128(addr + i * 512); r[4 * i] = v.x; r[4 * i + 1] = v.y; r[4 * i + 2] = v.z; r[4 * i + 3] = v.w; }
}
__device__ __forceinline__ float gelu2(float x) {
    float t = x * fmaf(x * x, 0.044715f * 0.7978845608028654f, 0.7978845608028654f), th;
    asm volatile("tanh.approx.f32 %0, %1;" : "=f"(th) : "f"(t));
    return fmaf(x, th, x);
}
constexpr uint32_t SM0 = 1024;
__device__ __forceinline__ constexpr uint32_t desc_lo(uint32_t off, uint32_t lbo) { return ((SM0 + off) >> 4) | ((lbo >> 4) << 16); }
constexpr uint32_t DHI_A = (1024 >> 4) | (1u << 30), DHI_H3 = 256 >> 4, DHI_U = 128 >> 4;
#define WG_FENCE() asm volatile("wgmma.fence.sync.aligned;" ::: "memory")
#define WG_COMMIT() asm volatile("wgmma.commit_group.sync.aligned;" ::: "memory")
#define WG_WAIT(n) asm volatile("wgmma.wait_group.sync.aligned %0;" :: "n"(n) : "memory")
#define R4(b) "+f"(d[b]), "+f"(d[b + 1]), "+f"(d[b + 2]), "+f"(d[b + 3])
#define R12(b) R4(b), R4(b + 4), R4(b + 8)
#define R36(b) R12(b), R12(b + 12), R12(b + 24)
template <uint32_t BHI> __device__ __forceinline__ void wgmma144(float (&d)[72], uint32_t da, uint32_t db, int acc) {
    asm volatile("{.reg .pred p; .reg .b64 a, b; setp.ne.b32 p, %74, 0; mov.b64 a, {%72, %75}; mov.b64 b, {%73, %76};\n"
        "wgmma.mma_async.sync.aligned.m64n144k16.f32.bf16.bf16 {%0,%1,%2,%3,%4,%5,%6,%7,%8,%9,%10,%11,%12,%13,%14,%15,%16,%17,%18,%19,%20,%21,%22,%23,"
        "%24,%25,%26,%27,%28,%29,%30,%31,%32,%33,%34,%35,%36,%37,%38,%39,%40,%41,%42,%43,%44,%45,%46,%47,"
        "%48,%49,%50,%51,%52,%53,%54,%55,%56,%57,%58,%59,%60,%61,%62,%63,%64,%65,%66,%67,%68,%69,%70,%71}, a, b, p, 1, 1, 1, 1;}\n"
        : R36(0), R36(36) : "r"(da), "r"(db), "r"(acc), "n"(DHI_A), "n"(BHI));
}
__device__ __forceinline__ void wgmma40_rs(float (&d)[20], uint32_t a0, uint32_t a1, uint32_t a2, uint32_t a3, uint32_t db, int acc) {
    asm volatile("{.reg .pred p; .reg .b64 b; setp.ne.b32 p, %25, 0; mov.b64 b, {%24, %26};\n"
        "wgmma.mma_async.sync.aligned.m64n40k16.f32.f16.f16 {%0,%1,%2,%3,%4,%5,%6,%7,%8,%9,%10,%11,%12,%13,%14,%15,%16,%17,%18,%19}, {%20,%21,%22,%23}, b, p, 1, 1, 0;}\n"
        : R12(0), R4(12), R4(16) : "r"(a0), "r"(a1), "r"(a2), "r"(a3), "r"(db), "r"(acc), "n"(DHI_H3));
}
__device__ __forceinline__ void wgmma72(float (&d)[36], uint32_t da, uint32_t db, int acc) {
    asm volatile("{.reg .pred p; .reg .b64 a, b; setp.ne.b32 p, %38, 0; mov.b64 a, {%36, %39}; mov.b64 b, {%37, %40};\n"
        "wgmma.mma_async.sync.aligned.m64n72k16.f32.bf16.bf16 {%0,%1,%2,%3,%4,%5,%6,%7,%8,%9,%10,%11,%12,%13,%14,%15,%16,%17,%18,%19,%20,%21,%22,%23,"
        "%24,%25,%26,%27,%28,%29,%30,%31,%32,%33,%34,%35}, a, b, p, 1, 1, 1, 1;}\n"
        : R36(0) : "r"(da), "r"(db), "r"(acc), "n"(DHI_A), "n"(DHI_H3));
}

__device__ __forceinline__ int g2_kb(int n, int kh, int gi, int c2) {
    if (n < 4) return 36 * kh + 9 * n + 8;
    if (n == 4) return 9 * gi + 4 * c2 + 2 * kh + 1;
    const int w = n > 20, m = n - (w ? 19 : 5);
    return 9 * ((gi * w + (m >> 1)) & 7) + 4 * (n == 35 ? 1 - c2 : m & 1) + 2 * kh + w;
}

template <uint32_t BHI, int S, int SN> __device__ __forceinline__ void mma_block(float (&d)[72], uint32_t bars, uint32_t da0, uint32_t db0, uint32_t ph, uint32_t& rdy) {
    if (!rdy) mbar_wait<false>(bars + 8 * (BAR_FULL + S), ph);
    WG_FENCE();
    #pragma unroll
    for (int k = 0; k < 4; k++) wgmma144<BHI>(d, da0 + S * (A_BYTES / 16) + k * 128, db0 + S * (B_BYTES / 16) + k * 288, 1);
    WG_COMMIT();
    rdy = PEEK ? __shfl_sync(~0u, (uint32_t)mbar_test(bars + 8 * (BAR_FULL + SN), SN < S ? ph ^ 1 : ph), 0) : 0;
    WG_WAIT(1);
}

struct Params {
    const uint16_t *wmod, *c, *x;
    Scratch* scr;
    const Tab* tab;
    const uint16_t *wr, *wi, *w1, *b1, *w2, *b2;
    uint16_t* out;
};

__device__ __forceinline__ void mma_bf(float (&d)[4], const uint32_t (&a)[4], uint32_t b0, uint32_t b1) {
    asm("mma.sync.aligned.m16n8k16.row.col.f32.bf16.bf16.f32 {%0,%1,%2,%3}, {%4,%5,%6,%7}, {%8,%9}, {%0,%1,%2,%3};"
        : "+f"(d[0]), "+f"(d[1]), "+f"(d[2]), "+f"(d[3]) : "r"(a[0]), "r"(a[1]), "r"(a[2]), "r"(a[3]), "r"(b0), "r"(b1)); }
__device__ __forceinline__ void ldsm4t(uint32_t (&a)[4], uint32_t addr) {
    asm volatile("ldmatrix.sync.aligned.m8n8.x4.trans.shared.b16 {%0,%1,%2,%3}, [%4];" : "=r"(a[0]), "=r"(a[1]), "=r"(a[2]), "=r"(a[3]) : "r"(addr) : "memory"); }
__device__ __forceinline__ void ln_stats(const uint32_t (&w)[9], const uint32_t (&one)[9], int g, int q, float& r, float& mr) {
    float c[2][4] = {};
    #pragma unroll
    for (int p = 0; p < 9; p++)
        asm("mma.sync.aligned.m16n8k8.row.col.f32.bf16.bf16.f32 {%0,%1,%2,%3}, {%4,%5}, {%4}, {%0,%1,%2,%3};"
            : "+f"(c[p & 1][0]), "+f"(c[p & 1][1]), "+f"(c[p & 1][2]), "+f"(c[p & 1][3]) : "r"(w[p]), "r"(one[p]));
    const float t = (g & 1) ? c[0][1] + c[1][1] : c[0][0] + c[1][0];
    float s1 = (c[0][2] + c[1][2]) + (c[0][3] + c[1][3]), s2 = __shfl_sync(~0u, t, 9 * q) + __shfl_sync(~0u, t, 9 * q + 4);
    #pragma unroll
    for (int o = 1; o < 4; o <<= 1) { s1 += __shfl_xor_sync(~0u, s1, o); s2 += __shfl_xor_sync(~0u, s2, o); }
    const float m = s1 * (1.f / D_);
    asm("rsqrt.approx.ftz.f32 %0, %1;" : "=f"(r) : "f"(fmaxf(fmaf(s2, 1.f / D_, -m * m), 0.f) + 1e-5f));
    mr = -m * r;
}
__device__ __forceinline__ float silu(float v) { return __fdividef(v, 1.f + __expf(-v)); }
__device__ __forceinline__ uint32_t bfma2(uint32_t a, uint32_t b, uint32_t c) { uint32_t r; asm("fma.rn.bf16x2 %0, %1, %2, %3;" : "=r"(r) : "r"(a), "r"(b), "r"(c)); return r; }
__device__ __forceinline__ void radix16(const uint4 (&V)[4], const uint32_t (&B)[16], uint4 (&o)[4]) {
    #pragma unroll
    for (int nt = 0; nt < 4; nt++) o[nt] = make_uint4(0, 0, 0, 0);
    #pragma unroll
    for (int u = 0; u < 4; u++)
        #pragma unroll
        for (int nt = 0; nt < 4; nt++) {
            const uint32_t b = B[((u >> 1) * 4 + nt) * 2 + (u & 1)];
            mma_h8(o[nt].x, o[nt].y, V[u].x, V[u].y, b); mma_h8(o[nt].z, o[nt].w, V[u].z, V[u].w, b);
        }
}
template <int OFF, int N> __device__ __forceinline__ void gelu_store(const float (&d)[N], char* p, int q) {
    uint32_t w[9];
    #pragma unroll
    for (int blk = 0; blk < 9; blk++) w[blk] = pack_bf(gelu2(d[OFF + 4 * blk]), gelu2(d[OFF + 4 * blk + 1]));
    asm volatile("st.v4.u32 [%0], {%1,%2,%3,%4};" :: "l"(p + q * 128), "r"(w[0]), "r"(w[1]), "r"(w[2]), "r"(w[3]) : "memory");
    asm volatile("st.v4.u32 [%0+512], {%1,%2,%3,%4};" :: "l"(p + q * 128), "r"(w[4]), "r"(w[5]), "r"(w[6]), "r"(w[7]) : "memory");
    asm volatile("st.u32 [%0+1024], %1;" :: "l"(p + q * 4), "r"(w[8]) : "memory");
}

__global__ void __cluster_dims__(2, 1, 1) __launch_bounds__(NTHR, 1)
fused_kernel(const Params p,
             const __grid_constant__ CUtensorMap tm_w1a, const __grid_constant__ CUtensorMap tm_w1b, const __grid_constant__ CUtensorMap tm_w2,
             const __grid_constant__ CUtensorMap tm_h3a, const __grid_constant__ CUtensorMap tm_h3b,
             const __grid_constant__ CUtensorMap tm_wr, const __grid_constant__ CUtensorMap tm_wi, const __grid_constant__ CUtensorMap tm_wm,
             const __grid_constant__ CUtensorMap tm_t, const __grid_constant__ CUtensorMap tm_tx, const __grid_constant__ CUtensorMap tm_o,
             const __grid_constant__ CUtensorMap tm_h3s, const __grid_constant__ CUtensorMap tm_ws)
{
    extern __shared__ __align__(1024) char smem_raw[];
    const uint32_t t0 = clk32();
    const uint32_t sm = __shfl_sync(~0u, ((uint32_t)__cvta_generic_to_shared(smem_raw) + 1023u) & ~1023u, 0);
    const int tid = threadIdx.x, warp = __shfl_sync(~0u, tid >> 5, 0), lane = tid & 31, g = lane >> 2, q = lane & 3;
    const int b = blockIdx.x;
    const uint32_t rank = b & 1;
    const uint32_t bars = sm + OFF_BAR;
    const bool rowcta = b < 128;

    auto nc_issue = [&](int st, uint32_t sl) {
        const int pass = st >= 18;
        mbar_expect(bars + 8 * (BAR_X + sl), 28672);
        tma3(sm + sl * 28672, &tm_wm, 0, 32 * (st - 18 * pass), 18 + 28 * pass + 7 * (b - 128), bars + 8 * (BAR_X + sl));
    };
    uint32_t epoch;
    const bool strip = b < 72 && !(b & 1);
    const bool sil = (warp >> 2) == 2 && lane < 24 && (strip || !rowcta);
    uint32_t cw[3];
    if (elect()) {
        mbar_init(bars + 8 * (BAR_X + warp), rowcta || warp < 6 ? 1 : 14);
        if (warp >= 12) {
            if (strip) { const uint32_t sb = bars + 8 * (BAR_ST + warp - 12);
                mbar_init(sb, 1); mbar_expect(sb, 9216); tma2(sm + OFF_STRIP + (warp - 12) * 9216, &tm_ws, 16 * b, 144 * (warp - 12), sb); }
        } else if (warp == 7) {
            mbar_init(bars + 8 * BAR_TAB, 1); mbar_expect(bars + 8 * BAR_TAB, rowcta ? QA * 512 + 16 : 16);
            bulk_load(sm + OFF_EPOCH, g_cnt + CNT_EPOCH * 32, 16, bars + 8 * BAR_TAB);
            if (rowcta) bulk_load(sm + OFF_TAB, p.tab, QA * 512, bars + 8 * BAR_TAB);
        } else if (b + 132 * warp < 576) {
            asm volatile("cp.async.bulk.prefetch.L2.global [%0], 2304;" :: "l"(p.wmod + (b + 132 * warp) * 3456) : "memory");
        }
    }
    if (sil) {
        #pragma unroll
        for (int u = 0; u < 3; u++) cw[u] = ldg_nc32(p.c + 144 * (warp - 8) + 48 * u + 2 * lane);
    }
    if (warp == 6) hb();
    __syncthreads();
    if (!rowcta) { if (warp < 6 && elect()) nc_issue(warp, warp); }
    if (warp == 5 || warp == 6) {
        if (elect()) {
            if (warp == 5) {
                for (int i = BAR_W; i < BAR_X; i++) mbar_init(bars + 8 * i, i == BAR_DONE || i == BAR_NC ? 4 : i == BAR_W1GO ? 2 : 1);
                mbar_expect(bars + 8 * BAR_W, 28672); mbar_expect(bars + 8 * BAR_TAB2, (QB + QC) * 512);
                mbar_expect(bars + 8 * BAR_ROLE, 4); mbar_expect(bars + 8 * BAR_P2R, 9216); mbar_expect(bars + 8 * BAR_RECV, 18432); mbar_expect(bars + 8 * BAR_XT, 18432);
            } else {
                for (int i = 0; i < 2 * NST; i++) mbar_init(bars + 8 * i, 2);
                for (int i = 0; i < NST; i++) mbar_expect(bars + 8 * (BAR_FULL + i), A_BYTES);
            }
            asm volatile("fence.mbarrier_init.release.cluster;" ::: "memory");
        }
    } else if (warp >= 12 && elect())
        asm volatile("prefetch.tensormap [%0];" :: "l"(warp == 12 ? &tm_wr : warp == 13 ? &tm_wi : warp == 14 ? &tm_t : &tm_tx) : "memory");
    uint32_t sb[18];
    if ((warp >> 2) == 2) {
        if (sil) {
            #pragma unroll
            for (int u = 0; u < 3; u++) sts32(sm + OFF_SILU + (72 * (warp - 8) + 24 * u + lane) * 4, pack_bf(silu(bf_lo(cw[u])), silu(bf_hi(cw[u]))));
        }
        __syncwarp();
        if (strip) {
            #pragma unroll
            for (int u = 0; u < 18; u++) sb[u] = lds32(sm + OFF_SILU + (72 * (warp - 8) + 4 * u + q) * 4);
        }
    }
    if (rowcta && elect()) {
        if (XDELAY) while ((int)(clk32() - t0) < XDELAY) {}
        mbar_expect(bars + 8 * (BAR_X + warp), 1152);
        bulk_load(sm + OFF_STAGE + warp * 1152, p.x + (size_t)(b + 128 * warp) * D_, 1152, bars + 8 * (BAR_X + warp));
    }
    __syncwarp();
    hb();

    const int trow = 4 * (b & 7) + ((b >> 4) & 3) + 64 * ((b >> 3) & 1) + 32 * (b >> 6);
    uint32_t* const tptr = g_T + (size_t)trow * TP + (warp < 9 ? q * 288 + 32 * warp : 4608 + 8 * q) + 4 * g;
    const int tstr = warp < 9 ? 1152 : 32;
    const uint32_t scol = sm + OFF_SPEC + (q * SPEC_P + (warp < 8 ? 72 * (warp >> 1) + 40 * (warp & 1) + 4 * g : warp == 8 ? 72 * (g >> 1) + 32 + 4 * (g & 1) : 288 + 4 * g)) * 4;
    const int wc0 = (b >> 3) * 289 + 72 * ((b & 7) >> 1) + 40 * (b & 1);

    uint32_t xw[9], one[9], t_st = t0, hexp = 0;
    if (!rowcta) {
        const int nst = b < 130 ? 36 : 18;
        __syncthreads();
        asm volatile("barrier.cluster.arrive.relaxed.aligned;" ::: "memory");
        mbar_wait(bars + 8 * BAR_TAB, 0);
        epoch = lds32(sm + OFF_EPOCH);
        if (warp == 14) {
            uint32_t sl = 0, ph = 0;
            #pragma unroll 1
            for (int st = 6; st < nst; st++) {
                mbar_wait(bars + 8 * (BAR_X + 6 + sl), ph);
                if (elect()) nc_issue(st, sl);
                if (++sl == 6) { sl = 0; ph ^= 1; }
            }
        } else if (warp < 14) {
            uint32_t sl = 0, ph = 0;
            const uint32_t ad0 = sm + (warp >> 1) * 4096 + ((lane & 7) + 8 * (lane >> 4)) * 128, ch = (warp & 1) * 4 + ((lane >> 3) & 1);
            #pragma unroll 1
            for (int pass = 0; pass * 18 < nst; pass++) {
                float acc[2][4] = {};
                #pragma unroll 1
                for (int st = 0; st < 18; st++) {
                    const uint32_t sa = sm + OFF_SILU + (16 * st + q) * 4;
                    const uint32_t b0 = lds32(sa), b1 = lds32(sa + 16), b2 = lds32(sa + 32), b3 = lds32(sa + 48);
                    mbar_wait(bars + 8 * (BAR_X + sl), ph);
                    #pragma unroll
                    for (int m = 0; m < 2; m++) {
                        uint32_t a[4], a2[4];
                        const uint32_t ad = ad0 + sl * 28672 + ((ch + 2 * m) ^ (lane & 7)) * 16;
                        ldsm4t(a, ad); ldsm4t(a2, ad + 2048);
                        mma_bf(acc[m], a, b0, b1); mma_bf(acc[m], a2, b2, b3);
                    }
                    if (elect()) mbar_arrive(bars + 8 * (BAR_X + 6 + sl));
                    if (++sl == 6) { sl = 0; ph ^= 1; }
                }
                const int cb = 28 * pass + 7 * (b - 128) + (warp >> 1), gg = (g >> 1) + 4 * q;
                uint32_t w[2];
                #pragma unroll
                for (int m = 0; m < 2; m++) {
                    float v = bf_round(q ? acc[m][2] : acc[m][0]); if (cb >= 27) v *= 0.5f; else if (cb >= 18) v += 1.f;
                    w[m] = max(pack_bf(v, __shfl_xor_sync(~0u, v, 4)), 1u);
                }
                if (q < 2 && !(g & 1)) {
                    const int qq = (warp & 1) * 2;
                    if (cb < 27) asm volatile("st.relaxed.gpu.global.v2.u32 [%0], {%1, %2};" :: "l"(p.scr->modc + 32 * cb + 4 * gg + qq), "r"(w[0]), "r"(w[1]) : "memory");
                    else if (cb < 36) { uint32_t* o = p.scr->modc + 896 + 32 * (cb - 27) + 8 * qq + gg; o[0] = w[0]; o[8] = w[1]; }
                }
                if (tid == 0 && pass == 0) PROFT(25);
                bar_sync(1, 448);
                if (tid == 0) { fence_async_g(); red_release(g_cnt + (CNT_NC + pass) * 32); }
                __syncwarp();
            }
            fence_async_s();
        }
        __syncthreads();
    } else {
        uint32_t ta[QA * 4];
        if (strip && (warp >> 2) == 2) {
            const int w = warp - 8;
            const uint32_t ra = sm + OFF_STRIP + (144 * w + (lane & 7) + 8 * (lane >> 4)) * 64, sw = (lane >> 1) & 3, ch = (lane >> 3) & 1;
            float acc[2][2][4] = {};
            mbar_wait(bars + 8 * (BAR_ST + w), 0);
            #pragma unroll
            for (int u = 0; u < 9; u++)
                #pragma unroll
                for (int m = 0; m < 2; m++) { uint32_t a[4]; ldsm4t(a, ra + u * 1024 + ((ch + 2 * m) ^ sw) * 16); mma_bf(acc[u & 1][m], a, sb[2 * u], sb[2 * u + 1]); }
            #define PICK(a_) ((q & 2) ? ((q & 1) ? a_[1][2] : a_[1][0]) : ((q & 1) ? a_[0][2] : a_[0][0]))
            sts32(sm + OFF_RED + ((8 * q + g) * 4 + w) * 4, __float_as_uint(PICK(acc[0]) + PICK(acc[1])));
            if (tid == 256) PROFT(0);
            bar_sync(10, 128);
            if (warp == 8) {
                mbar_wait(bars + 8 * BAR_TAB, 0);
                const uint4 v = lds128(sm + OFF_RED + lane * 16);
                float sum = bf_round((__uint_as_float(v.x) + __uint_as_float(v.y)) + (__uint_as_float(v.z) + __uint_as_float(v.w)));
                if (b >= 36) sum = bf_round(1.f + sum);
                st_relaxed(g_mod + b * 16 + (lane & 16) + (lane & 1) * 8 + ((lane & 15) >> 1), (fabsf(sum) < 8.f ? pack_h(0.f, sum) : __float_as_uint(sum) | 0x8000u) | ((lds32(sm + OFF_EPOCH) + 1) & 0x7FFFu));
                asm volatile("bar.arrive 11, 416;" ::: "memory");
                if (tid == 256) PROFT(1);
            }
        }
        mbar_wait(bars + 8 * BAR_TAB, 0);
        load_tab<QA>(ta, sm + OFF_TAB + lane * 16);
        epoch = lds32(sm + OFF_EPOCH);
        const uint32_t tag = (epoch + 1) & 0x7FFFu;
        auto w_prefetch = [&]() {
            if (warp >= 14 && elect()) asm volatile("cp.async.bulk.prefetch.L2.global [%0], 9248;" :: "l"((warp == 14 ? p.wr : p.wi) + b * 4624) : "memory");
            __syncwarp();
        };
        uint32_t nb[2][5];
        uint4 mv = make_uint4(tag, tag, tag, tag);
        const bool poller = warp < 8 || warp == 12;
        const int mc = warp < 8 ? tid : tid - 128, mst = (mc >> 2) % 36, midx = (mc < 144 ? 10 : 0) + 5 * ((mc >> 1) & 1) + (mst >> 3);
        const uint32_t* mp = g_mod + mc * 4;
        const uint32_t ma = sm + OFF_MODA + ((midx >> 2) * 32 + (mc & 1) * 16 + (mst & 3)) * 16 + (midx & 3) * 4 + ((mst >> 2) & 1) * 2;
        #define MOD_MISSING ((((mv.x ^ tag) | (mv.y ^ tag) | (mv.z ^ tag) | (mv.w ^ tag)) & 0x7FFFu) != 0)
        if (strip && (warp >> 2) != 2) bar_sync(11, 416);
        #pragma unroll
        for (int i = 0; i < 9; i++) one[i] = lds32(sm + OFF_TAB + (QA - 1) * 512 + i * 16 + 8);
        hb();
        mbar_wait(bars + 8 * (BAR_X + warp), 0);
        if (poller) mv = ldx128(mp);
        PROF0(28);
        #pragma unroll
        for (int i = 0; i < 9; i++) xw[i] = lds32(sm + OFF_STAGE + warp * 1152 + (32 * i + 8 * q + g) * 4);
        {
            float r, mr;
            ln_stats(xw, one, g, q, r, mr);
            #pragma unroll
            for (int pp = 0; pp < 5; pp++) {
                nb[0][pp] = pack_h(fmaf(bf_lo(xw[2 * pp]), r, mr), pp < 4 ? fmaf(bf_lo(xw[pp < 4 ? 2 * pp + 1 : 0]), r, mr) : 0.f);
                nb[1][pp] = pack_h(fmaf(bf_hi(xw[2 * pp]), r, mr), pp < 4 ? fmaf(bf_hi(xw[pp < 4 ? 2 * pp + 1 : 0]), r, mr) : 0.f);
            }
        }
        PROF0(2);
        w_prefetch();
        if (poller && MOD_MISSING) mv = ldx128(mp);
        if (warp < 8) {
            if (warp >= 4) sts16(sm + OFF_MODA + ((warp - 3) * 32 + lane) * 16 + (warp - 4) * 4 + 2, 0);
            const int k1 = tid & 15, s1 = tid >> 4;
            float s, c;
            __sincosf((float)(((k1 * (128 * s1 + b) + 1024) & 2047) - 1024) * (3.14159265358979f / 1024.f), &s, &c); s *= 0.25f; c *= 0.25f;
            const int rf = ((s1 >> 3) * 4 + (k1 >> 2)) * 2 + ((s1 >> 2) & 1), ri = ((k1 >> 3) * 4 + (s1 >> 2)) * 2 + ((k1 >> 2) & 1);
            const uint32_t af = sm + OFF_B3 + ((rf >> 2) * 32 + (k1 & 3) * 8 + (s1 & 3)) * 16 + (rf & 3) * 4;
            const uint32_t ai = sm + OFF_B3 + 2048 + ((ri >> 2) * 32 + (s1 & 3) * 8 + (k1 & 3)) * 16 + (ri & 3) * 4;
            sts32(af, pack_h(c, s)); sts32(af + 64, pack_h(-s, c)); sts32(ai, pack_h(c, -s)); sts32(ai + 64, pack_h(s, c));
        }
        if (poller) {
            for (int it = 0; __any_sync(~0u, MOD_MISSING); it++) { if (MOD_MISSING) mv = ldx128(mp); hb(); if (it > SPIN_LIMIT) __trap(); }
            sts16(ma, mv.x >> 16); sts16(ma + 64, mv.y >> 16); sts16(ma + 128, mv.z >> 16); sts16(ma + 192, mv.w >> 16);
        }
        uint32_t redo = 0; asm volatile("" : "+r"(redo));
        #pragma unroll 1
        do { if (redo) {
            const uint32_t w[4] = {mv.x, mv.y, mv.z, mv.w}; float f[4]; uint32_t big = 0;
            #pragma unroll
            for (int e = 0; e < 4; e++) { f[e] = (w[e] & 0x8000u) ? bf_hi(w[e]) : __half2float(__ushort_as_half(w[e] >> 16)); big = max(big, __float_as_uint(f[e]) << 1 >> 24); }
            sts32(sm + OFF_HEXP + warp * 4, __reduce_max_sync(~0u, big));
            __syncthreads();
            hexp = min(__reduce_max_sync(~0u, lds32(sm + OFF_HEXP + (lane & 15) * 4)), 253u) - 127;
            const float sc = __uint_as_float((127 - hexp) << 23);
            if (poller) {
                #pragma unroll
                for (int e = 0; e < 4; e++) sts16(ma + 64 * e, pack_h(f[e] * sc, 0.f));
            }
            mv = make_uint4(0, 0, 0, 0);
          }
          redo = __syncthreads_or((mv.x | mv.y | mv.z | mv.w) & 0x8000u);
          asm volatile("" : "+r"(redo));
        } while (redo);
        PROF0(3);
        asm volatile("barrier.cluster.arrive.relaxed.aligned;" ::: "memory");
        if (warp >= 13 && elect()) {
            if (warp == 15) bulk_load(sm + OFF_TAB + QA * 512, p.tab->w + QA * 128, (QB + QC) * 512, bars + 8 * BAR_TAB2);
            else tma3(sm + OFF_WRAW + (warp - 13) * 14336, warp == 13 ? &tm_wr : &tm_wi, wc0 & ~7, 0, 0, bars + 8 * BAR_W);
        }
        __syncwarp();
        {
            uint32_t md[20];
            load_tab<5>(md, sm + OFF_MODA + lane * 16);
            #pragma unroll
            for (int v = 0; v < 2; v++)
                #pragma unroll
                for (int pp = 0; pp < 5; pp++) nb[v][pp] = hfma2(nb[v][pp], md[v * 5 + pp], md[10 + v * 5 + pp]);
        }
        uint32_t re[3][2], im[3][2];
        #pragma unroll
        for (int mt = 0; mt < 3; mt++)
            #pragma unroll
            for (int v = 0; v < 2; v++) {
                re[mt][v] = 0; im[mt][v] = 0;
                mma_h8(re[mt][v], im[mt][v], ta[24 + 2 * mt], ta[25 + 2 * mt], nb[v][4]);
                mma_h(re[mt][v], im[mt][v], ta[mt * 8], ta[mt * 8 + 1], ta[mt * 8 + 2], ta[mt * 8 + 3], nb[v][0], nb[v][1]);
                mma_h(re[mt][v], im[mt][v], ta[mt * 8 + 4], ta[mt * 8 + 5], ta[mt * 8 + 6], ta[mt * 8 + 7], nb[v][2], nb[v][3]);
                cmul_neg(re[mt][v], im[mt][v], ta[30 + (mt * 2 + v) * 2], ta[31 + (mt * 2 + v) * 2]);
            }
        const uint32_t srow = sm + OFF_SPEC + warp * (SPEC_P * 4);
        #pragma unroll
        for (int nt = 0; nt < 2; nt++) {
            uint32_t o[2][4];
            #pragma unroll
            for (int v = 0; v < 2; v++) {
                const uint32_t b0 = ta[42 + (v * 2 + nt) * 2], b1 = ta[43 + (v * 2 + nt) * 2];
                o[v][0] = o[v][1] = o[v][2] = o[v][3] = 0;
                mma_h(o[v][0], o[v][1], re[0][v], re[1][v], im[0][v], im[1][v], b0, b1);
                mma_h(o[v][2], o[v][3], re[2][0], re[2][1], im[2][0], im[2][1], b0, b1);
            }
            const uint32_t a = srow + (g + 72 * q + 36 * nt) * 4, a2 = srow + (288 - g - 72 * q - 36 * nt) * 4;
            sts32(a, hadd2(o[0][0], o[1][0])); sts32(a + 32, hadd2(o[0][1], o[1][1])); if (g < 3) sts32(a + 64, hadd2(o[0][2], o[1][3]));
            if (g > 0 || (q == 0 && nt == 0)) sts32(a2, hsub2(o[0][0], o[1][0]) ^ 0x80000000u);
            sts32(a2 - 32, hsub2(o[0][1], o[1][1]) ^ 0x80000000u); if (g < 2) sts32(a2 - 64, hsub2(o[0][2], o[1][3]) ^ 0x80000000u);
        }
        uint32_t b3[16];
        if (warp < 10) load_tab<4>(b3, sm + OFF_B3 + lane * 16);
        __syncthreads();
        t_st = clk32();
        PROF0(4);
        if (warp < 10) {
            uint4 V[4], o[4];
            #pragma unroll
            for (int u = 0; u < 4; u++) V[u] = lds128(scol + u * (16 * SPEC_P));
            radix16(V, b3, o);
            #pragma unroll
            for (int nt = 0; nt < 4; nt++) { o[nt].x |= 1u; if (warp < 9 || g < 2) stx128(tptr + nt * tstr, o[nt]); }
        }
        PROF0(5);
    }

    int role = 0;
    asm volatile("barrier.cluster.wait.aligned;" ::: "memory");
    if (warp >= 12) {
        const int t = tid - 384;
        if (tid == 448 && rank == 0) {
            uint32_t smid; asm volatile("mov.u32 %0, %%smid;" : "=r"(smid));
            const uint32_t tp = smid >> 1;
            uint32_t pr = tp < 32 ? (tp & 7) * 8 + (tp >> 3) : tp < 60 ? (1 + (tp - 32) % 7) * 8 + 4 + (tp - 32) / 7 : tp < 62 ? 4 + tp : tp < 66 ? tp - 58 : 0;
            while (atomicExch(g_slot + pr, epoch + 1) == epoch + 1) pr = pr == 65 ? 0 : pr + 1;
            #pragma unroll
            for (int r = 0; r < 2; r++)
                asm volatile("st.async.weak.shared::cluster.mbarrier::complete_tx::bytes.u32 [%0], %1, [%2];" :: "r"(mapa(sm + OFF_MISC, r)), "r"(pr), "r"(mapa(bars + 8 * BAR_ROLE, r)) : "memory");
        }
        __syncwarp();
        if (t == 0) {
            asm volatile("prefetch.tensormap [%0];" :: "l"(&tm_w1a) : "memory");
            asm volatile("prefetch.tensormap [%0];" :: "l"(&tm_h3a) : "memory"); asm volatile("prefetch.tensormap [%0];" :: "l"(&tm_w1b) : "memory");
            asm volatile("prefetch.tensormap [%0];" :: "l"(&tm_h3b) : "memory"); asm volatile("prefetch.tensormap [%0];" :: "l"(&tm_w2) : "memory");
            asm volatile("prefetch.tensormap [%0];" :: "l"(&tm_o) : "memory"); asm volatile("prefetch.tensormap [%0];" :: "l"(&tm_h3s) : "memory");
        }
        __syncwarp();
        if (rowcta) {
            spin_until(t0 + NCP);
            uint4 v[2];
            v[1] = make_uint4(1, 1, 1, 1);
            for (int it = 0;; it++) {
                v[0] = ldx128(p.scr->modc + 4 * t); if (t < 88) v[1] = ldx128(p.scr->modc + 512 + 4 * t);
                if (__all_sync(~0u, min(min(min(v[0].x, v[0].y), min(v[0].z, v[0].w)), min(min(v[1].x, v[1].y), min(v[1].z, v[1].w))) != 0)) break;
                __nanosleep(100); if (it > SPIN_LIMIT) __trap();
            }
            if (t < 72) { const uint32_t sc = ((127 + hexp) << 7) * 0x10001u;
                v[0] = make_uint4(bfma2(v[0].x, sc, 0x80008000u), bfma2(v[0].y, sc, 0x80008000u), bfma2(v[0].z, sc, 0x80008000u), bfma2(v[0].w, sc, 0x80008000u)); }
            #pragma unroll
            for (int u = 0; u < 2; u++) if (u == 0 || t < 88) {
                const uint32_t a = sm + OFF_MODC + (((t >> 5) + 4 * u) * 32 + 4 * (t & 7)) * 16 + ((t >> 3) & 3) * 4;
                sts32(a, v[u].x); sts32(a + 16, v[u].y); sts32(a + 32, v[u].z); sts32(a + 48, v[u].w);
            }
            __syncwarp();
            if (elect()) mbar_arrive(bars + 8 * BAR_NC);
            if (t == 0) PROFT(29);
        }
    } else if (rowcta && warp < 11) {
        const int nw = !(b & 1) ? 10 : (b & 7) == 7 ? 9 : 8;
        const int cm = (b >> 3) * 288 + (b & 7) * 32, cx = (b & 1) ? 4608 + 8 * (b >> 3) : (b >> 3) * 288 + 256 + 4 * (b & 7);
        auto load_in = [&]() {
            if (elect()) {
                mbar_expect(bars + 8 * BAR_XB, nw > 8 ? 20480 : 16384);
                tma2(sm + OFF_STAGE, &tm_t, cm, 0, bars + 8 * BAR_XB);
                if (nw > 8) tma2(sm + OFF_STX, &tm_tx, cx, 0, bars + 8 * BAR_XB);
            }
            __syncwarp();
        };
        if (warp == 10) { fence_async_s(); spin_until(t_st + X1D); load_in(); }
        uint32_t tb[QB * 4], wre[4][2], wim[4][2];
        if (warp < nw) {
            mbar_wait(bars + 8 * BAR_TAB2, 0);
            load_tab<QB>(tb, sm + OFF_TAB + QA * 512 + lane * 16);
            mbar_wait(bars + 8 * BAR_W, 0);
            const int off = wc0 & 7;
            const uint32_t wa = sm + OFF_WRAW + lane * 112 + ((off >> 1) + 2 * warp) * 4, sh = (off & 1) * 16;
            #pragma unroll
            for (int c = 0; c < 2; c++)
                #pragma unroll
                for (int h = 0; h < 2; h++) {
                    uint32_t y[2][2];
                    #pragma unroll
                    for (int e = 0; e < 2; e++) {
                        const uint32_t a = wa + c * 14336 + (h + 2 * e) * 3584, x0 = lds32(a), x1 = lds32(a + 4), x2 = lds32(a + 8);
                        y[e][0] = __funnelshift_r(x0, x1, sh); y[e][1] = __funnelshift_r(x1, x2, sh);
                    }
                    #pragma unroll
                    for (int x = 0; x < 4; x++) {
                        const uint32_t v = (x & 1) ? pack_h(bf_hi(y[0][x >> 1]), bf_hi(y[1][x >> 1])) : pack_h(bf_lo(y[0][x >> 1]), bf_lo(y[1][x >> 1]));
                        if (c) wim[x][h] = v; else wre[x][h] = v;
                    }
                }
        }
        const uint32_t ca = warp < 8 ? sm + OFF_STAGE + lane * 128 + (warp ^ (lane & 7)) * 16 : sm + OFF_STX + lane * 32 + ((warp ^ g) & 1) * 16, cs = warp < 8 ? 4096 : 1024;
        uint32_t V[4][4];
        for (int it = 0;; it++) {
            mbar_wait(bars + 8 * BAR_XB, it & 1);
            uint32_t ok = 1;
            if (warp < nw) {
                #pragma unroll
                for (int u = 0; u < 4; u++) { uint4 t4 = lds128(ca + u * cs); V[u][0] = t4.x; V[u][1] = t4.y; V[u][2] = t4.z; V[u][3] = t4.w; ok &= t4.x; }
            }
            asm volatile("{.reg .pred p; setp.ne.u32 p, %0, 0; bar.red.and.pred p, 1, 352, p; selp.u32 %0, 1, 0, p;}" : "+r"(ok) :: "memory");
            if (ok) break;
            if (warp == 10) { load_in(); hb(); }
            if (it > SPIN_LIMIT / 64) __trap();
        }
        PROF0(7);
        if (warp < nw) {
            uint32_t zr[4][2], zi[4][2];
            #pragma unroll
            for (int x = 0; x < 4; x++) {
                uint32_t er = 0, ei = 0, or_ = 0, oi = 0;
                mma_h(er, ei, tb[0], tb[1], tb[2], tb[3], V[0][x], V[1][x]);
                mma_h(or_, oi, tb[4], tb[5], tb[6], tb[7], V[2][x], V[3][x]);
                uint32_t r0 = hadd2(er, or_), r1 = hsub2(er, or_), i0 = hadd2(ei, oi), i1 = hsub2(ei, oi);
                cmul_neg(r0, i0, tb[8], tb[9]); cmul_neg(r1, i1, tb[10], tb[11]);
                uint32_t xr0 = 0, xr1 = 0, xi0 = 0, xi1 = 0;
                mma_h(xr0, xr1, r0, r1, i0, i1, tb[12], tb[13]);
                mma_h(xi0, xi1, r0, r1, i0, i1, tb[14], tb[15]);
                cmul_pos(xr0, xi0, wre[x][0], wim[x][0]); cmul_pos(xr1, xi1, wre[x][1], wim[x][1]);
                r0 = 0; i0 = 0; r1 = 0; i1 = 0;
                mma_h(r0, i0, tb[12], tb[13], tb[14], tb[15], xr0, xi0);
                mma_h(r1, i1, tb[12], tb[13], tb[14], tb[15], xr1, xi1);
                cmul_pos(r0, i0, tb[16], tb[17]); cmul_pos(r1, i1, tb[18], tb[19]);
                zr[x][0] = hadd2(r0, r1); zr[x][1] = hsub2(r0, r1); zi[x][0] = hadd2(i0, i1); zi[x][1] = hsub2(i0, i1);
            }
            #pragma unroll
            for (int nt = 0; nt < 4; nt++) {
                uint4 o = make_uint4(0, 0, 0, 0);
                const int h = nt >> 1;
                mma_h(o.x, o.y, zr[0][h], zr[1][h], zi[0][h], zi[1][h], tb[20 + 2 * nt], tb[21 + 2 * nt]);
                mma_h(o.z, o.w, zr[2][h], zr[3][h], zi[2][h], zi[3][h], tb[20 + 2 * nt], tb[21 + 2 * nt]);
                o.x &= ~1u;
                sts128(ca + nt * cs, o);
            }
        }
        fence_async_s();
        bar_sync(1, 352);
        t_st = clk32();
        PROF0(8);
        if (warp == 10 && elect()) {
            asm volatile("cp.async.bulk.tensor.2d.global.shared::cta.bulk_group [%0, {%2, %3}], [%1];" :: "l"(&tm_t), "r"(sm + OFF_STAGE), "r"(cm), "r"(0) : "memory");
            if (nw > 8) asm volatile("cp.async.bulk.tensor.2d.global.shared::cta.bulk_group [%0, {%2, %3}], [%1];" :: "l"(&tm_tx), "r"(sm + OFF_STX), "r"(cx), "r"(0) : "memory");
            asm volatile("cp.async.bulk.commit_group;" ::: "memory");
            asm volatile("cp.async.bulk.wait_group.read 0;" ::: "memory");
        }
        __syncwarp();
    }

    if (warp >= 10) { mbar_wait(bars + 8 * BAR_ROLE, 0); role = __shfl_sync(~0u, lds32(sm + OFF_MISC), 0); fence_async_s(); }
    auto first_a = [&]() {
        if (warp >= 10 && role < 64 && elect()) {
            const int it = warp - 10, hi = it >= 3; const bool p2 = it - 3 * hi == 2;
            tma4(sm + OFF_A + it * A_BYTES, p2 ? &tm_w1b : &tm_w1a, 0, 0, p2 ? 64 * rank + 8 * hi : 4 * (it - hi),
                 9 * (role >> 3) + (p2 ? 8 : (role & 4) + 2 * rank), bars + 8 * (BAR_FULL + it));
        }
        __syncwarp();
    };
    if (!rowcta) first_a();
    else {
        uint32_t tc[20], md[28];
        mbar_wait(bars + 8 * BAR_TAB2, 0);
        load_tab<5>(tc, sm + OFF_TAB + (QA + QB) * 512 + lane * 16);
        bool md_early = warp >= 10;
        if (md_early) { mbar_wait(bars + 8 * BAR_NC, 0); load_tab<7>(md, sm + OFF_MODC + lane * 16); }
        if (warp < 10) {
            uint32_t b3[16];
            load_tab<4>(b3, sm + OFF_B3 + 2048 + lane * 16);
            uint4 V[4], o[4];
            const bool tact = warp < 9 || g == 0;
            spin_until(t_st + X2D);
            #pragma unroll
            for (int u = 0; u < 4; u++) { V[u] = make_uint4(0, 0, 0, 0); if (tact) V[u] = ldx128(tptr + u * tstr); }
            md_early = __any_sync(~0u, mbar_test(bars + 8 * BAR_NC, 0));
            if (md_early) load_tab<7>(md, sm + OFF_MODC + lane * 16);
            for (int it = 0; __any_sync(~0u, (V[0].x | V[1].x | V[2].x | V[3].x) & 1u); it++) {
                #pragma unroll
                for (int u = 0; u < 4; u++) if (V[u].x & 1u) V[u] = ldx128(tptr + u * tstr);
                hb();
                if (it > SPIN_LIMIT) __trap();
            }
            PROF0(10);
            radix16(V, b3, o);
            if (tact) {
                #pragma unroll
                for (int nt = 0; nt < 4; nt++) sts128(scol + nt * (16 * SPEC_P), o[nt]);
            }
        }
        __syncthreads();
        PROF0(11);
        first_a();
        const uint32_t srow = sm + OFF_SPEC + warp * (SPEC_P * 4);
        uint32_t re[2][3], im[2][3];
        #pragma unroll
        for (int mt = 0; mt < 3; mt++) {
            const uint32_t a = srow + (g + 72 * q + 8 * mt) * 4, a2 = srow + (288 - g - 72 * q - 8 * mt) * 4;
            const uint32_t z0 = lds32(a), z1 = lds32(a + 144), z2 = lds32(a2), z3 = lds32(a2 - 144);
            #pragma unroll
            for (int m2 = 0; m2 < 2; m2++) {
                re[m2][mt] = 0; im[m2][mt] = 0;
                const uint32_t sg = m2 ? 0x3C00BC00u : 0xBC003C00u;
                mma_h(re[m2][mt], im[m2][mt], tc[m2 * 4], tc[m2 * 4 + 1], tc[m2 * 4 + 2], tc[m2 * 4 + 3], hfma2(z2, sg, z0), hfma2(z3, sg, z1));
                cmul_pos(re[m2][mt], im[m2][mt], tc[8 + (m2 * 3 + mt) * 2], tc[9 + (m2 * 3 + mt) * 2]);
            }
        }
        float y[20];
        WG_FENCE();
        #pragma unroll
        for (int mt = 0; mt < 3; mt++)
            wgmma40_rs(y, re[0][mt], re[1][mt], im[0][mt], im[1][mt], desc_lo(OFF_TAB + (QA + QB + 5) * 512 + mt * 1280, 128), mt);
        WG_COMMIT();
        if (!md_early) { mbar_wait(bars + 8 * BAR_NC, 0); load_tab<7>(md, sm + OFF_MODC + lane * 16); }
        WG_WAIT(0);
        #pragma unroll
        for (int i = 0; i < 9; i++) xw[i] = bfma2(md[i], pack_bf(y[4 * (i >> 1) + (i & 1)], y[4 * (i >> 1) + 2 + (i & 1)]), xw[i]);
        float r, mr;
        ln_stats(xw, one, g, q, r, mr);
        uint32_t r2 = pack_bf(r, r), m2 = pack_bf(mr, mr);
        #pragma unroll
        for (int i = 0; i < 9; i++) {
            sts32(sm + OFF_X1 + warp * 1152 + (32 * i + 8 * q + g) * 4, xw[i]);
            xw[i] = bfma2(bfma2(xw[i], r2, m2), md[18 + i], md[9 + i]);
        }
        ln_stats(xw, one, g, q, r, mr);
        r2 = pack_bf(r, r); m2 = pack_bf(mr, mr);
        {
            const int n7 = 2 * q + (g >> 2);
            const uint32_t a = sm + OFF_STAGE + (warp >> 3) * 9216 + n7 * 128 + ((warp & 7) ^ n7) * 16 + (g & 3) * 4;
            #pragma unroll
            for (int i = 0; i < 9; i++) sts32(a + i * 1024, bfma2(xw[i], r2, m2));
        }
        fence_async_s();
        __syncthreads();
        PROF0(12);
        if (tid == 0) {
            asm volatile("cp.async.bulk.tensor.4d.global.shared::cta.bulk_group [%0, {%2, %2, %2, %3}], [%1];" :: "l"(&tm_h3s), "r"(sm + OFF_STAGE), "r"(0), "r"(b) : "memory");
            asm volatile("cp.async.bulk.commit_group;" ::: "memory");
        }
    }
    if (!rowcta) __syncthreads();
    else {
        if (tid == 0) { asm volatile("cp.async.bulk.wait_group 0;" ::: "memory"); fence_async_g(); red_release(g_cnt + CNT_H3 * 32); }
        PROF0(13);
        if (warp == 15) {
            __nanosleep(X1DELAY);
            #pragma unroll 1
            for (int r = 0; r < 16; r++) {
                uint4* dst = (uint4*)(p.out + (size_t)(b + 128 * r) * D_) + lane;
                const uint32_t src = sm + OFF_X1 + r * 1152 + lane * 16;
                dst[0] = lds128(src); dst[32] = lds128(src + 512); if (lane < 8) dst[64] = lds128(src + 1024);
                const uint32_t t1 = clk32(); while ((int)(clk32() - t1) < X1PACE) __nanosleep(50);
            }
            __syncwarp();
            if (lane == 0) { fence_async_g(); red_release(g_cnt + CNT_X1 * 32); }
        }
    }
    role = __shfl_sync(~0u, lds32(sm + OFF_MISC), 0);
    if ((sm & 0xFFFFFFu) != SM0) __trap();
    if (role >= 64) { if (warp == 0) PROFDUMP(); return; }

    const int gi = role >> 3, dt = role & 3, c2 = (role >> 2) & 1;
    const int wg = warp >> 2, wi = warp & 3;
    if (wg == 3) {
        uint32_t so = 0, eph = 1;
        #define RING_STEP(BYTES, OFF, ISSUE) do { \
            mbar_wait(bars + 8 * BAR_EMPTY + so, eph); \
            if (elect()) { const uint32_t fb = bars + 8 * BAR_FULL + so, dst = sm + (OFF) + so * ((BYTES) / 8); mbar_expect(fb, BYTES); ISSUE; } \
            so += 8; if (so == 8 * NST) { so = 0; eph ^= 1; } } while (0)
        const uint32_t kbt = g2_kb(lane, rank, gi, c2) | (g2_kb(32 + (lane & 3), rank, gi, c2) << 8);
        #define KB(n_) ((__shfl_sync(~0u, kbt, (n_) & 31) >> (((n_) >> 2) & 8)) & 255)
        if (warp == 12) {
            eph = 0;
            const int fb1 = 9 * gi + 4 * c2 + 2 * rank, sb2 = 4 * gi + 2 * c2;
            int pft = dt, pfj = 4 * (PF0 + PFS * dt);
            #pragma unroll 1
            for (int j = 16; j < 128; j += 4) {
                RING_STEP(A_BYTES, OFF_A, tma4(dst, &tm_w1a, 0, 0, j, fb1, fb));
                if (j < 64) { if (j & 4) RING_STEP(A_BYTES, OFF_A, tma4(dst, &tm_w1b, 0, 0, 64 * rank + j - 4, 9 * gi + 8, fb)); }
                if (j == pfj && pft < PFN) {
                    const int kb = KB(pft); pft += 4; pfj += 16 * PFS;
                    if (elect()) asm volatile("cp.async.bulk.prefetch.tensor.3d.L2.global [%0, {%1, %2, %3}];" :: "l"(&tm_w2), "r"(0), "r"(64 * kb), "r"(sb2) : "memory");
                }
            }
            #pragma unroll 1
            for (int n = 0; n < 36; n++) {
                const int kb = KB(n);
                RING_STEP(A_BYTES, OFF_A, tma3(dst, &tm_w2, 0, 64 * kb, sb2, fb));
            }
        } else if (warp == 13) {
            const uint32_t e1 = __shfl_sync(~0u, epoch + 1, 0);
            fence_async_s();
            wait_count<0>(g_cnt + CNT_H3 * 32, e1 * 128);
            fence_async_g();
            if (lane == 0) PROFT(14);
            #pragma unroll 1
            for (int j = 0; j < 128; j += 4) {
                RING_STEP(B_BYTES, OFF_B, tma3(dst, &tm_h3a, 0, 18 * dt, j, fb));
                if (j < 64 && (j & 4)) RING_STEP(B_BYTES, OFF_B, tma3(dst, &tm_h3b, 0, 18 * dt + 9 * c2, 64 * rank + j - 4, fb));
            }
            int n = 0;
            #pragma unroll 1
            for (int cls = 0; cls < 3; cls++) {
                mbar_wait(bars + 8 * (BAR_UOK + cls), 0);
                fence_async_g();
                if (cls == 1 && lane == 0) PROFT(19);
                if (cls == 0 && lane == 0) PROFT(22);
                static_assert((IT_G2 + 4) % NST != NST - 1, "no wrap at the skipped stage");
                if (cls == 1) { n++; so += 8; }
                #pragma unroll 1
                for (; n < (cls == 0 ? 4 : cls == 1 ? 21 : 36); n++) {
                    const int kb = KB(n);
                    RING_STEP(B_BYTES, OFF_B, bulk_load(dst, g_U + (kb * 4 + dt) * 1152, B_BYTES, fb));
                }
            }
            if (role == 0 && rank == 0 && lane == 0) st_relaxed(g_cnt + CNT_EPOCH * 32, e1);
        } else if (warp == 15) {
            if (elect()) mbar_arrive_remote(mapa(bars + 8 * BAR_HOLD, rank ^ 1));
            __syncwarp();
            bar_sync(6, 160);
            if (elect()) mbar_arrive(bars + 8 * (BAR_FULL + (IT_G2 + 4) % NST));
            __syncwarp();
            mbar_wait(bars + 8 * BAR_W1GO, 0);
            if (elect()) {
                char* dst = (char*)(g_U + ((9 * gi + 4 * c2 + 2 * rank + 1) * 4 + dt) * 1152);
                #pragma unroll 1
                for (int i = 0; i < W1N; i++) {
                    asm volatile("cp.async.bulk.global.shared::cta.bulk_group [%0], [%1], %2;" :: "l"(dst + i * (18432 / W1N)), "r"(sm + OFF_X1 + i * (18432 / W1N)), "n"(18432 / W1N) : "memory");
                    const uint32_t t1 = clk32(); while ((int)(clk32() - t1) < W1P) {}
                }
                asm volatile("cp.async.bulk.commit_group;" ::: "memory");
                asm volatile("cp.async.bulk.wait_group 0;" ::: "memory");
                fence_async_g(); red_release(g_cnt + (CNT_U + 16) * 32);
                #pragma unroll 1
                for (int n = 0; n < 4; n++) { __nanosleep(300); tma2(sm + OFF_X1 + n * 4608, &tm_o, 144 * dt, 256 * gi + 128 * c2 + 64 * (rank ^ 1) + 16 * n, bars + 8 * BAR_XT); }
            }
        } else {
            const uint32_t e1 = epoch + 1;
            if (lane == 0) {
                __nanosleep(4000);
                wait_count<200>(g_cnt + CNT_NC * 32, e1 * 4); wait_count<200>(g_cnt + (CNT_NC + 1) * 32, e1 * 2);
                fence_async_g();
                mbar_expect(bars + 8 * BAR_GB, 1152);
                bulk_load(sm + OFF_GB, p.scr->modc + 896, 1152, bars + 8 * BAR_GB);
                wait_count<200>(g_cnt + CNT_X1 * 32, e1 * 128);
                if (role * 2 + rank < 108) {
                    uint4* z = (uint4*)p.scr->modc + (role * 2 + rank) * 2; z[0] = z[1] = make_uint4(0, 0, 0, 0);
                }
                wait_count<50>(g_cnt + (CNT_U + dt * 2 + rank) * 32, e1 * 16);
                mbar_arrive(bars + 8 * BAR_UOK);
            }
            __syncwarp();
            bar_sync(4, 160);
            if (lane == 0) {
                fence_async_g(); red_release(g_cnt + (CNT_U + 8) * 32);
                PROFT(17);
                wait_count<0>(g_cnt + (CNT_U + 8) * 32, e1 * 128);
                mbar_arrive(bars + 8 * (BAR_UOK + 1));
                __nanosleep(1000);
                wait_count<100>(g_cnt + (CNT_U + 16) * 32, e1 * 128);
                mbar_arrive(bars + 8 * (BAR_UOK + 2));
            }
        }
    } else if (wg == 2) {
        float d0[36];
        const float bias = bf_lo(ldg_nc16(p.b1 + 576 * gi + 512 + 16 * wi + g + 8 * rank));
        for (int it = 0; it < 200 && !__any_sync(~0u, mbar_test(bars + 8 * BAR_FULL, 0)); it++) { hb(); __nanosleep(100); }
        const bool lead = wi == 0 && elect();
        #pragma unroll 1
        for (int i = 0; i < 8; i++) {
            const uint32_t s = P2S + 3 * (i & 1);
            mbar_wait(bars + 8 * BAR_FULL + 8 * s, (i >> 1) & 1);
            const uint32_t da = desc_lo(OFF_A, 8192) + s * (A_BYTES / 16), db = desc_lo(OFF_B, 128) + s * (B_BYTES / 16);
            WG_FENCE();
            wgmma72(d0, da, db, i);
            #pragma unroll
            for (int k = 1; k < 8; k++) wgmma72(d0, da + k * 128, db + k * 144, 1);
            WG_COMMIT();
            WG_WAIT(0);
            if (lead) mbar_arrive_n(bars + 8 * BAR_EMPTY + 8 * s, 2);
        }
        if (lead) PROFT(18);
        const uint32_t slot = sm + OFF_P2R + (tid & 127) * 16, ra = mapa(slot, rank ^ 1), rb = mapa(bars + 8 * BAR_P2R, rank ^ 1);
        float sv[18];
        #pragma unroll
        for (int i = 0; i < 18; i++) { const float lo = d0[4 * (i >> 1) + (i & 1)], hi = d0[4 * (i >> 1) + 2 + (i & 1)];
            sv[i] = rank ? lo : hi; d0[4 * (i >> 1) + (i & 1)] = (rank ? hi : lo) + bias; }
        mbar_wait(bars + 8 * BAR_HOLD, 0);
        #pragma unroll
        for (int i = 0; i < 4; i++)
            asm volatile("st.async.weak.shared::cluster.mbarrier::complete_tx::bytes.v4.f32 [%0], {%1,%2,%3,%4}, [%5];"
                :: "r"(ra + i * 2048), "f"(sv[4 * i]), "f"(sv[4 * i + 1]), "f"(sv[4 * i + 2]), "f"(sv[4 * i + 3]), "r"(rb) : "memory");
        asm volatile("st.async.weak.shared::cluster.mbarrier::complete_tx::bytes.v2.f32 [%0], {%1,%2}, [%3];" :: "r"(ra + 8192), "f"(sv[16]), "f"(sv[17]), "r"(rb) : "memory");
        mbar_wait(bars + 8 * BAR_P2R, 0);
        #pragma unroll
        for (int i = 0; i < 5; i++) {
            const uint4 v = lds128(slot + i * 2048);
            d0[8 * i] += __uint_as_float(v.x); d0[8 * i + 1] += __uint_as_float(v.y);
            if (i < 4) { d0[8 * i + 4] += __uint_as_float(v.z); d0[8 * i + 5] += __uint_as_float(v.w); }
        }
        asm volatile("bar.arrive 5, 256;" ::: "memory");
        gelu_store<0>(d0, (char*)(g_U + ((9 * gi + 8) * 4 + dt) * 1152) + wi * 4608 + rank * 2304 + c2 * 1152 + g * 16, q);
        bar_sync(8, 128);
        if (lead) { fence_async_g(); red_release(g_cnt + (CNT_U + dt * 2 + (gi >> 2)) * 32); PROFT(26); }
    } else {
        float d[72];
        const bool lead = wi == 0 && elect();
        const uint32_t da0 = desc_lo(OFF_A, 8192) + wg * 512;
        const bool owner = (uint32_t)wg == rank;
        const int srow = 256 * gi + 128 * c2 + 64 * wg + 16 * wi;
        const uint32_t b2w0 = ldg_nc16(p.b2 + srow + g), b2w1 = ldg_nc16(p.b2 + srow + g + 8);
        const int fr = 576 * gi + 256 * c2 + 128 * rank + 64 * wg + 16 * wi + g;
        const float bias0 = bf_lo(ldg_nc16(p.b1 + fr)), bias1 = bf_lo(ldg_nc16(p.b1 + fr + 8));
        {
            #pragma unroll
            for (int i = 0; i < 72; i++) d[i] = (i & 2) ? bias1 : bias0;
            constexpr uint32_t db1 = desc_lo(OFF_B, 128);
            static_assert(IT_G2 - LEAD1 == 6 * NST && IT_P1 == 4 * NST && P2S == 2, "loop structure");
            #define REL(s_) if (lead) mbar_arrive(bars + 8 * (BAR_EMPTY + (s_)))
            uint32_t rdy = 0;
            mma_block<DHI_H3, 0, 1>(d, bars, da0, db1, 0, rdy);
            #pragma unroll 1
            for (int c = 0; c < 4; c++) {
                const uint32_t ph = c & 1;
                mma_block<DHI_H3, 1, 3>(d, bars, da0, db1, ph, rdy); REL(0);
                mbar_wait(bars + 8 * (BAR_FULL + 2), ph);
                mma_block<DHI_H3, 3, 4>(d, bars, da0, db1, ph, rdy); REL(1);
                mma_block<DHI_H3, 4, 0>(d, bars, da0, db1, ph, rdy); REL(3);
                mbar_wait(bars + 8 * (BAR_FULL + 5), ph);
                mma_block<DHI_H3, 0, 1>(d, bars, da0, db1, ph ^ 1, rdy); REL(4);
            }
            #pragma unroll 1
            for (uint32_t ph = 0; ph < 2; ph++) {
                mma_block<DHI_H3, 1, 2>(d, bars, da0, db1, ph, rdy); REL(0);
                mma_block<DHI_H3, 2, 3>(d, bars, da0, db1, ph, rdy); REL(1);
                mma_block<DHI_H3, 3, 4>(d, bars, da0, db1, ph, rdy); REL(2);
                mma_block<DHI_H3, 4, 5>(d, bars, da0, db1, ph, rdy); REL(3);
                mma_block<DHI_H3, 5, 0>(d, bars, da0, db1, ph, rdy); REL(4);
                const bool pause = ph && wg == 1;
                if (pause) { WG_WAIT(0); REL(5); bar_sync(9, 256); }
                mma_block<DHI_H3, 0, 1>(d, bars, da0, db1, ph ^ 1, rdy); if (!pause) REL(5);
            }
            #pragma unroll
            for (int i = IT_G2 - LEAD1 + 1; i < IT_G2; i++) {
                mbar_wait(bars + 8 * (BAR_FULL + i % NST), (i / NST) & 1);
                WG_FENCE();
                #pragma unroll
                for (int k = 0; k < 4; k++) {
                    if (i == IT_G2 - 1 && k == HOK1) WG_COMMIT();
                    wgmma144<DHI_H3>(d, da0 + (i % NST) * (A_BYTES / 16) + k * 128, db1 + (i % NST) * (B_BYTES / 16) + k * 288, 1);
                }
                WG_COMMIT();
                if (i == IT_G2 - 1 && HOK1 < 4) WG_WAIT(2); else WG_WAIT(1);
                REL((i - 1) % NST);
            }
            if (wg == 0) { WG_WAIT(1); asm volatile("bar.arrive 9, 256;" ::: "memory"); }
            WG_WAIT(0);
            if (lead) mbar_arrive(bars + 8 * (BAR_EMPTY + (IT_G2 - 1) % NST));
            PROF0(16);
            if (wg == 1) bar_sync(5, 256);
            char* const ub = (wg == 0 ? (char*)(g_U + ((9 * gi + 4 * c2 + 2 * rank) * 4 + dt) * 1152) : (char*)__cvta_shared_to_generic(sm + OFF_X1)) + wi * 4608 + g * 16;
            gelu_store<0>(d, ub, q); gelu_store<2>(d, ub + 2304, q); gelu_store<36>(d, ub + 1152, q); gelu_store<38>(d, ub + 3456, q);
            PROF0(27);
            if (wg == 0) asm volatile("bar.arrive 4, 160;" ::: "memory");
            else { fence_async_s(); asm volatile("bar.arrive 6, 160;" ::: "memory"); }
        }
        constexpr uint32_t db0 = desc_lo(OFF_B, 2304);
        const bool keep = role < 0;
        constexpr int IT_L = IT_END - NST;
        #pragma unroll
        for (int i = IT_G2; i <= IT_G2 + W1S; i++) {
            const uint32_t db = db0 + (i == IT_G2 + 4 ? OFF_X1 - OFF_B : (i % NST) * B_BYTES) / 16;
            mbar_wait(bars + 8 * (BAR_FULL + i % NST), (i / NST) & 1);
            WG_FENCE();
            #pragma unroll
            for (int k = 0; k < 4; k++) wgmma144<DHI_U>(d, da0 + (i % NST) * (A_BYTES / 16) + k * 128, db + k * 288, i > IT_G2 || k > 0 || keep);
            WG_COMMIT();
            if (i > IT_G2) { WG_WAIT(1); if (lead) mbar_arrive(bars + 8 * (BAR_EMPTY + (i - 1) % NST)); }
        }
        if (lead) mbar_arrive(bars + 8 * BAR_W1GO);
        const uint32_t ga0 = sm + OFF_GB + (144 * dt + 8 * q) * 2, tile = sm + OFF_X1 + wi * 4608, to = g * 288 + q * 16;
        #define QOFF(i_) (((i_) >> 2) * 2304 + 144 * (((i_) >> 1) & 1) + 64 * ((i_) & 1))
        #define SOFF(k_) (((k_) >> 1) * 2304 + 144 * ((k_) & 1) + 128 - 12 * q)
        #define DIDX(i_, k_) ((i_) < 8 ? 36 * (((i_) >> 1) & 1) + 16 * ((i_) & 1) + 4 * (k_) + 2 * ((i_) >> 2) : 36 * ((k_) & 1) + 32 + 2 * ((k_) >> 1))
        #define FIN(k_, f_) bfma2(g4.f_, pack_bf(d[DIDX(i, k_)], d[DIDX(i, k_) + 1]), xq[i].f_)
        uint4 xq[9];
        auto load_g = [&](int i) { uint4 r; if (i < 4) r = lds128(ga0 + QOFF(i)); else { r.x = r.z = lds32(ga0 + SOFF(0)); r.y = r.w = lds32(ga0 + SOFF(1)); } return r; };
        static_assert(W1S == 5 && (IT_G2 + 6) % NST == 4 && ((IT_G2 + 6) / NST) % 2 == 1 && IT_L == IT_G2 + 30, "loop structure");
        uint32_t rdy = 0;
        #pragma unroll 1
        for (int c = 0; c < 4; c++) {
            const uint32_t ph = c & 1, xa = tile + to; const bool xl = c == 3 && !owner;
            mma_block<DHI_U, 4, 5>(d, bars, da0, db0, ph ^ 1, rdy); REL(3);
            mma_block<DHI_U, 5, 0>(d, bars, da0, db0, ph ^ 1, rdy); REL(4);
            mma_block<DHI_U, 0, 1>(d, bars, da0, db0, ph, rdy); REL(5);
            if (xl) { mbar_wait(bars + 8 * BAR_XT, 0); xq[0] = lds128(xa + QOFF(0)); xq[4] = lds128(xa + QOFF(4)); xq[1] = lds128(xa + QOFF(1)); }
            mma_block<DHI_U, 1, 2>(d, bars, da0, db0, ph, rdy); REL(0);
            if (xl) { xq[5] = lds128(xa + QOFF(5)); xq[2] = lds128(xa + QOFF(2)); xq[6] = lds128(xa + QOFF(6)); }
            mma_block<DHI_U, 2, 3>(d, bars, da0, db0, ph, rdy); REL(1);
            if (xl) { xq[3] = lds128(xa + QOFF(3)); xq[7] = lds128(xa + QOFF(7));
                      xq[8] = make_uint4(lds32(xa + SOFF(0)), lds32(xa + SOFF(1)), lds32(xa + SOFF(2)), lds32(xa + SOFF(3))); }
            mma_block<DHI_U, 3, 4>(d, bars, da0, db0, ph, rdy); REL(2);
        }
        if (!owner && elect()) mbar_arrive_remote(mapa(bars + 8 * BAR_DONE, rank ^ 1));
        if (owner) { WG_WAIT(0); if (lead) mbar_arrive(bars + 8 * (BAR_EMPTY + (IT_L - 1) % NST)); bar_sync(7, 256); }
        #pragma unroll
        for (int i = IT_L; i < IT_END; i++) {
            mbar_wait(bars + 8 * (BAR_FULL + i % NST), (i / NST) & 1);
            WG_FENCE();
            #pragma unroll
            for (int k = 0; k < 4; k++) {
                if (i == IT_END - 1 && k == HOK) WG_COMMIT();
                wgmma144<DHI_U>(d, da0 + (i % NST) * (A_BYTES / 16) + k * 128, db0 + (i % NST) * (B_BYTES / 16) + k * 288, 1);
            }
            WG_COMMIT();
            if (i == IT_L) { WG_WAIT(1); if (lead && !owner) mbar_arrive(bars + 8 * (BAR_EMPTY + (IT_L - 1) % NST)); }
        }
        PROF0(9);
        mbar_wait(bars + 8 * BAR_GB, 0);
        if (!owner) {
            const uint32_t ra = mapa(tile + lane * 16, rank ^ 1), rb = mapa(bars + 8 * BAR_RECV, rank ^ 1);
            mbar_wait(bars + 8 * BAR_DONE, 0);
            uint4 gn = load_g(0);
            WG_WAIT(1);
            asm volatile("bar.arrive 7, 256;" ::: "memory");
            WG_WAIT(0);
            #pragma unroll
            for (int i = 0; i < 72; i++) d[i] = fmaf(bf_lo((i & 2) ? b2w1 : b2w0), 2.f, d[i]);
            #pragma unroll
            for (int j = 0; j < 5; j++) {
                const uint4 g4 = gn;
                if (j < 4) gn = load_g(j + 1);
                #pragma unroll
                for (int i = j < 4 ? j : 8; i < 9; i += 4) if (i < 8 || j == 4)
                    asm volatile("st.async.weak.shared::cluster.mbarrier::complete_tx::bytes.v4.b32 [%0], {%1,%2,%3,%4}, [%5];"
                        :: "r"(ra + i * 512), "r"(FIN(0, x)), "r"(FIN(1, y)), "r"(FIN(2, z)), "r"(FIN(3, w)), "r"(rb) : "memory");
            }
            PROF0(6);
            if (warp == 0) PROFDUMP();
            return;
        }
        PROF0(24);
        mbar_wait(bars + 8 * BAR_RECV, 0);
        #pragma unroll
        for (int i = 0; i < 9; i++) xq[i] = lds128(tile + lane * 16 + i * 512);
        uint4 gn = load_g(0);
        WG_WAIT(0);
        __syncwarp();
        PROF0(21);
        #pragma unroll
        for (int j = 0; j < 5; j++) {
            const uint4 g4 = gn;
            if (j < 4) gn = load_g(j + 1);
            #pragma unroll
            for (int i = j < 4 ? j : 8; i < 9; i += 4) if (i < 8 || j == 4) {
                const uint4 o = make_uint4(FIN(0, x), FIN(1, y), FIN(2, z), FIN(3, w));
                if (i < 8) sts128(tile + to + QOFF(i), o);
                else { sts32(tile + to + SOFF(0), o.x); sts32(tile + to + SOFF(1), o.y); sts32(tile + to + SOFF(2), o.z); sts32(tile + to + SOFF(3), o.w); }
            }
        }
        fence_async_s();
        __syncwarp();
        if (elect()) {
            asm volatile("cp.async.bulk.tensor.2d.global.shared::cta.bulk_group [%0, {%2, %3}], [%1];" :: "l"(&tm_o), "r"(tile), "r"(144 * dt), "r"(srow) : "memory");
            asm volatile("cp.async.bulk.commit_group;" ::: "memory");
            asm volatile("cp.async.bulk.wait_group.read 0;" ::: "memory");
        }
        PROF0(23);
        if (warp == 0) { __syncwarp(); PROFDUMP(); }
    }
}

typedef CUresult (*EncodeFn)(CUtensorMap*, CUtensorMapDataType, cuuint32_t, void*, const cuuint64_t*, const cuuint64_t*, const cuuint32_t*,
                             const cuuint32_t*, CUtensorMapInterleave, CUtensorMapSwizzle, CUtensorMapL2promotion, CUtensorMapFloatOOBfill);

void encode(EncodeFn fn, CUtensorMap* m, CUtensorMapDataType dt, int rank, const void* ptr, const cuuint64_t* dims, const cuuint64_t* strides,
            const cuuint32_t* box, CUtensorMapSwizzle sw, CUtensorMapL2promotion promo = CU_TENSOR_MAP_L2_PROMOTION_L2_128B) {
    const cuuint32_t es[5] = {1, 1, 1, 1, 1};
    fn(m, dt, rank, (void*)ptr, dims, strides, box, es, CU_TENSOR_MAP_INTERLEAVE_NONE, sw, promo, CU_TENSOR_MAP_FLOAT_OOB_FILL_NONE);
}

}

extern "C" void kernel_launch(void* const* d_in, const int* in_sizes, int n_in, void* d_out, int out_size) {
    (void)in_sizes; (void)n_in; (void)out_size;
    Params p;
    p.x = (const uint16_t*)d_in[0]; p.wr = (const uint16_t*)d_in[1]; p.wi = (const uint16_t*)d_in[2];
    p.w1 = (const uint16_t*)d_in[4]; p.b1 = (const uint16_t*)d_in[5]; p.w2 = (const uint16_t*)d_in[6]; p.b2 = (const uint16_t*)d_in[7];
    p.c = (const uint16_t*)d_in[8]; p.wmod = (const uint16_t*)d_in[9]; p.out = (uint16_t*)d_out;

    void* fnp = nullptr; cudaDriverEntryPointQueryResult qr;
    cudaGetDriverEntryPoint("cuTensorMapEncodeTiled", &fnp, cudaEnableDefault, &qr);
    EncodeFn fn = (EncodeFn)fnp;
    cudaGetSymbolAddress((void**)&p.scr, g_scr); cudaGetSymbolAddress((void**)&p.tab, g_tab);
    void* h3p = p.scr->h3;
    CUtensorMap tw1a, tw1b, tw2, th3a, th3b, twr, twi, twm, tt, ttx, to, th3s, tws;
    {
        const cuuint64_t dims[4] = {64, 16, 128, 72}, st[3] = {128ull * F_ * 2, (cuuint64_t)F_ * 2, 128};
        const cuuint32_t ba[4] = {64, 16, 4, 2}, bb[4] = {64, 16, 8, 1};
        encode(fn, &tw1a, CU_TENSOR_MAP_DATA_TYPE_BFLOAT16, 4, p.w1, dims, st, ba, CU_TENSOR_MAP_SWIZZLE_128B);
        encode(fn, &tw1b, CU_TENSOR_MAP_DATA_TYPE_BFLOAT16, 4, p.w1, dims, st, bb, CU_TENSOR_MAP_SWIZZLE_128B);
    }
    {
        const cuuint64_t dims[3] = {64, F_, 32}, st[2] = {(cuuint64_t)S_ * 2, 128};
        const cuuint32_t bx[3] = {64, 64, 2};
        encode(fn, &tw2, CU_TENSOR_MAP_DATA_TYPE_BFLOAT16, 3, p.w2, dims, st, bx, CU_TENSOR_MAP_SWIZZLE_128B);
    }
    {
        const cuuint64_t dims[3] = {64, 72, 128}, st[2] = {256, 18432};
        const cuuint32_t ba[3] = {64, 18, 4}, bb[3] = {64, 9, 8};
        encode(fn, &th3a, CU_TENSOR_MAP_DATA_TYPE_UINT32, 3, h3p, dims, st, ba, CU_TENSOR_MAP_SWIZZLE_NONE);
        encode(fn, &th3b, CU_TENSOR_MAP_DATA_TYPE_UINT32, 3, h3p, dims, st, bb, CU_TENSOR_MAP_SWIZZLE_NONE);
    }
    {
        const cuuint64_t dims[4] = {32, 72, 2, 128}, st[3] = {256, 128, 18432};
        const cuuint32_t bx[4] = {32, 72, 2, 1};
        encode(fn, &th3s, CU_TENSOR_MAP_DATA_TYPE_UINT32, 4, h3p, dims, st, bx, CU_TENSOR_MAP_SWIZZLE_128B, CU_TENSOR_MAP_L2_PROMOTION_NONE);
    }
    {
        const cuuint64_t dims[3] = {4624, 4, 32}, st[2] = {9248 * 32, 9248};
        const cuuint32_t bx[3] = {56, 4, 32};
        encode(fn, &twr, CU_TENSOR_MAP_DATA_TYPE_BFLOAT16, 3, p.wr, dims, st, bx, CU_TENSOR_MAP_SWIZZLE_NONE);
        encode(fn, &twi, CU_TENSOR_MAP_DATA_TYPE_BFLOAT16, 3, p.wi, dims, st, bx, CU_TENSOR_MAP_SWIZZLE_NONE);
    }
    {
        const cuuint64_t dims[2] = {3456, 576}, st[1] = {6912};
        const cuuint32_t bx[2] = {32, 144};
        encode(fn, &tws, CU_TENSOR_MAP_DATA_TYPE_BFLOAT16, 2, p.wmod, dims, st, bx, CU_TENSOR_MAP_SWIZZLE_64B);
    }
    {
        const cuuint64_t dims[3] = {64, 576, 54}, st[2] = {6912, 128};
        const cuuint32_t bx[3] = {64, 32, 7};
        encode(fn, &twm, CU_TENSOR_MAP_DATA_TYPE_BFLOAT16, 3, p.wmod, dims, st, bx, CU_TENSOR_MAP_SWIZZLE_128B);
    }
    {
        const cuuint64_t dims[2] = {TP, 128}, st[1] = {TP * 4};
        const cuuint32_t ba[2] = {32, 128}, bb[2] = {8, 128};
        encode(fn, &tt, CU_TENSOR_MAP_DATA_TYPE_UINT32, 2, p.scr->T, dims, st, ba, CU_TENSOR_MAP_SWIZZLE_128B, CU_TENSOR_MAP_L2_PROMOTION_NONE);
        encode(fn, &ttx, CU_TENSOR_MAP_DATA_TYPE_UINT32, 2, p.scr->T, dims, st, bb, CU_TENSOR_MAP_SWIZZLE_32B, CU_TENSOR_MAP_L2_PROMOTION_NONE);
    }
    {
        const cuuint64_t dims[2] = {D_, S_}, st[1] = {D_ * 2};
        const cuuint32_t bx[2] = {144, 16};
        encode(fn, &to, CU_TENSOR_MAP_DATA_TYPE_BFLOAT16, 2, p.out, dims, st, bx, CU_TENSOR_MAP_SWIZZLE_NONE, CU_TENSOR_MAP_L2_PROMOTION_NONE);
    }
    cudaFuncSetAttribute(fused_kernel, cudaFuncAttributeMaxDynamicSharedMemorySize, SMEM_BYTES);
    cudaLaunchConfig_t cfg = {};
    cfg.gridDim = dim3(NCTA); cfg.blockDim = dim3(NTHR); cfg.dynamicSmemBytes = SMEM_BYTES; cfg.stream = cudaStreamPerThread;
    cudaLaunchAttribute at[1];
    at[0].id = cudaLaunchAttributeCooperative; at[0].val.cooperative = 1;
    cfg.attrs = at; cfg.numAttrs = 1;
    cudaLaunchKernelEx(&cfg, fused_kernel, p, tw1a, tw1b, tw2, th3a, th3b, twr, twi, twm, tt, ttx, to, th3s, tws);
}
```

```cpp
#include <cuda_runtime.h>
#include <cuda_bf16.h>
#include <cuda_fp16.h>
#include <cuda.h>
#include <stdint.h>

namespace {

constexpr int S_ = 2048, D_ = 576, F_ = 4608;
constexpr int NCTA = 132, NTHR = 512;
constexpr int TP = 4736;
constexpr int SPEC_P = 296;
constexpr int NST = 6;
constexpr int A_BYTES = 16384, B_BYTES = 18432;
constexpr int IT_P1 = 24, IT_G2 = 40, IT_END = 76;
constexpr int SPIN_LIMIT = 1 << 22;
#define X2D 1350
constexpr int P2S = 2;
#define LEAD1 4
#define W1N 8
#define W1P 100
#define W1S 5
#define XDELAY 1100
#define HOK 2
#define HOK1 2
#define NCP 10800
#define P2K 4
#define SLP 64
#define X1D 2100
#define PF0 4
#define PFS 3
#define PFN 9
#define X1DELAY 2000
#define X1PACE 400

constexpr int OFF_A = 0;
constexpr int OFF_B = NST * A_BYTES;
constexpr int OFF_P = OFF_B + NST * B_BYTES;
constexpr int OFF_BAR = OFF_P;
constexpr int OFF_EPOCH = OFF_P + 480;
constexpr int OFF_MISC = OFF_P + 496;
constexpr int OFF_GB = OFF_P + 512;
constexpr int OFF_P2R = OFF_P + 1664;
constexpr int OFF_X1 = OFF_P2R;
constexpr int OFF_PROF = OFF_X1 + 18432;
constexpr int SMEM_BYTES = OFF_PROF + 512;
constexpr int QA = 13, QB = 7, QC = 13;
constexpr int TAB_BYTES = (QA + QB + QC) * 512;
constexpr int OFF_STAGE = OFF_B;
constexpr int OFF_STX = OFF_STAGE + 16384;
constexpr int OFF_TAB = OFF_STAGE + 20480;
constexpr int OFF_SPEC = OFF_TAB + TAB_BYTES;
constexpr int OFF_WRAW = OFF_SPEC + 19072;
constexpr int OFF_B3 = OFF_WRAW + 28672;
constexpr int OFF_MODA = OFF_B3 + 4096;
constexpr int OFF_MODC = OFF_MODA + 2560;
constexpr int OFF_RED = OFF_MODC + 3584;
constexpr int OFF_HEXP = OFF_RED + 512;
constexpr int OFF_SILU = OFF_RED + 1536;
static_assert(OFF_SILU + 1152 <= OFF_P && 6 * 28672 <= OFF_B3, "scratch overflow");
constexpr int OFF_STRIP = OFF_A;
static_assert(OFF_WRAW % 128 == 0 && OFF_STAGE % 128 == 0 && OFF_STX % 128 == 0, "align");
constexpr int BAR_FULL = 0, BAR_EMPTY = 6, BAR_TAB = 12, BAR_W = 13, BAR_P2N = 14, BAR_P2R = 16,
              BAR_XT = 17, BAR_RECV = 18, BAR_ROLE = 19, BAR_NC = 20, BAR_TAB2 = 21, BAR_XB = 22, BAR_GB = 23, BAR_HOLD = 24, BAR_W1GO = 25, BAR_UOK = 26, BAR_DONE = 30, BAR_X = 31, BAR_ST = 47;

struct Cos1152 { double c[1152]; };
constexpr double cx_cos(double x) { double t = 1, s = 1; for (int i = 1; i < 14; i++) { t *= -x * x / ((2 * i - 1) * (2 * i)); s += t; } return s; }
constexpr Cos1152 make_cos() {
    Cos1152 r{};
    for (int i = 0; i <= 288; i++) {
        double v = (i == 288) ? 0.0 : cx_cos(3.14159265358979323846 * 2.0 * i / 1152.0);
        r.c[i] = v; r.c[576 - i] = -v; r.c[576 + i] = -v; r.c[(1152 - i) % 1152] = v;
    }
    return r;
}
constexpr uint32_t cx_f2h(double v) {
    uint32_t s = v < 0 ? 0x8000u : 0u; double a = v < 0 ? -v : v;
    if (a < 1e-9) return 0;
    int e = 0;
    while (a >= 2.0) { a *= 0.5; e++; }
    while (a < 1.0 && e > -14) { a *= 2.0; e--; }
    double m = a * 1024.0; uint32_t mi = (uint32_t)m; double fr = m - mi;
    if (fr > 0.5 || (fr == 0.5 && (mi & 1))) mi++;
    return s | (uint32_t)(((e + 14) << 10) + mi);
}
struct Tab { uint32_t w[(QA + QB + QC) * 128]; };
constexpr Tab make_tab() {
    Tab t{};
    Cos1152 ct = make_cos();
    auto C = [&](int num, int den) { return ct.c[(num % den) * (1152 / den)]; };
    auto Sn = [&](int num, int den) { return ct.c[((num % den) * (1152 / den) + 864) % 1152]; };
    auto put = [&](int q0, int idx, int lane, double lo, double hi) { t.w[((q0 + idx / 4) * 32 + lane) * 4 + idx % 4] = cx_f2h(lo) | (cx_f2h(hi) << 16); };
    for (int lane = 0; lane < 32; lane++) {
        const int g = lane >> 2, q = lane & 3;
        for (int mt = 0; mt < 3; mt++) {
            const int ka = 8 * mt + g;
            for (int r = 0; r < 10; r++) {
                const int im = r & 1, i0 = (r >> 1) * 2;
                double v[2] = {0, 0};
                for (int e = 0; e < 2; e++) { int i = i0 + e, d1 = 4 * i + q; if (i < 9 && ka <= 18) v[e] = (im ? -Sn(ka * d1, 36) : C(ka * d1, 36)) / 8; }
                put(0, r < 8 ? mt * 8 + r : 16 + 2 * mt + r, lane, v[0], v[1]);
            }
            for (int v = 0; v < 2; v++) {
                const int d2 = 4 * q + v;
                put(0, 30 + (mt * 2 + v) * 2, lane, C(ka * d2, 576) * 4 / 3, C(ka * (d2 + 2), 576) * 4 / 3);
                put(0, 31 + (mt * 2 + v) * 2, lane, Sn(ka * d2, 576) * 4 / 3, Sn(ka * (d2 + 2), 576) * 4 / 3);
            }
        }
        for (int v = 0; v < 2; v++) for (int nt = 0; nt < 2; nt++) {
            const int kb = 2 * (g >> 1) + nt, part = g & 1;
            double b0[2] = {0, 0}, b1[2] = {0, 0};
            for (int e = 0; e < 2; e++) { int d2 = 4 * q + 2 * e + v; double c = C(kb * d2, 16) / 4, s = Sn(kb * d2, 16) / 4;
                b0[e] = part ? -s : c; b1[e] = part ? c : s; }
            put(0, 42 + (v * 2 + nt) * 2, lane, b0[0], b0[1]); put(0, 43 + (v * 2 + nt) * 2, lane, b1[0], b1[1]);
        }
        t.w[((QA - 1) * 32 + lane) * 4 + 2] = 0x3F803F80u;
        for (int par = 0; par < 2; par++) for (int a = 0; a < 4; a++) {
            const int ja = 2 * (q + 4 * (a >> 1)) + par; const double c = C(g * ja, 16) / 4, s = Sn(g * ja, 16) / 4;
            put(QA, par * 4 + a, lane, (a & 1) ? -s : c, (a & 1) ? c : s);
        }
        for (int h = 0; h < 2; h++) {
            put(QA, 8 + 2 * h, lane, C((g + 8 * h) * (2 * q), 128) / 2, C((g + 8 * h) * (2 * q + 1), 128) / 2);
            put(QA, 9 + 2 * h, lane, Sn((g + 8 * h) * (2 * q), 128) / 2, Sn((g + 8 * h) * (2 * q + 1), 128) / 2);
            put(QA, 16 + 2 * h, lane, C(g * (8 * h + 2 * q), 128), C(g * (8 * h + 2 * q + 1), 128));
            put(QA, 17 + 2 * h, lane, Sn(g * (8 * h + 2 * q), 128), Sn(g * (8 * h + 2 * q + 1), 128));
        }
        put(QA, 12, lane, C(g * 2 * q, 8) / 2, C(g * (2 * q + 1), 8) / 2);
        put(QA, 15, lane, C(g * 2 * q, 8) / 2, C(g * (2 * q + 1), 8) / 2);
        put(QA, 13, lane, Sn(g * 2 * q, 8) / 2, Sn(g * (2 * q + 1), 8) / 2);
        put(QA, 14, lane, -Sn(g * 2 * q, 8) / 2, -Sn(g * (2 * q + 1), 8) / 2);
        for (int u = 0; u < 4; u++) {
            const int ja = 2 * ((g >> 1) + 4 * (u & 1)) + (u >> 1), part = g & 1; double b0[2] = {0, 0}, b1[2] = {0, 0};
            for (int e = 0; e < 2; e++) { int ka = 2 * q + e; double c = C(ja * ka, 16) / 4, s = Sn(ja * ka, 16) / 4;
                b0[e] = part ? s : c; b1[e] = part ? c : -s; }
            put(QA, 20 + u * 2, lane, b0[0], b0[1]); put(QA, 21 + u * 2, lane, b1[0], b1[1]);
        }
        for (int m2 = 0; m2 < 2; m2++) {
            const int d2 = 2 * g + m2;
            for (int a = 0; a < 4; a++) {
                const int kb = 2 * q + (a >> 1); const double c = C(d2 * kb, 16) / 4, s = Sn(d2 * kb, 16) / 4;
                put(QA + QB, m2 * 4 + a, lane, (a & 1) ? s : c, (a & 1) ? c : -s);
            }
            for (int mt = 0; mt < 3; mt++) {
                const int ka = 8 * mt + 2 * q;
                put(QA + QB, 8 + (m2 * 3 + mt) * 2, lane, C(ka * d2, 576) * 4 / 3, C((ka + 1) * d2, 576) * 4 / 3);
                put(QA + QB, 9 + (m2 * 3 + mt) * 2, lane, Sn(ka * d2, 576) * 4 / 3, Sn((ka + 1) * d2, 576) * 4 / 3);
            }
        }
        for (int mt = 0; mt < 3; mt++) for (int nt = 0; nt < 5; nt++) {
            const int i = 2 * nt + (g & 1), d1 = 4 * i + (g >> 1); double b0[2] = {0, 0}, b1[2] = {0, 0};
            for (int e = 0; e < 2; e++) { int ka = 8 * mt + 2 * q + e;
                if (ka <= 18 && i < 9) { double wt = (ka == 0 || ka == 18) ? 0.125 : 0.25; b0[e] = wt * C(ka * d1, 36); b1[e] = -wt * Sn(ka * d1, 36); } }
            const int o = (QA + QB + 5) * 128 + (mt * 5 + nt) * 64 + lane;
            t.w[o] = cx_f2h(b0[0]) | (cx_f2h(b0[1]) << 16); t.w[o + 32] = cx_f2h(b1[0]) | (cx_f2h(b1[1]) << 16);
        }
    }
    return t;
}
__device__ __align__(128) const Tab g_tab = make_tab();

struct Scratch {
    uint32_t cnt[30 * 32];
    uint32_t slot[96];
    uint32_t mod[2304];
    uint32_t modc[896 + 288];
    uint32_t T[128 * TP];
    uint4 h3[128 * 1152];
    uint4 U[72 * 4 * 1152];
};
__device__ __align__(1024) Scratch g_scr;
#define g_cnt (p.scr->cnt)
#define g_slot (p.scr->slot)
#define g_mod (p.scr->mod)
#define g_T (p.scr->T)
#define g_h3 (p.scr->h3)
#define g_U (p.scr->U)
constexpr int CNT_EPOCH = 0, CNT_H3 = 1, CNT_X1 = 26, CNT_NC = 27, CNT_U = 2;
#define PROFT(i) do {} while (0)
#define PROFDUMP() do {} while (0)
#define PROF0(i) do {} while (0)

__device__ __forceinline__ void mbar_init(uint32_t bar, uint32_t cnt) { asm volatile("mbarrier.init.shared::cta.b64 [%0], %1;" :: "r"(bar), "r"(cnt) : "memory"); }
__device__ __forceinline__ void mbar_expect(uint32_t bar, uint32_t bytes) { asm volatile("mbarrier.arrive.expect_tx.shared::cta.b64 _, [%0], %1;" :: "r"(bar), "r"(bytes) : "memory"); }
__device__ __forceinline__ void mbar_arrive(uint32_t bar) { asm volatile("mbarrier.arrive.shared::cta.b64 _, [%0];" :: "r"(bar) : "memory"); }
__device__ __forceinline__ void mbar_arrive_n(uint32_t bar, uint32_t n) { asm volatile("mbarrier.arrive.shared::cta.b64 _, [%0], %1;" :: "r"(bar), "r"(n) : "memory"); }
__device__ __forceinline__ void mbar_arrive_remote(uint32_t rbar) { asm volatile("mbarrier.arrive.relaxed.cluster.shared::cluster.b64 _, [%0];" :: "r"(rbar) : "memory"); }
__device__ __forceinline__ void mbar_wait(uint32_t bar, uint32_t parity) {
    asm volatile("{.reg .pred p; .reg .u32 c;\n"
        "mbarrier.try_wait.parity.shared::cta.b64 p, [%0], %1;\n@p bra.uni DONE;\nmov.u32 c, 0;\n"
        "LOOP: mbarrier.try_wait.parity.shared::cta.b64 p, [%0], %1;\n@p bra.uni DONE;\n"
        "add.u32 c, c, 1;\nsetp.lt.u32 p, c, %2;\n@p bra.uni LOOP;\ntrap;\nDONE:}" :: "r"(bar), "r"(parity), "n"(SPIN_LIMIT) : "memory");
}
__device__ __forceinline__ bool mbar_test(uint32_t bar, uint32_t parity) {
    uint32_t ok; asm volatile("{.reg .pred p; mbarrier.test_wait.parity.shared::cta.b64 p, [%1], %2; selp.u32 %0, 1, 0, p;}" : "=r"(ok) : "r"(bar), "r"(parity) : "memory"); return ok; }
__device__ __forceinline__ uint32_t mapa(uint32_t a, uint32_t rank) { uint32_t r; asm("mapa.shared::cluster.u32 %0, %1, %2;" : "=r"(r) : "r"(a), "r"(rank)); return r; }
__device__ __forceinline__ uint32_t clk32() { uint32_t r; asm volatile("mov.u32 %0, %%clock;" : "=r"(r)); return r; }
__device__ __forceinline__ void hb() {
    asm volatile("{.reg .b32 a, b; .reg .pred p; mma.sync.aligned.m16n8k8.row.col.f16.f16.f16.f16 {a, b}, {%0,%0}, {%0}, {%0,%0};\n"
                 "setp.ne.u32 p, a, 0; @p trap;}" :: "r"(0));
}
__device__ __forceinline__ void spin_until(uint32_t t) {
    while (__any_sync(~0u, (int)(clk32() - t) < -SLP * 4)) { __nanosleep(SLP); hb(); }
    while (__any_sync(~0u, (int)(clk32() - t) < 0)) {}
}
__device__ __forceinline__ bool elect() { uint32_t r; asm volatile("{.reg .pred p; elect.sync _|p, 0xffffffff; selp.u32 %0, 1, 0, p;}" : "=r"(r)); return r; }
__device__ __forceinline__ void bar_sync(int id, int n) { asm volatile("bar.sync %0, %1;" :: "r"(id), "r"(n) : "memory"); }
__device__ __forceinline__ void bulk_load(uint32_t dst, const void* src, uint32_t bytes, uint32_t bar) {
    asm volatile("cp.async.bulk.shared::cluster.global.mbarrier::complete_tx::bytes [%0], [%1], %2, [%3];" :: "r"(dst), "l"(src), "r"(bytes), "r"(bar) : "memory"); }
__device__ __forceinline__ void tma2(uint32_t dst, const CUtensorMap* m, int c0, int c1, uint32_t bar) {
    asm volatile("cp.async.bulk.tensor.2d.shared::cluster.global.mbarrier::complete_tx::bytes [%0], [%1, {%3, %4}], [%2];" :: "r"(dst), "l"(m), "r"(bar), "r"(c0), "r"(c1) : "memory"); }
__device__ __forceinline__ void tma3(uint32_t dst, const CUtensorMap* m, int c0, int c1, int c2, uint32_t bar) {
    asm volatile("cp.async.bulk.tensor.3d.shared::cluster.global.mbarrier::complete_tx::bytes [%0], [%1, {%3, %4, %5}], [%2];" :: "r"(dst), "l"(m), "r"(bar), "r"(c0), "r"(c1), "r"(c2) : "memory"); }
__device__ __forceinline__ void tma4(uint32_t dst, const CUtensorMap* m, int c0, int c1, int c2, int c3, uint32_t bar) {
    asm volatile("cp.async.bulk.tensor.4d.shared::cluster.global.mbarrier::complete_tx::bytes [%0], [%1, {%3, %4, %5, %6}], [%2];" :: "r"(dst), "l"(m), "r"(bar), "r"(c0), "r"(c1), "r"(c2), "r"(c3) : "memory"); }
__device__ __forceinline__ void fence_async_g() { asm volatile("fence.proxy.async.global;" ::: "memory"); }
__device__ __forceinline__ void fence_async_s() { asm volatile("fence.proxy.async.shared::cta;" ::: "memory"); }
__device__ __forceinline__ uint4 lds128(uint32_t a) { uint4 v; asm volatile("ld.shared.v4.u32 {%0,%1,%2,%3}, [%4];" : "=r"(v.x), "=r"(v.y), "=r"(v.z), "=r"(v.w) : "r"(a) : "memory"); return v; }
__device__ __forceinline__ uint32_t lds32(uint32_t a) { uint32_t v; asm volatile("ld.shared.u32 %0, [%1];" : "=r"(v) : "r"(a) : "memory"); return v; }
__device__ __forceinline__ void sts128(uint32_t a, uint4 v) { asm volatile("st.shared.v4.u32 [%0], {%1,%2,%3,%4};" :: "r"(a), "r"(v.x), "r"(v.y), "r"(v.z), "r"(v.w) : "memory"); }
__device__ __forceinline__ void sts32(uint32_t a, uint32_t v) { asm volatile("st.shared.u32 [%0], %1;" :: "r"(a), "r"(v) : "memory"); }
__device__ __forceinline__ void sts16(uint32_t a, uint32_t v) { asm volatile("st.shared.u16 [%0], %1;" :: "r"(a), "h"((uint16_t)v) : "memory"); }
__device__ __forceinline__ uint4 ldx128(const void* p) {
    uint4 v; asm volatile("{.reg .b128 t; .reg .b64 a, b; ld.relaxed.gpu.global.b128 t, [%4]; mov.b128 {a, b}, t; mov.b64 {%0,%1}, a; mov.b64 {%2,%3}, b;}"
        : "=r"(v.x), "=r"(v.y), "=r"(v.z), "=r"(v.w) : "l"(p) : "memory"); return v; }
__device__ __forceinline__ void stx128(void* p, uint4 v) {
    asm volatile("{.reg .b128 t; .reg .b64 a, b; mov.b64 a, {%1,%2}; mov.b64 b, {%3,%4}; mov.b128 t, {a, b}; st.relaxed.gpu.global.b128 [%0], t;}"
        :: "l"(p), "r"(v.x), "r"(v.y), "r"(v.z), "r"(v.w) : "memory"); }
__device__ __forceinline__ uint32_t ld_acquire(const uint32_t* p) { uint32_t v; asm volatile("ld.acquire.gpu.global.u32 %0, [%1];" : "=r"(v) : "l"(p) : "memory"); return v; }
__device__ __forceinline__ void st_relaxed(uint32_t* p, uint32_t v) { asm volatile("st.relaxed.gpu.global.u32 [%0], %1;" :: "l"(p), "r"(v) : "memory"); }
__device__ __forceinline__ void red_release(uint32_t* p) { asm volatile("red.release.gpu.global.add.u32 [%0], 1;" :: "l"(p) : "memory"); }
template <int SLEEP> __device__ __forceinline__ void wait_count(const uint32_t* p, uint32_t target) {
    int it = 0; while ((int)(ld_acquire(p) - target) < 0) { if (SLEEP) __nanosleep(SLEEP); if (++it > SPIN_LIMIT) __trap(); }
}
__device__ __forceinline__ uint32_t ldg_nc32(const void* p) { uint32_t v; asm volatile("ld.global.nc.L1::no_allocate.u32 %0, [%1];" : "=r"(v) : "l"(p)); return v; }
__device__ __forceinline__ uint32_t ldg_nc16(const void* p) { uint16_t v; asm volatile("ld.global.nc.u16 %0, [%1];" : "=h"(v) : "l"(p)); return v; }
__device__ __forceinline__ float bf_lo(uint32_t w) { return __uint_as_float(w << 16); }
__device__ __forceinline__ float bf_hi(uint32_t w) { return __uint_as_float(w & 0xFFFF0000u); }
__device__ __forceinline__ uint32_t pack_bf(float lo, float hi) { uint32_t r; asm("cvt.rn.bf16x2.f32 %0, %1, %2;" : "=r"(r) : "f"(hi), "f"(lo)); return r; }
__device__ __forceinline__ uint32_t pack_h(float lo, float hi) { uint32_t r; asm("cvt.rn.f16x2.f32 %0, %1, %2;" : "=r"(r) : "f"(hi), "f"(lo)); return r; }
__device__ __forceinline__ float bf_round(float v) { return bf_lo(pack_bf(v, 0.f)); }
__device__ __forceinline__ uint32_t hmul2(uint32_t a, uint32_t b) { uint32_t r; asm("mul.rn.f16x2 %0, %1, %2;" : "=r"(r) : "r"(a), "r"(b)); return r; }
__device__ __forceinline__ uint32_t hfma2(uint32_t a, uint32_t b, uint32_t c) { uint32_t r; asm("fma.rn.f16x2 %0, %1, %2, %3;" : "=r"(r) : "r"(a), "r"(b), "r"(c)); return r; }
__device__ __forceinline__ uint32_t hfms2(uint32_t a, uint32_t b, uint32_t c) { uint32_t r; asm("{.reg .b32 t; neg.f16x2 t, %3; fma.rn.f16x2 %0, %1, %2, t;}" : "=r"(r) : "r"(a), "r"(b), "r"(c)); return r; }
__device__ __forceinline__ uint32_t hadd2(uint32_t a, uint32_t b) { uint32_t r; asm("add.rn.f16x2 %0, %1, %2;" : "=r"(r) : "r"(a), "r"(b)); return r; }
__device__ __forceinline__ uint32_t hsub2(uint32_t a, uint32_t b) { uint32_t r; asm("sub.rn.f16x2 %0, %1, %2;" : "=r"(r) : "r"(a), "r"(b)); return r; }
__device__ __forceinline__ void cmul_neg(uint32_t& re, uint32_t& im, uint32_t c, uint32_t s) { uint32_t a = hfma2(re, c, hmul2(im, s)), b = hfms2(im, c, hmul2(re, s)); re = a; im = b; }
__device__ __forceinline__ void cmul_pos(uint32_t& re, uint32_t& im, uint32_t c, uint32_t s) { uint32_t a = hfms2(re, c, hmul2(im, s)), b = hfma2(im, c, hmul2(re, s)); re = a; im = b; }
__device__ __forceinline__ void mma_h(uint32_t& d0, uint32_t& d1, uint32_t a0, uint32_t a1, uint32_t a2, uint32_t a3, uint32_t b0, uint32_t b1) {
    asm("mma.sync.aligned.m16n8k16.row.col.f16.f16.f16.f16 {%0,%1}, {%2,%3,%4,%5}, {%6,%7}, {%0,%1};" : "+r"(d0), "+r"(d1) : "r"(a0), "r"(a1), "r"(a2), "r"(a3), "r"(b0), "r"(b1)); }
__device__ __forceinline__ void mma_h8(uint32_t& d0, uint32_t& d1, uint32_t a0, uint32_t a1, uint32_t b0) {
    asm("mma.sync.aligned.m16n8k8.row.col.f16.f16.f16.f16 {%0,%1}, {%2,%3}, {%4}, {%0,%1};" : "+r"(d0), "+r"(d1) : "r"(a0), "r"(a1), "r"(b0)); }
template <int NQ> __device__ __forceinline__ void load_tab(uint32_t (&r)[NQ * 4], uint32_t addr) {
    #pragma unroll
    for (int i = 0; i < NQ; i++) { uint4 v = lds128(addr + i * 512); r[4 * i] = v.x; r[4 * i + 1] = v.y; r[4 * i + 2] = v.z; r[4 * i + 3] = v.w; }
}
__device__ __forceinline__ float gelu2(float x) {
    float t = x * fmaf(x * x, 0.044715f * 0.7978845608028654f, 0.7978845608028654f), th;
    asm volatile("tanh.approx.f32 %0, %1;" : "=f"(th) : "f"(t));
    return fmaf(x, th, x);
}
constexpr uint32_t SM0 = 1024;
__device__ __forceinline__ constexpr uint32_t desc_lo(uint32_t off, uint32_t lbo) { return ((SM0 + off) >> 4) | ((lbo >> 4) << 16); }
constexpr uint32_t DHI_A = (1024 >> 4) | (1u << 30), DHI_H3 = 256 >> 4, DHI_U = 128 >> 4;
#define WG_FENCE() asm volatile("wgmma.fence.sync.aligned;" ::: "memory")
#define WG_COMMIT() asm volatile("wgmma.commit_group.sync.aligned;" ::: "memory")
#define WG_WAIT(n) asm volatile("wgmma.wait_group.sync.aligned %0;" :: "n"(n) : "memory")
#define R4(b) "+f"(d[b]), "+f"(d[b + 1]), "+f"(d[b + 2]), "+f"(d[b + 3])
#define R12(b) R4(b), R4(b + 4), R4(b + 8)
#define R36(b) R12(b), R12(b + 12), R12(b + 24)
template <uint32_t BHI> __device__ __forceinline__ void wgmma144(float (&d)[72], uint32_t da, uint32_t db, int acc) {
    asm volatile("{.reg .pred p; .reg .b64 a, b; setp.ne.b32 p, %74, 0; mov.b64 a, {%72, %75}; mov.b64 b, {%73, %76};\n"
        "wgmma.mma_async.sync.aligned.m64n144k16.f32.bf16.bf16 {%0,%1,%2,%3,%4,%5,%6,%7,%8,%9,%10,%11,%12,%13,%14,%15,%16,%17,%18,%19,%20,%21,%22,%23,"
        "%24,%25,%26,%27,%28,%29,%30,%31,%32,%33,%34,%35,%36,%37,%38,%39,%40,%41,%42,%43,%44,%45,%46,%47,"
        "%48,%49,%50,%51,%52,%53,%54,%55,%56,%57,%58,%59,%60,%61,%62,%63,%64,%65,%66,%67,%68,%69,%70,%71}, a, b, p, 1, 1, 1, 1;}\n"
        : R36(0), R36(36) : "r"(da), "r"(db), "r"(acc), "n"(DHI_A), "n"(BHI));
}
__device__ __forceinline__ void wgmma40_rs(float (&d)[20], uint32_t a0, uint32_t a1, uint32_t a2, uint32_t a3, uint32_t db, int acc) {
    asm volatile("{.reg .pred p; .reg .b64 b; setp.ne.b32 p, %25, 0; mov.b64 b, {%24, %26};\n"
        "wgmma.mma_async.sync.aligned.m64n40k16.f32.f16.f16 {%0,%1,%2,%3,%4,%5,%6,%7,%8,%9,%10,%11,%12,%13,%14,%15,%16,%17,%18,%19}, {%20,%21,%22,%23}, b, p, 1, 1, 0;}\n"
        : R12(0), R4(12), R4(16) : "r"(a0), "r"(a1), "r"(a2), "r"(a3), "r"(db), "r"(acc), "n"(DHI_H3));
}
__device__ __forceinline__ void wgmma72(float (&d)[36], uint32_t da, uint32_t db, int acc) {
    asm volatile("{.reg .pred p; .reg .b64 a, b; setp.ne.b32 p, %38, 0; mov.b64 a, {%36, %39}; mov.b64 b, {%37, %40};\n"
        "wgmma.mma_async.sync.aligned.m64n72k16.f32.bf16.bf16 {%0,%1,%2,%3,%4,%5,%6,%7,%8,%9,%10,%11,%12,%13,%14,%15,%16,%17,%18,%19,%20,%21,%22,%23,"
        "%24,%25,%26,%27,%28,%29,%30,%31,%32,%33,%34,%35}, a, b, p, 1, 1, 1, 1;}\n"
        : R36(0) : "r"(da), "r"(db), "r"(acc), "n"(DHI_A), "n"(DHI_H3));
}

__device__ __forceinline__ int g2_kb(int n, int kh, int gi, int c2) {
    if (n < 4) return 36 * kh + 9 * n + 8;
    if (n == 4) return 9 * gi + 4 * c2 + 2 * kh + 1;
    const int w = n > 20, m = n - (w ? 19 : 5);
    return 9 * ((gi * w + (m >> 1)) & 7) + 4 * (n == 35 ? 1 - c2 : m & 1) + 2 * kh + w;
}

template <uint32_t BHI, int S> __device__ __forceinline__ void mma_block(float (&d)[72], uint32_t bars, uint32_t da0, uint32_t db0, uint32_t ph) {
    mbar_wait(bars + 8 * (BAR_FULL + S), ph);
    WG_FENCE();
    #pragma unroll
    for (int k = 0; k < 4; k++) wgmma144<BHI>(d, da0 + S * (A_BYTES / 16) + k * 128, db0 + S * (B_BYTES / 16) + k * 288, 1);
    WG_COMMIT();
    WG_WAIT(1);
}

struct Params {
    const uint16_t *wmod, *c, *x;
    Scratch* scr;
    const Tab* tab;
    const uint16_t *wr, *wi, *w1, *b1, *w2, *b2;
    uint16_t* out;
};

__device__ __forceinline__ void mma_bf(float (&d)[4], const uint32_t (&a)[4], uint32_t b0, uint32_t b1) {
    asm("mma.sync.aligned.m16n8k16.row.col.f32.bf16.bf16.f32 {%0,%1,%2,%3}, {%4,%5,%6,%7}, {%8,%9}, {%0,%1,%2,%3};"
        : "+f"(d[0]), "+f"(d[1]), "+f"(d[2]), "+f"(d[3]) : "r"(a[0]), "r"(a[1]), "r"(a[2]), "r"(a[3]), "r"(b0), "r"(b1)); }
__device__ __forceinline__ void ldsm4t(uint32_t (&a)[4], uint32_t addr) {
    asm volatile("ldmatrix.sync.aligned.m8n8.x4.trans.shared.b16 {%0,%1,%2,%3}, [%4];" : "=r"(a[0]), "=r"(a[1]), "=r"(a[2]), "=r"(a[3]) : "r"(addr) : "memory"); }
__device__ __forceinline__ void ln_stats(const uint32_t (&w)[9], const uint32_t (&one)[9], int g, int q, float& r, float& mr) {
    float c[2][4] = {};
    #pragma unroll
    for (int p = 0; p < 9; p++)
        asm("mma.sync.aligned.m16n8k8.row.col.f32.bf16.bf16.f32 {%0,%1,%2,%3}, {%4,%5}, {%4}, {%0,%1,%2,%3};"
            : "+f"(c[p & 1][0]), "+f"(c[p & 1][1]), "+f"(c[p & 1][2]), "+f"(c[p & 1][3]) : "r"(w[p]), "r"(one[p]));
    const float t = (g & 1) ? c[0][1] + c[1][1] : c[0][0] + c[1][0];
    float s1 = (c[0][2] + c[1][2]) + (c[0][3] + c[1][3]), s2 = __shfl_sync(~0u, t, 9 * q) + __shfl_sync(~0u, t, 9 * q + 4);
    #pragma unroll
    for (int o = 1; o < 4; o <<= 1) { s1 += __shfl_xor_sync(~0u, s1, o); s2 += __shfl_xor_sync(~0u, s2, o); }
    const float m = s1 * (1.f / D_);
    asm("rsqrt.approx.ftz.f32 %0, %1;" : "=f"(r) : "f"(fmaxf(fmaf(s2, 1.f / D_, -m * m), 0.f) + 1e-5f));
    mr = -m * r;
}
__device__ __forceinline__ float silu(float v) { return __fdividef(v, 1.f + __expf(-v)); }
__device__ __forceinline__ uint32_t bfma2(uint32_t a, uint32_t b, uint32_t c) { uint32_t r; asm("fma.rn.bf16x2 %0, %1, %2, %3;" : "=r"(r) : "r"(a), "r"(b), "r"(c)); return r; }
__device__ __forceinline__ void radix16(const uint4 (&V)[4], const uint32_t (&B)[16], uint4 (&o)[4]) {
    #pragma unroll
    for (int nt = 0; nt < 4; nt++) o[nt] = make_uint4(0, 0, 0, 0);
    #pragma unroll
    for (int u = 0; u < 4; u++)
        #pragma unroll
        for (int nt = 0; nt < 4; nt++) {
            const uint32_t b = B[((u >> 1) * 4 + nt) * 2 + (u & 1)];
            mma_h8(o[nt].x, o[nt].y, V[u].x, V[u].y, b); mma_h8(o[nt].z, o[nt].w, V[u].z, V[u].w, b);
        }
}
template <int OFF, int N> __device__ __forceinline__ void gelu_store(const float (&d)[N], char* p, int q) {
    uint32_t w[9];
    #pragma unroll
    for (int blk = 0; blk < 9; blk++) w[blk] = pack_bf(gelu2(d[OFF + 4 * blk]), gelu2(d[OFF + 4 * blk + 1]));
    asm volatile("st.v4.u32 [%0], {%1,%2,%3,%4};" :: "l"(p + q * 128), "r"(w[0]), "r"(w[1]), "r"(w[2]), "r"(w[3]) : "memory");
    asm volatile("st.v4.u32 [%0+512], {%1,%2,%3,%4};" :: "l"(p + q * 128), "r"(w[4]), "r"(w[5]), "r"(w[6]), "r"(w[7]) : "memory");
    asm volatile("st.u32 [%0+1024], %1;" :: "l"(p + q * 4), "r"(w[8]) : "memory");
}

__global__ void __cluster_dims__(2, 1, 1) __launch_bounds__(NTHR, 1)
fused_kernel(const Params p,
             const __grid_constant__ CUtensorMap tm_w1a, const __grid_constant__ CUtensorMap tm_w1b, const __grid_constant__ CUtensorMap tm_w2,
             const __grid_constant__ CUtensorMap tm_h3a, const __grid_constant__ CUtensorMap tm_h3b,
             const __grid_constant__ CUtensorMap tm_wr, const __grid_constant__ CUtensorMap tm_wi, const __grid_constant__ CUtensorMap tm_wm,
             const __grid_constant__ CUtensorMap tm_t, const __grid_constant__ CUtensorMap tm_tx, const __grid_constant__ CUtensorMap tm_o,
             const __grid_constant__ CUtensorMap tm_h3s, const __grid_constant__ CUtensorMap tm_ws)
{
    extern __shared__ __align__(1024) char smem_raw[];
    const uint32_t t0 = clk32();
    const uint32_t sm = __shfl_sync(~0u, ((uint32_t)__cvta_generic_to_shared(smem_raw) + 1023u) & ~1023u, 0);
    const int tid = threadIdx.x, warp = __shfl_sync(~0u, tid >> 5, 0), lane = tid & 31, g = lane >> 2, q = lane & 3;
    const int b = blockIdx.x;
    const uint32_t rank = b & 1;
    const uint32_t bars = sm + OFF_BAR;
    const bool rowcta = b < 128;

    auto nc_issue = [&](int st, uint32_t sl) {
        const int pass = st >= 18;
        mbar_expect(bars + 8 * (BAR_X + sl), 28672);
        tma3(sm + sl * 28672, &tm_wm, 0, 32 * (st - 18 * pass), 18 + 28 * pass + 7 * (b - 128), bars + 8 * (BAR_X + sl));
    };
    uint32_t epoch;
    const bool strip = b < 72 && !(b & 1);
    const bool sil = (warp >> 2) == 2 && lane < 24 && (strip || !rowcta);
    uint32_t cw[3];
    if (elect()) {
        mbar_init(bars + 8 * (BAR_X + warp), rowcta || warp < 6 ? 1 : 14);
        if (warp >= 12) {
            if (strip) { const uint32_t sb = bars + 8 * (BAR_ST + warp - 12);
                mbar_init(sb, 1); mbar_expect(sb, 9216); tma2(sm + OFF_STRIP + (warp - 12) * 9216, &tm_ws, 16 * b, 144 * (warp - 12), sb); }
        } else if (warp == 7) {
            mbar_init(bars + 8 * BAR_TAB, 1); mbar_expect(bars + 8 * BAR_TAB, rowcta ? QA * 512 + 16 : 16);
            bulk_load(sm + OFF_EPOCH, g_cnt + CNT_EPOCH * 32, 16, bars + 8 * BAR_TAB);
            if (rowcta) bulk_load(sm + OFF_TAB, p.tab, QA * 512, bars + 8 * BAR_TAB);
        } else if (b + 132 * warp < 576) {
            asm volatile("cp.async.bulk.prefetch.L2.global [%0], 2304;" :: "l"(p.wmod + (b + 132 * warp) * 3456) : "memory");
        }
    }
    if (sil) {
        #pragma unroll
        for (int u = 0; u < 3; u++) cw[u] = ldg_nc32(p.c + 144 * (warp - 8) + 48 * u + 2 * lane);
    }
    if (warp == 6) hb();
    __syncthreads();
    if (!rowcta) { if (warp < 6 && elect()) nc_issue(warp, warp); }
    if (warp == 5 || warp == 6) {
        if (elect()) {
            if (warp == 5) {
                for (int i = BAR_W; i < BAR_X; i++) mbar_init(bars + 8 * i, i == BAR_DONE || i == BAR_NC ? 4 : i == BAR_W1GO ? 2 : 1);
                mbar_expect(bars + 8 * BAR_W, 28672); mbar_expect(bars + 8 * BAR_TAB2, (QB + QC) * 512);
                mbar_expect(bars + 8 * BAR_ROLE, 4); mbar_expect(bars + 8 * BAR_P2R, 9216); mbar_expect(bars + 8 * BAR_RECV, 18432); mbar_expect(bars + 8 * BAR_XT, 18432);
            } else {
                for (int i = 0; i < 2 * NST; i++) mbar_init(bars + 8 * i, 2);
                for (int i = 0; i < NST; i++) mbar_expect(bars + 8 * (BAR_FULL + i), A_BYTES);
            }
            asm volatile("fence.mbarrier_init.release.cluster;" ::: "memory");
        }
    } else if (warp >= 12 && elect())
        asm volatile("prefetch.tensormap [%0];" :: "l"(warp == 12 ? &tm_wr : warp == 13 ? &tm_wi : warp == 14 ? &tm_t : &tm_tx) : "memory");
    uint32_t sb[18];
    if ((warp >> 2) == 2) {
        if (sil) {
            #pragma unroll
            for (int u = 0; u < 3; u++) sts32(sm + OFF_SILU + (72 * (warp - 8) + 24 * u + lane) * 4, pack_bf(silu(bf_lo(cw[u])), silu(bf_hi(cw[u]))));
        }
        __syncwarp();
        if (strip) {
            #pragma unroll
            for (int u = 0; u < 18; u++) sb[u] = lds32(sm + OFF_SILU + (72 * (warp - 8) + 4 * u + q) * 4);
        }
    }
    if (rowcta && elect()) {
        if (XDELAY) while ((int)(clk32() - t0) < XDELAY) {}
        mbar_expect(bars + 8 * (BAR_X + warp), 1152);
        bulk_load(sm + OFF_STAGE + warp * 1152, p.x + (size_t)(b + 128 * warp) * D_, 1152, bars + 8 * (BAR_X + warp));
    }
    __syncwarp();
    hb();

    const int trow = 4 * (b & 7) + ((b >> 4) & 3) + 64 * ((b >> 3) & 1) + 32 * (b >> 6);
    uint32_t* const tptr = g_T + (size_t)trow * TP + (warp < 9 ? q * 288 + 32 * warp : 4608 + 8 * q) + 4 * g;
    const int tstr = warp < 9 ? 1152 : 32;
    const uint32_t scol = sm + OFF_SPEC + (q * SPEC_P + (warp < 8 ? 72 * (warp >> 1) + 40 * (warp & 1) + 4 * g : warp == 8 ? 72 * (g >> 1) + 32 + 4 * (g & 1) : 288 + 4 * g)) * 4;
    const int wc0 = (b >> 3) * 289 + 72 * ((b & 7) >> 1) + 40 * (b & 1);

    uint32_t xw[9], one[9], t_st = t0, hexp = 0;
    if (!rowcta) {
        const int nst = b < 130 ? 36 : 18;
        __syncthreads();
        asm volatile("barrier.cluster.arrive.relaxed.aligned;" ::: "memory");
        mbar_wait(bars + 8 * BAR_TAB, 0);
        epoch = lds32(sm + OFF_EPOCH);
        if (warp == 14) {
            uint32_t sl = 0, ph = 0;
            #pragma unroll 1
            for (int st = 6; st < nst; st++) {
                mbar_wait(bars + 8 * (BAR_X + 6 + sl), ph);
                if (elect()) nc_issue(st, sl);
                if (++sl == 6) { sl = 0; ph ^= 1; }
            }
        } else if (warp < 14) {
            uint32_t sl = 0, ph = 0;
            const uint32_t ad0 = sm + (warp >> 1) * 4096 + ((lane & 7) + 8 * (lane >> 4)) * 128, ch = (warp & 1) * 4 + ((lane >> 3) & 1);
            #pragma unroll 1
            for (int pass = 0; pass * 18 < nst; pass++) {
                float acc[2][4] = {};
                #pragma unroll 1
                for (int st = 0; st < 18; st++) {
                    const uint32_t sa = sm + OFF_SILU + (16 * st + q) * 4;
                    const uint32_t b0 = lds32(sa), b1 = lds32(sa + 16), b2 = lds32(sa + 32), b3 = lds32(sa + 48);
                    mbar_wait(bars + 8 * (BAR_X + sl), ph);
                    #pragma unroll
                    for (int m = 0; m < 2; m++) {
                        uint32_t a[4], a2[4];
                        const uint32_t ad = ad0 + sl * 28672 + ((ch + 2 * m) ^ (lane & 7)) * 16;
                        ldsm4t(a, ad); ldsm4t(a2, ad + 2048);
                        mma_bf(acc[m], a, b0, b1); mma_bf(acc[m], a2, b2, b3);
                    }
                    if (elect()) mbar_arrive(bars + 8 * (BAR_X + 6 + sl));
                    if (++sl == 6) { sl = 0; ph ^= 1; }
                }
                const int cb = 28 * pass + 7 * (b - 128) + (warp >> 1), gg = (g >> 1) + 4 * q;
                uint32_t w[2];
                #pragma unroll
                for (int m = 0; m < 2; m++) {
                    float v = bf_round(q ? acc[m][2] : acc[m][0]); if (cb >= 27) v *= 0.5f; else if (cb >= 18) v += 1.f;
                    w[m] = max(pack_bf(v, __shfl_xor_sync(~0u, v, 4)), 1u);
                }
                if (q < 2 && !(g & 1)) {
                    const int qq = (warp & 1) * 2;
                    if (cb < 27) asm volatile("st.relaxed.gpu.global.v2.u32 [%0], {%1, %2};" :: "l"(p.scr->modc + 32 * cb + 4 * gg + qq), "r"(w[0]), "r"(w[1]) : "memory");
                    else if (cb < 36) { uint32_t* o = p.scr->modc + 896 + 32 * (cb - 27) + 8 * qq + gg; o[0] = w[0]; o[8] = w[1]; }
                }
                if (tid == 0 && pass == 0) PROFT(25);
                bar_sync(1, 448);
                if (tid == 0) { fence_async_g(); red_release(g_cnt + (CNT_NC + pass) * 32); }
                __syncwarp();
            }
            fence_async_s();
        }
        __syncthreads();
    } else {
        uint32_t ta[QA * 4];
        if (strip && (warp >> 2) == 2) {
            const int w = warp - 8;
            const uint32_t ra = sm + OFF_STRIP + (144 * w + (lane & 7) + 8 * (lane >> 4)) * 64, sw = (lane >> 1) & 3, ch = (lane >> 3) & 1;
            float acc[2][2][4] = {};
            mbar_wait(bars + 8 * (BAR_ST + w), 0);
            #pragma unroll
            for (int u = 0; u < 9; u++)
                #pragma unroll
                for (int m = 0; m < 2; m++) { uint32_t a[4]; ldsm4t(a, ra + u * 1024 + ((ch + 2 * m) ^ sw) * 16); mma_bf(acc[u & 1][m], a, sb[2 * u], sb[2 * u + 1]); }
            #define PICK(a_) ((q & 2) ? ((q & 1) ? a_[1][2] : a_[1][0]) : ((q & 1) ? a_[0][2] : a_[0][0]))
            sts32(sm + OFF_RED + ((8 * q + g) * 4 + w) * 4, __float_as_uint(PICK(acc[0]) + PICK(acc[1])));
            if (tid == 256) PROFT(0);
            bar_sync(10, 128);
            if (warp == 8) {
                mbar_wait(bars + 8 * BAR_TAB, 0);
                const uint4 v = lds128(sm + OFF_RED + lane * 16);
                float sum = bf_round((__uint_as_float(v.x) + __uint_as_float(v.y)) + (__uint_as_float(v.z) + __uint_as_float(v.w)));
                if (b >= 36) sum = bf_round(1.f + sum);
                st_relaxed(g_mod + b * 16 + (lane & 16) + (lane & 1) * 8 + ((lane & 15) >> 1), (fabsf(sum) < 8.f ? pack_h(0.f, sum) : __float_as_uint(sum) | 0x8000u) | ((lds32(sm + OFF_EPOCH) + 1) & 0x7FFFu));
                asm volatile("bar.arrive 11, 416;" ::: "memory");
                if (tid == 256) PROFT(1);
            }
        }
        mbar_wait(bars + 8 * BAR_TAB, 0);
        load_tab<QA>(ta, sm + OFF_TAB + lane * 16);
        epoch = lds32(sm + OFF_EPOCH);
        const uint32_t tag = (epoch + 1) & 0x7FFFu;
        auto w_prefetch = [&]() {
            if (warp >= 14 && elect()) asm volatile("cp.async.bulk.prefetch.L2.global [%0], 9248;" :: "l"((warp == 14 ? p.wr : p.wi) + b * 4624) : "memory");
            __syncwarp();
        };
        uint32_t nb[2][5];
        uint4 mv = make_uint4(tag, tag, tag, tag);
        const bool poller = warp < 8 || warp == 12;
        const int mc = warp < 8 ? tid : tid - 128, mst = (mc >> 2) % 36, midx = (mc < 144 ? 10 : 0) + 5 * ((mc >> 1) & 1) + (mst >> 3);
        const uint32_t* mp = g_mod + mc * 4;
        const uint32_t ma = sm + OFF_MODA + ((midx >> 2) * 32 + (mc & 1) * 16 + (mst & 3)) * 16 + (midx & 3) * 4 + ((mst >> 2) & 1) * 2;
        #define MOD_MISSING ((((mv.x ^ tag) | (mv.y ^ tag) | (mv.z ^ tag) | (mv.w ^ tag)) & 0x7FFFu) != 0)
        if (strip && (warp >> 2) != 2) bar_sync(11, 416);
        #pragma unroll
        for (int i = 0; i < 9; i++) one[i] = lds32(sm + OFF_TAB + (QA - 1) * 512 + i * 16 + 8);
        hb();
        mbar_wait(bars + 8 * (BAR_X + warp), 0);
        if (poller) mv = ldx128(mp);
        PROF0(28);
        #pragma unroll
        for (int i = 0; i < 9; i++) xw[i] = lds32(sm + OFF_STAGE + warp * 1152 + (32 * i + 8 * q + g) * 4);
        {
            float r, mr;
            ln_stats(xw, one, g, q, r, mr);
            #pragma unroll
            for (int pp = 0; pp < 5; pp++) {
                nb[0][pp] = pack_h(fmaf(bf_lo(xw[2 * pp]), r, mr), pp < 4 ? fmaf(bf_lo(xw[pp < 4 ? 2 * pp + 1 : 0]), r, mr) : 0.f);
                nb[1][pp] = pack_h(fmaf(bf_hi(xw[2 * pp]), r, mr), pp < 4 ? fmaf(bf_hi(xw[pp < 4 ? 2 * pp + 1 : 0]), r, mr) : 0.f);
            }
        }
        PROF0(2);
        w_prefetch();
        if (poller && MOD_MISSING) mv = ldx128(mp);
        if (warp < 8) {
            if (warp >= 4) sts16(sm + OFF_MODA + ((warp - 3) * 32 + lane) * 16 + (warp - 4) * 4 + 2, 0);
            const int k1 = tid & 15, s1 = tid >> 4;
            float s, c;
            __sincosf((float)(((k1 * (128 * s1 + b) + 1024) & 2047) - 1024) * (3.14159265358979f / 1024.f), &s, &c); s *= 0.25f; c *= 0.25f;
            const int rf = ((s1 >> 3) * 4 + (k1 >> 2)) * 2 + ((s1 >> 2) & 1), ri = ((k1 >> 3) * 4 + (s1 >> 2)) * 2 + ((k1 >> 2) & 1);
            const uint32_t af = sm + OFF_B3 + ((rf >> 2) * 32 + (k1 & 3) * 8 + (s1 & 3)) * 16 + (rf & 3) * 4;
            const uint32_t ai = sm + OFF_B3 + 2048 + ((ri >> 2) * 32 + (s1 & 3) * 8 + (k1 & 3)) * 16 + (ri & 3) * 4;
            sts32(af, pack_h(c, s)); sts32(af + 64, pack_h(-s, c)); sts32(ai, pack_h(c, -s)); sts32(ai + 64, pack_h(s, c));
        }
        if (poller) {
            for (int it = 0; __any_sync(~0u, MOD_MISSING); it++) { if (MOD_MISSING) mv = ldx128(mp); hb(); if (it > SPIN_LIMIT) __trap(); }
            sts16(ma, mv.x >> 16); sts16(ma + 64, mv.y >> 16); sts16(ma + 128, mv.z >> 16); sts16(ma + 192, mv.w >> 16);
        }
        uint32_t redo = 0; asm volatile("" : "+r"(redo));
        #pragma unroll 1
        do { if (redo) {
            const uint32_t w[4] = {mv.x, mv.y, mv.z, mv.w}; float f[4]; uint32_t big = 0;
            #pragma unroll
            for (int e = 0; e < 4; e++) { f[e] = (w[e] & 0x8000u) ? bf_hi(w[e]) : __half2float(__ushort_as_half(w[e] >> 16)); big = max(big, __float_as_uint(f[e]) << 1 >> 24); }
            sts32(sm + OFF_HEXP + warp * 4, __reduce_max_sync(~0u, big));
            __syncthreads();
            hexp = min(__reduce_max_sync(~0u, lds32(sm + OFF_HEXP + (lane & 15) * 4)), 253u) - 127;
            const float sc = __uint_as_float((127 - hexp) << 23);
            if (poller) {
                #pragma unroll
                for (int e = 0; e < 4; e++) sts16(ma + 64 * e, pack_h(f[e] * sc, 0.f));
            }
            mv = make_uint4(0, 0, 0, 0);
          }
          redo = __syncthreads_or((mv.x | mv.y | mv.z | mv.w) & 0x8000u);
          asm volatile("" : "+r"(redo));
        } while (redo);
        PROF0(3);
        asm volatile("barrier.cluster.arrive.relaxed.aligned;" ::: "memory");
        if (warp >= 13 && elect()) {
            if (warp == 15) bulk_load(sm + OFF_TAB + QA * 512, p.tab->w + QA * 128, (QB + QC) * 512, bars + 8 * BAR_TAB2);
            else tma3(sm + OFF_WRAW + (warp - 13) * 14336, warp == 13 ? &tm_wr : &tm_wi, wc0 & ~7, 0, 0, bars + 8 * BAR_W);
        }
        __syncwarp();
        {
            uint32_t md[20];
            load_tab<5>(md, sm + OFF_MODA + lane * 16);
            #pragma unroll
            for (int v = 0; v < 2; v++)
                #pragma unroll
                for (int pp = 0; pp < 5; pp++) nb[v][pp] = hfma2(nb[v][pp], md[v * 5 + pp], md[10 + v * 5 + pp]);
        }
        uint32_t re[3][2], im[3][2];
        #pragma unroll
        for (int mt = 0; mt < 3; mt++)
            #pragma unroll
            for (int v = 0; v < 2; v++) {
                re[mt][v] = 0; im[mt][v] = 0;
                mma_h8(re[mt][v], im[mt][v], ta[24 + 2 * mt], ta[25 + 2 * mt], nb[v][4]);
                mma_h(re[mt][v], im[mt][v], ta[mt * 8], ta[mt * 8 + 1], ta[mt * 8 + 2], ta[mt * 8 + 3], nb[v][0], nb[v][1]);
                mma_h(re[mt][v], im[mt][v], ta[mt * 8 + 4], ta[mt * 8 + 5], ta[mt * 8 + 6], ta[mt * 8 + 7], nb[v][2], nb[v][3]);
                cmul_neg(re[mt][v], im[mt][v], ta[30 + (mt * 2 + v) * 2], ta[31 + (mt * 2 + v) * 2]);
            }
        const uint32_t srow = sm + OFF_SPEC + warp * (SPEC_P * 4);
        #pragma unroll
        for (int nt = 0; nt < 2; nt++) {
            uint32_t o[2][4];
            #pragma unroll
            for (int v = 0; v < 2; v++) {
                const uint32_t b0 = ta[42 + (v * 2 + nt) * 2], b1 = ta[43 + (v * 2 + nt) * 2];
                o[v][0] = o[v][1] = o[v][2] = o[v][3] = 0;
                mma_h(o[v][0], o[v][1], re[0][v], re[1][v], im[0][v], im[1][v], b0, b1);
                mma_h(o[v][2], o[v][3], re[2][0], re[2][1], im[2][0], im[2][1], b0, b1);
            }
            const uint32_t a = srow + (g + 72 * q + 36 * nt) * 4, a2 = srow + (288 - g - 72 * q - 36 * nt) * 4;
            sts32(a, hadd2(o[0][0], o[1][0])); sts32(a + 32, hadd2(o[0][1], o[1][1])); if (g < 3) sts32(a + 64, hadd2(o[0][2], o[1][3]));
            if (g > 0 || (q == 0 && nt == 0)) sts32(a2, hsub2(o[0][0], o[1][0]) ^ 0x80000000u);
            sts32(a2 - 32, hsub2(o[0][1], o[1][1]) ^ 0x80000000u); if (g < 2) sts32(a2 - 64, hsub2(o[0][2], o[1][3]) ^ 0x80000000u);
        }
        uint32_t b3[16];
        if (warp < 10) load_tab<4>(b3, sm + OFF_B3 + lane * 16);
        __syncthreads();
        t_st = clk32();
        PROF0(4);
        if (warp < 10) {
            uint4 V[4], o[4];
            #pragma unroll
            for (int u = 0; u < 4; u++) V[u] = lds128(scol + u * (16 * SPEC_P));
            radix16(V, b3, o);
            #pragma unroll
            for (int nt = 0; nt < 4; nt++) { o[nt].x |= 1u; if (warp < 9 || g < 2) stx128(tptr + nt * tstr, o[nt]); }
        }
        PROF0(5);
    }

    int role = 0;
    asm volatile("barrier.cluster.wait.aligned;" ::: "memory");
    if (warp >= 12) {
        const int t = tid - 384;
        if (tid == 448 && rank == 0) {
            uint32_t smid; asm volatile("mov.u32 %0, %%smid;" : "=r"(smid));
            const uint32_t tp = smid >> 1;
            uint32_t pr = tp < 32 ? (tp & 7) * 8 + (tp >> 3) : tp < 60 ? (1 + (tp - 32) % 7) * 8 + 4 + (tp - 32) / 7 : tp < 62 ? 4 + tp : tp < 66 ? tp - 58 : 0;
            while (atomicExch(g_slot + pr, epoch + 1) == epoch + 1) pr = pr == 65 ? 0 : pr + 1;
            #pragma unroll
            for (int r = 0; r < 2; r++)
                asm volatile("st.async.weak.shared::cluster.mbarrier::complete_tx::bytes.u32 [%0], %1, [%2];" :: "r"(mapa(sm + OFF_MISC, r)), "r"(pr), "r"(mapa(bars + 8 * BAR_ROLE, r)) : "memory");
        }
        __syncwarp();
        if (t == 0) {
            asm volatile("prefetch.tensormap [%0];" :: "l"(&tm_w1a) : "memory");
            asm volatile("prefetch.tensormap [%0];" :: "l"(&tm_h3a) : "memory"); asm volatile("prefetch.tensormap [%0];" :: "l"(&tm_w1b) : "memory");
            asm volatile("prefetch.tensormap [%0];" :: "l"(&tm_h3b) : "memory"); asm volatile("prefetch.tensormap [%0];" :: "l"(&tm_w2) : "memory");
            asm volatile("prefetch.tensormap [%0];" :: "l"(&tm_o) : "memory"); asm volatile("prefetch.tensormap [%0];" :: "l"(&tm_h3s) : "memory");
        }
        __syncwarp();
        if (rowcta) {
            spin_until(t0 + NCP);
            uint4 v[2];
            v[1] = make_uint4(1, 1, 1, 1);
            for (int it = 0;; it++) {
                v[0] = ldx128(p.scr->modc + 4 * t); if (t < 88) v[1] = ldx128(p.scr->modc + 512 + 4 * t);
                if (__all_sync(~0u, min(min(min(v[0].x, v[0].y), min(v[0].z, v[0].w)), min(min(v[1].x, v[1].y), min(v[1].z, v[1].w))) != 0)) break;
                __nanosleep(100); if (it > SPIN_LIMIT) __trap();
            }
            if (t < 72) { const uint32_t sc = ((127 + hexp) << 7) * 0x10001u;
                v[0] = make_uint4(bfma2(v[0].x, sc, 0x80008000u), bfma2(v[0].y, sc, 0x80008000u), bfma2(v[0].z, sc, 0x80008000u), bfma2(v[0].w, sc, 0x80008000u)); }
            #pragma unroll
            for (int u = 0; u < 2; u++) if (u == 0 || t < 88) {
                const uint32_t a = sm + OFF_MODC + (((t >> 5) + 4 * u) * 32 + 4 * (t & 7)) * 16 + ((t >> 3) & 3) * 4;
                sts32(a, v[u].x); sts32(a + 16, v[u].y); sts32(a + 32, v[u].z); sts32(a + 48, v[u].w);
            }
            __syncwarp();
            if (elect()) mbar_arrive(bars + 8 * BAR_NC);
            if (t == 0) PROFT(29);
        }
    } else if (rowcta && warp < 11) {
        const int nw = !(b & 1) ? 10 : (b & 7) == 7 ? 9 : 8;
        const int cm = (b >> 3) * 288 + (b & 7) * 32, cx = (b & 1) ? 4608 + 8 * (b >> 3) : (b >> 3) * 288 + 256 + 4 * (b & 7);
        auto load_in = [&]() {
            if (elect()) {
                mbar_expect(bars + 8 * BAR_XB, nw > 8 ? 20480 : 16384);
                tma2(sm + OFF_STAGE, &tm_t, cm, 0, bars + 8 * BAR_XB);
                if (nw > 8) tma2(sm + OFF_STX, &tm_tx, cx, 0, bars + 8 * BAR_XB);
            }
            __syncwarp();
        };
        if (warp == 10) { fence_async_s(); spin_until(t_st + X1D); load_in(); }
        uint32_t tb[QB * 4], wre[4][2], wim[4][2];
        if (warp < nw) {
            mbar_wait(bars + 8 * BAR_TAB2, 0);
            load_tab<QB>(tb, sm + OFF_TAB + QA * 512 + lane * 16);
            mbar_wait(bars + 8 * BAR_W, 0);
            const int off = wc0 & 7;
            const uint32_t wa = sm + OFF_WRAW + lane * 112 + ((off >> 1) + 2 * warp) * 4, sh = (off & 1) * 16;
            #pragma unroll
            for (int c = 0; c < 2; c++)
                #pragma unroll
                for (int h = 0; h < 2; h++) {
                    uint32_t y[2][2];
                    #pragma unroll
                    for (int e = 0; e < 2; e++) {
                        const uint32_t a = wa + c * 14336 + (h + 2 * e) * 3584, x0 = lds32(a), x1 = lds32(a + 4), x2 = lds32(a + 8);
                        y[e][0] = __funnelshift_r(x0, x1, sh); y[e][1] = __funnelshift_r(x1, x2, sh);
                    }
                    #pragma unroll
                    for (int x = 0; x < 4; x++) {
                        const uint32_t v = (x & 1) ? pack_h(bf_hi(y[0][x >> 1]), bf_hi(y[1][x >> 1])) : pack_h(bf_lo(y[0][x >> 1]), bf_lo(y[1][x >> 1]));
                        if (c) wim[x][h] = v; else wre[x][h] = v;
                    }
                }
        }
        const uint32_t ca = warp < 8 ? sm + OFF_STAGE + lane * 128 + (warp ^ (lane & 7)) * 16 : sm + OFF_STX + lane * 32 + ((warp ^ g) & 1) * 16, cs = warp < 8 ? 4096 : 1024;
        uint32_t V[4][4];
        for (int it = 0;; it++) {
            mbar_wait(bars + 8 * BAR_XB, it & 1);
            uint32_t ok = 1;
            if (warp < nw) {
                #pragma unroll
                for (int u = 0; u < 4; u++) { uint4 t4 = lds128(ca + u * cs); V[u][0] = t4.x; V[u][1] = t4.y; V[u][2] = t4.z; V[u][3] = t4.w; ok &= t4.x; }
            }
            asm volatile("{.reg .pred p; setp.ne.u32 p, %0, 0; bar.red.and.pred p, 1, 352, p; selp.u32 %0, 1, 0, p;}" : "+r"(ok) :: "memory");
            if (ok) break;
            if (warp == 10) { load_in(); hb(); }
            if (it > SPIN_LIMIT / 64) __trap();
        }
        PROF0(7);
        if (warp < nw) {
            uint32_t zr[4][2], zi[4][2];
            #pragma unroll
            for (int x = 0; x < 4; x++) {
                uint32_t er = 0, ei = 0, or_ = 0, oi = 0;
                mma_h(er, ei, tb[0], tb[1], tb[2], tb[3], V[0][x], V[1][x]);
                mma_h(or_, oi, tb[4], tb[5], tb[6], tb[7], V[2][x], V[3][x]);
                uint32_t r0 = hadd2(er, or_), r1 = hsub2(er, or_), i0 = hadd2(ei, oi), i1 = hsub2(ei, oi);
                cmul_neg(r0, i0, tb[8], tb[9]); cmul_neg(r1, i1, tb[10], tb[11]);
                uint32_t xr0 = 0, xr1 = 0, xi0 = 0, xi1 = 0;
                mma_h(xr0, xr1, r0, r1, i0, i1, tb[12], tb[13]);
                mma_h(xi0, xi1, r0, r1, i0, i1, tb[14], tb[15]);
                cmul_pos(xr0, xi0, wre[x][0], wim[x][0]); cmul_pos(xr1, xi1, wre[x][1], wim[x][1]);
                r0 = 0; i0 = 0; r1 = 0; i1 = 0;
                mma_h(r0, i0, tb[12], tb[13], tb[14], tb[15], xr0, xi0);
                mma_h(r1, i1, tb[12], tb[13], tb[14], tb[15], xr1, xi1);
                cmul_pos(r0, i0, tb[16], tb[17]); cmul_pos(r1, i1, tb[18], tb[19]);
                zr[x][0] = hadd2(r0, r1); zr[x][1] = hsub2(r0, r1); zi[x][0] = hadd2(i0, i1); zi[x][1] = hsub2(i0, i1);
            }
            #pragma unroll
            for (int nt = 0; nt < 4; nt++) {
                uint4 o = make_uint4(0, 0, 0, 0);
                const int h = nt >> 1;
                mma_h(o.x, o.y, zr[0][h], zr[1][h], zi[0][h], zi[1][h], tb[20 + 2 * nt], tb[21 + 2 * nt]);
                mma_h(o.z, o.w, zr[2][h], zr[3][h], zi[2][h], zi[3][h], tb[20 + 2 * nt], tb[21 + 2 * nt]);
                o.x &= ~1u;
                sts128(ca + nt * cs, o);
            }
        }
        fence_async_s();
        bar_sync(1, 352);
        t_st = clk32();
        PROF0(8);
        if (warp == 10 && elect()) {
            asm volatile("cp.async.bulk.tensor.2d.global.shared::cta.bulk_group [%0, {%2, %3}], [%1];" :: "l"(&tm_t), "r"(sm + OFF_STAGE), "r"(cm), "r"(0) : "memory");
            if (nw > 8) asm volatile("cp.async.bulk.tensor.2d.global.shared::cta.bulk_group [%0, {%2, %3}], [%1];" :: "l"(&tm_tx), "r"(sm + OFF_STX), "r"(cx), "r"(0) : "memory");
            asm volatile("cp.async.bulk.commit_group;" ::: "memory");
            asm volatile("cp.async.bulk.wait_group.read 0;" ::: "memory");
        }
        __syncwarp();
    }

    if (warp >= 10) { mbar_wait(bars + 8 * BAR_ROLE, 0); role = __shfl_sync(~0u, lds32(sm + OFF_MISC), 0); fence_async_s(); }
    auto first_a = [&]() {
        if (warp >= 10 && role < 64 && elect()) {
            const int it = warp - 10, hi = it >= 3; const bool p2 = it - 3 * hi == 2;
            tma4(sm + OFF_A + it * A_BYTES, p2 ? &tm_w1b : &tm_w1a, 0, 0, p2 ? 64 * rank + 8 * hi : 4 * (it - hi),
                 9 * (role >> 3) + (p2 ? 8 : (role & 4) + 2 * rank), bars + 8 * (BAR_FULL + it));
        }
        __syncwarp();
    };
    if (!rowcta) first_a();
    else {
        uint32_t tc[20], md[28];
        mbar_wait(bars + 8 * BAR_TAB2, 0);
        load_tab<5>(tc, sm + OFF_TAB + (QA + QB) * 512 + lane * 16);
        bool md_early = warp >= 10;
        if (md_early) { mbar_wait(bars + 8 * BAR_NC, 0); load_tab<7>(md, sm + OFF_MODC + lane * 16); }
        if (warp < 10) {
            uint32_t b3[16];
            load_tab<4>(b3, sm + OFF_B3 + 2048 + lane * 16);
            uint4 V[4], o[4];
            const bool tact = warp < 9 || g == 0;
            spin_until(t_st + X2D);
            #pragma unroll
            for (int u = 0; u < 4; u++) { V[u] = make_uint4(0, 0, 0, 0); if (tact) V[u] = ldx128(tptr + u * tstr); }
            md_early = __any_sync(~0u, mbar_test(bars + 8 * BAR_NC, 0));
            if (md_early) load_tab<7>(md, sm + OFF_MODC + lane * 16);
            for (int it = 0; __any_sync(~0u, (V[0].x | V[1].x | V[2].x | V[3].x) & 1u); it++) {
                #pragma unroll
                for (int u = 0; u < 4; u++) if (V[u].x & 1u) V[u] = ldx128(tptr + u * tstr);
                hb();
                if (it > SPIN_LIMIT) __trap();
            }
            PROF0(10);
            radix16(V, b3, o);
            if (tact) {
                #pragma unroll
                for (int nt = 0; nt < 4; nt++) sts128(scol + nt * (16 * SPEC_P), o[nt]);
            }
        }
        __syncthreads();
        PROF0(11);
        first_a();
        const uint32_t srow = sm + OFF_SPEC + warp * (SPEC_P * 4);
        uint32_t re[2][3], im[2][3];
        #pragma unroll
        for (int mt = 0; mt < 3; mt++) {
            const uint32_t a = srow + (g + 72 * q + 8 * mt) * 4, a2 = srow + (288 - g - 72 * q - 8 * mt) * 4;
            const uint32_t z0 = lds32(a), z1 = lds32(a + 144), z2 = lds32(a2), z3 = lds32(a2 - 144);
            #pragma unroll
            for (int m2 = 0; m2 < 2; m2++) {
                re[m2][mt] = 0; im[m2][mt] = 0;
                const uint32_t sg = m2 ? 0x3C00BC00u : 0xBC003C00u;
                mma_h(re[m2][mt], im[m2][mt], tc[m2 * 4], tc[m2 * 4 + 1], tc[m2 * 4 + 2], tc[m2 * 4 + 3], hfma2(z2, sg, z0), hfma2(z3, sg, z1));
                cmul_pos(re[m2][mt], im[m2][mt], tc[8 + (m2 * 3 + mt) * 2], tc[9 + (m2 * 3 + mt) * 2]);
            }
        }
        float y[20];
        WG_FENCE();
        #pragma unroll
        for (int mt = 0; mt < 3; mt++)
            wgmma40_rs(y, re[0][mt], re[1][mt], im[0][mt], im[1][mt], desc_lo(OFF_TAB + (QA + QB + 5) * 512 + mt * 1280, 128), mt);
        WG_COMMIT();
        if (!md_early) { mbar_wait(bars + 8 * BAR_NC, 0); load_tab<7>(md, sm + OFF_MODC + lane * 16); }
        WG_WAIT(0);
        #pragma unroll
        for (int i = 0; i < 9; i++) xw[i] = bfma2(md[i], pack_bf(y[4 * (i >> 1) + (i & 1)], y[4 * (i >> 1) + 2 + (i & 1)]), xw[i]);
        float r, mr;
        ln_stats(xw, one, g, q, r, mr);
        uint32_t r2 = pack_bf(r, r), m2 = pack_bf(mr, mr);
        #pragma unroll
        for (int i = 0; i < 9; i++) {
            sts32(sm + OFF_X1 + warp * 1152 + (32 * i + 8 * q + g) * 4, xw[i]);
            xw[i] = bfma2(bfma2(xw[i], r2, m2), md[18 + i], md[9 + i]);
        }
        ln_stats(xw, one, g, q, r, mr);
        r2 = pack_bf(r, r); m2 = pack_bf(mr, mr);
        {
            const int n7 = 2 * q + (g >> 2);
            const uint32_t a = sm + OFF_STAGE + (warp >> 3) * 9216 + n7 * 128 + ((warp & 7) ^ n7) * 16 + (g & 3) * 4;
            #pragma unroll
            for (int i = 0; i < 9; i++) sts32(a + i * 1024, bfma2(xw[i], r2, m2));
        }
        fence_async_s();
        __syncthreads();
        PROF0(12);
        if (tid == 0) {
            asm volatile("cp.async.bulk.tensor.4d.global.shared::cta.bulk_group [%0, {%2, %2, %2, %3}], [%1];" :: "l"(&tm_h3s), "r"(sm + OFF_STAGE), "r"(0), "r"(b) : "memory");
            asm volatile("cp.async.bulk.commit_group;" ::: "memory");
        }
    }
    if (!rowcta) __syncthreads();
    else {
        if (tid == 0) { asm volatile("cp.async.bulk.wait_group 0;" ::: "memory"); fence_async_g(); red_release(g_cnt + CNT_H3 * 32); }
        PROF0(13);
        if (warp == 15) {
            __nanosleep(X1DELAY);
            #pragma unroll 1
            for (int r = 0; r < 16; r++) {
                uint4* dst = (uint4*)(p.out + (size_t)(b + 128 * r) * D_) + lane;
                const uint32_t src = sm + OFF_X1 + r * 1152 + lane * 16;
                dst[0] = lds128(src); dst[32] = lds128(src + 512); if (lane < 8) dst[64] = lds128(src + 1024);
                const uint32_t t1 = clk32(); while ((int)(clk32() - t1) < X1PACE) __nanosleep(50);
            }
            __syncwarp();
            if (lane == 0) { fence_async_g(); red_release(g_cnt + CNT_X1 * 32); }
        }
    }
    role = __shfl_sync(~0u, lds32(sm + OFF_MISC), 0);
    if ((sm & 0xFFFFFFu) != SM0) __trap();
    if (role >= 64) { if (warp == 0) PROFDUMP(); return; }

    const int gi = role >> 3, dt = role & 3, c2 = (role >> 2) & 1;
    const int wg = warp >> 2, wi = warp & 3;
    if (wg == 3) {
        uint32_t so = 0, eph = 1;
        #define RING_STEP(BYTES, OFF, ISSUE) do { \
            mbar_wait(bars + 8 * BAR_EMPTY + so, eph); \
            if (elect()) { const uint32_t fb = bars + 8 * BAR_FULL + so, dst = sm + (OFF) + so * ((BYTES) / 8); mbar_expect(fb, BYTES); ISSUE; } \
            so += 8; if (so == 8 * NST) { so = 0; eph ^= 1; } } while (0)
        const uint32_t kbt = g2_kb(lane, rank, gi, c2) | (g2_kb(32 + (lane & 3), rank, gi, c2) << 8);
        #define KB(n_) ((__shfl_sync(~0u, kbt, (n_) & 31) >> (((n_) >> 2) & 8)) & 255)
        if (warp == 12) {
            eph = 0;
            const int fb1 = 9 * gi + 4 * c2 + 2 * rank, sb2 = 4 * gi + 2 * c2;
            int pft = dt, pfj = 4 * (PF0 + PFS * dt);
            #pragma unroll 1
            for (int j = 16; j < 128; j += 4) {
                RING_STEP(A_BYTES, OFF_A, tma4(dst, &tm_w1a, 0, 0, j, fb1, fb));
                if (j < 64) { if (j & 4) RING_STEP(A_BYTES, OFF_A, tma4(dst, &tm_w1b, 0, 0, 64 * rank + j - 4, 9 * gi + 8, fb)); }
                if (j == pfj && pft < PFN) {
                    const int kb = KB(pft); pft += 4; pfj += 16 * PFS;
                    if (elect()) asm volatile("cp.async.bulk.prefetch.tensor.3d.L2.global [%0, {%1, %2, %3}];" :: "l"(&tm_w2), "r"(0), "r"(64 * kb), "r"(sb2) : "memory");
                }
            }
            #pragma unroll 1
            for (int n = 0; n < 36; n++) {
                const int kb = KB(n);
                RING_STEP(A_BYTES, OFF_A, tma3(dst, &tm_w2, 0, 64 * kb, sb2, fb));
            }
        } else if (warp == 13) {
            const uint32_t e1 = __shfl_sync(~0u, epoch + 1, 0);
            fence_async_s();
            wait_count<0>(g_cnt + CNT_H3 * 32, e1 * 128);
            fence_async_g();
            if (lane == 0) PROFT(14);
            #pragma unroll 1
            for (int j = 0; j < 128; j += 4) {
                RING_STEP(B_BYTES, OFF_B, tma3(dst, &tm_h3a, 0, 18 * dt, j, fb));
                if (j < 64 && (j & 4)) RING_STEP(B_BYTES, OFF_B, tma3(dst, &tm_h3b, 0, 18 * dt + 9 * c2, 64 * rank + j - 4, fb));
            }
            int n = 0;
            #pragma unroll 1
            for (int cls = 0; cls < 3; cls++) {
                mbar_wait(bars + 8 * (BAR_UOK + cls), 0);
                fence_async_g();
                if (cls == 1 && lane == 0) PROFT(19);
                if (cls == 0 && lane == 0) PROFT(22);
                static_assert((IT_G2 + 4) % NST != NST - 1, "no wrap at the skipped stage");
                if (cls == 1) { n++; so += 8; }
                #pragma unroll 1
                for (; n < (cls == 0 ? 4 : cls == 1 ? 21 : 36); n++) {
                    const int kb = KB(n);
                    RING_STEP(B_BYTES, OFF_B, bulk_load(dst, g_U + (kb * 4 + dt) * 1152, B_BYTES, fb));
                }
            }
            if (role == 0 && rank == 0 && lane == 0) st_relaxed(g_cnt + CNT_EPOCH * 32, e1);
        } else if (warp == 15) {
            if (elect()) mbar_arrive_remote(mapa(bars + 8 * BAR_HOLD, rank ^ 1));
            __syncwarp();
            bar_sync(6, 160);
            if (elect()) mbar_arrive(bars + 8 * (BAR_FULL + (IT_G2 + 4) % NST));
            __syncwarp();
            mbar_wait(bars + 8 * BAR_W1GO, 0);
            if (elect()) {
                char* dst = (char*)(g_U + ((9 * gi + 4 * c2 + 2 * rank + 1) * 4 + dt) * 1152);
                #pragma unroll 1
                for (int i = 0; i < W1N; i++) {
                    asm volatile("cp.async.bulk.global.shared::cta.bulk_group [%0], [%1], %2;" :: "l"(dst + i * (18432 / W1N)), "r"(sm + OFF_X1 + i * (18432 / W1N)), "n"(18432 / W1N) : "memory");
                    const uint32_t t1 = clk32(); while ((int)(clk32() - t1) < W1P) {}
                }
                asm volatile("cp.async.bulk.commit_group;" ::: "memory");
                asm volatile("cp.async.bulk.wait_group 0;" ::: "memory");
                fence_async_g(); red_release(g_cnt + (CNT_U + 16) * 32);
                #pragma unroll 1
                for (int n = 0; n < 4; n++) { __nanosleep(300); tma2(sm + OFF_X1 + n * 4608, &tm_o, 144 * dt, 256 * gi + 128 * c2 + 64 * (rank ^ 1) + 16 * n, bars + 8 * BAR_XT); }
            }
        } else {
            const uint32_t e1 = epoch + 1;
            if (lane == 0) {
                __nanosleep(4000);
                wait_count<200>(g_cnt + CNT_NC * 32, e1 * 4); wait_count<200>(g_cnt + (CNT_NC + 1) * 32, e1 * 2);
                fence_async_g();
                mbar_expect(bars + 8 * BAR_GB, 1152);
                bulk_load(sm + OFF_GB, p.scr->modc + 896, 1152, bars + 8 * BAR_GB);
                wait_count<200>(g_cnt + CNT_X1 * 32, e1 * 128);
                if (role * 2 + rank < 108) {
                    uint4* z = (uint4*)p.scr->modc + (role * 2 + rank) * 2; z[0] = z[1] = make_uint4(0, 0, 0, 0);
                }
                wait_count<50>(g_cnt + (CNT_U + dt * 2 + rank) * 32, e1 * 16);
                mbar_arrive(bars + 8 * BAR_UOK);
            }
            __syncwarp();
            bar_sync(4, 160);
            if (lane == 0) {
                fence_async_g(); red_release(g_cnt + (CNT_U + 8) * 32);
                PROFT(17);
                wait_count<0>(g_cnt + (CNT_U + 8) * 32, e1 * 128);
                mbar_arrive(bars + 8 * (BAR_UOK + 1));
                __nanosleep(1000);
                wait_count<100>(g_cnt + (CNT_U + 16) * 32, e1 * 128);
                mbar_arrive(bars + 8 * (BAR_UOK + 2));
            }
        }
    } else if (wg == 2) {
        float d0[36];
        const float bias = bf_lo(ldg_nc16(p.b1 + 576 * gi + 512 + 16 * wi + g + 8 * rank));
        for (int it = 0; it < 200 && !__any_sync(~0u, mbar_test(bars + 8 * BAR_FULL, 0)); it++) { hb(); __nanosleep(100); }
        const bool lead = wi == 0 && elect();
        #pragma unroll 1
        for (int i = 0; i < 8; i++) {
            const uint32_t s = P2S + 3 * (i & 1);
            mbar_wait(bars + 8 * BAR_FULL + 8 * s, (i >> 1) & 1);
            const uint32_t da = desc_lo(OFF_A, 8192) + s * (A_BYTES / 16), db = desc_lo(OFF_B, 128) + s * (B_BYTES / 16);
            WG_FENCE();
            wgmma72(d0, da, db, i);
            #pragma unroll
            for (int k = 1; k < 9; k++) {
                if (k == P2K) asm volatile("{.reg .pred p; setp.ne.u32 p, %1, 0; @p mbarrier.arrive.shared::cta.b64 _, [%0];}" :: "r"(bars + 8 * (BAR_P2N + (i & 1))), "r"((uint32_t)lead) : "memory");
                if (k < 8) wgmma72(d0, da + k * 128, db + k * 144, 1);
            }
            WG_COMMIT();
            WG_WAIT(0);
            if (lead) mbar_arrive_n(bars + 8 * BAR_EMPTY + 8 * s, 2);
        }
        if (lead) PROFT(18);
        const uint32_t slot = sm + OFF_P2R + (tid & 127) * 16, ra = mapa(slot, rank ^ 1), rb = mapa(bars + 8 * BAR_P2R, rank ^ 1);
        float sv[18];
        #pragma unroll
        for (int i = 0; i < 18; i++) { const float lo = d0[4 * (i >> 1) + (i & 1)], hi = d0[4 * (i >> 1) + 2 + (i & 1)];
            sv[i] = rank ? lo : hi; d0[4 * (i >> 1) + (i & 1)] = (rank ? hi : lo) + bias; }
        mbar_wait(bars + 8 * BAR_HOLD, 0);
        #pragma unroll
        for (int i = 0; i < 4; i++)
            asm volatile("st.async.weak.shared::cluster.mbarrier::complete_tx::bytes.v4.f32 [%0], {%1,%2,%3,%4}, [%5];"
                :: "r"(ra + i * 2048), "f"(sv[4 * i]), "f"(sv[4 * i + 1]), "f"(sv[4 * i + 2]), "f"(sv[4 * i + 3]), "r"(rb) : "memory");
        asm volatile("st.async.weak.shared::cluster.mbarrier::complete_tx::bytes.v2.f32 [%0], {%1,%2}, [%3];" :: "r"(ra + 8192), "f"(sv[16]), "f"(sv[17]), "r"(rb) : "memory");
        mbar_wait(bars + 8 * BAR_P2R, 0);
        #pragma unroll
        for (int i = 0; i < 5; i++) {
            const uint4 v = lds128(slot + i * 2048);
            d0[8 * i] += __uint_as_float(v.x); d0[8 * i + 1] += __uint_as_float(v.y);
            if (i < 4) { d0[8 * i + 4] += __uint_as_float(v.z); d0[8 * i + 5] += __uint_as_float(v.w); }
        }
        asm volatile("bar.arrive 5, 256;" ::: "memory");
        gelu_store<0>(d0, (char*)(g_U + ((9 * gi + 8) * 4 + dt) * 1152) + wi * 4608 + rank * 2304 + c2 * 1152 + g * 16, q);
        bar_sync(8, 128);
        if (lead) { fence_async_g(); red_release(g_cnt + (CNT_U + dt * 2 + (gi >> 2)) * 32); PROFT(26); }
    } else {
        float d[72];
        const bool lead = wi == 0 && elect();
        const uint32_t da0 = desc_lo(OFF_A, 8192) + wg * 512;
        const bool owner = (uint32_t)wg == rank;
        const int srow = 256 * gi + 128 * c2 + 64 * wg + 16 * wi;
        const uint32_t b2w0 = ldg_nc16(p.b2 + srow + g), b2w1 = ldg_nc16(p.b2 + srow + g + 8);
        const int fr = 576 * gi + 256 * c2 + 128 * rank + 64 * wg + 16 * wi + g;
        const float bias0 = bf_lo(ldg_nc16(p.b1 + fr)), bias1 = bf_lo(ldg_nc16(p.b1 + fr + 8));
        {
            #pragma unroll
            for (int i = 0; i < 72; i++) d[i] = (i & 2) ? bias1 : bias0;
            constexpr uint32_t db1 = desc_lo(OFF_B, 128);
            static_assert(IT_G2 - LEAD1 == 6 * NST && IT_P1 == 4 * NST && P2S == 2, "loop structure");
            #define REL(s_) if (lead) mbar_arrive(bars + 8 * (BAR_EMPTY + (s_)))
            mma_block<DHI_H3, 0>(d, bars, da0, db1, 0);
            #pragma unroll 1
            for (int c = 0; c < 4; c++) {
                const uint32_t ph = c & 1;
                mma_block<DHI_H3, 1>(d, bars, da0, db1, ph); REL(0);
                mbar_wait(bars + 8 * (P2K ? BAR_P2N : BAR_FULL + 2), ph);
                mma_block<DHI_H3, 3>(d, bars, da0, db1, ph); REL(1);
                mma_block<DHI_H3, 4>(d, bars, da0, db1, ph); REL(3);
                mbar_wait(bars + 8 * (P2K ? BAR_P2N + 1 : BAR_FULL + 5), ph);
                mma_block<DHI_H3, 0>(d, bars, da0, db1, ph ^ 1); REL(4);
            }
            #pragma unroll 1
            for (uint32_t ph = 0; ph < 2; ph++) {
                mma_block<DHI_H3, 1>(d, bars, da0, db1, ph); REL(0);
                mma_block<DHI_H3, 2>(d, bars, da0, db1, ph); REL(1);
                mma_block<DHI_H3, 3>(d, bars, da0, db1, ph); REL(2);
                mma_block<DHI_H3, 4>(d, bars, da0, db1, ph); REL(3);
                mma_block<DHI_H3, 5>(d, bars, da0, db1, ph); REL(4);
                const bool pause = ph && wg == 1;
                if (pause) { WG_WAIT(0); REL(5); bar_sync(9, 256); }
                mma_block<DHI_H3, 0>(d, bars, da0, db1, ph ^ 1); if (!pause) REL(5);
            }
            #pragma unroll
            for (int i = IT_G2 - LEAD1 + 1; i < IT_G2; i++) {
                mbar_wait(bars + 8 * (BAR_FULL + i % NST), (i / NST) & 1);
                WG_FENCE();
                #pragma unroll
                for (int k = 0; k < 4; k++) {
                    if (i == IT_G2 - 1 && k == HOK1) WG_COMMIT();
                    wgmma144<DHI_H3>(d, da0 + (i % NST) * (A_BYTES / 16) + k * 128, db1 + (i % NST) * (B_BYTES / 16) + k * 288, 1);
                }
                WG_COMMIT();
                if (i == IT_G2 - 1 && HOK1 < 4) WG_WAIT(2); else WG_WAIT(1);
                REL((i - 1) % NST);
            }
            if (wg == 0) { WG_WAIT(1); asm volatile("bar.arrive 9, 256;" ::: "memory"); }
            WG_WAIT(0);
            if (lead) mbar_arrive(bars + 8 * (BAR_EMPTY + (IT_G2 - 1) % NST));
            PROF0(16);
            if (wg == 1) bar_sync(5, 256);
            char* const ub = (wg == 0 ? (char*)(g_U + ((9 * gi + 4 * c2 + 2 * rank) * 4 + dt) * 1152) : (char*)__cvta_shared_to_generic(sm + OFF_X1)) + wi * 4608 + g * 16;
            gelu_store<0>(d, ub, q); gelu_store<2>(d, ub + 2304, q); gelu_store<36>(d, ub + 1152, q); gelu_store<38>(d, ub + 3456, q);
            PROF0(27);
            if (wg == 0) asm volatile("bar.arrive 4, 160;" ::: "memory");
            else { fence_async_s(); asm volatile("bar.arrive 6, 160;" ::: "memory"); }
        }
        constexpr uint32_t db0 = desc_lo(OFF_B, 2304);
        const bool keep = role < 0;
        constexpr int IT_L = IT_END - NST;
        #pragma unroll
        for (int i = IT_G2; i <= IT_G2 + W1S; i++) {
            const uint32_t db = db0 + (i == IT_G2 + 4 ? OFF_X1 - OFF_B : (i % NST) * B_BYTES) / 16;
            mbar_wait(bars + 8 * (BAR_FULL + i % NST), (i / NST) & 1);
            WG_FENCE();
            #pragma unroll
            for (int k = 0; k < 4; k++) wgmma144<DHI_U>(d, da0 + (i % NST) * (A_BYTES / 16) + k * 128, db + k * 288, i > IT_G2 || k > 0 || keep);
            WG_COMMIT();
            if (i > IT_G2) { WG_WAIT(1); if (lead) mbar_arrive(bars + 8 * (BAR_EMPTY + (i - 1) % NST)); }
        }
        if (lead) mbar_arrive(bars + 8 * BAR_W1GO);
        const uint32_t ga0 = sm + OFF_GB + (144 * dt + 8 * q) * 2, tile = sm + OFF_X1 + wi * 4608, to = g * 288 + q * 16;
        #define QOFF(i_) (((i_) >> 2) * 2304 + 144 * (((i_) >> 1) & 1) + 64 * ((i_) & 1))
        #define SOFF(k_) (((k_) >> 1) * 2304 + 144 * ((k_) & 1) + 128 - 12 * q)
        #define DIDX(i_, k_) ((i_) < 8 ? 36 * (((i_) >> 1) & 1) + 16 * ((i_) & 1) + 4 * (k_) + 2 * ((i_) >> 2) : 36 * ((k_) & 1) + 32 + 2 * ((k_) >> 1))
        #define FIN(k_, f_) bfma2(g4.f_, pack_bf(d[DIDX(i, k_)], d[DIDX(i, k_) + 1]), xq[i].f_)
        uint4 xq[9];
        auto load_g = [&](int i) { uint4 r; if (i < 4) r = lds128(ga0 + QOFF(i)); else { r.x = r.z = lds32(ga0 + SOFF(0)); r.y = r.w = lds32(ga0 + SOFF(1)); } return r; };
        static_assert(W1S == 5 && (IT_G2 + 6) % NST == 4 && ((IT_G2 + 6) / NST) % 2 == 1 && IT_L == IT_G2 + 30, "loop structure");
        #pragma unroll 1
        for (int c = 0; c < 4; c++) {
            const uint32_t ph = c & 1, xa = tile + to; const bool xl = c == 3 && !owner;
            mma_block<DHI_U, 4>(d, bars, da0, db0, ph ^ 1); REL(3);
            mma_block<DHI_U, 5>(d, bars, da0, db0, ph ^ 1); REL(4);
            mma_block<DHI_U, 0>(d, bars, da0, db0, ph); REL(5);
            if (xl) { mbar_wait(bars + 8 * BAR_XT, 0); xq[0] = lds128(xa + QOFF(0)); xq[4] = lds128(xa + QOFF(4)); xq[1] = lds128(xa + QOFF(1)); }
            mma_block<DHI_U, 1>(d, bars, da0, db0, ph); REL(0);
            if (xl) { xq[5] = lds128(xa + QOFF(5)); xq[2] = lds128(xa + QOFF(2)); xq[6] = lds128(xa + QOFF(6)); }
            mma_block<DHI_U, 2>(d, bars, da0, db0, ph); REL(1);
            if (xl) { xq[3] = lds128(xa + QOFF(3)); xq[7] = lds128(xa + QOFF(7));
                      xq[8] = make_uint4(lds32(xa + SOFF(0)), lds32(xa + SOFF(1)), lds32(xa + SOFF(2)), lds32(xa + SOFF(3))); }
            mma_block<DHI_U, 3>(d, bars, da0, db0, ph); REL(2);
        }
        if (!owner && elect()) mbar_arrive_remote(mapa(bars + 8 * BAR_DONE, rank ^ 1));
        if (owner) { WG_WAIT(0); if (lead) mbar_arrive(bars + 8 * (BAR_EMPTY + (IT_L - 1) % NST)); bar_sync(7, 256); }
        #pragma unroll
        for (int i = IT_L; i < IT_END; i++) {
            mbar_wait(bars + 8 * (BAR_FULL + i % NST), (i / NST) & 1);
            WG_FENCE();
            #pragma unroll
            for (int k = 0; k < 4; k++) {
                if (i == IT_END - 1 && k == HOK) WG_COMMIT();
                wgmma144<DHI_U>(d, da0 + (i % NST) * (A_BYTES / 16) + k * 128, db0 + (i % NST) * (B_BYTES / 16) + k * 288, 1);
            }
            WG_COMMIT();
            if (i == IT_L) { WG_WAIT(1); if (lead && !owner) mbar_arrive(bars + 8 * (BAR_EMPTY + (IT_L - 1) % NST)); }
        }
        PROF0(9);
        mbar_wait(bars + 8 * BAR_GB, 0);
        if (!owner) {
            const uint32_t ra = mapa(tile + lane * 16, rank ^ 1), rb = mapa(bars + 8 * BAR_RECV, rank ^ 1);
            mbar_wait(bars + 8 * BAR_DONE, 0);
            uint4 gn = load_g(0);
            WG_WAIT(1);
            asm volatile("bar.arrive 7, 256;" ::: "memory");
            WG_WAIT(0);
            #pragma unroll
            for (int i = 0; i < 72; i++) d[i] = fmaf(bf_lo((i & 2) ? b2w1 : b2w0), 2.f, d[i]);
            #pragma unroll
            for (int j = 0; j < 5; j++) {
                const uint4 g4 = gn;
                if (j < 4) gn = load_g(j + 1);
                #pragma unroll
                for (int i = j < 4 ? j : 8; i < 9; i += 4) if (i < 8 || j == 4)
                    asm volatile("st.async.weak.shared::cluster.mbarrier::complete_tx::bytes.v4.b32 [%0], {%1,%2,%3,%4}, [%5];"
                        :: "r"(ra + i * 512), "r"(FIN(0, x)), "r"(FIN(1, y)), "r"(FIN(2, z)), "r"(FIN(3, w)), "r"(rb) : "memory");
            }
            PROF0(6);
            if (warp == 0) PROFDUMP();
            return;
        }
        PROF0(24);
        mbar_wait(bars + 8 * BAR_RECV, 0);
        #pragma unroll
        for (int i = 0; i < 9; i++) xq[i] = lds128(tile + lane * 16 + i * 512);
        uint4 gn = load_g(0);
        WG_WAIT(0);
        __syncwarp();
        PROF0(21);
        #pragma unroll
        for (int j = 0; j < 5; j++) {
            const uint4 g4 = gn;
            if (j < 4) gn = load_g(j + 1);
            #pragma unroll
            for (int i = j < 4 ? j : 8; i < 9; i += 4) if (i < 8 || j == 4) {
                const uint4 o = make_uint4(FIN(0, x), FIN(1, y), FIN(2, z), FIN(3, w));
                if (i < 8) sts128(tile + to + QOFF(i), o);
                else { sts32(tile + to + SOFF(0), o.x); sts32(tile + to + SOFF(1), o.y); sts32(tile + to + SOFF(2), o.z); sts32(tile + to + SOFF(3), o.w); }
            }
        }
        fence_async_s();
        __syncwarp();
        if (elect()) {
            asm volatile("cp.async.bulk.tensor.2d.global.shared::cta.bulk_group [%0, {%2, %3}], [%1];" :: "l"(&tm_o), "r"(tile), "r"(144 * dt), "r"(srow) : "memory");
            asm volatile("cp.async.bulk.commit_group;" ::: "memory");
            asm volatile("cp.async.bulk.wait_group.read 0;" ::: "memory");
        }
        PROF0(23);
        if (warp == 0) { __syncwarp(); PROFDUMP(); }
    }
}

typedef CUresult (*EncodeFn)(CUtensorMap*, CUtensorMapDataType, cuuint32_t, void*, const cuuint64_t*, const cuuint64_t*, const cuuint32_t*,
                             const cuuint32_t*, CUtensorMapInterleave, CUtensorMapSwizzle, CUtensorMapL2promotion, CUtensorMapFloatOOBfill);

void encode(EncodeFn fn, CUtensorMap* m, CUtensorMapDataType dt, int rank, const void* ptr, const cuuint64_t* dims, const cuuint64_t* strides,
            const cuuint32_t* box, CUtensorMapSwizzle sw, CUtensorMapL2promotion promo = CU_TENSOR_MAP_L2_PROMOTION_L2_128B) {
    const cuuint32_t es[5] = {1, 1, 1, 1, 1};
    fn(m, dt, rank, (void*)ptr, dims, strides, box, es, CU_TENSOR_MAP_INTERLEAVE_NONE, sw, promo, CU_TENSOR_MAP_FLOAT_OOB_FILL_NONE);
}

}

extern "C" void kernel_launch(void* const* d_in, const int* in_sizes, int n_in, void* d_out, int out_size) {
    (void)in_sizes; (void)n_in; (void)out_size;
    Params p;
    p.x = (const uint16_t*)d_in[0]; p.wr = (const uint16_t*)d_in[1]; p.wi = (const uint16_t*)d_in[2];
    p.w1 = (const uint16_t*)d_in[4]; p.b1 = (const uint16_t*)d_in[5]; p.w2 = (const uint16_t*)d_in[6]; p.b2 = (const uint16_t*)d_in[7];
    p.c = (const uint16_t*)d_in[8]; p.wmod = (const uint16_t*)d_in[9]; p.out = (uint16_t*)d_out;

    void* fnp = nullptr; cudaDriverEntryPointQueryResult qr;
    cudaGetDriverEntryPoint("cuTensorMapEncodeTiled", &fnp, cudaEnableDefault, &qr);
    EncodeFn fn = (EncodeFn)fnp;
    cudaGetSymbolAddress((void**)&p.scr, g_scr); cudaGetSymbolAddress((void**)&p.tab, g_tab);
    void* h3p = p.scr->h3;
    CUtensorMap tw1a, tw1b, tw2, th3a, th3b, twr, twi, twm, tt, ttx, to, th3s, tws;
    {
        const cuuint64_t dims[4] = {64, 16, 128, 72}, st[3] = {128ull * F_ * 2, (cuuint64_t)F_ * 2, 128};
        const cuuint32_t ba[4] = {64, 16, 4, 2}, bb[4] = {64, 16, 8, 1};
        encode(fn, &tw1a, CU_TENSOR_MAP_DATA_TYPE_BFLOAT16, 4, p.w1, dims, st, ba, CU_TENSOR_MAP_SWIZZLE_128B);
        encode(fn, &tw1b, CU_TENSOR_MAP_DATA_TYPE_BFLOAT16, 4, p.w1, dims, st, bb, CU_TENSOR_MAP_SWIZZLE_128B);
    }
    {
        const cuuint64_t dims[3] = {64, F_, 32}, st[2] = {(cuuint64_t)S_ * 2, 128};
        const cuuint32_t bx[3] = {64, 64, 2};
        encode(fn, &tw2, CU_TENSOR_MAP_DATA_TYPE_BFLOAT16, 3, p.w2, dims, st, bx, CU_TENSOR_MAP_SWIZZLE_128B);
    }
    {
        const cuuint64_t dims[3] = {64, 72, 128}, st[2] = {256, 18432};
        const cuuint32_t ba[3] = {64, 18, 4}, bb[3] = {64, 9, 8};
        encode(fn, &th3a, CU_TENSOR_MAP_DATA_TYPE_UINT32, 3, h3p, dims, st, ba, CU_TENSOR_MAP_SWIZZLE_NONE);
        encode(fn, &th3b, CU_TENSOR_MAP_DATA_TYPE_UINT32, 3, h3p, dims, st, bb, CU_TENSOR_MAP_SWIZZLE_NONE);
    }
    {
        const cuuint64_t dims[4] = {32, 72, 2, 128}, st[3] = {256, 128, 18432};
        const cuuint32_t bx[4] = {32, 72, 2, 1};
        encode(fn, &th3s, CU_TENSOR_MAP_DATA_TYPE_UINT32, 4, h3p, dims, st, bx, CU_TENSOR_MAP_SWIZZLE_128B, CU_TENSOR_MAP_L2_PROMOTION_NONE);
    }
    {
        const cuuint64_t dims[3] = {4624, 4, 32}, st[2] = {9248 * 32, 9248};
        const cuuint32_t bx[3] = {56, 4, 32};
        encode(fn, &twr, CU_TENSOR_MAP_DATA_TYPE_BFLOAT16, 3, p.wr, dims, st, bx, CU_TENSOR_MAP_SWIZZLE_NONE);
        encode(fn, &twi, CU_TENSOR_MAP_DATA_TYPE_BFLOAT16, 3, p.wi, dims, st, bx, CU_TENSOR_MAP_SWIZZLE_NONE);
    }
    {
        const cuuint64_t dims[2] = {3456, 576}, st[1] = {6912};
        const cuuint32_t bx[2] = {32, 144};
        encode(fn, &tws, CU_TENSOR_MAP_DATA_TYPE_BFLOAT16, 2, p.wmod, dims, st, bx, CU_TENSOR_MAP_SWIZZLE_64B);
    }
    {
        const cuuint64_t dims[3] = {64, 576, 54}, st[2] = {6912, 128};
        const cuuint32_t bx[3] = {64, 32, 7};
        encode(fn, &twm, CU_TENSOR_MAP_DATA_TYPE_BFLOAT16, 3, p.wmod, dims, st, bx, CU_TENSOR_MAP_SWIZZLE_128B);
    }
    {
        const cuuint64_t dims[2] = {TP, 128}, st[1] = {TP * 4};
        const cuuint32_t ba[2] = {32, 128}, bb[2] = {8, 128};
        encode(fn, &tt, CU_TENSOR_MAP_DATA_TYPE_UINT32, 2, p.scr->T, dims, st, ba, CU_TENSOR_MAP_SWIZZLE_128B, CU_TENSOR_MAP_L2_PROMOTION_NONE);
        encode(fn, &ttx, CU_TENSOR_MAP_DATA_TYPE_UINT32, 2, p.scr->T, dims, st, bb, CU_TENSOR_MAP_SWIZZLE_32B, CU_TENSOR_MAP_L2_PROMOTION_NONE);
    }
    {
        const cuuint64_t dims[2] = {D_, S_}, st[1] = {D_ * 2};
        const cuuint32_t bx[2] = {144, 16};
        encode(fn, &to, CU_TENSOR_MAP_DATA_TYPE_BFLOAT16, 2, p.out, dims, st, bx, CU_TENSOR_MAP_SWIZZLE_NONE, CU_TENSOR_MAP_L2_PROMOTION_NONE);
    }
    cudaFuncSetAttribute(fused_kernel, cudaFuncAttributeMaxDynamicSharedMemorySize, SMEM_BYTES);
    cudaLaunchConfig_t cfg = {};
    cfg.gridDim = dim3(NCTA); cfg.blockDim = dim3(NTHR); cfg.dynamicSmemBytes = SMEM_BYTES; cfg.stream = cudaStreamPerThread;
    cudaLaunchAttribute at[1];
    at[0].id = cudaLaunchAttributeCooperative; at[0].val.cooperative = 1;
    cfg.attrs = at; cfg.numAttrs = 1;
    cudaLaunchKernelEx(&cfg, fused_kernel, p, tw1a, tw1b, tw2, th3a, th3b, twr, twi, twm, tt, ttx, to, th3s, tws);
}
```

```cpp
#include <cuda_runtime.h>
#include <cuda_bf16.h>
#include <cuda_fp16.h>
#include <cuda.h>
#include <stdint.h>

namespace {

constexpr int S_ = 2048, D_ = 576, F_ = 4608;
constexpr int NCTA = 132, NTHR = 512;
constexpr int TP = 4736;
constexpr int SPEC_P = 296;
constexpr int NST = 6;
constexpr int A_BYTES = 16384, B_BYTES = 18432;
constexpr int IT_P1 = 24, IT_G2 = 40, IT_END = 76;
constexpr int SPIN_LIMIT = 1 << 22;
#define X2D 1350
constexpr int P2S = 2;
#define LEAD1 4
#define W1N 8
#define W1P 100
#define W1S 5
#define XDELAY 1100
#define HOK 2
#define HOK1 2
#define NCP 10800
#define P2K 4
#define SLP 64
#define X1D 2100
#define PF0 4
#define PFS 3
#define PFN 9
#define X1DELAY 2000
#define X1PACE 400

constexpr int OFF_A = 0;
constexpr int OFF_B = NST * A_BYTES;
constexpr int OFF_P = OFF_B + NST * B_BYTES;
constexpr int OFF_BAR = OFF_P;
constexpr int OFF_EPOCH = OFF_P + 480;
constexpr int OFF_MISC = OFF_P + 496;
constexpr int OFF_GB = OFF_P + 512;
constexpr int OFF_P2R = OFF_P + 1664;
constexpr int OFF_X1 = OFF_P2R;
constexpr int OFF_PROF = OFF_X1 + 18432;
constexpr int SMEM_BYTES = OFF_PROF + 512;
constexpr int QA = 13, QB = 7, QC = 13;
constexpr int TAB_BYTES = (QA + QB + QC) * 512;
constexpr int OFF_STAGE = OFF_B;
constexpr int OFF_STX = OFF_STAGE + 16384;
constexpr int OFF_TAB = OFF_STAGE + 20480;
constexpr int OFF_SPEC = OFF_TAB + TAB_BYTES;
constexpr int OFF_WRAW = OFF_SPEC + 19072;
constexpr int OFF_B3 = OFF_WRAW + 28672;
constexpr int OFF_MODA = OFF_B3 + 4096;
constexpr int OFF_MODC = OFF_MODA + 2560;
constexpr int OFF_RED = OFF_MODC + 3584;
constexpr int OFF_HEXP = OFF_RED + 512;
constexpr int OFF_SILU = OFF_RED + 1536;
static_assert(OFF_SILU + 1152 <= OFF_P && 6 * 28672 <= OFF_B3, "scratch overflow");
constexpr int OFF_STRIP = OFF_A;
static_assert(OFF_WRAW % 128 == 0 && OFF_STAGE % 128 == 0 && OFF_STX % 128 == 0, "align");
constexpr int BAR_FULL = 0, BAR_EMPTY = 6, BAR_TAB = 12, BAR_W = 13, BAR_P2N = 14, BAR_P2R = 16,
              BAR_XT = 17, BAR_RECV = 18, BAR_ROLE = 19, BAR_NC = 20, BAR_TAB2 = 21, BAR_XB = 22, BAR_GB = 23, BAR_HOLD = 24, BAR_W1GO = 25, BAR_UOK = 26, BAR_DONE = 30, BAR_X = 31, BAR_ST = 47;

struct Cos1152 { double c[1152]; };
constexpr double cx_cos(double x) { double t = 1, s = 1; for (int i = 1; i < 14; i++) { t *= -x * x / ((2 * i - 1) * (2 * i)); s += t; } return s; }
constexpr Cos1152 make_cos() {
    Cos1152 r{};
    for (int i = 0; i <= 288; i++) {
        double v = (i == 288) ? 0.0 : cx_cos(3.14159265358979323846 * 2.0 * i / 1152.0);
        r.c[i] = v; r.c[576 - i] = -v; r.c[576 + i] = -v; r.c[(1152 - i) % 1152] = v;
    }
    return r;
}
constexpr uint32_t cx_f2h(double v) {
    uint32_t s = v < 0 ? 0x8000u : 0u; double a = v < 0 ? -v : v;
    if (a < 1e-9) return 0;
    int e = 0;
    while (a >= 2.0) { a *= 0.5; e++; }
    while (a < 1.0 && e > -14) { a *= 2.0; e--; }
    double m = a * 1024.0; uint32_t mi = (uint32_t)m; double fr = m - mi;
    if (fr > 0.5 || (fr == 0.5 && (mi & 1))) mi++;
    return s | (uint32_t)(((e + 14) << 10) + mi);
}
struct Tab { uint32_t w[(QA + QB + QC) * 128]; };
constexpr Tab make_tab() {
    Tab t{};
    Cos1152 ct = make_cos();
    auto C = [&](int num, int den) { return ct.c[(num % den) * (1152 / den)]; };
    auto Sn = [&](int num, int den) { return ct.c[((num % den) * (1152 / den) + 864) % 1152]; };
    auto put = [&](int q0, int idx, int lane, double lo, double hi) { t.w[((q0 + idx / 4) * 32 + lane) * 4 + idx % 4] = cx_f2h(lo) | (cx_f2h(hi) << 16); };
    for (int lane = 0; lane < 32; lane++) {
        const int g = lane >> 2, q = lane & 3;
        for (int mt = 0; mt < 3; mt++) {
            const int ka = 8 * mt + g;
            for (int r = 0; r < 10; r++) {
                const int im = r & 1, i0 = (r >> 1) * 2;
                double v[2] = {0, 0};
                for (int e = 0; e < 2; e++) { int i = i0 + e, d1 = 4 * i + q; if (i < 9 && ka <= 18) v[e] = (im ? -Sn(ka * d1, 36) : C(ka * d1, 36)) / 8; }
                put(0, r < 8 ? mt * 8 + r : 16 + 2 * mt + r, lane, v[0], v[1]);
            }
            for (int v = 0; v < 2; v++) {
                const int d2 = 4 * q + v;
                put(0, 30 + (mt * 2 + v) * 2, lane, C(ka * d2, 576) * 4 / 3, C(ka * (d2 + 2), 576) * 4 / 3);
                put(0, 31 + (mt * 2 + v) * 2, lane, Sn(ka * d2, 576) * 4 / 3, Sn(ka * (d2 + 2), 576) * 4 / 3);
            }
        }
        for (int v = 0; v < 2; v++) for (int nt = 0; nt < 2; nt++) {
            const int kb = 2 * (g >> 1) + nt, part = g & 1;
            double b0[2] = {0, 0}, b1[2] = {0, 0};
            for (int e = 0; e < 2; e++) { int d2 = 4 * q + 2 * e + v; double c = C(kb * d2, 16) / 4, s = Sn(kb * d2, 16) / 4;
                b0[e] = part ? -s : c; b1[e] = part ? c : s; }
            put(0, 42 + (v * 2 + nt) * 2, lane, b0[0], b0[1]); put(0, 43 + (v * 2 + nt) * 2, lane, b1[0], b1[1]);
        }
        t.w[((QA - 1) * 32 + lane) * 4 + 2] = 0x3F803F80u;
        for (int par = 0; par < 2; par++) for (int a = 0; a < 4; a++) {
            const int ja = 2 * (q + 4 * (a >> 1)) + par; const double c = C(g * ja, 16) / 4, s = Sn(g * ja, 16) / 4;
            put(QA, par * 4 + a, lane, (a & 1) ? -s : c, (a & 1) ? c : s);
        }
        for (int h = 0; h < 2; h++) {
            put(QA, 8 + 2 * h, lane, C((g + 8 * h) * (2 * q), 128) / 2, C((g + 8 * h) * (2 * q + 1), 128) / 2);
            put(QA, 9 + 2 * h, lane, Sn((g + 8 * h) * (2 * q), 128) / 2, Sn((g + 8 * h) * (2 * q + 1), 128) / 2);
            put(QA, 16 + 2 * h, lane, C(g * (8 * h + 2 * q), 128), C(g * (8 * h + 2 * q + 1), 128));
            put(QA, 17 + 2 * h, lane, Sn(g * (8 * h + 2 * q), 128), Sn(g * (8 * h + 2 * q + 1), 128));
        }
        put(QA, 12, lane, C(g * 2 * q, 8) / 2, C(g * (2 * q + 1), 8) / 2);
        put(QA, 15, lane, C(g * 2 * q, 8) / 2, C(g * (2 * q + 1), 8) / 2);
        put(QA, 13, lane, Sn(g * 2 * q, 8) / 2, Sn(g * (2 * q + 1), 8) / 2);
        put(QA, 14, lane, -Sn(g * 2 * q, 8) / 2, -Sn(g * (2 * q + 1), 8) / 2);
        for (int u = 0; u < 4; u++) {
            const int ja = 2 * ((g >> 1) + 4 * (u & 1)) + (u >> 1), part = g & 1; double b0[2] = {0, 0}, b1[2] = {0, 0};
            for (int e = 0; e < 2; e++) { int ka = 2 * q + e; double c = C(ja * ka, 16) / 4, s = Sn(ja * ka, 16) / 4;
                b0[e] = part ? s : c; b1[e] = part ? c : -s; }
            put(QA, 20 + u * 2, lane, b0[0], b0[1]); put(QA, 21 + u * 2, lane, b1[0], b1[1]);
        }
        for (int m2 = 0; m2 < 2; m2++) {
            const int d2 = 2 * g + m2;
            for (int a = 0; a < 4; a++) {
                const int kb = 2 * q + (a >> 1); const double c = C(d2 * kb, 16) / 4, s = Sn(d2 * kb, 16) / 4;
                put(QA + QB, m2 * 4 + a, lane, (a & 1) ? s : c, (a & 1) ? c : -s);
            }
            for (int mt = 0; mt < 3; mt++) {
                const int ka = 8 * mt + 2 * q;
                put(QA + QB, 8 + (m2 * 3 + mt) * 2, lane, C(ka * d2, 576) * 4 / 3, C((ka + 1) * d2, 576) * 4 / 3);
                put(QA + QB, 9 + (m2 * 3 + mt) * 2, lane, Sn(ka * d2, 576) * 4 / 3, Sn((ka + 1) * d2, 576) * 4 / 3);
            }
        }
        for (int mt = 0; mt < 3; mt++) for (int nt = 0; nt < 5; nt++) {
            const int i = 2 * nt + (g & 1), d1 = 4 * i + (g >> 1); double b0[2] = {0, 0}, b1[2] = {0, 0};
            for (int e = 0; e < 2; e++) { int ka = 8 * mt + 2 * q + e;
                if (ka <= 18 && i < 9) { double wt = (ka == 0 || ka == 18) ? 0.125 : 0.25; b0[e] = wt * C(ka * d1, 36); b1[e] = -wt * Sn(ka * d1, 36); } }
            const int o = (QA + QB + 5) * 128 + (mt * 5 + nt) * 64 + lane;
            t.w[o] = cx_f2h(b0[0]) | (cx_f2h(b0[1]) << 16); t.w[o + 32] = cx_f2h(b1[0]) | (cx_f2h(b1[1]) << 16);
        }
    }
    return t;
}
__device__ __align__(128) const Tab g_tab = make_tab();

struct Scratch {
    uint32_t cnt[30 * 32];
    uint32_t slot[96];
    uint32_t mod[2304];
    uint32_t modc[896 + 288];
    uint32_t T[128 * TP];
    uint4 h3[128 * 1152];
    uint4 U[72 * 4 * 1152];
};
__device__ __align__(1024) Scratch g_scr;
#define g_cnt (p.scr->cnt)
#define g_slot (p.scr->slot)
#define g_mod (p.scr->mod)
#define g_T (p.scr->T)
#define g_h3 (p.scr->h3)
#define g_U (p.scr->U)
constexpr int CNT_EPOCH = 0, CNT_H3 = 1, CNT_X1 = 26, CNT_NC = 27, CNT_U = 2;
#define PROFT(i) do {} while (0)
#define PROFDUMP() do {} while (0)
#define PROF0(i) do {} while (0)

__device__ __forceinline__ void mbar_init(uint32_t bar, uint32_t cnt) { asm volatile("mbarrier.init.shared::cta.b64 [%0], %1;" :: "r"(bar), "r"(cnt) : "memory"); }
__device__ __forceinline__ void mbar_expect(uint32_t bar, uint32_t bytes) { asm volatile("mbarrier.arrive.expect_tx.shared::cta.b64 _, [%0], %1;" :: "r"(bar), "r"(bytes) : "memory"); }
__device__ __forceinline__ void mbar_arrive(uint32_t bar) { asm volatile("mbarrier.arrive.shared::cta.b64 _, [%0];" :: "r"(bar) : "memory"); }
__device__ __forceinline__ void mbar_arrive_n(uint32_t bar, uint32_t n) { asm volatile("mbarrier.arrive.shared::cta.b64 _, [%0], %1;" :: "r"(bar), "r"(n) : "memory"); }
__device__ __forceinline__ void mbar_arrive_remote(uint32_t rbar) { asm volatile("mbarrier.arrive.relaxed.cluster.shared::cluster.b64 _, [%0];" :: "r"(rbar) : "memory"); }
__device__ __forceinline__ void mbar_wait(uint32_t bar, uint32_t parity) {
    asm volatile("{.reg .pred p; .reg .u32 c;\n"
        "mbarrier.try_wait.parity.shared::cta.b64 p, [%0], %1;\n@p bra.uni DONE;\nmov.u32 c, 0;\n"
        "LOOP: mbarrier.try_wait.parity.shared::cta.b64 p, [%0], %1;\n@p bra.uni DONE;\n"
        "add.u32 c, c, 1;\nsetp.lt.u32 p, c, %2;\n@p bra.uni LOOP;\ntrap;\nDONE:}" :: "r"(bar), "r"(parity), "n"(SPIN_LIMIT) : "memory");
}
__device__ __forceinline__ bool mbar_test(uint32_t bar, uint32_t parity) {
    uint32_t ok; asm volatile("{.reg .pred p; mbarrier.test_wait.parity.shared::cta.b64 p, [%1], %2; selp.u32 %0, 1, 0, p;}" : "=r"(ok) : "r"(bar), "r"(parity) : "memory"); return ok; }
__device__ __forceinline__ uint32_t mapa(uint32_t a, uint32_t rank) { uint32_t r; asm("mapa.shared::cluster.u32 %0, %1, %2;" : "=r"(r) : "r"(a), "r"(rank)); return r; }
__device__ __forceinline__ uint32_t clk32() { uint32_t r; asm volatile("mov.u32 %0, %%clock;" : "=r"(r)); return r; }
__device__ __forceinline__ void hb() {
    asm volatile("{.reg .b32 a, b; .reg .pred p; mma.sync.aligned.m16n8k8.row.col.f16.f16.f16.f16 {a, b}, {%0,%0}, {%0}, {%0,%0};\n"
                 "setp.ne.u32 p, a, 0; @p trap;}" :: "r"(0));
}
__device__ __forceinline__ void spin_until(uint32_t t) {
    while (__any_sync(~0u, (int)(clk32() - t) < -SLP * 4)) { __nanosleep(SLP); hb(); }
    while (__any_sync(~0u, (int)(clk32() - t) < 0)) {}
}
__device__ __forceinline__ bool elect() { uint32_t r; asm volatile("{.reg .pred p; elect.sync _|p, 0xffffffff; selp.u32 %0, 1, 0, p;}" : "=r"(r)); return r; }
__device__ __forceinline__ void bar_sync(int id, int n) { asm volatile("bar.sync %0, %1;" :: "r"(id), "r"(n) : "memory"); }
__device__ __forceinline__ void bulk_load(uint32_t dst, const void* src, uint32_t bytes, uint32_t bar) {
    asm volatile("cp.async.bulk.shared::cluster.global.mbarrier::complete_tx::bytes [%0], [%1], %2, [%3];" :: "r"(dst), "l"(src), "r"(bytes), "r"(bar) : "memory"); }
__device__ __forceinline__ void tma2(uint32_t dst, const CUtensorMap* m, int c0, int c1, uint32_t bar) {
    asm volatile("cp.async.bulk.tensor.2d.shared::cluster.global.mbarrier::complete_tx::bytes [%0], [%1, {%3, %4}], [%2];" :: "r"(dst), "l"(m), "r"(bar), "r"(c0), "r"(c1) : "memory"); }
__device__ __forceinline__ void tma3(uint32_t dst, const CUtensorMap* m, int c0, int c1, int c2, uint32_t bar) {
    asm volatile("cp.async.bulk.tensor.3d.shared::cluster.global.mbarrier::complete_tx::bytes [%0], [%1, {%3, %4, %5}], [%2];" :: "r"(dst), "l"(m), "r"(bar), "r"(c0), "r"(c1), "r"(c2) : "memory"); }
__device__ __forceinline__ void tma4(uint32_t dst, const CUtensorMap* m, int c0, int c1, int c2, int c3, uint32_t bar) {
    asm volatile("cp.async.bulk.tensor.4d.shared::cluster.global.mbarrier::complete_tx::bytes [%0], [%1, {%3, %4, %5, %6}], [%2];" :: "r"(dst), "l"(m), "r"(bar), "r"(c0), "r"(c1), "r"(c2), "r"(c3) : "memory"); }
__device__ __forceinline__ void fence_async_g() { asm volatile("fence.proxy.async.global;" ::: "memory"); }
__device__ __forceinline__ void fence_async_s() { asm volatile("fence.proxy.async.shared::cta;" ::: "memory"); }
__device__ __forceinline__ uint4 lds128(uint32_t a) { uint4 v; asm volatile("ld.shared.v4.u32 {%0,%1,%2,%3}, [%4];" : "=r"(v.x), "=r"(v.y), "=r"(v.z), "=r"(v.w) : "r"(a) : "memory"); return v; }
__device__ __forceinline__ uint32_t lds32(uint32_t a) { uint32_t v; asm volatile("ld.shared.u32 %0, [%1];" : "=r"(v) : "r"(a) : "memory"); return v; }
__device__ __forceinline__ void sts128(uint32_t a, uint4 v) { asm volatile("st.shared.v4.u32 [%0], {%1,%2,%3,%4};" :: "r"(a), "r"(v.x), "r"(v.y), "r"(v.z), "r"(v.w) : "memory"); }
__device__ __forceinline__ void sts32(uint32_t a, uint32_t v) { asm volatile("st.shared.u32 [%0], %1;" :: "r"(a), "r"(v) : "memory"); }
__device__ __forceinline__ void sts16(uint32_t a, uint32_t v) { asm volatile("st.shared.u16 [%0], %1;" :: "r"(a), "h"((uint16_t)v) : "memory"); }
__device__ __forceinline__ uint4 ldx128(const void* p) {
    uint4 v; asm volatile("{.reg .b128 t; .reg .b64 a, b; ld.relaxed.gpu.global.b128 t, [%4]; mov.b128 {a, b}, t; mov.b64 {%0,%1}, a; mov.b64 {%2,%3}, b;}"
        : "=r"(v.x), "=r"(v.y), "=r"(v.z), "=r"(v.w) : "l"(p) : "memory"); return v; }
__device__ __forceinline__ void stx128(void* p, uint4 v) {
    asm volatile("{.reg .b128 t; .reg .b64 a, b; mov.b64 a, {%1,%2}; mov.b64 b, {%3,%4}; mov.b128 t, {a, b}; st.relaxed.gpu.global.b128 [%0], t;}"
        :: "l"(p), "r"(v.x), "r"(v.y), "r"(v.z), "r"(v.w) : "memory"); }
__device__ __forceinline__ uint32_t ld_acquire(const uint32_t* p) { uint32_t v; asm volatile("ld.acquire.gpu.global.u32 %0, [%1];" : "=r"(v) : "l"(p) : "memory"); return v; }
__device__ __forceinline__ void st_relaxed(uint32_t* p, uint32_t v) { asm volatile("st.relaxed.gpu.global.u32 [%0], %1;" :: "l"(p), "r"(v) : "memory"); }
__device__ __forceinline__ void red_release(uint32_t* p) { asm volatile("red.release.gpu.global.add.u32 [%0], 1;" :: "l"(p) : "memory"); }
template <int SLEEP> __device__ __forceinline__ void wait_count(const uint32_t* p, uint32_t target) {
    int it = 0; while ((int)(ld_acquire(p) - target) < 0) { if (SLEEP) __nanosleep(SLEEP); if (++it > SPIN_LIMIT) __trap(); }
}
__device__ __forceinline__ uint32_t ldg_nc32(const void* p) { uint32_t v; asm volatile("ld.global.nc.L1::no_allocate.u32 %0, [%1];" : "=r"(v) : "l"(p)); return v; }
__device__ __forceinline__ uint32_t ldg_nc16(const void* p) { uint16_t v; asm volatile("ld.global.nc.u16 %0, [%1];" : "=h"(v) : "l"(p)); return v; }
__device__ __forceinline__ float bf_lo(uint32_t w) { return __uint_as_float(w << 16); }
__device__ __forceinline__ float bf_hi(uint32_t w) { return __uint_as_float(w & 0xFFFF0000u); }
__device__ __forceinline__ uint32_t pack_bf(float lo, float hi) { uint32_t r; asm("cvt.rn.bf16x2.f32 %0, %1, %2;" : "=r"(r) : "f"(hi), "f"(lo)); return r; }
__device__ __forceinline__ uint32_t pack_h(float lo, float hi) { uint32_t r; asm("cvt.rn.f16x2.f32 %0, %1, %2;" : "=r"(r) : "f"(hi), "f"(lo)); return r; }
__device__ __forceinline__ float bf_round(float v) { return bf_lo(pack_bf(v, 0.f)); }
__device__ __forceinline__ uint32_t hmul2(uint32_t a, uint32_t b) { uint32_t r; asm("mul.rn.f16x2 %0, %1, %2;" : "=r"(r) : "r"(a), "r"(b)); return r; }
__device__ __forceinline__ uint32_t hfma2(uint32_t a, uint32_t b, uint32_t c) { uint32_t r; asm("fma.rn.f16x2 %0, %1, %2, %3;" : "=r"(r) : "r"(a), "r"(b), "r"(c)); return r; }
__device__ __forceinline__ uint32_t hfms2(uint32_t a, uint32_t b, uint32_t c) { uint32_t r; asm("{.reg .b32 t; neg.f16x2 t, %3; fma.rn.f16x2 %0, %1, %2, t;}" : "=r"(r) : "r"(a), "r"(b), "r"(c)); return r; }
__device__ __forceinline__ uint32_t hadd2(uint32_t a, uint32_t b) { uint32_t r; asm("add.rn.f16x2 %0, %1, %2;" : "=r"(r) : "r"(a), "r"(b)); return r; }
__device__ __forceinline__ uint32_t hsub2(uint32_t a, uint32_t b) { uint32_t r; asm("sub.rn.f16x2 %0, %1, %2;" : "=r"(r) : "r"(a), "r"(b)); return r; }
__device__ __forceinline__ void cmul_neg(uint32_t& re, uint32_t& im, uint32_t c, uint32_t s) { uint32_t a = hfma2(re, c, hmul2(im, s)), b = hfms2(im, c, hmul2(re, s)); re = a; im = b; }
__device__ __forceinline__ void cmul_pos(uint32_t& re, uint32_t& im, uint32_t c, uint32_t s) { uint32_t a = hfms2(re, c, hmul2(im, s)), b = hfma2(im, c, hmul2(re, s)); re = a; im = b; }
__device__ __forceinline__ void mma_h(uint32_t& d0, uint32_t& d1, uint32_t a0, uint32_t a1, uint32_t a2, uint32_t a3, uint32_t b0, uint32_t b1) {
    asm("mma.sync.aligned.m16n8k16.row.col.f16.f16.f16.f16 {%0,%1}, {%2,%3,%4,%5}, {%6,%7}, {%0,%1};" : "+r"(d0), "+r"(d1) : "r"(a0), "r"(a1), "r"(a2), "r"(a3), "r"(b0), "r"(b1)); }
__device__ __forceinline__ void mma_h8(uint32_t& d0, uint32_t& d1, uint32_t a0, uint32_t a1, uint32_t b0) {
    asm("mma.sync.aligned.m16n8k8.row.col.f16.f16.f16.f16 {%0,%1}, {%2,%3}, {%4}, {%0,%1};" : "+r"(d0), "+r"(d1) : "r"(a0), "r"(a1), "r"(b0)); }
template <int NQ> __device__ __forceinline__ void load_tab(uint32_t (&r)[NQ * 4], uint32_t addr) {
    #pragma unroll
    for (int i = 0; i < NQ; i++) { uint4 v = lds128(addr + i * 512); r[4 * i] = v.x; r[4 * i + 1] = v.y; r[4 * i + 2] = v.z; r[4 * i + 3] = v.w; }
}
__device__ __forceinline__ float gelu2(float x) {
    float t = x * fmaf(x * x, 0.044715f * 0.7978845608028654f, 0.7978845608028654f), th;
    asm volatile("tanh.approx.f32 %0, %1;" : "=f"(th) : "f"(t));
    return fmaf(x, th, x);
}
constexpr uint32_t SM0 = 1024;
__device__ __forceinline__ constexpr uint32_t desc_lo(uint32_t off, uint32_t lbo) { return ((SM0 + off) >> 4) | ((lbo >> 4) << 16); }
constexpr uint32_t DHI_A = (1024 >> 4) | (1u << 30), DHI_H3 = 256 >> 4, DHI_U = 128 >> 4;
#define WG_FENCE() asm volatile("wgmma.fence.sync.aligned;" ::: "memory")
#define WG_COMMIT() asm volatile("wgmma.commit_group.sync.aligned;" ::: "memory")
#define WG_WAIT(n) asm volatile("wgmma.wait_group.sync.aligned %0;" :: "n"(n) : "memory")
#define R4(b) "+f"(d[b]), "+f"(d[b + 1]), "+f"(d[b + 2]), "+f"(d[b + 3])
#define R12(b) R4(b), R4(b + 4), R4(b + 8)
#define R36(b) R12(b), R12(b + 12), R12(b + 24)
template <uint32_t BHI> __device__ __forceinline__ void wgmma144(float (&d)[72], uint32_t da, uint32_t db, int acc) {
    asm volatile("{.reg .pred p; .reg .b64 a, b; setp.ne.b32 p, %74, 0; mov.b64 a, {%72, %75}; mov.b64 b, {%73, %76};\n"
        "wgmma.mma_async.sync.aligned.m64n144k16.f32.bf16.bf16 {%0,%1,%2,%3,%4,%5,%6,%7,%8,%9,%10,%11,%12,%13,%14,%15,%16,%17,%18,%19,%20,%21,%22,%23,"
        "%24,%25,%26,%27,%28,%29,%30,%31,%32,%33,%34,%35,%36,%37,%38,%39,%40,%41,%42,%43,%44,%45,%46,%47,"
        "%48,%49,%50,%51,%52,%53,%54,%55,%56,%57,%58,%59,%60,%61,%62,%63,%64,%65,%66,%67,%68,%69,%70,%71}, a, b, p, 1, 1, 1, 1;}\n"
        : R36(0), R36(36) : "r"(da), "r"(db), "r"(acc), "n"(DHI_A), "n"(BHI));
}
__device__ __forceinline__ void wgmma40_rs(float (&d)[20], uint32_t a0, uint32_t a1, uint32_t a2, uint32_t a3, uint32_t db, int acc) {
    asm volatile("{.reg .pred p; .reg .b64 b; setp.ne.b32 p, %25, 0; mov.b64 b, {%24, %26};\n"
        "wgmma.mma_async.sync.aligned.m64n40k16.f32.f16.f16 {%0,%1,%2,%3,%4,%5,%6,%7,%8,%9,%10,%11,%12,%13,%14,%15,%16,%17,%18,%19}, {%20,%21,%22,%23}, b, p, 1, 1, 0;}\n"
        : R12(0), R4(12), R4(16) : "r"(a0), "r"(a1), "r"(a2), "r"(a3), "r"(db), "r"(acc), "n"(DHI_H3));
}
__device__ __forceinline__ void wgmma72(float (&d)[36], uint32_t da, uint32_t db, int acc) {
    asm volatile("{.reg .pred p; .reg .b64 a, b; setp.ne.b32 p, %38, 0; mov.b64 a, {%36, %39}; mov.b64 b, {%37, %40};\n"
        "wgmma.mma_async.sync.aligned.m64n72k16.f32.bf16.bf16 {%0,%1,%2,%3,%4,%5,%6,%7,%8,%9,%10,%11,%12,%13,%14,%15,%16,%17,%18,%19,%20,%21,%22,%23,"
        "%24,%25,%26,%27,%28,%29,%30,%31,%32,%33,%34,%35}, a, b, p, 1, 1, 1, 1;}\n"
        : R36(0) : "r"(da), "r"(db), "r"(acc), "n"(DHI_A), "n"(DHI_H3));
}

__device__ __forceinline__ int g2_kb(int n, int kh, int gi, int c2) {
    if (n < 4) return 36 * kh + 9 * n + 8;
    if (n == 4) return 9 * gi + 4 * c2 + 2 * kh + 1;
    const int w = n > 20, m = n - (w ? 19 : 5);
    return 9 * ((gi * w + (m >> 1)) & 7) + 4 * (n == 35 ? 1 - c2 : m & 1) + 2 * kh + w;
}

template <uint32_t BHI, int S> __device__ __forceinline__ void mma_block(float (&d)[72], uint32_t bars, uint32_t da0, uint32_t db0, uint32_t ph) {
    mbar_wait(bars + 8 * (BAR_FULL + S), ph);
    WG_FENCE();
    #pragma unroll
    for (int k = 0; k < 4; k++) wgmma144<BHI>(d, da0 + S * (A_BYTES / 16) + k * 128, db0 + S * (B_BYTES / 16) + k * 288, 1);
    WG_COMMIT();
    WG_WAIT(1);
}

struct Params {
    const uint16_t *wmod, *c, *x;
    Scratch* scr;
    const Tab* tab;
    const uint16_t *wr, *wi, *w1, *b1, *w2, *b2;
    uint16_t* out;
};

__device__ __forceinline__ void mma_bf(float (&d)[4], const uint32_t (&a)[4], uint32_t b0, uint32_t b1) {
    asm("mma.sync.aligned.m16n8k16.row.col.f32.bf16.bf16.f32 {%0,%1,%2,%3}, {%4,%5,%6,%7}, {%8,%9}, {%0,%1,%2,%3};"
        : "+f"(d[0]), "+f"(d[1]), "+f"(d[2]), "+f"(d[3]) : "r"(a[0]), "r"(a[1]), "r"(a[2]), "r"(a[3]), "r"(b0), "r"(b1)); }
__device__ __forceinline__ void ldsm4t(uint32_t (&a)[4], uint32_t addr) {
    asm volatile("ldmatrix.sync.aligned.m8n8.x4.trans.shared.b16 {%0,%1,%2,%3}, [%4];" : "=r"(a[0]), "=r"(a[1]), "=r"(a[2]), "=r"(a[3]) : "r"(addr) : "memory"); }
__device__ __forceinline__ void ln_stats(const uint32_t (&w)[9], const uint32_t (&one)[9], int g, int q, float& r, float& mr) {
    float c[2][4] = {};
    #pragma unroll
    for (int p = 0; p < 9; p++)
        asm("mma.sync.aligned.m16n8k8.row.col.f32.bf16.bf16.f32 {%0,%1,%2,%3}, {%4,%5}, {%4}, {%0,%1,%2,%3};"
            : "+f"(c[p & 1][0]), "+f"(c[p & 1][1]), "+f"(c[p & 1][2]), "+f"(c[p & 1][3]) : "r"(w[p]), "r"(one[p]));
    const float t = (g & 1) ? c[0][1] + c[1][1] : c[0][0] + c[1][0];
    float s1 = (c[0][2] + c[1][2]) + (c[0][3] + c[1][3]), s2 = __shfl_sync(~0u, t, 9 * q) + __shfl_sync(~0u, t, 9 * q + 4);
    #pragma unroll
    for (int o = 1; o < 4; o <<= 1) { s1 += __shfl_xor_sync(~0u, s1, o); s2 += __shfl_xor_sync(~0u, s2, o); }
    const float m = s1 * (1.f / D_);
    asm("rsqrt.approx.ftz.f32 %0, %1;" : "=f"(r) : "f"(fmaxf(fmaf(s2, 1.f / D_, -m * m), 0.f) + 1e-5f));
    mr = -m * r;
}
__device__ __forceinline__ float silu(float v) { return __fdividef(v, 1.f + __expf(-v)); }
__device__ __forceinline__ uint32_t bfma2(uint32_t a, uint32_t b, uint32_t c) { uint32_t r; asm("fma.rn.bf16x2 %0, %1, %2, %3;" : "=r"(r) : "r"(a), "r"(b), "r"(c)); return r; }
__device__ __forceinline__ void radix16(const uint4 (&V)[4], const uint32_t (&B)[16], uint4 (&o)[4]) {
    #pragma unroll
    for (int nt = 0; nt < 4; nt++) o[nt] = make_uint4(0, 0, 0, 0);
    #pragma unroll
    for (int u = 0; u < 4; u++)
        #pragma unroll
        for (int nt = 0; nt < 4; nt++) {
            const uint32_t b = B[((u >> 1) * 4 + nt) * 2 + (u & 1)];
            mma_h8(o[nt].x, o[nt].y, V[u].x, V[u].y, b); mma_h8(o[nt].z, o[nt].w, V[u].z, V[u].w, b);
        }
}
template <int OFF, int N> __device__ __forceinline__ void gelu_store(const float (&d)[N], char* p, int q) {
    uint32_t w[9];
    #pragma unroll
    for (int blk = 0; blk < 9; blk++) w[blk] = pack_bf(gelu2(d[OFF + 4 * blk]), gelu2(d[OFF + 4 * blk + 1]));
    asm volatile("st.v4.u32 [%0], {%1,%2,%3,%4};" :: "l"(p + q * 128), "r"(w[0]), "r"(w[1]), "r"(w[2]), "r"(w[3]) : "memory");
    asm volatile("st.v4.u32 [%0+512], {%1,%2,%3,%4};" :: "l"(p + q * 128), "r"(w[4]), "r"(w[5]), "r"(w[6]), "r"(w[7]) : "memory");
    asm volatile("st.u32 [%0+1024], %1;" :: "l"(p + q * 4), "r"(w[8]) : "memory");
}

__global__ void __cluster_dims__(2, 1, 1) __launch_bounds__(NTHR, 1)
fused_kernel(const Params p,
             const __grid_constant__ CUtensorMap tm_w1a, const __grid_constant__ CUtensorMap tm_w1b, const __grid_constant__ CUtensorMap tm_w2,
             const __grid_constant__ CUtensorMap tm_h3a, const __grid_constant__ CUtensorMap tm_h3b,
             const __grid_constant__ CUtensorMap tm_wr, const __grid_constant__ CUtensorMap tm_wi, const __grid_constant__ CUtensorMap tm_wm,
             const __grid_constant__ CUtensorMap tm_t, const __grid_constant__ CUtensorMap tm_tx, const __grid_constant__ CUtensorMap tm_o,
             const __grid_constant__ CUtensorMap tm_h3s, const __grid_constant__ CUtensorMap tm_ws)
{
    extern __shared__ __align__(1024) char smem_raw[];
    const uint32_t t0 = clk32();
    const uint32_t sm = __shfl_sync(~0u, ((uint32_t)__cvta_generic_to_shared(smem_raw) + 1023u) & ~1023u, 0);
    const int tid = threadIdx.x, warp = __shfl_sync(~0u, tid >> 5, 0), lane = tid & 31, g = lane >> 2, q = lane & 3;
    const int b = blockIdx.x;
    const uint32_t rank = b & 1;
    const uint32_t bars = sm + OFF_BAR;
    const bool rowcta = b < 128;

    auto nc_issue = [&](int st, uint32_t sl) {
        const int pass = st >= 18;
        mbar_expect(bars + 8 * (BAR_X + sl), 28672);
        tma3(sm + sl * 28672, &tm_wm, 0, 32 * (st - 18 * pass), 18 + 28 * pass + 7 * (b - 128), bars + 8 * (BAR_X + sl));
    };
    uint32_t epoch;
    const bool strip = b < 72 && !(b & 1);
    const bool sil = (warp >> 2) == 2 && lane < 24 && (strip || !rowcta);
    uint32_t cw[3];
    if (elect()) {
        mbar_init(bars + 8 * (BAR_X + warp), rowcta || warp < 6 ? 1 : 14);
        if (warp >= 12) {
            if (strip) { const uint32_t sb = bars + 8 * (BAR_ST + warp - 12);
                mbar_init(sb, 1); mbar_expect(sb, 9216); tma2(sm + OFF_STRIP + (warp - 12) * 9216, &tm_ws, 16 * b, 144 * (warp - 12), sb); }
        } else if (warp == 7) {
            mbar_init(bars + 8 * BAR_TAB, 1); mbar_expect(bars + 8 * BAR_TAB, rowcta ? QA * 512 + 16 : 16);
            bulk_load(sm + OFF_EPOCH, g_cnt + CNT_EPOCH * 32, 16, bars + 8 * BAR_TAB);
            if (rowcta) bulk_load(sm + OFF_TAB, p.tab, QA * 512, bars + 8 * BAR_TAB);
        } else if (b + 132 * warp < 576) {
            asm volatile("cp.async.bulk.prefetch.L2.global [%0], 2304;" :: "l"(p.wmod + (b + 132 * warp) * 3456) : "memory");
        }
    }
    if (sil) {
        #pragma unroll
        for (int u = 0; u < 3; u++) cw[u] = ldg_nc32(p.c + 144 * (warp - 8) + 48 * u + 2 * lane);
    }
    if (warp == 6) hb();
    __syncthreads();
    if (!rowcta) { if (warp < 6 && elect()) nc_issue(warp, warp); }
    if (warp == 5 || warp == 6) {
        if (elect()) {
            if (warp == 5) {
                for (int i = BAR_W; i < BAR_X; i++) mbar_init(bars + 8 * i, i == BAR_DONE || i == BAR_NC ? 4 : i == BAR_W1GO ? 2 : 1);
                mbar_expect(bars + 8 * BAR_W, 28672); mbar_expect(bars + 8 * BAR_TAB2, (QB + QC) * 512);
                mbar_expect(bars + 8 * BAR_ROLE, 4); mbar_expect(bars + 8 * BAR_P2R, 9216); mbar_expect(bars + 8 * BAR_RECV, 18432); mbar_expect(bars + 8 * BAR_XT, 18432);
            } else {
                for (int i = 0; i < 2 * NST; i++) mbar_init(bars + 8 * i, 2);
                for (int i = 0; i < NST; i++) mbar_expect(bars + 8 * (BAR_FULL + i), A_BYTES);
            }
            asm volatile("fence.mbarrier_init.release.cluster;" ::: "memory");
        }
    } else if (warp >= 12 && elect())
        asm volatile("prefetch.tensormap [%0];" :: "l"(warp == 12 ? &tm_wr : warp == 13 ? &tm_wi : warp == 14 ? &tm_t : &tm_tx) : "memory");
    uint32_t sb[18];
    if ((warp >> 2) == 2) {
        if (sil) {
            #pragma unroll
            for (int u = 0; u < 3; u++) sts32(sm + OFF_SILU + (72 * (warp - 8) + 24 * u + lane) * 4, pack_bf(silu(bf_lo(cw[u])), silu(bf_hi(cw[u]))));
        }
        __syncwarp();
        if (strip) {
            #pragma unroll
            for (int u = 0; u < 18; u++) sb[u] = lds32(sm + OFF_SILU + (72 * (warp - 8) + 4 * u + q) * 4);
        }
    }
    if (rowcta && elect()) {
        if (XDELAY) while ((int)(clk32() - t0) < XDELAY) {}
        mbar_expect(bars + 8 * (BAR_X + warp), 1152);
        bulk_load(sm + OFF_STAGE + warp * 1152, p.x + (size_t)(b + 128 * warp) * D_, 1152, bars + 8 * (BAR_X + warp));
    }
    __syncwarp();
    hb();

    const int trow = 4 * (b & 7) + ((b >> 4) & 3) + 64 * ((b >> 3) & 1) + 32 * (b >> 6);
    uint32_t* const tptr = g_T + (size_t)trow * TP + (warp < 9 ? q * 288 + 32 * warp : 4608 + 8 * q) + 4 * g;
    const int tstr = warp < 9 ? 1152 : 32;
    const uint32_t scol = sm + OFF_SPEC + (q * SPEC_P + (warp < 8 ? 72 * (warp >> 1) + 40 * (warp & 1) + 4 * g : warp == 8 ? 72 * (g >> 1) + 32 + 4 * (g & 1) : 288 + 4 * g)) * 4;
    const int wc0 = (b >> 3) * 289 + 72 * ((b & 7) >> 1) + 40 * (b & 1);

    uint32_t xw[9], one[9], t_st = t0, hexp = 0;
    if (!rowcta) {
        const int nst = b < 130 ? 36 : 18;
        __syncthreads();
        asm volatile("barrier.cluster.arrive.relaxed.aligned;" ::: "memory");
        mbar_wait(bars + 8 * BAR_TAB, 0);
        epoch = lds32(sm + OFF_EPOCH);
        if (warp == 14) {
            uint32_t sl = 0, ph = 0;
            #pragma unroll 1
            for (int st = 6; st < nst; st++) {
                mbar_wait(bars + 8 * (BAR_X + 6 + sl), ph);
                if (elect()) nc_issue(st, sl);
                if (++sl == 6) { sl = 0; ph ^= 1; }
            }
        } else if (warp < 14) {
            uint32_t sl = 0, ph = 0;
            const uint32_t ad0 = sm + (warp >> 1) * 4096 + ((lane & 7) + 8 * (lane >> 4)) * 128, ch = (warp & 1) * 4 + ((lane >> 3) & 1);
            #pragma unroll 1
            for (int pass = 0; pass * 18 < nst; pass++) {
                float acc[2][4] = {};
                #pragma unroll 1
                for (int st = 0; st < 18; st++) {
                    const uint32_t sa = sm + OFF_SILU + (16 * st + q) * 4;
                    const uint32_t b0 = lds32(sa), b1 = lds32(sa + 16), b2 = lds32(sa + 32), b3 = lds32(sa + 48);
                    mbar_wait(bars + 8 * (BAR_X + sl), ph);
                    #pragma unroll
                    for (int m = 0; m < 2; m++) {
                        uint32_t a[4], a2[4];
                        const uint32_t ad = ad0 + sl * 28672 + ((ch + 2 * m) ^ (lane & 7)) * 16;
                        ldsm4t(a, ad); ldsm4t(a2, ad + 2048);
                        mma_bf(acc[m], a, b0, b1); mma_bf(acc[m], a2, b2, b3);
                    }
                    if (elect()) mbar_arrive(bars + 8 * (BAR_X + 6 + sl));
                    if (++sl == 6) { sl = 0; ph ^= 1; }
                }
                const int cb = 28 * pass + 7 * (b - 128) + (warp >> 1), gg = (g >> 1) + 4 * q;
                uint32_t w[2];
                #pragma unroll
                for (int m = 0; m < 2; m++) {
                    float v = bf_round(q ? acc[m][2] : acc[m][0]); if (cb >= 27) v *= 0.5f; else if (cb >= 18) v += 1.f;
                    w[m] = max(pack_bf(v, __shfl_xor_sync(~0u, v, 4)), 1u);
                }
                if (q < 2 && !(g & 1)) {
                    const int qq = (warp & 1) * 2;
                    if (cb < 27) asm volatile("st.relaxed.gpu.global.v2.u32 [%0], {%1, %2};" :: "l"(p.scr->modc + 32 * cb + 4 * gg + qq), "r"(w[0]), "r"(w[1]) : "memory");
                    else if (cb < 36) { uint32_t* o = p.scr->modc + 896 + 32 * (cb - 27) + 8 * qq + gg; o[0] = w[0]; o[8] = w[1]; }
                }
                if (tid == 0 && pass == 0) PROFT(25);
                bar_sync(1, 448);
                if (tid == 0) { fence_async_g(); red_release(g_cnt + (CNT_NC + pass) * 32); }
                __syncwarp();
            }
            fence_async_s();
        }
        __syncthreads();
    } else {
        uint32_t ta[QA * 4];
        if (strip && (warp >> 2) == 2) {
            const int w = warp - 8;
            const uint32_t ra = sm + OFF_STRIP + (144 * w + (lane & 7) + 8 * (lane >> 4)) * 64, sw = (lane >> 1) & 3, ch = (lane >> 3) & 1;
            float acc[2][2][4] = {};
            mbar_wait(bars + 8 * (BAR_ST + w), 0);
            #pragma unroll
            for (int u = 0; u < 9; u++)
                #pragma unroll
                for (int m = 0; m < 2; m++) { uint32_t a[4]; ldsm4t(a, ra + u * 1024 + ((ch + 2 * m) ^ sw) * 16); mma_bf(acc[u & 1][m], a, sb[2 * u], sb[2 * u + 1]); }
            #define PICK(a_) ((q & 2) ? ((q & 1) ? a_[1][2] : a_[1][0]) : ((q & 1) ? a_[0][2] : a_[0][0]))
            sts32(sm + OFF_RED + ((8 * q + g) * 4 + w) * 4, __float_as_uint(PICK(acc[0]) + PICK(acc[1])));
            if (tid == 256) PROFT(0);
            bar_sync(10, 128);
            if (warp == 8) {
                mbar_wait(bars + 8 * BAR_TAB, 0);
                const uint4 v = lds128(sm + OFF_RED + lane * 16);
                float sum = bf_round((__uint_as_float(v.x) + __uint_as_float(v.y)) + (__uint_as_float(v.z) + __uint_as_float(v.w)));
                if (b >= 36) sum = bf_round(1.f + sum);
                st_relaxed(g_mod + b * 16 + (lane & 16) + (lane & 1) * 8 + ((lane & 15) >> 1), (fabsf(sum) < 8.f ? pack_h(0.f, sum) : __float_as_uint(sum) | 0x8000u) | ((lds32(sm + OFF_EPOCH) + 1) & 0x7FFFu));
                asm volatile("bar.arrive 11, 416;" ::: "memory");
                if (tid == 256) PROFT(1);
            }
        }
        mbar_wait(bars + 8 * BAR_TAB, 0);
        load_tab<QA>(ta, sm + OFF_TAB + lane * 16);
        epoch = lds32(sm + OFF_EPOCH);
        const uint32_t tag = (epoch + 1) & 0x7FFFu;
        auto w_prefetch = [&]() {
            if (warp >= 14 && elect()) asm volatile("cp.async.bulk.prefetch.L2.global [%0], 9248;" :: "l"((warp == 14 ? p.wr : p.wi) + b * 4624) : "memory");
            __syncwarp();
        };
        uint32_t nb[2][5];
        uint4 mv = make_uint4(tag, tag, tag, tag);
        const bool poller = warp < 8 || warp == 12;
        const int mc = warp < 8 ? tid : tid - 128, mst = (mc >> 2) % 36, midx = (mc < 144 ? 10 : 0) + 5 * ((mc >> 1) & 1) + (mst >> 3);
        const uint32_t* mp = g_mod + mc * 4;
        const uint32_t ma = sm + OFF_MODA + ((midx >> 2) * 32 + (mc & 1) * 16 + (mst & 3)) * 16 + (midx & 3) * 4 + ((mst >> 2) & 1) * 2;
        #define MOD_MISSING ((((mv.x ^ tag) | (mv.y ^ tag) | (mv.z ^ tag) | (mv.w ^ tag)) & 0x7FFFu) != 0)
        if (strip && (warp >> 2) != 2) bar_sync(11, 416);
        #pragma unroll
        for (int i = 0; i < 9; i++) one[i] = lds32(sm + OFF_TAB + (QA - 1) * 512 + i * 16 + 8);
        hb();
        mbar_wait(bars + 8 * (BAR_X + warp), 0);
        if (poller) mv = ldx128(mp);
        PROF0(28);
        #pragma unroll
        for (int i = 0; i < 9; i++) xw[i] = lds32(sm + OFF_STAGE + warp * 1152 + (32 * i + 8 * q + g) * 4);
        {
            float r, mr;
            ln_stats(xw, one, g, q, r, mr);
            #pragma unroll
            for (int pp = 0; pp < 5; pp++) {
                nb[0][pp] = pack_h(fmaf(bf_lo(xw[2 * pp]), r, mr), pp < 4 ? fmaf(bf_lo(xw[pp < 4 ? 2 * pp + 1 : 0]), r, mr) : 0.f);
                nb[1][pp] = pack_h(fmaf(bf_hi(xw[2 * pp]), r, mr), pp < 4 ? fmaf(bf_hi(xw[pp < 4 ? 2 * pp + 1 : 0]), r, mr) : 0.f);
            }
        }
        PROF0(2);
        w_prefetch();
        if (poller && MOD_MISSING) mv = ldx128(mp);
        if (warp < 8) {
            if (warp >= 4) sts16(sm + OFF_MODA + ((warp - 3) * 32 + lane) * 16 + (warp - 4) * 4 + 2, 0);
            const int k1 = tid & 15, s1 = tid >> 4;
            float s, c;
            __sincosf((float)(((k1 * (128 * s1 + b) + 1024) & 2047) - 1024) * (3.14159265358979f / 1024.f), &s, &c); s *= 0.25f; c *= 0.25f;
            const int rf = ((s1 >> 3) * 4 + (k1 >> 2)) * 2 + ((s1 >> 2) & 1), ri = ((k1 >> 3) * 4 + (s1 >> 2)) * 2 + ((k1 >> 2) & 1);
            const uint32_t af = sm + OFF_B3 + ((rf >> 2) * 32 + (k1 & 3) * 8 + (s1 & 3)) * 16 + (rf & 3) * 4;
            const uint32_t ai = sm + OFF_B3 + 2048 + ((ri >> 2) * 32 + (s1 & 3) * 8 + (k1 & 3)) * 16 + (ri & 3) * 4;
            sts32(af, pack_h(c, s)); sts32(af + 64, pack_h(-s, c)); sts32(ai, pack_h(c, -s)); sts32(ai + 64, pack_h(s, c));
        }
        if (poller) {
            for (int it = 0; __any_sync(~0u, MOD_MISSING); it++) { if (MOD_MISSING) mv = ldx128(mp); hb(); if (it > SPIN_LIMIT) __trap(); }
            sts16(ma, mv.x >> 16); sts16(ma + 64, mv.y >> 16); sts16(ma + 128, mv.z >> 16); sts16(ma + 192, mv.w >> 16);
        }
        uint32_t redo = 0; asm volatile("" : "+r"(redo));
        #pragma unroll 1
        do { if (redo) {
            const uint32_t w[4] = {mv.x, mv.y, mv.z, mv.w}; float f[4]; uint32_t big = 0;
            #pragma unroll
            for (int e = 0; e < 4; e++) { f[e] = (w[e] & 0x8000u) ? bf_hi(w[e]) : __half2float(__ushort_as_half(w[e] >> 16)); big = max(big, __float_as_uint(f[e]) << 1 >> 24); }
            sts32(sm + OFF_HEXP + warp * 4, __reduce_max_sync(~0u, big));
            __syncthreads();
            hexp = min(__reduce_max_sync(~0u, lds32(sm + OFF_HEXP + (lane & 15) * 4)), 253u) - 127;
            const float sc = __uint_as_float((127 - hexp) << 23);
            if (poller) {
                #pragma unroll
                for (int e = 0; e < 4; e++) sts16(ma + 64 * e, pack_h(f[e] * sc, 0.f));
            }
            mv = make_uint4(0, 0, 0, 0);
          }
          redo = __syncthreads_or((mv.x | mv.y | mv.z | mv.w) & 0x8000u);
          asm volatile("" : "+r"(redo));
        } while (redo);
        PROF0(3);
        asm volatile("barrier.cluster.arrive.relaxed.aligned;" ::: "memory");
        if (warp >= 13 && elect()) {
            if (warp == 15) bulk_load(sm + OFF_TAB + QA * 512, p.tab->w + QA * 128, (QB + QC) * 512, bars + 8 * BAR_TAB2);
            else tma3(sm + OFF_WRAW + (warp - 13) * 14336, warp == 13 ? &tm_wr : &tm_wi, wc0 & ~7, 0, 0, bars + 8 * BAR_W);
        }
        __syncwarp();
        {
            uint32_t md[20];
            load_tab<5>(md, sm + OFF_MODA + lane * 16);
            #pragma unroll
            for (int v = 0; v < 2; v++)
                #pragma unroll
                for (int pp = 0; pp < 5; pp++) nb[v][pp] = hfma2(nb[v][pp], md[v * 5 + pp], md[10 + v * 5 + pp]);
        }
        uint32_t re[3][2], im[3][2];
        #pragma unroll
        for (int mt = 0; mt < 3; mt++)
            #pragma unroll
            for (int v = 0; v < 2; v++) {
                re[mt][v] = 0; im[mt][v] = 0;
                mma_h8(re[mt][v], im[mt][v], ta[24 + 2 * mt], ta[25 + 2 * mt], nb[v][4]);
                mma_h(re[mt][v], im[mt][v], ta[mt * 8], ta[mt * 8 + 1], ta[mt * 8 + 2], ta[mt * 8 + 3], nb[v][0], nb[v][1]);
                mma_h(re[mt][v], im[mt][v], ta[mt * 8 + 4], ta[mt * 8 + 5], ta[mt * 8 + 6], ta[mt * 8 + 7], nb[v][2], nb[v][3]);
                cmul_neg(re[mt][v], im[mt][v], ta[30 + (mt * 2 + v) * 2], ta[31 + (mt * 2 + v) * 2]);
            }
        const uint32_t srow = sm + OFF_SPEC + warp * (SPEC_P * 4);
        #pragma unroll
        for (int nt = 0; nt < 2; nt++) {
            uint32_t o[2][4];
            #pragma unroll
            for (int v = 0; v < 2; v++) {
                const uint32_t b0 = ta[42 + (v * 2 + nt) * 2], b1 = ta[43 + (v * 2 + nt) * 2];
                o[v][0] = o[v][1] = o[v][2] = o[v][3] = 0;
                mma_h(o[v][0], o[v][1], re[0][v], re[1][v], im[0][v], im[1][v], b0, b1);
                mma_h(o[v][2], o[v][3], re[2][0], re[2][1], im[2][0], im[2][1], b0, b1);
            }
            const uint32_t a = srow + (g + 72 * q + 36 * nt) * 4, a2 = srow + (288 - g - 72 * q - 36 * nt) * 4;
            sts32(a, hadd2(o[0][0], o[1][0])); sts32(a + 32, hadd2(o[0][1], o[1][1])); if (g < 3) sts32(a + 64, hadd2(o[0][2], o[1][3]));
            if (g > 0 || (q == 0 && nt == 0)) sts32(a2, hsub2(o[0][0], o[1][0]) ^ 0x80000000u);
            sts32(a2 - 32, hsub2(o[0][1], o[1][1]) ^ 0x80000000u); if (g < 2) sts32(a2 - 64, hsub2(o[0][2], o[1][3]) ^ 0x80000000u);
        }
        uint32_t b3[16];
        if (warp < 10) load_tab<4>(b3, sm + OFF_B3 + lane * 16);
        __syncthreads();
        t_st = clk32();
        PROF0(4);
        if (warp < 10) {
            uint4 V[4], o[4];
            #pragma unroll
            for (int u = 0; u < 4; u++) V[u] = lds128(scol + u * (16 * SPEC_P));
            radix16(V, b3, o);
            #pragma unroll
            for (int nt = 0; nt < 4; nt++) { o[nt].x |= 1u; if (warp < 9 || g < 2) stx128(tptr + nt * tstr, o[nt]); }
        }
        PROF0(5);
    }

    int role = 0;
    asm volatile("barrier.cluster.wait.aligned;" ::: "memory");
    if (warp >= 12) {
        const int t = tid - 384;
        if (tid == 448 && rank == 0) {
            uint32_t smid; asm volatile("mov.u32 %0, %%smid;" : "=r"(smid));
            const uint32_t tp = smid >> 1;
            uint32_t pr = tp < 32 ? (tp & 7) * 8 + (tp >> 3) : tp < 60 ? (1 + (tp - 32) % 7) * 8 + 4 + (tp - 32) / 7 : tp < 62 ? 4 + tp : tp < 66 ? tp - 58 : 0;
            while (atomicExch(g_slot + pr, epoch + 1) == epoch + 1) pr = pr == 65 ? 0 : pr + 1;
            #pragma unroll
            for (int r = 0; r < 2; r++)
                asm volatile("st.async.weak.shared::cluster.mbarrier::complete_tx::bytes.u32 [%0], %1, [%2];" :: "r"(mapa(sm + OFF_MISC, r)), "r"(pr), "r"(mapa(bars + 8 * BAR_ROLE, r)) : "memory");
        }
        __syncwarp();
        if (t == 0) {
            asm volatile("prefetch.tensormap [%0];" :: "l"(&tm_w1a) : "memory");
            asm volatile("prefetch.tensormap [%0];" :: "l"(&tm_h3a) : "memory"); asm volatile("prefetch.tensormap [%0];" :: "l"(&tm_w1b) : "memory");
            asm volatile("prefetch.tensormap [%0];" :: "l"(&tm_h3b) : "memory"); asm volatile("prefetch.tensormap [%0];" :: "l"(&tm_w2) : "memory");
            asm volatile("prefetch.tensormap [%0];" :: "l"(&tm_o) : "memory"); asm volatile("prefetch.tensormap [%0];" :: "l"(&tm_h3s) : "memory");
        }
        __syncwarp();
        if (rowcta) {
            spin_until(t0 + NCP);
            uint4 v[2];
            v[1] = make_uint4(1, 1, 1, 1);
            for (int it = 0;; it++) {
                v[0] = ldx128(p.scr->modc + 4 * t); if (t < 88) v[1] = ldx128(p.scr->modc + 512 + 4 * t);
                if (__all_sync(~0u, min(min(min(v[0].x, v[0].y), min(v[0].z, v[0].w)), min(min(v[1].x, v[1].y), min(v[1].z, v[1].w))) != 0)) break;
                __nanosleep(100); if (it > SPIN_LIMIT) __trap();
            }
            if (t < 72) { const uint32_t sc = ((127 + hexp) << 7) * 0x10001u;
                v[0] = make_uint4(bfma2(v[0].x, sc, 0x80008000u), bfma2(v[0].y, sc, 0x80008000u), bfma2(v[0].z, sc, 0x80008000u), bfma2(v[0].w, sc, 0x80008000u)); }
            #pragma unroll
            for (int u = 0; u < 2; u++) if (u == 0 || t < 88) {
                const uint32_t a = sm + OFF_MODC + (((t >> 5) + 4 * u) * 32 + 4 * (t & 7)) * 16 + ((t >> 3) & 3) * 4;
                sts32(a, v[u].x); sts32(a + 16, v[u].y); sts32(a + 32, v[u].z); sts32(a + 48, v[u].w);
            }
            __syncwarp();
            if (elect()) mbar_arrive(bars + 8 * BAR_NC);
            if (t == 0) PROFT(29);
        }
    } else if (rowcta && warp < 11) {
        const int nw = !(b & 1) ? 10 : (b & 7) == 7 ? 9 : 8;
        const int cm = (b >> 3) * 288 + (b & 7) * 32, cx = (b & 1) ? 4608 + 8 * (b >> 3) : (b >> 3) * 288 + 256 + 4 * (b & 7);
        auto load_in = [&]() {
            if (elect()) {
                mbar_expect(bars + 8 * BAR_XB, nw > 8 ? 20480 : 16384);
                tma2(sm + OFF_STAGE, &tm_t, cm, 0, bars + 8 * BAR_XB);
                if (nw > 8) tma2(sm + OFF_STX, &tm_tx, cx, 0, bars + 8 * BAR_XB);
            }
            __syncwarp();
        };
        if (warp == 10) { fence_async_s(); spin_until(t_st + X1D); load_in(); }
        uint32_t tb[QB * 4], wre[4][2], wim[4][2];
        if (warp < nw) {
            mbar_wait(bars + 8 * BAR_TAB2, 0);
            load_tab<QB>(tb, sm + OFF_TAB + QA * 512 + lane * 16);
            mbar_wait(bars + 8 * BAR_W, 0);
            const int off = wc0 & 7;
            const uint32_t wa = sm + OFF_WRAW + lane * 112 + ((off >> 1) + 2 * warp) * 4, sh = (off & 1) * 16;
            #pragma unroll
            for (int c = 0; c < 2; c++)
                #pragma unroll
                for (int h = 0; h < 2; h++) {
                    uint32_t y[2][2];
                    #pragma unroll
                    for (int e = 0; e < 2; e++) {
                        const uint32_t a = wa + c * 14336 + (h + 2 * e) * 3584, x0 = lds32(a), x1 = lds32(a + 4), x2 = lds32(a + 8);
                        y[e][0] = __funnelshift_r(x0, x1, sh); y[e][1] = __funnelshift_r(x1, x2, sh);
                    }
                    #pragma unroll
                    for (int x = 0; x < 4; x++) {
                        const uint32_t v = (x & 1) ? pack_h(bf_hi(y[0][x >> 1]), bf_hi(y[1][x >> 1])) : pack_h(bf_lo(y[0][x >> 1]), bf_lo(y[1][x >> 1]));
                        if (c) wim[x][h] = v; else wre[x][h] = v;
                    }
                }
        }
        const uint32_t ca = warp < 8 ? sm + OFF_STAGE + lane * 128 + (warp ^ (lane & 7)) * 16 : sm + OFF_STX + lane * 32 + ((warp ^ g) & 1) * 16, cs = warp < 8 ? 4096 : 1024;
        uint32_t V[4][4];
        for (int it = 0;; it++) {
            mbar_wait(bars + 8 * BAR_XB, it & 1);
            uint32_t ok = 1;
            if (warp < nw) {
                #pragma unroll
                for (int u = 0; u < 4; u++) { uint4 t4 = lds128(ca + u * cs); V[u][0] = t4.x; V[u][1] = t4.y; V[u][2] = t4.z; V[u][3] = t4.w; ok &= t4.x; }
            }
            asm volatile("{.reg .pred p; setp.ne.u32 p, %0, 0; bar.red.and.pred p, 1, 352, p; selp.u32 %0, 1, 0, p;}" : "+r"(ok) :: "memory");
            if (ok) break;
            if (warp == 10) { load_in(); hb(); }
            if (it > SPIN_LIMIT / 64) __trap();
        }
        PROF0(7);
        if (warp < nw) {
            uint32_t zr[4][2], zi[4][2];
            #pragma unroll
            for (int x = 0; x < 4; x++) {
                uint32_t er = 0, ei = 0, or_ = 0, oi = 0;
                mma_h(er, ei, tb[0], tb[1], tb[2], tb[3], V[0][x], V[1][x]);
                mma_h(or_, oi, tb[4], tb[5], tb[6], tb[7], V[2][x], V[3][x]);
                uint32_t r0 = hadd2(er, or_), r1 = hsub2(er, or_), i0 = hadd2(ei, oi), i1 = hsub2(ei, oi);
                cmul_neg(r0, i0, tb[8], tb[9]); cmul_neg(r1, i1, tb[10], tb[11]);
                uint32_t xr0 = 0, xr1 = 0, xi0 = 0, xi1 = 0;
                mma_h(xr0, xr1, r0, r1, i0, i1, tb[12], tb[13]);
                mma_h(xi0, xi1, r0, r1, i0, i1, tb[14], tb[15]);
                cmul_pos(xr0, xi0, wre[x][0], wim[x][0]); cmul_pos(xr1, xi1, wre[x][1], wim[x][1]);
                r0 = 0; i0 = 0; r1 = 0; i1 = 0;
                mma_h(r0, i0, tb[12], tb[13], tb[14], tb[15], xr0, xi0);
                mma_h(r1, i1, tb[12], tb[13], tb[14], tb[15], xr1, xi1);
                cmul_pos(r0, i0, tb[16], tb[17]); cmul_pos(r1, i1, tb[18], tb[19]);
                zr[x][0] = hadd2(r0, r1); zr[x][1] = hsub2(r0, r1); zi[x][0] = hadd2(i0, i1); zi[x][1] = hsub2(i0, i1);
            }
            #pragma unroll
            for (int nt = 0; nt < 4; nt++) {
                uint4 o = make_uint4(0, 0, 0, 0);
                const int h = nt >> 1;
                mma_h(o.x, o.y, zr[0][h], zr[1][h], zi[0][h], zi[1][h], tb[20 + 2 * nt], tb[21 + 2 * nt]);
                mma_h(o.z, o.w, zr[2][h], zr[3][h], zi[2][h], zi[3][h], tb[20 + 2 * nt], tb[21 + 2 * nt]);
                o.x &= ~1u;
                sts128(ca + nt * cs, o);
            }
        }
        fence_async_s();
        bar_sync(1, 352);
        t_st = clk32();
        PROF0(8);
        if (warp == 10 && elect()) {
            asm volatile("cp.async.bulk.tensor.2d.global.shared::cta.bulk_group [%0, {%2, %3}], [%1];" :: "l"(&tm_t), "r"(sm + OFF_STAGE), "r"(cm), "r"(0) : "memory");
            if (nw > 8) asm volatile("cp.async.bulk.tensor.2d.global.shared::cta.bulk_group [%0, {%2, %3}], [%1];" :: "l"(&tm_tx), "r"(sm + OFF_STX), "r"(cx), "r"(0) : "memory");
            asm volatile("cp.async.bulk.commit_group;" ::: "memory");
            asm volatile("cp.async.bulk.wait_group.read 0;" ::: "memory");
        }
        __syncwarp();
    }

    if (warp >= 10) { mbar_wait(bars + 8 * BAR_ROLE, 0); role = __shfl_sync(~0u, lds32(sm + OFF_MISC), 0); fence_async_s(); }
    auto first_a = [&]() {
        if (warp >= 10 && role < 64 && elect()) {
            const int it = warp - 10, hi = it >= 3; const bool p2 = it - 3 * hi == 2;
            tma4(sm + OFF_A + it * A_BYTES, p2 ? &tm_w1b : &tm_w1a, 0, 0, p2 ? 64 * rank + 8 * hi : 4 * (it - hi),
                 9 * (role >> 3) + (p2 ? 8 : (role & 4) + 2 * rank), bars + 8 * (BAR_FULL + it));
        }
        __syncwarp();
    };
    if (!rowcta) first_a();
    else {
        uint32_t tc[20], md[28];
        mbar_wait(bars + 8 * BAR_TAB2, 0);
        load_tab<5>(tc, sm + OFF_TAB + (QA + QB) * 512 + lane * 16);
        bool md_early = warp >= 10;
        if (md_early) { mbar_wait(bars + 8 * BAR_NC, 0); load_tab<7>(md, sm + OFF_MODC + lane * 16); }
        if (warp < 10) {
            uint32_t b3[16];
            load_tab<4>(b3, sm + OFF_B3 + 2048 + lane * 16);
            uint4 V[4], o[4];
            const bool tact = warp < 9 || g == 0;
            spin_until(t_st + X2D);
            #pragma unroll
            for (int u = 0; u < 4; u++) { V[u] = make_uint4(0, 0, 0, 0); if (tact) V[u] = ldx128(tptr + u * tstr); }
            md_early = __any_sync(~0u, mbar_test(bars + 8 * BAR_NC, 0));
            if (md_early) load_tab<7>(md, sm + OFF_MODC + lane * 16);
            for (int it = 0; __any_sync(~0u, (V[0].x | V[1].x | V[2].x | V[3].x) & 1u); it++) {
                #pragma unroll
                for (int u = 0; u < 4; u++) if (V[u].x & 1u) V[u] = ldx128(tptr + u * tstr);
                hb();
                if (it > SPIN_LIMIT) __trap();
            }
            PROF0(10);
            radix16(V, b3, o);
            if (tact) {
                #pragma unroll
                for (int nt = 0; nt < 4; nt++) sts128(scol + nt * (16 * SPEC_P), o[nt]);
            }
        }
        __syncthreads();
        PROF0(11);
        first_a();
        const uint32_t srow = sm + OFF_SPEC + warp * (SPEC_P * 4);
        uint32_t re[2][3], im[2][3];
        #pragma unroll
        for (int mt = 0; mt < 3; mt++) {
            const uint32_t a = srow + (g + 72 * q + 8 * mt) * 4, a2 = srow + (288 - g - 72 * q - 8 * mt) * 4;
            const uint32_t z0 = lds32(a), z1 = lds32(a + 144), z2 = lds32(a2), z3 = lds32(a2 - 144);
            #pragma unroll
            for (int m2 = 0; m2 < 2; m2++) {
                re[m2][mt] = 0; im[m2][mt] = 0;
                const uint32_t sg = m2 ? 0x3C00BC00u : 0xBC003C00u;
                mma_h(re[m2][mt], im[m2][mt], tc[m2 * 4], tc[m2 * 4 + 1], tc[m2 * 4 + 2], tc[m2 * 4 + 3], hfma2(z2, sg, z0), hfma2(z3, sg, z1));
                cmul_pos(re[m2][mt], im[m2][mt], tc[8 + (m2 * 3 + mt) * 2], tc[9 + (m2 * 3 + mt) * 2]);
            }
        }
        float y[20];
        WG_FENCE();
        #pragma unroll
        for (int mt = 0; mt < 3; mt++)
            wgmma40_rs(y, re[0][mt], re[1][mt], im[0][mt], im[1][mt], desc_lo(OFF_TAB + (QA + QB + 5) * 512 + mt * 1280, 128), mt);
        WG_COMMIT();
        if (!md_early) { mbar_wait(bars + 8 * BAR_NC, 0); load_tab<7>(md, sm + OFF_MODC + lane * 16); }
        WG_WAIT(0);
        #pragma unroll
        for (int i = 0; i < 9; i++) xw[i] = bfma2(md[i], pack_bf(y[4 * (i >> 1) + (i & 1)], y[4 * (i >> 1) + 2 + (i & 1)]), xw[i]);
        float r, mr;
        ln_stats(xw, one, g, q, r, mr);
        uint32_t r2 = pack_bf(r, r), m2 = pack_bf(mr, mr);
        #pragma unroll
        for (int i = 0; i < 9; i++) {
            sts32(sm + OFF_X1 + warp * 1152 + (32 * i + 8 * q + g) * 4, xw[i]);
            xw[i] = bfma2(bfma2(xw[i], r2, m2), md[18 + i], md[9 + i]);
        }
        ln_stats(xw, one, g, q, r, mr);
        r2 = pack_bf(r, r); m2 = pack_bf(mr, mr);
        {
            const int n7 = 2 * q + (g >> 2);
            const uint32_t a = sm + OFF_STAGE + (warp >> 3) * 9216 + n7 * 128 + ((warp & 7) ^ n7) * 16 + (g & 3) * 4;
            #pragma unroll
            for (int i = 0; i < 9; i++) sts32(a + i * 1024, bfma2(xw[i], r2, m2));
        }
        fence_async_s();
        __syncthreads();
        PROF0(12);
        if (tid == 0) {
            asm volatile("cp.async.bulk.tensor.4d.global.shared::cta.bulk_group [%0, {%2, %2, %2, %3}], [%1];" :: "l"(&tm_h3s), "r"(sm + OFF_STAGE), "r"(0), "r"(b) : "memory");
            asm volatile("cp.async.bulk.commit_group;" ::: "memory");
        }
    }
    if (!rowcta) __syncthreads();
    else {
        if (tid == 0) { asm volatile("cp.async.bulk.wait_group 0;" ::: "memory"); fence_async_g(); red_release(g_cnt + CNT_H3 * 32); }
        PROF0(13);
        if (warp == 15) {
            __nanosleep(X1DELAY);
            #pragma unroll 1
            for (int r = 0; r < 16; r++) {
                uint4* dst = (uint4*)(p.out + (size_t)(b + 128 * r) * D_) + lane;
                const uint32_t src = sm + OFF_X1 + r * 1152 + lane * 16;
                dst[0] = lds128(src); dst[32] = lds128(src + 512); if (lane < 8) dst[64] = lds128(src + 1024);
                const uint32_t t1 = clk32(); while ((int)(clk32() - t1) < X1PACE) __nanosleep(50);
            }
            __syncwarp();
            if (lane == 0) { fence_async_g(); red_release(g_cnt + CNT_X1 * 32); }
        }
    }
    role = __shfl_sync(~0u, lds32(sm + OFF_MISC), 0);
    if ((sm & 0xFFFFFFu) != SM0) __trap();
    if (role >= 64) { if (warp == 0) PROFDUMP(); return; }

    const int gi = role >> 3, dt = role & 3, c2 = (role >> 2) & 1;
    const int wg = warp >> 2, wi = warp & 3;
    if (wg == 3) {
        uint32_t so = 0, eph = 1;
        #define RING_STEP(BYTES, OFF, ISSUE) do { \
            mbar_wait(bars + 8 * BAR_EMPTY + so, eph); \
            if (elect()) { const uint32_t fb = bars + 8 * BAR_FULL + so, dst = sm + (OFF) + so * ((BYTES) / 8); mbar_expect(fb, BYTES); ISSUE; } \
            so += 8; if (so == 8 * NST) { so = 0; eph ^= 1; } } while (0)
        const uint32_t kbt = g2_kb(lane, rank, gi, c2) | (g2_kb(32 + (lane & 3), rank, gi, c2) << 8);
        #define KB(n_) ((__shfl_sync(~0u, kbt, (n_) & 31) >> (((n_) >> 2) & 8)) & 255)
        if (warp == 12) {
            eph = 0;
            const int fb1 = 9 * gi + 4 * c2 + 2 * rank, sb2 = 4 * gi + 2 * c2;
            int pft = dt, pfj = 4 * (PF0 + PFS * dt);
            #pragma unroll 1
            for (int j = 16; j < 128; j += 4) {
                RING_STEP(A_BYTES, OFF_A, tma4(dst, &tm_w1a, 0, 0, j, fb1, fb));
                if (j < 64) { if (j & 4) RING_STEP(A_BYTES, OFF_A, tma4(dst, &tm_w1b, 0, 0, 64 * rank + j - 4, 9 * gi + 8, fb)); }
                if (j == pfj && pft < PFN) {
                    const int kb = KB(pft); pft += 4; pfj += 16 * PFS;
                    if (elect()) asm volatile("cp.async.bulk.prefetch.tensor.3d.L2.global [%0, {%1, %2, %3}];" :: "l"(&tm_w2), "r"(0), "r"(64 * kb), "r"(sb2) : "memory");
                }
            }
            #pragma unroll 1
            for (int n = 0; n < 36; n++) {
                const int kb = KB(n);
                RING_STEP(A_BYTES, OFF_A, tma3(dst, &tm_w2, 0, 64 * kb, sb2, fb));
            }
        } else if (warp == 13) {
            const uint32_t e1 = __shfl_sync(~0u, epoch + 1, 0);
            fence_async_s();
            wait_count<0>(g_cnt + CNT_H3 * 32, e1 * 128);
            fence_async_g();
            if (lane == 0) PROFT(14);
            #pragma unroll 1
            for (int j = 0; j < 128; j += 4) {
                RING_STEP(B_BYTES, OFF_B, tma3(dst, &tm_h3a, 0, 18 * dt, j, fb));
                if (j < 64 && (j & 4)) RING_STEP(B_BYTES, OFF_B, tma3(dst, &tm_h3b, 0, 18 * dt + 9 * c2, 64 * rank + j - 4, fb));
            }
            int n = 0;
            #pragma unroll 1
            for (int cls = 0; cls < 3; cls++) {
                mbar_wait(bars + 8 * (BAR_UOK + cls), 0);
                fence_async_g();
                if (cls == 1 && lane == 0) PROFT(19);
                if (cls == 0 && lane == 0) PROFT(22);
                static_assert((IT_G2 + 4) % NST != NST - 1, "no wrap at the skipped stage");
                if (cls == 1) { n++; so += 8; }
                #pragma unroll 1
                for (; n < (cls == 0 ? 4 : cls == 1 ? 21 : 36); n++) {
                    const int kb = KB(n);
                    RING_STEP(B_BYTES, OFF_B, bulk_load(dst, g_U + (kb * 4 + dt) * 1152, B_BYTES, fb));
                }
            }
            if (role == 0 && rank == 0 && lane == 0) st_relaxed(g_cnt + CNT_EPOCH * 32, e1);
        } else if (warp == 15) {
            if (elect()) mbar_arrive_remote(mapa(bars + 8 * BAR_HOLD, rank ^ 1));
            __syncwarp();
            bar_sync(6, 160);
            if (elect()) mbar_arrive(bars + 8 * (BAR_FULL + (IT_G2 + 4) % NST));
            __syncwarp();
            mbar_wait(bars + 8 * BAR_W1GO, 0);
            if (elect()) {
                char* dst = (char*)(g_U + ((9 * gi + 4 * c2 + 2 * rank + 1) * 4 + dt) * 1152);
                #pragma unroll 1
                for (int i = 0; i < W1N; i++) {
                    asm volatile("cp.async.bulk.global.shared::cta.bulk_group [%0], [%1], %2;" :: "l"(dst + i * (18432 / W1N)), "r"(sm + OFF_X1 + i * (18432 / W1N)), "n"(18432 / W1N) : "memory");
                    const uint32_t t1 = clk32(); while ((int)(clk32() - t1) < W1P) {}
                }
                asm volatile("cp.async.bulk.commit_group;" ::: "memory");
                asm volatile("cp.async.bulk.wait_group 0;" ::: "memory");
                fence_async_g(); red_release(g_cnt + (CNT_U + 16) * 32);
                #pragma unroll 1
                for (int n = 0; n < 4; n++) { __nanosleep(300); tma2(sm + OFF_X1 + n * 4608, &tm_o, 144 * dt, 256 * gi + 128 * c2 + 64 * (rank ^ 1) + 16 * n, bars + 8 * BAR_XT); }
            }
        } else {
            const uint32_t e1 = epoch + 1;
            if (lane == 0) {
                __nanosleep(4000);
                wait_count<200>(g_cnt + CNT_NC * 32, e1 * 4); wait_count<200>(g_cnt + (CNT_NC + 1) * 32, e1 * 2);
                fence_async_g();
                mbar_expect(bars + 8 * BAR_GB, 1152);
                bulk_load(sm + OFF_GB, p.scr->modc + 896, 1152, bars + 8 * BAR_GB);
                wait_count<200>(g_cnt + CNT_X1 * 32, e1 * 128);
                if (role * 2 + rank < 108) {
                    uint4* z = (uint4*)p.scr->modc + (role * 2 + rank) * 2; z[0] = z[1] = make_uint4(0, 0, 0, 0);
                }
                wait_count<50>(g_cnt + (CNT_U + dt * 2 + rank) * 32, e1 * 16);
                mbar_arrive(bars + 8 * BAR_UOK);
            }
            __syncwarp();
            bar_sync(4, 160);
            if (lane == 0) {
                fence_async_g(); red_release(g_cnt + (CNT_U + 8) * 32);
                PROFT(17);
                wait_count<0>(g_cnt + (CNT_U + 8) * 32, e1 * 128);
                mbar_arrive(bars + 8 * (BAR_UOK + 1));
                __nanosleep(1000);
                wait_count<100>(g_cnt + (CNT_U + 16) * 32, e1 * 128);
                mbar_arrive(bars + 8 * (BAR_UOK + 2));
            }
        }
    } else if (wg == 2) {
        float d0[36];
        const float bias = bf_lo(ldg_nc16(p.b1 + 576 * gi + 512 + 16 * wi + g + 8 * rank));
        for (int it = 0; it < 200 && !__any_sync(~0u, mbar_test(bars + 8 * BAR_FULL, 0)); it++) { hb(); __nanosleep(100); }
        const bool lead = wi == 0 && elect();
        #pragma unroll 1
        for (int i = 0; i < 8; i++) {
            const uint32_t s = P2S + 3 * (i & 1);
            mbar_wait(bars + 8 * BAR_FULL + 8 * s, (i >> 1) & 1);
            const uint32_t da = desc_lo(OFF_A, 8192) + s * (A_BYTES / 16), db = desc_lo(OFF_B, 128) + s * (B_BYTES / 16);
            WG_FENCE();
            wgmma72(d0, da, db, i);
            #pragma unroll
            for (int k = 1; k < 9; k++) {
                if (k == P2K) asm volatile("{.reg .pred p; setp.ne.u32 p, %1, 0; @p mbarrier.arrive.shared::cta.b64 _, [%0];}" :: "r"(bars + 8 * (BAR_P2N + (i & 1))), "r"((uint32_t)lead) : "memory");
                if (k < 8) wgmma72(d0, da + k * 128, db + k * 144, 1);
            }
            WG_COMMIT();
            WG_WAIT(0);
            if (lead) mbar_arrive_n(bars + 8 * BAR_EMPTY + 8 * s, 2);
        }
        if (lead) PROFT(18);
        const uint32_t slot = sm + OFF_P2R + (tid & 127) * 16, ra = mapa(slot, rank ^ 1), rb = mapa(bars + 8 * BAR_P2R, rank ^ 1);
        float sv[18];
        #pragma unroll
        for (int i = 0; i < 18; i++) { const float lo = d0[4 * (i >> 1) + (i & 1)], hi = d0[4 * (i >> 1) + 2 + (i & 1)];
            sv[i] = rank ? lo : hi; d0[4 * (i >> 1) + (i & 1)] = (rank ? hi : lo) + bias; }
        mbar_wait(bars + 8 * BAR_HOLD, 0);
        #pragma unroll
        for (int i = 0; i < 4; i++)
            asm volatile("st.async.weak.shared::cluster.mbarrier::complete_tx::bytes.v4.f32 [%0], {%1,%2,%3,%4}, [%5];"
                :: "r"(ra + i * 2048), "f"(sv[4 * i]), "f"(sv[4 * i + 1]), "f"(sv[4 * i + 2]), "f"(sv[4 * i + 3]), "r"(rb) : "memory");
        asm volatile("st.async.weak.shared::cluster.mbarrier::complete_tx::bytes.v2.f32 [%0], {%1,%2}, [%3];" :: "r"(ra + 8192), "f"(sv[16]), "f"(sv[17]), "r"(rb) : "memory");
        mbar_wait(bars + 8 * BAR_P2R, 0);
        #pragma unroll
        for (int i = 0; i < 5; i++) {
            const uint4 v = lds128(slot + i * 2048);
            d0[8 * i] += __uint_as_float(v.x); d0[8 * i + 1] += __uint_as_float(v.y);
            if (i < 4) { d0[8 * i + 4] += __uint_as_float(v.z); d0[8 * i + 5] += __uint_as_float(v.w); }
        }
        asm volatile("bar.arrive 5, 256;" ::: "memory");
        gelu_store<0>(d0, (char*)(g_U + ((9 * gi + 8) * 4 + dt) * 1152) + wi * 4608 + rank * 2304 + c2 * 1152 + g * 16, q);
        bar_sync(8, 128);
        if (lead) { fence_async_g(); red_release(g_cnt + (CNT_U + dt * 2 + (gi >> 2)) * 32); PROFT(26); }
    } else {
        float d[72];
        const bool lead = wi == 0 && elect();
        const uint32_t da0 = desc_lo(OFF_A, 8192) + wg * 512;
        const bool owner = (uint32_t)wg == rank;
        const int srow = 256 * gi + 128 * c2 + 64 * wg + 16 * wi;
        const uint32_t b2w0 = ldg_nc16(p.b2 + srow + g), b2w1 = ldg_nc16(p.b2 + srow + g + 8);
        const int fr = 576 * gi + 256 * c2 + 128 * rank + 64 * wg + 16 * wi + g;
        const float bias0 = bf_lo(ldg_nc16(p.b1 + fr)), bias1 = bf_lo(ldg_nc16(p.b1 + fr + 8));
        {
            #pragma unroll
            for (int i = 0; i < 72; i++) d[i] = (i & 2) ? bias1 : bias0;
            constexpr uint32_t db1 = desc_lo(OFF_B, 128);
            static_assert(IT_G2 - LEAD1 == 6 * NST && IT_P1 == 4 * NST && P2S == 2, "loop structure");
            #define REL(s_) if (lead) mbar_arrive(bars + 8 * (BAR_EMPTY + (s_)))
            mma_block<DHI_H3, 0>(d, bars, da0, db1, 0);
            #pragma unroll 1
            for (int c = 0; c < 4; c++) {
                const uint32_t ph = c & 1;
                mma_block<DHI_H3, 1>(d, bars, da0, db1, ph); REL(0);
                mbar_wait(bars + 8 * (P2K ? BAR_P2N : BAR_FULL + 2), ph);
                mma_block<DHI_H3, 3>(d, bars, da0, db1, ph); REL(1);
                mma_block<DHI_H3, 4>(d, bars, da0, db1, ph); REL(3);
                mbar_wait(bars + 8 * (P2K ? BAR_P2N + 1 : BAR_FULL + 5), ph);
                mma_block<DHI_H3, 0>(d, bars, da0, db1, ph ^ 1); REL(4);
            }
            #pragma unroll 1
            for (uint32_t ph = 0; ph < 2; ph++) {
                mma_block<DHI_H3, 1>(d, bars, da0, db1, ph); REL(0);
                mma_block<DHI_H3, 2>(d, bars, da0, db1, ph); REL(1);
                mma_block<DHI_H3, 3>(d, bars, da0, db1, ph); REL(2);
                mma_block<DHI_H3, 4>(d, bars, da0, db1, ph); REL(3);
                mma_block<DHI_H3, 5>(d, bars, da0, db1, ph); REL(4);
                const bool pause = ph && wg == 1;
                if (pause) { WG_WAIT(0); REL(5); bar_sync(9, 256); }
                mma_block<DHI_H3, 0>(d, bars, da0, db1, ph ^ 1); if (!pause) REL(5);
            }
            #pragma unroll
            for (int i = IT_G2 - LEAD1 + 1; i < IT_G2; i++) {
                mbar_wait(bars + 8 * (BAR_FULL + i % NST), (i / NST) & 1);
                WG_FENCE();
                #pragma unroll
                for (int k = 0; k < 4; k++) {
                    if (i == IT_G2 - 1 && k == HOK1) WG_COMMIT();
                    wgmma144<DHI_H3>(d, da0 + (i % NST) * (A_BYTES / 16) + k * 128, db1 + (i % NST) * (B_BYTES / 16) + k * 288, 1);
                }
                WG_COMMIT();
                if (i == IT_G2 - 1 && HOK1 < 4) WG_WAIT(2); else WG_WAIT(1);
                REL((i - 1) % NST);
            }
            if (wg == 0) { WG_WAIT(1); asm volatile("bar.arrive 9, 256;" ::: "memory"); }
            WG_WAIT(0);
            if (lead) mbar_arrive(bars + 8 * (BAR_EMPTY + (IT_G2 - 1) % NST));
            PROF0(16);
            if (wg == 1) bar_sync(5, 256);
            char* const ub = (wg == 0 ? (char*)(g_U + ((9 * gi + 4 * c2 + 2 * rank) * 4 + dt) * 1152) : (char*)__cvta_shared_to_generic(sm + OFF_X1)) + wi * 4608 + g * 16;
            gelu_store<0>(d, ub, q); gelu_store<2>(d, ub + 2304, q); gelu_store<36>(d, ub + 1152, q); gelu_store<38>(d, ub + 3456, q);
            PROF0(27);
            if (wg == 0) asm volatile("bar.arrive 4, 160;" ::: "memory");
            else { fence_async_s(); asm volatile("bar.arrive 6, 160;" ::: "memory"); }
        }
        constexpr uint32_t db0 = desc_lo(OFF_B, 2304);
        const bool keep = role < 0;
        constexpr int IT_L = IT_END - NST;
        #pragma unroll
        for (int i = IT_G2; i <= IT_G2 + W1S; i++) {
            const uint32_t db = db0 + (i == IT_G2 + 4 ? OFF_X1 - OFF_B : (i % NST) * B_BYTES) / 16;
            mbar_wait(bars + 8 * (BAR_FULL + i % NST), (i / NST) & 1);
            WG_FENCE();
            #pragma unroll
            for (int k = 0; k < 4; k++) wgmma144<DHI_U>(d, da0 + (i % NST) * (A_BYTES / 16) + k * 128, db + k * 288, i > IT_G2 || k > 0 || keep);
            WG_COMMIT();
            if (i > IT_G2) { WG_WAIT(1); if (lead) mbar_arrive(bars + 8 * (BAR_EMPTY + (i - 1) % NST)); }
        }
        if (lead) mbar_arrive(bars + 8 * BAR_W1GO);
        const uint32_t ga0 = sm + OFF_GB + (144 * dt + 8 * q) * 2, tile = sm + OFF_X1 + wi * 4608, to = g * 288 + q * 16;
        #define QOFF(i_) (((i_) >> 2) * 2304 + 144 * (((i_) >> 1) & 1) + 64 * ((i_) & 1))
        #define SOFF(k_) (((k_) >> 1) * 2304 + 144 * ((k_) & 1) + 128 - 12 * q)
        #define DIDX(i_, k_) ((i_) < 8 ? 36 * (((i_) >> 1) & 1) + 16 * ((i_) & 1) + 4 * (k_) + 2 * ((i_) >> 2) : 36 * ((k_) & 1) + 32 + 2 * ((k_) >> 1))
        #define FIN(k_, f_) bfma2(g4.f_, pack_bf(d[DIDX(i, k_)], d[DIDX(i, k_) + 1]), xq[i].f_)
        uint4 xq[9];
        auto load_g = [&](int i) { uint4 r; if (i < 4) r = lds128(ga0 + QOFF(i)); else { r.x = r.z = lds32(ga0 + SOFF(0)); r.y = r.w = lds32(ga0 + SOFF(1)); } return r; };
        static_assert(W1S == 5 && (IT_G2 + 6) % NST == 4 && ((IT_G2 + 6) / NST) % 2 == 1 && IT_L == IT_G2 + 30, "loop structure");
        #pragma unroll 1
        for (int c = 0; c < 4; c++) {
            const uint32_t ph = c & 1, xa = tile + to; const bool xl = c == 3 && !owner;
            mma_block<DHI_U, 4>(d, bars, da0, db0, ph ^ 1); REL(3);
            mma_block<DHI_U, 5>(d, bars, da0, db0, ph ^ 1); REL(4);
            mma_block<DHI_U, 0>(d, bars, da0, db0, ph); REL(5);
            if (xl) { mbar_wait(bars + 8 * BAR_XT, 0); xq[0] = lds128(xa + QOFF(0)); xq[4] = lds128(xa + QOFF(4)); xq[1] = lds128(xa + QOFF(1)); }
            mma_block<DHI_U, 1>(d, bars, da0, db0, ph); REL(0);
            if (xl) { xq[5] = lds128(xa + QOFF(5)); xq[2] = lds128(xa + QOFF(2)); xq[6] = lds128(xa + QOFF(6)); }
            mma_block<DHI_U, 2>(d, bars, da0, db0, ph); REL(1);
            if (xl) { xq[3] = lds128(xa + QOFF(3)); xq[7] = lds128(xa + QOFF(7));
                      xq[8] = make_uint4(lds32(xa + SOFF(0)), lds32(xa + SOFF(1)), lds32(xa + SOFF(2)), lds32(xa + SOFF(3))); }
            mma_block<DHI_U, 3>(d, bars, da0, db0, ph); REL(2);
        }
        if (!owner && elect()) mbar_arrive_remote(mapa(bars + 8 * BAR_DONE, rank ^ 1));
        if (owner) { WG_WAIT(0); if (lead) mbar_arrive(bars + 8 * (BAR_EMPTY + (IT_L - 1) % NST)); bar_sync(7, 256); }
        #pragma unroll
        for (int i = IT_L; i < IT_END; i++) {
            mbar_wait(bars + 8 * (BAR_FULL + i % NST), (i / NST) & 1);
            WG_FENCE();
            #pragma unroll
            for (int k = 0; k < 4; k++) {
                if (i == IT_END - 1 && k == HOK) WG_COMMIT();
                wgmma144<DHI_U>(d, da0 + (i % NST) * (A_BYTES / 16) + k * 128, db0 + (i % NST) * (B_BYTES / 16) + k * 288, 1);
            }
            WG_COMMIT();
            if (i == IT_L) { WG_WAIT(1); if (lead && !owner) mbar_arrive(bars + 8 * (BAR_EMPTY + (IT_L - 1) % NST)); }
        }
        PROF0(9);
        mbar_wait(bars + 8 * BAR_GB, 0);
        if (!owner) {
            const uint32_t ra = mapa(tile + lane * 16, rank ^ 1), rb = mapa(bars + 8 * BAR_RECV, rank ^ 1);
            mbar_wait(bars + 8 * BAR_DONE, 0);
            uint4 gn = load_g(0);
            WG_WAIT(1);
            asm volatile("bar.arrive 7, 256;" ::: "memory");
            WG_WAIT(0);
            #pragma unroll
            for (int i = 0; i < 72; i++) d[i] = fmaf(bf_lo((i & 2) ? b2w1 : b2w0), 2.f, d[i]);
            #pragma unroll
            for (int j = 0; j < 5; j++) {
                const uint4 g4 = gn;
                if (j < 4) gn = load_g(j + 1);
                #pragma unroll
                for (int i = j < 4 ? j : 8; i < 9; i += 4) if (i < 8 || j == 4)
                    asm volatile("st.async.weak.shared::cluster.mbarrier::complete_tx::bytes.v4.b32 [%0], {%1,%2,%3,%4}, [%5];"
                        :: "r"(ra + i * 512), "r"(FIN(0, x)), "r"(FIN(1, y)), "r"(FIN(2, z)), "r"(FIN(3, w)), "r"(rb) : "memory");
            }
            PROF0(6);
            if (warp == 0) PROFDUMP();
            return;
        }
        PROF0(24);
        mbar_wait(bars + 8 * BAR_RECV, 0);
        #pragma unroll
        for (int i = 0; i < 9; i++) xq[i] = lds128(tile + lane * 16 + i * 512);
        uint4 gn = load_g(0);
        WG_WAIT(0);
        __syncwarp();
        PROF0(21);
        #pragma unroll
        for (int j = 0; j < 5; j++) {
            const uint4 g4 = gn;
            if (j < 4) gn = load_g(j + 1);
            #pragma unroll
            for (int i = j < 4 ? j : 8; i < 9; i += 4) if (i < 8 || j == 4) {
                const uint4 o = make_uint4(FIN(0, x), FIN(1, y), FIN(2, z), FIN(3, w));
                if (i < 8) sts128(tile + to + QOFF(i), o);
                else { sts32(tile + to + SOFF(0), o.x); sts32(tile + to + SOFF(1), o.y); sts32(tile + to + SOFF(2), o.z); sts32(tile + to + SOFF(3), o.w); }
            }
        }
        fence_async_s();
        __syncwarp();
        if (elect()) {
            asm volatile("cp.async.bulk.tensor.2d.global.shared::cta.bulk_group [%0, {%2, %3}], [%1];" :: "l"(&tm_o), "r"(tile), "r"(144 * dt), "r"(srow) : "memory");
            asm volatile("cp.async.bulk.commit_group;" ::: "memory");
            asm volatile("cp.async.bulk.wait_group.read 0;" ::: "memory");
        }
        PROF0(23);
        if (warp == 0) { __syncwarp(); PROFDUMP(); }
    }
}

typedef CUresult (*EncodeFn)(CUtensorMap*, CUtensorMapDataType, cuuint32_t, void*, const cuuint64_t*, const cuuint64_t*, const cuuint32_t*,
                             const cuuint32_t*, CUtensorMapInterleave, CUtensorMapSwizzle, CUtensorMapL2promotion, CUtensorMapFloatOOBfill);

void encode(EncodeFn fn, CUtensorMap* m, CUtensorMapDataType dt, int rank, const void* ptr, const cuuint64_t* dims, const cuuint64_t* strides,
            const cuuint32_t* box, CUtensorMapSwizzle sw, CUtensorMapL2promotion promo = CU_TENSOR_MAP_L2_PROMOTION_L2_128B) {
    const cuuint32_t es[5] = {1, 1, 1, 1, 1};
    fn(m, dt, rank, (void*)ptr, dims, strides, box, es, CU_TENSOR_MAP_INTERLEAVE_NONE, sw, promo, CU_TENSOR_MAP_FLOAT_OOB_FILL_NONE);
}

}

extern "C" void kernel_launch(void* const* d_in, const int* in_sizes, int n_in, void* d_out, int out_size) {
    (void)in_sizes; (void)n_in; (void)out_size;
    Params p;
    p.x = (const uint16_t*)d_in[0]; p.wr = (const uint16_t*)d_in[1]; p.wi = (const uint16_t*)d_in[2];
    p.w1 = (const uint16_t*)d_in[4]; p.b1 = (const uint16_t*)d_in[5]; p.w2 = (const uint16_t*)d_in[6]; p.b2 = (const uint16_t*)d_in[7];
    p.c = (const uint16_t*)d_in[8]; p.wmod = (const uint16_t*)d_in[9]; p.out = (uint16_t*)d_out;

    void* fnp = nullptr; cudaDriverEntryPointQueryResult qr;
    cudaGetDriverEntryPoint("cuTensorMapEncodeTiled", &fnp, cudaEnableDefault, &qr);
    EncodeFn fn = (EncodeFn)fnp;
    cudaGetSymbolAddress((void**)&p.scr, g_scr); cudaGetSymbolAddress((void**)&p.tab, g_tab);
    void* h3p = p.scr->h3;
    CUtensorMap tw1a, tw1b, tw2, th3a, th3b, twr, twi, twm, tt, ttx, to, th3s, tws;
    {
        const cuuint64_t dims[4] = {64, 16, 128, 72}, st[3] = {128ull * F_ * 2, (cuuint64_t)F_ * 2, 128};
        const cuuint32_t ba[4] = {64, 16, 4, 2}, bb[4] = {64, 16, 8, 1};
        encode(fn, &tw1a, CU_TENSOR_MAP_DATA_TYPE_BFLOAT16, 4, p.w1, dims, st, ba, CU_TENSOR_MAP_SWIZZLE_128B);
        encode(fn, &tw1b, CU_TENSOR_MAP_DATA_TYPE_BFLOAT16, 4, p.w1, dims, st, bb, CU_TENSOR_MAP_SWIZZLE_128B);
    }
    {
        const cuuint64_t dims[3] = {64, F_, 32}, st[2] = {(cuuint64_t)S_ * 2, 128};
        const cuuint32_t bx[3] = {64, 64, 2};
        encode(fn, &tw2, CU_TENSOR_MAP_DATA_TYPE_BFLOAT16, 3, p.w2, dims, st, bx, CU_TENSOR_MAP_SWIZZLE_128B);
    }
    {
        const cuuint64_t dims[3] = {64, 72, 128}, st[2] = {256, 18432};
        const cuuint32_t ba[3] = {64, 18, 4}, bb[3] = {64, 9, 8};
        encode(fn, &th3a, CU_TENSOR_MAP_DATA_TYPE_UINT32, 3, h3p, dims, st, ba, CU_TENSOR_MAP_SWIZZLE_NONE);
        encode(fn, &th3b, CU_TENSOR_MAP_DATA_TYPE_UINT32, 3, h3p, dims, st, bb, CU_TENSOR_MAP_SWIZZLE_NONE);
    }
    {
        const cuuint64_t dims[4] = {32, 72, 2, 128}, st[3] = {256, 128, 18432};
        const cuuint32_t bx[4] = {32, 72, 2, 1};
        encode(fn, &th3s, CU_TENSOR_MAP_DATA_TYPE_UINT32, 4, h3p, dims, st, bx, CU_TENSOR_MAP_SWIZZLE_128B, CU_TENSOR_MAP_L2_PROMOTION_NONE);
    }
    {
        const cuuint64_t dims[3] = {4624, 4, 32}, st[2] = {9248 * 32, 9248};
        const cuuint32_t bx[3] = {56, 4, 32};
        encode(fn, &twr, CU_TENSOR_MAP_DATA_TYPE_BFLOAT16, 3, p.wr, dims, st, bx, CU_TENSOR_MAP_SWIZZLE_NONE);
        encode(fn, &twi, CU_TENSOR_MAP_DATA_TYPE_BFLOAT16, 3, p.wi, dims, st, bx, CU_TENSOR_MAP_SWIZZLE_NONE);
    }
    {
        const cuuint64_t dims[2] = {3456, 576}, st[1] = {6912};
        const cuuint32_t bx[2] = {32, 144};
        encode(fn, &tws, CU_TENSOR_MAP_DATA_TYPE_BFLOAT16, 2, p.wmod, dims, st, bx, CU_TENSOR_MAP_SWIZZLE_64B);
    }
    {
        const cuuint64_t dims[3] = {64, 576, 54}, st[2] = {6912, 128};
        const cuuint32_t bx[3] = {64, 32, 7};
        encode(fn, &twm, CU_TENSOR_MAP_DATA_TYPE_BFLOAT16, 3, p.wmod, dims, st, bx, CU_TENSOR_MAP_SWIZZLE_128B);
    }
    {
        const cuuint64_t dims[2] = {TP, 128}, st[1] = {TP * 4};
        const cuuint32_t ba[2] = {32, 128}, bb[2] = {8, 128};
        encode(fn, &tt, CU_TENSOR_MAP_DATA_TYPE_UINT32, 2, p.scr->T, dims, st, ba, CU_TENSOR_MAP_SWIZZLE_128B, CU_TENSOR_MAP_L2_PROMOTION_NONE);
        encode(fn, &ttx, CU_TENSOR_MAP_DATA_TYPE_UINT32, 2, p.scr->T, dims, st, bb, CU_TENSOR_MAP_SWIZZLE_32B, CU_TENSOR_MAP_L2_PROMOTION_NONE);
    }
    {
        const cuuint64_t dims[2] = {D_, S_}, st[1] = {D_ * 2};
        const cuuint32_t bx[2] = {144, 16};
        encode(fn, &to, CU_TENSOR_MAP_DATA_TYPE_BFLOAT16, 2, p.out, dims, st, bx, CU_TENSOR_MAP_SWIZZLE_NONE, CU_TENSOR_MAP_L2_PROMOTION_NONE);
    }
    cudaFuncSetAttribute(fused_kernel, cudaFuncAttributeMaxDynamicSharedMemorySize, SMEM_BYTES);
    cudaLaunchConfig_t cfg = {};
    cfg.gridDim = dim3(NCTA); cfg.blockDim = dim3(NTHR); cfg.dynamicSmemBytes = SMEM_BYTES; cfg.stream = cudaStreamPerThread;
    cudaLaunchAttribute at[1];
    at[0].id = cudaLaunchAttributeClusterDimension; at[0].val.clusterDim.x = 2; at[0].val.clusterDim.y = 1; at[0].val.clusterDim.z = 1;
    cfg.attrs = at; cfg.numAttrs = 1;
    int nclusters = 0;
    cudaOccupancyMaxActiveClusters(&nclusters, fused_kernel, &cfg);
    at[0].id = cudaLaunchAttributeCooperative; at[0].val.cooperative = 1;
    cfg.numAttrs = nclusters * 2 >= NCTA ? 0 : 1;
    cudaLaunchKernelEx(&cfg, fused_kernel, p, tw1a, tw1b, tw2, th3a, th3b, twr, twi, twm, tt, ttx, to, th3s, tws);
}
```

```cpp
#include <cuda_runtime.h>
#include <cuda_bf16.h>
#include <cuda_fp16.h>
#include <cuda.h>
#include <stdint.h>

namespace {

constexpr int S_ = 2048, D_ = 576, F_ = 4608;
constexpr int NCTA = 132, NTHR = 512;
constexpr int TP = 4736;
constexpr int SPEC_P = 296;
constexpr int NST = 6;
constexpr int A_BYTES = 16384, B_BYTES = 18432;
constexpr int IT_P1 = 24, IT_G2 = 40, IT_END = 76;
constexpr int SPIN_LIMIT = 1 << 22;
#define X2D 1350
constexpr int P2S = 2;
#define LEAD1 4
#define W1N 8
#define W1P 100
#define W1S 5
#define XDELAY 1100
#define HOK 2
#define HOK1 2
#define NCP 10800
#define P2K 4
#define SLP 64
#define X1D 2100
#define PF0 4
#define PFS 3
#define PFN 9
#define X1DELAY 2000
#define X1PACE 400

constexpr int OFF_A = 0;
constexpr int OFF_B = NST * A_BYTES;
constexpr int OFF_P = OFF_B + NST * B_BYTES;
constexpr int OFF_BAR = OFF_P;
constexpr int OFF_EPOCH = OFF_P + 480;
constexpr int OFF_MISC = OFF_P + 496;
constexpr int OFF_GB = OFF_P + 512;
constexpr int OFF_P2R = OFF_P + 1664;
constexpr int OFF_X1 = OFF_P2R;
constexpr int OFF_PROF = OFF_X1 + 18432;
constexpr int SMEM_BYTES = OFF_PROF + 512;
constexpr int QA = 13, QB = 7, QC = 13;
constexpr int TAB_BYTES = (QA + QB + QC) * 512;
constexpr int OFF_STAGE = OFF_B;
constexpr int OFF_STX = OFF_STAGE + 16384;
constexpr int OFF_TAB = OFF_STAGE + 20480;
constexpr int OFF_SPEC = OFF_TAB + TAB_BYTES;
constexpr int OFF_WRAW = OFF_SPEC + 19072;
constexpr int OFF_B3 = OFF_WRAW + 28672;
constexpr int OFF_MODA = OFF_B3 + 4096;
constexpr int OFF_MODC = OFF_MODA + 2560;
constexpr int OFF_RED = OFF_MODC + 3584;
constexpr int OFF_HEXP = OFF_RED + 512;
constexpr int OFF_SILU = OFF_RED + 1536;
static_assert(OFF_SILU + 1152 <= OFF_P && 6 * 28672 <= OFF_B3, "scratch overflow");
constexpr int OFF_STRIP = OFF_A;
static_assert(OFF_WRAW % 128 == 0 && OFF_STAGE % 128 == 0 && OFF_STX % 128 == 0, "align");
constexpr int BAR_FULL = 0, BAR_EMPTY = 6, BAR_TAB = 12, BAR_W = 13, BAR_P2N = 14, BAR_P2R = 16,
              BAR_XT = 17, BAR_RECV = 18, BAR_ROLE = 19, BAR_NC = 20, BAR_TAB2 = 21, BAR_XB = 22, BAR_GB = 23, BAR_HOLD = 24, BAR_W1GO = 25, BAR_UOK = 26, BAR_DONE = 30, BAR_X = 31, BAR_ST = 47;

struct Cos1152 { double c[1152]; };
constexpr double cx_cos(double x) { double t = 1, s = 1; for (int i = 1; i < 14; i++) { t *= -x * x / ((2 * i - 1) * (2 * i)); s += t; } return s; }
constexpr Cos1152 make_cos() {
    Cos1152 r{};
    for (int i = 0; i <= 288; i++) {
        double v = (i == 288) ? 0.0 : cx_cos(3.14159265358979323846 * 2.0 * i / 1152.0);
        r.c[i] = v; r.c[576 - i] = -v; r.c[576 + i] = -v; r.c[(1152 - i) % 1152] = v;
    }
    return r;
}
constexpr uint32_t cx_f2h(double v) {
    uint32_t s = v < 0 ? 0x8000u : 0u; double a = v < 0 ? -v : v;
    if (a < 1e-9) return 0;
    int e = 0;
    while (a >= 2.0) { a *= 0.5; e++; }
    while (a < 1.0 && e > -14) { a *= 2.0; e--; }
    double m = a * 1024.0; uint32_t mi = (uint32_t)m; double fr = m - mi;
    if (fr > 0.5 || (fr == 0.5 && (mi & 1))) mi++;
    return s | (uint32_t)(((e + 14) << 10) + mi);
}
struct Tab { uint32_t w[(QA + QB + QC) * 128]; };
constexpr Tab make_tab() {
    Tab t{};
    Cos1152 ct = make_cos();
    auto C = [&](int num, int den) { return ct.c[(num % den) * (1152 / den)]; };
    auto Sn = [&](int num, int den) { return ct.c[((num % den) * (1152 / den) + 864) % 1152]; };
    auto put = [&](int q0, int idx, int lane, double lo, double hi) { t.w[((q0 + idx / 4) * 32 + lane) * 4 + idx % 4] = cx_f2h(lo) | (cx_f2h(hi) << 16); };
    for (int lane = 0; lane < 32; lane++) {
        const int g = lane >> 2, q = lane & 3;
        for (int mt = 0; mt < 3; mt++) {
            const int ka = 8 * mt + g;
            for (int r = 0; r < 10; r++) {
                const int im = r & 1, i0 = (r >> 1) * 2;
                double v[2] = {0, 0};
                for (int e = 0; e < 2; e++) { int i = i0 + e, d1 = 4 * i + q; if (i < 9 && ka <= 18) v[e] = (im ? -Sn(ka * d1, 36) : C(ka * d1, 36)) / 8; }
                put(0, r < 8 ? mt * 8 + r : 16 + 2 * mt + r, lane, v[0], v[1]);
            }
            for (int v = 0; v < 2; v++) {
                const int d2 = 4 * q + v;
                put(0, 30 + (mt * 2 + v) * 2, lane, C(ka * d2, 576) * 4 / 3, C(ka * (d2 + 2), 576) * 4 / 3);
                put(0, 31 + (mt * 2 + v) * 2, lane, Sn(ka * d2, 576) * 4 / 3, Sn(ka * (d2 + 2), 576) * 4 / 3);
            }
        }
        for (int v = 0; v < 2; v++) for (int nt = 0; nt < 2; nt++) {
            const int kb = 2 * (g >> 1) + nt, part = g & 1;
            double b0[2] = {0, 0}, b1[2] = {0, 0};
            for (int e = 0; e < 2; e++) { int d2 = 4 * q + 2 * e + v; double c = C(kb * d2, 16) / 4, s = Sn(kb * d2, 16) / 4;
                b0[e] = part ? -s : c; b1[e] = part ? c : s; }
            put(0, 42 + (v * 2 + nt) * 2, lane, b0[0], b0[1]); put(0, 43 + (v * 2 + nt) * 2, lane, b1[0], b1[1]);
        }
        t.w[((QA - 1) * 32 + lane) * 4 + 2] = 0x3F803F80u;
        for (int par = 0; par < 2; par++) for (int a = 0; a < 4; a++) {
            const int ja = 2 * (q + 4 * (a >> 1)) + par; const double c = C(g * ja, 16) / 4, s = Sn(g * ja, 16) / 4;
            put(QA, par * 4 + a, lane, (a & 1) ? -s : c, (a & 1) ? c : s);
        }
        for (int h = 0; h < 2; h++) {
            put(QA, 8 + 2 * h, lane, C((g + 8 * h) * (2 * q), 128) / 2, C((g + 8 * h) * (2 * q + 1), 128) / 2);
            put(QA, 9 + 2 * h, lane, Sn((g + 8 * h) * (2 * q), 128) / 2, Sn((g + 8 * h) * (2 * q + 1), 128) / 2);
            put(QA, 16 + 2 * h, lane, C(g * (8 * h + 2 * q), 128), C(g * (8 * h + 2 * q + 1), 128));
            put(QA, 17 + 2 * h, lane, Sn(g * (8 * h + 2 * q), 128), Sn(g * (8 * h + 2 * q + 1), 128));
        }
        put(QA, 12, lane, C(g * 2 * q, 8) / 2, C(g * (2 * q + 1), 8) / 2);
        put(QA, 15, lane, C(g * 2 * q, 8) / 2, C(g * (2 * q + 1), 8) / 2);
        put(QA, 13, lane, Sn(g * 2 * q, 8) / 2, Sn(g * (2 * q + 1), 8) / 2);
        put(QA, 14, lane, -Sn(g * 2 * q, 8) / 2, -Sn(g * (2 * q + 1), 8) / 2);
        for (int u = 0; u < 4; u++) {
            const int ja = 2 * ((g >> 1) + 4 * (u & 1)) + (u >> 1), part = g & 1; double b0[2] = {0, 0}, b1[2] = {0, 0};
            for (int e = 0; e < 2; e++) { int ka = 2 * q + e; double c = C(ja * ka, 16) / 4, s = Sn(ja * ka, 16) / 4;
                b0[e] = part ? s : c; b1[e] = part ? c : -s; }
            put(QA, 20 + u * 2, lane, b0[0], b0[1]); put(QA, 21 + u * 2, lane, b1[0], b1[1]);
        }
        for (int m2 = 0; m2 < 2; m2++) {
            const int d2 = 2 * g + m2;
            for (int a = 0; a < 4; a++) {
                const int kb = 2 * q + (a >> 1); const double c = C(d2 * kb, 16) / 4, s = Sn(d2 * kb, 16) / 4;
                put(QA + QB, m2 * 4 + a, lane, (a & 1) ? s : c, (a & 1) ? c : -s);
            }
            for (int mt = 0; mt < 3; mt++) {
                const int ka = 8 * mt + 2 * q;
                put(QA + QB, 8 + (m2 * 3 + mt) * 2, lane, C(ka * d2, 576) * 4 / 3, C((ka + 1) * d2, 576) * 4 / 3);
                put(QA + QB, 9 + (m2 * 3 + mt) * 2, lane, Sn(ka * d2, 576) * 4 / 3, Sn((ka + 1) * d2, 576) * 4 / 3);
            }
        }
        for (int mt = 0; mt < 3; mt++) for (int nt = 0; nt < 5; nt++) {
            const int i = 2 * nt + (g & 1), d1 = 4 * i + (g >> 1); double b0[2] = {0, 0}, b1[2] = {0, 0};
            for (int e = 0; e < 2; e++) { int ka = 8 * mt + 2 * q + e;
                if (ka <= 18 && i < 9) { double wt = (ka == 0 || ka == 18) ? 0.125 : 0.25; b0[e] = wt * C(ka * d1, 36); b1[e] = -wt * Sn(ka * d1, 36); } }
            const int o = (QA + QB + 5) * 128 + (mt * 5 + nt) * 64 + lane;
            t.w[o] = cx_f2h(b0[0]) | (cx_f2h(b0[1]) << 16); t.w[o + 32] = cx_f2h(b1[0]) | (cx_f2h(b1[1]) << 16);
        }
    }
    return t;
}
__device__ __align__(128) const Tab g_tab = make_tab();

struct Scratch {
    uint32_t cnt[30 * 32];
    uint32_t slot[96];
    uint32_t mod[2304];
    uint32_t modc[896 + 288];
    uint32_t T[128 * TP];
    uint4 h3[128 * 1152];
    uint4 U[72 * 4 * 1152];
};
__device__ __align__(1024) Scratch g_scr;
#define g_cnt (p.scr->cnt)
#define g_slot (p.scr->slot)
#define g_mod (p.scr->mod)
#define g_T (p.scr->T)
#define g_h3 (p.scr->h3)
#define g_U (p.scr->U)
constexpr int CNT_EPOCH = 0, CNT_H3 = 1, CNT_X1 = 26, CNT_NC = 27, CNT_U = 2;
#define PROFT(i) do {} while (0)
#define PROFDUMP() do {} while (0)
#define PROF0(i) do {} while (0)

__device__ __forceinline__ void mbar_init(uint32_t bar, uint32_t cnt) { asm volatile("mbarrier.init.shared::cta.b64 [%0], %1;" :: "r"(bar), "r"(cnt) : "memory"); }
__device__ __forceinline__ void mbar_expect(uint32_t bar, uint32_t bytes) { asm volatile("mbarrier.arrive.expect_tx.shared::cta.b64 _, [%0], %1;" :: "r"(bar), "r"(bytes) : "memory"); }
__device__ __forceinline__ void mbar_arrive(uint32_t bar) { asm volatile("mbarrier.arrive.shared::cta.b64 _, [%0];" :: "r"(bar) : "memory"); }
__device__ __forceinline__ void mbar_arrive_n(uint32_t bar, uint32_t n) { asm volatile("mbarrier.arrive.shared::cta.b64 _, [%0], %1;" :: "r"(bar), "r"(n) : "memory"); }
__device__ __forceinline__ void mbar_arrive_remote(uint32_t rbar) { asm volatile("mbarrier.arrive.relaxed.cluster.shared::cluster.b64 _, [%0];" :: "r"(rbar) : "memory"); }
__device__ __forceinline__ void mbar_wait(uint32_t bar, uint32_t parity) {
    asm volatile("{.reg .pred p; .reg .u32 c;\n"
        "mbarrier.try_wait.parity.shared::cta.b64 p, [%0], %1;\n@p bra.uni DONE;\nmov.u32 c, 0;\n"
        "LOOP: mbarrier.try_wait.parity.shared::cta.b64 p, [%0], %1;\n@p bra.uni DONE;\n"
        "add.u32 c, c, 1;\nsetp.lt.u32 p, c, %2;\n@p bra.uni LOOP;\ntrap;\nDONE:}" :: "r"(bar), "r"(parity), "n"(SPIN_LIMIT) : "memory");
}
__device__ __forceinline__ bool mbar_test(uint32_t bar, uint32_t parity) {
    uint32_t ok; asm volatile("{.reg .pred p; mbarrier.test_wait.parity.shared::cta.b64 p, [%1], %2; selp.u32 %0, 1, 0, p;}" : "=r"(ok) : "r"(bar), "r"(parity) : "memory"); return ok; }
__device__ __forceinline__ uint32_t mapa(uint32_t a, uint32_t rank) { uint32_t r; asm("mapa.shared::cluster.u32 %0, %1, %2;" : "=r"(r) : "r"(a), "r"(rank)); return r; }
__device__ __forceinline__ uint32_t clk32() { uint32_t r; asm volatile("mov.u32 %0, %%clock;" : "=r"(r)); return r; }
__device__ __forceinline__ void hb() {
    asm volatile("{.reg .b32 a, b; .reg .pred p; mma.sync.aligned.m16n8k8.row.col.f16.f16.f16.f16 {a, b}, {%0,%0}, {%0}, {%0,%0};\n"
                 "setp.ne.u32 p, a, 0; @p trap;}" :: "r"(0));
}
__device__ __forceinline__ void spin_until(uint32_t t) {
    #pragma unroll 1
    while (__any_sync(~0u, (int)(clk32() - t) < -SLP * 4)) { __nanosleep(SLP); hb(); }
    #pragma unroll 1
    while (__any_sync(~0u, (int)(clk32() - t) < 0)) {}
}
__device__ __forceinline__ bool elect() { uint32_t r; asm volatile("{.reg .pred p; elect.sync _|p, 0xffffffff; selp.u32 %0, 1, 0, p;}" : "=r"(r)); return r; }
__device__ __forceinline__ void bar_sync(int id, int n) { asm volatile("bar.sync %0, %1;" :: "r"(id), "r"(n) : "memory"); }
__device__ __forceinline__ void bulk_load(uint32_t dst, const void* src, uint32_t bytes, uint32_t bar) {
    asm volatile("cp.async.bulk.shared::cluster.global.mbarrier::complete_tx::bytes [%0], [%1], %2, [%3];" :: "r"(dst), "l"(src), "r"(bytes), "r"(bar) : "memory"); }
__device__ __forceinline__ void tma2(uint32_t dst, const CUtensorMap* m, int c0, int c1, uint32_t bar) {
    asm volatile("cp.async.bulk.tensor.2d.shared::cluster.global.mbarrier::complete_tx::bytes [%0], [%1, {%3, %4}], [%2];" :: "r"(dst), "l"(m), "r"(bar), "r"(c0), "r"(c1) : "memory"); }
__device__ __forceinline__ void tma3(uint32_t dst, const CUtensorMap* m, int c0, int c1, int c2, uint32_t bar) {
    asm volatile("cp.async.bulk.tensor.3d.shared::cluster.global.mbarrier::complete_tx::bytes [%0], [%1, {%3, %4, %5}], [%2];" :: "r"(dst), "l"(m), "r"(bar), "r"(c0), "r"(c1), "r"(c2) : "memory"); }
__device__ __forceinline__ void tma4(uint32_t dst, const CUtensorMap* m, int c0, int c1, int c2, int c3, uint32_t bar) {
    asm volatile("cp.async.bulk.tensor.4d.shared::cluster.global.mbarrier::complete_tx::bytes [%0], [%1, {%3, %4, %5, %6}], [%2];" :: "r"(dst), "l"(m), "r"(bar), "r"(c0), "r"(c1), "r"(c2), "r"(c3) : "memory"); }
__device__ __forceinline__ void fence_async_g() { asm volatile("fence.proxy.async.global;" ::: "memory"); }
__device__ __forceinline__ void fence_async_s() { asm volatile("fence.proxy.async.shared::cta;" ::: "memory"); }
__device__ __forceinline__ uint4 lds128(uint32_t a) { uint4 v; asm volatile("ld.shared.v4.u32 {%0,%1,%2,%3}, [%4];" : "=r"(v.x), "=r"(v.y), "=r"(v.z), "=r"(v.w) : "r"(a) : "memory"); return v; }
__device__ __forceinline__ uint32_t lds32(uint32_t a) { uint32_t v; asm volatile("ld.shared.u32 %0, [%1];" : "=r"(v) : "r"(a) : "memory"); return v; }
__device__ __forceinline__ void sts128(uint32_t a, uint4 v) { asm volatile("st.shared.v4.u32 [%0], {%1,%2,%3,%4};" :: "r"(a), "r"(v.x), "r"(v.y), "r"(v.z), "r"(v.w) : "memory"); }
__device__ __forceinline__ void sts32(uint32_t a, uint32_t v) { asm volatile("st.shared.u32 [%0], %1;" :: "r"(a), "r"(v) : "memory"); }
__device__ __forceinline__ void sts16(uint32_t a, uint32_t v) { asm volatile("st.shared.u16 [%0], %1;" :: "r"(a), "h"((uint16_t)v) : "memory"); }
__device__ __forceinline__ uint4 ldx128(const void* p) {
    uint4 v; asm volatile("{.reg .b128 t; .reg .b64 a, b; ld.relaxed.gpu.global.b128 t, [%4]; mov.b128 {a, b}, t; mov.b64 {%0,%1}, a; mov.b64 {%2,%3}, b;}"
        : "=r"(v.x), "=r"(v.y), "=r"(v.z), "=r"(v.w) : "l"(p) : "memory"); return v; }
__device__ __forceinline__ void stx128(void* p, uint4 v) {
    asm volatile("{.reg .b128 t; .reg .b64 a, b; mov.b64 a, {%1,%2}; mov.b64 b, {%3,%4}; mov.b128 t, {a, b}; st.relaxed.gpu.global.b128 [%0], t;}"
        :: "l"(p), "r"(v.x), "r"(v.y), "r"(v.z), "r"(v.w) : "memory"); }
__device__ __forceinline__ uint32_t ld_acquire(const uint32_t* p) { uint32_t v; asm volatile("ld.acquire.gpu.global.u32 %0, [%1];" : "=r"(v) : "l"(p) : "memory"); return v; }
__device__ __forceinline__ void st_relaxed(uint32_t* p, uint32_t v) { asm volatile("st.relaxed.gpu.global.u32 [%0], %1;" :: "l"(p), "r"(v) : "memory"); }
__device__ __forceinline__ void red_release(uint32_t* p) { asm volatile("red.release.gpu.global.add.u32 [%0], 1;" :: "l"(p) : "memory"); }
template <int SLEEP> __device__ __forceinline__ void wait_count(const uint32_t* p, uint32_t target) {
    int it = 0; while ((int)(ld_acquire(p) - target) < 0) { if (SLEEP) __nanosleep(SLEEP); if (++it > SPIN_LIMIT) __trap(); }
}
__device__ __forceinline__ uint32_t ldg_nc32(const void* p) { uint32_t v; asm volatile("ld.global.nc.L1::no_allocate.u32 %0, [%1];" : "=r"(v) : "l"(p)); return v; }
__device__ __forceinline__ uint32_t ldg_nc16(const void* p) { uint16_t v; asm volatile("ld.global.nc.u16 %0, [%1];" : "=h"(v) : "l"(p)); return v; }
__device__ __forceinline__ float bf_lo(uint32_t w) { return __uint_as_float(w << 16); }
__device__ __forceinline__ float bf_hi(uint32_t w) { return __uint_as_float(w & 0xFFFF0000u); }
__device__ __forceinline__ uint32_t pack_bf(float lo, float hi) { uint32_t r; asm("cvt.rn.bf16x2.f32 %0, %1, %2;" : "=r"(r) : "f"(hi), "f"(lo)); return r; }
__device__ __forceinline__ uint32_t pack_h(float lo, float hi) { uint32_t r; asm("cvt.rn.f16x2.f32 %0, %1, %2;" : "=r"(r) : "f"(hi), "f"(lo)); return r; }
__device__ __forceinline__ float bf_round(float v) { return bf_lo(pack_bf(v, 0.f)); }
__device__ __forceinline__ uint32_t hmul2(uint32_t a, uint32_t b) { uint32_t r; asm("mul.rn.f16x2 %0, %1, %2;" : "=r"(r) : "r"(a), "r"(b)); return r; }
__device__ __forceinline__ uint32_t hfma2(uint32_t a, uint32_t b, uint32_t c) { uint32_t r; asm("fma.rn.f16x2 %0, %1, %2, %3;" : "=r"(r) : "r"(a), "r"(b), "r"(c)); return r; }
__device__ __forceinline__ uint32_t hfms2(uint32_t a, uint32_t b, uint32_t c) { uint32_t r; asm("{.reg .b32 t; neg.f16x2 t, %3; fma.rn.f16x2 %0, %1, %2, t;}" : "=r"(r) : "r"(a), "r"(b), "r"(c)); return r; }
__device__ __forceinline__ uint32_t hadd2(uint32_t a, uint32_t b) { uint32_t r; asm("add.rn.f16x2 %0, %1, %2;" : "=r"(r) : "r"(a), "r"(b)); return r; }
__device__ __forceinline__ uint32_t hsub2(uint32_t a, uint32_t b) { uint32_t r; asm("sub.rn.f16x2 %0, %1, %2;" : "=r"(r) : "r"(a), "r"(b)); return r; }
__device__ __forceinline__ void cmul_neg(uint32_t& re, uint32_t& im, uint32_t c, uint32_t s) { uint32_t a = hfma2(re, c, hmul2(im, s)), b = hfms2(im, c, hmul2(re, s)); re = a; im = b; }
__device__ __forceinline__ void cmul_pos(uint32_t& re, uint32_t& im, uint32_t c, uint32_t s) { uint32_t a = hfms2(re, c, hmul2(im, s)), b = hfma2(im, c, hmul2(re, s)); re = a; im = b; }
__device__ __forceinline__ void mma_h(uint32_t& d0, uint32_t& d1, uint32_t a0, uint32_t a1, uint32_t a2, uint32_t a3, uint32_t b0, uint32_t b1) {
    asm("mma.sync.aligned.m16n8k16.row.col.f16.f16.f16.f16 {%0,%1}, {%2,%3,%4,%5}, {%6,%7}, {%0,%1};" : "+r"(d0), "+r"(d1) : "r"(a0), "r"(a1), "r"(a2), "r"(a3), "r"(b0), "r"(b1)); }
__device__ __forceinline__ void mma_h8(uint32_t& d0, uint32_t& d1, uint32_t a0, uint32_t a1, uint32_t b0) {
    asm("mma.sync.aligned.m16n8k8.row.col.f16.f16.f16.f16 {%0,%1}, {%2,%3}, {%4}, {%0,%1};" : "+r"(d0), "+r"(d1) : "r"(a0), "r"(a1), "r"(b0)); }
template <int NQ> __device__ __forceinline__ void load_tab(uint32_t (&r)[NQ * 4], uint32_t addr) {
    #pragma unroll
    for (int i = 0; i < NQ; i++) { uint4 v = lds128(addr + i * 512); r[4 * i] = v.x; r[4 * i + 1] = v.y; r[4 * i + 2] = v.z; r[4 * i + 3] = v.w; }
}
__device__ __forceinline__ float gelu2(float x) {
    float t = x * fmaf(x * x, 0.044715f * 0.7978845608028654f, 0.7978845608028654f), th;
    asm volatile("tanh.approx.f32 %0, %1;" : "=f"(th) : "f"(t));
    return fmaf(x, th, x);
}
constexpr uint32_t SM0 = 1024;
__device__ __forceinline__ constexpr uint32_t desc_lo(uint32_t off, uint32_t lbo) { return ((SM0 + off) >> 4) | ((lbo >> 4) << 16); }
constexpr uint32_t DHI_A = (1024 >> 4) | (1u << 30), DHI_H3 = 256 >> 4, DHI_U = 128 >> 4;
#define WG_FENCE() asm volatile("wgmma.fence.sync.aligned;" ::: "memory")
#define WG_COMMIT() asm volatile("wgmma.commit_group.sync.aligned;" ::: "memory")
#define WG_WAIT(n) asm volatile("wgmma.wait_group.sync.aligned %0;" :: "n"(n) : "memory")
#define R4(b) "+f"(d[b]), "+f"(d[b + 1]), "+f"(d[b + 2]), "+f"(d[b + 3])
#define R12(b) R4(b), R4(b + 4), R4(b + 8)
#define R36(b) R12(b), R12(b + 12), R12(b + 24)
template <uint32_t BHI> __device__ __forceinline__ void wgmma144(float (&d)[72], uint32_t da, uint32_t db, int acc) {
    asm volatile("{.reg .pred p; .reg .b64 a, b; setp.ne.b32 p, %74, 0; mov.b64 a, {%72, %75}; mov.b64 b, {%73, %76};\n"
        "wgmma.mma_async.sync.aligned.m64n144k16.f32.bf16.bf16 {%0,%1,%2,%3,%4,%5,%6,%7,%8,%9,%10,%11,%12,%13,%14,%15,%16,%17,%18,%19,%20,%21,%22,%23,"
        "%24,%25,%26,%27,%28,%29,%30,%31,%32,%33,%34,%35,%36,%37,%38,%39,%40,%41,%42,%43,%44,%45,%46,%47,"
        "%48,%49,%50,%51,%52,%53,%54,%55,%56,%57,%58,%59,%60,%61,%62,%63,%64,%65,%66,%67,%68,%69,%70,%71}, a, b, p, 1, 1, 1, 1;}\n"
        : R36(0), R36(36) : "r"(da), "r"(db), "r"(acc), "n"(DHI_A), "n"(BHI));
}
__device__ __forceinline__ void wgmma40_rs(float (&d)[20], uint32_t a0, uint32_t a1, uint32_t a2, uint32_t a3, uint32_t db, int acc) {
    asm volatile("{.reg .pred p; .reg .b64 b; setp.ne.b32 p, %25, 0; mov.b64 b, {%24, %26};\n"
        "wgmma.mma_async.sync.aligned.m64n40k16.f32.f16.f16 {%0,%1,%2,%3,%4,%5,%6,%7,%8,%9,%10,%11,%12,%13,%14,%15,%16,%17,%18,%19}, {%20,%21,%22,%23}, b, p, 1, 1, 0;}\n"
        : R12(0), R4(12), R4(16) : "r"(a0), "r"(a1), "r"(a2), "r"(a3), "r"(db), "r"(acc), "n"(DHI_H3));
}
__device__ __forceinline__ void wgmma72(float (&d)[36], uint32_t da, uint32_t db, int acc) {
    asm volatile("{.reg .pred p; .reg .b64 a, b; setp.ne.b32 p, %38, 0; mov.b64 a, {%36, %39}; mov.b64 b, {%37, %40};\n"
        "wgmma.mma_async.sync.aligned.m64n72k16.f32.bf16.bf16 {%0,%1,%2,%3,%4,%5,%6,%7,%8,%9,%10,%11,%12,%13,%14,%15,%16,%17,%18,%19,%20,%21,%22,%23,"
        "%24,%25,%26,%27,%28,%29,%30,%31,%32,%33,%34,%35}, a, b, p, 1, 1, 1, 1;}\n"
        : R36(0) : "r"(da), "r"(db), "r"(acc), "n"(DHI_A), "n"(DHI_H3));
}

__device__ __forceinline__ int g2_kb(int n, int kh, int gi, int c2) {
    if (n < 4) return 36 * kh + 9 * n + 8;
    if (n == 4) return 9 * gi + 4 * c2 + 2 * kh + 1;
    const int w = n > 20, m = n - (w ? 19 : 5);
    return 9 * ((gi * w + (m >> 1)) & 7) + 4 * (n == 35 ? 1 - c2 : m & 1) + 2 * kh + w;
}

template <uint32_t BHI, int S> __device__ __forceinline__ void mma_block(float (&d)[72], uint32_t bars, uint32_t da0, uint32_t db0, uint32_t ph) {
    mbar_wait(bars + 8 * (BAR_FULL + S), ph);
    WG_FENCE();
    #pragma unroll
    for (int k = 0; k < 4; k++) wgmma144<BHI>(d, da0 + S * (A_BYTES / 16) + k * 128, db0 + S * (B_BYTES / 16) + k * 288, 1);
    WG_COMMIT();
    WG_WAIT(1);
}

struct Params {
    const uint16_t *wmod, *c, *x;
    Scratch* scr;
    const Tab* tab;
    const uint16_t *wr, *wi, *w1, *b1, *w2, *b2;
    uint16_t* out;
};

__device__ __forceinline__ void mma_bf(float (&d)[4], const uint32_t (&a)[4], uint32_t b0, uint32_t b1) {
    asm("mma.sync.aligned.m16n8k16.row.col.f32.bf16.bf16.f32 {%0,%1,%2,%3}, {%4,%5,%6,%7}, {%8,%9}, {%0,%1,%2,%3};"
        : "+f"(d[0]), "+f"(d[1]), "+f"(d[2]), "+f"(d[3]) : "r"(a[0]), "r"(a[1]), "r"(a[2]), "r"(a[3]), "r"(b0), "r"(b1)); }
__device__ __forceinline__ void ldsm4t(uint32_t (&a)[4], uint32_t addr) {
    asm volatile("ldmatrix.sync.aligned.m8n8.x4.trans.shared.b16 {%0,%1,%2,%3}, [%4];" : "=r"(a[0]), "=r"(a[1]), "=r"(a[2]), "=r"(a[3]) : "r"(addr) : "memory"); }
__device__ __forceinline__ void ln_stats(const uint32_t (&w)[9], const uint32_t (&one)[9], int g, int q, float& r, float& mr) {
    float c[2][4] = {};
    #pragma unroll
    for (int p = 0; p < 9; p++)
        asm("mma.sync.aligned.m16n8k8.row.col.f32.bf16.bf16.f32 {%0,%1,%2,%3}, {%4,%5}, {%4}, {%0,%1,%2,%3};"
            : "+f"(c[p & 1][0]), "+f"(c[p & 1][1]), "+f"(c[p & 1][2]), "+f"(c[p & 1][3]) : "r"(w[p]), "r"(one[p]));
    const float t = (g & 1) ? c[0][1] + c[1][1] : c[0][0] + c[1][0];
    float s1 = (c[0][2] + c[1][2]) + (c[0][3] + c[1][3]), s2 = __shfl_sync(~0u, t, 9 * q) + __shfl_sync(~0u, t, 9 * q + 4);
    #pragma unroll
    for (int o = 1; o < 4; o <<= 1) { s1 += __shfl_xor_sync(~0u, s1, o); s2 += __shfl_xor_sync(~0u, s2, o); }
    const float m = s1 * (1.f / D_);
    asm("rsqrt.approx.ftz.f32 %0, %1;" : "=f"(r) : "f"(fmaxf(fmaf(s2, 1.f / D_, -m * m), 0.f) + 1e-5f));
    mr = -m * r;
}
__device__ __forceinline__ float silu(float v) { return __fdividef(v, 1.f + __expf(-v)); }
__device__ __forceinline__ uint32_t bfma2(uint32_t a, uint32_t b, uint32_t c) { uint32_t r; asm("fma.rn.bf16x2 %0, %1, %2, %3;" : "=r"(r) : "r"(a), "r"(b), "r"(c)); return r; }
__device__ __forceinline__ void radix16(const uint4 (&V)[4], const uint32_t (&B)[16], uint4 (&o)[4]) {
    #pragma unroll
    for (int nt = 0; nt < 4; nt++) o[nt] = make_uint4(0, 0, 0, 0);
    #pragma unroll
    for (int u = 0; u < 4; u++)
        #pragma unroll
        for (int nt = 0; nt < 4; nt++) {
            const uint32_t b = B[((u >> 1) * 4 + nt) * 2 + (u & 1)];
            mma_h8(o[nt].x, o[nt].y, V[u].x, V[u].y, b); mma_h8(o[nt].z, o[nt].w, V[u].z, V[u].w, b);
        }
}
template <int OFF, int N> __device__ __forceinline__ void gelu_store(const float (&d)[N], char* p, int q) {
    uint32_t w[9];
    #pragma unroll
    for (int blk = 0; blk < 9; blk++) w[blk] = pack_bf(gelu2(d[OFF + 4 * blk]), gelu2(d[OFF + 4 * blk + 1]));
    asm volatile("st.v4.u32 [%0], {%1,%2,%3,%4};" :: "l"(p + q * 128), "r"(w[0]), "r"(w[1]), "r"(w[2]), "r"(w[3]) : "memory");
    asm volatile("st.v4.u32 [%0+512], {%1,%2,%3,%4};" :: "l"(p + q * 128), "r"(w[4]), "r"(w[5]), "r"(w[6]), "r"(w[7]) : "memory");
    asm volatile("st.u32 [%0+1024], %1;" :: "l"(p + q * 4), "r"(w[8]) : "memory");
}

__global__ void __cluster_dims__(2, 1, 1) __launch_bounds__(NTHR, 1)
fused_kernel(const Params p,
             const __grid_constant__ CUtensorMap tm_w1a, const __grid_constant__ CUtensorMap tm_w1b, const __grid_constant__ CUtensorMap tm_w2,
             const __grid_constant__ CUtensorMap tm_h3a, const __grid_constant__ CUtensorMap tm_h3b,
             const __grid_constant__ CUtensorMap tm_wr, const __grid_constant__ CUtensorMap tm_wi, const __grid_constant__ CUtensorMap tm_wm,
             const __grid_constant__ CUtensorMap tm_t, const __grid_constant__ CUtensorMap tm_tx, const __grid_constant__ CUtensorMap tm_o,
             const __grid_constant__ CUtensorMap tm_h3s, const __grid_constant__ CUtensorMap tm_ws)
{
    extern __shared__ __align__(1024) char smem_raw[];
    const uint32_t t0 = clk32();
    const uint32_t sm = __shfl_sync(~0u, ((uint32_t)__cvta_generic_to_shared(smem_raw) + 1023u) & ~1023u, 0);
    const int tid = threadIdx.x, warp = __shfl_sync(~0u, tid >> 5, 0), lane = tid & 31, g = lane >> 2, q = lane & 3;
    const int b = blockIdx.x;
    const uint32_t rank = b & 1;
    const uint32_t bars = sm + OFF_BAR;
    const bool rowcta = b < 128;

    auto nc_issue = [&](int st, uint32_t sl) {
        const int pass = st >= 18;
        mbar_expect(bars + 8 * (BAR_X + sl), 28672);
        tma3(sm + sl * 28672, &tm_wm, 0, 32 * (st - 18 * pass), 18 + 28 * pass + 7 * (b - 128), bars + 8 * (BAR_X + sl));
    };
    uint32_t epoch;
    const bool strip = b < 72 && !(b & 1);
    const bool sil = (warp >> 2) == 2 && lane < 24 && (strip || !rowcta);
    uint32_t cw[3];
    if (elect()) {
        mbar_init(bars + 8 * (BAR_X + warp), rowcta || warp < 6 ? 1 : 14);
        if (warp >= 12) {
            if (strip) { const uint32_t sb = bars + 8 * (BAR_ST + warp - 12);
                mbar_init(sb, 1); mbar_expect(sb, 9216); tma2(sm + OFF_STRIP + (warp - 12) * 9216, &tm_ws, 16 * b, 144 * (warp - 12), sb); }
        } else if (warp == 7) {
            mbar_init(bars + 8 * BAR_TAB, 1); mbar_expect(bars + 8 * BAR_TAB, rowcta ? QA * 512 + 16 : 16);
            bulk_load(sm + OFF_EPOCH, g_cnt + CNT_EPOCH * 32, 16, bars + 8 * BAR_TAB);
            if (rowcta) bulk_load(sm + OFF_TAB, p.tab, QA * 512, bars + 8 * BAR_TAB);
        } else if (b + 132 * warp < 576) {
            asm volatile("cp.async.bulk.prefetch.L2.global [%0], 2304;" :: "l"(p.wmod + (b + 132 * warp) * 3456) : "memory");
        }
    }
    if (sil) {
        #pragma unroll
        for (int u = 0; u < 3; u++) cw[u] = ldg_nc32(p.c + 144 * (warp - 8) + 48 * u + 2 * lane);
    }
    if (warp == 6) hb();
    __syncthreads();
    if (!rowcta) { if (warp < 6 && elect()) nc_issue(warp, warp); }
    if (warp == 5 || warp == 6) {
        if (elect()) {
            if (warp == 5) {
                for (int i = BAR_W; i < BAR_X; i++) mbar_init(bars + 8 * i, i == BAR_DONE || i == BAR_NC ? 4 : i == BAR_W1GO ? 2 : 1);
                mbar_expect(bars + 8 * BAR_W, 28672); mbar_expect(bars + 8 * BAR_TAB2, (QB + QC) * 512);
                mbar_expect(bars + 8 * BAR_ROLE, 4); mbar_expect(bars + 8 * BAR_P2R, 9216); mbar_expect(bars + 8 * BAR_RECV, 18432); mbar_expect(bars + 8 * BAR_XT, 18432);
            } else {
                for (int i = 0; i < 2 * NST; i++) mbar_init(bars + 8 * i, 2);
                for (int i = 0; i < NST; i++) mbar_expect(bars + 8 * (BAR_FULL + i), A_BYTES);
            }
            asm volatile("fence.mbarrier_init.release.cluster;" ::: "memory");
        }
    } else if (warp >= 12 && elect())
        asm volatile("prefetch.tensormap [%0];" :: "l"(warp == 12 ? &tm_wr : warp == 13 ? &tm_wi : warp == 14 ? &tm_t : &tm_tx) : "memory");
    uint32_t sb[18];
    if ((warp >> 2) == 2) {
        if (sil) {
            #pragma unroll
            for (int u = 0; u < 3; u++) sts32(sm + OFF_SILU + (72 * (warp - 8) + 24 * u + lane) * 4, pack_bf(silu(bf_lo(cw[u])), silu(bf_hi(cw[u]))));
        }
        __syncwarp();
        if (strip) {
            #pragma unroll
            for (int u = 0; u < 18; u++) sb[u] = lds32(sm + OFF_SILU + (72 * (warp - 8) + 4 * u + q) * 4);
        }
    }
    if (rowcta && elect()) {
        if (XDELAY) while ((int)(clk32() - t0) < XDELAY) {}
        mbar_expect(bars + 8 * (BAR_X + warp), 1152);
        bulk_load(sm + OFF_STAGE + warp * 1152, p.x + (size_t)(b + 128 * warp) * D_, 1152, bars + 8 * (BAR_X + warp));
    }
    __syncwarp();
    hb();

    const int trow = 4 * (b & 7) + ((b >> 4) & 3) + 64 * ((b >> 3) & 1) + 32 * (b >> 6);
    uint32_t* const tptr = g_T + (size_t)trow * TP + (warp < 9 ? q * 288 + 32 * warp : 4608 + 8 * q) + 4 * g;
    const int tstr = warp < 9 ? 1152 : 32;
    const uint32_t scol = sm + OFF_SPEC + (q * SPEC_P + (warp < 8 ? 72 * (warp >> 1) + 40 * (warp & 1) + 4 * g : warp == 8 ? 72 * (g >> 1) + 32 + 4 * (g & 1) : 288 + 4 * g)) * 4;
    const int wc0 = (b >> 3) * 289 + 72 * ((b & 7) >> 1) + 40 * (b & 1);

    uint32_t xw[9], one[9], t_st = t0, hexp = 0;
    if (!rowcta) {
        const int nst = b < 130 ? 36 : 18;
        __syncthreads();
        asm volatile("barrier.cluster.arrive.relaxed.aligned;" ::: "memory");
        mbar_wait(bars + 8 * BAR_TAB, 0);
        epoch = lds32(sm + OFF_EPOCH);
        if (warp == 14) {
            uint32_t sl = 0, ph = 0;
            #pragma unroll 1
            for (int st = 6; st < nst; st++) {
                mbar_wait(bars + 8 * (BAR_X + 6 + sl), ph);
                if (elect()) nc_issue(st, sl);
                if (++sl == 6) { sl = 0; ph ^= 1; }
            }
        } else if (warp < 14) {
            uint32_t sl = 0, ph = 0;
            const uint32_t ad0 = sm + (warp >> 1) * 4096 + ((lane & 7) + 8 * (lane >> 4)) * 128, ch = (warp & 1) * 4 + ((lane >> 3) & 1);
            #pragma unroll 1
            for (int pass = 0; pass * 18 < nst; pass++) {
                float acc[2][4] = {};
                #pragma unroll 1
                for (int st = 0; st < 18; st++) {
                    const uint32_t sa = sm + OFF_SILU + (16 * st + q) * 4;
                    const uint32_t b0 = lds32(sa), b1 = lds32(sa + 16), b2 = lds32(sa + 32), b3 = lds32(sa + 48);
                    mbar_wait(bars + 8 * (BAR_X + sl), ph);
                    #pragma unroll
                    for (int m = 0; m < 2; m++) {
                        uint32_t a[4], a2[4];
                        const uint32_t ad = ad0 + sl * 28672 + ((ch + 2 * m) ^ (lane & 7)) * 16;
                        ldsm4t(a, ad); ldsm4t(a2, ad + 2048);
                        mma_bf(acc[m], a, b0, b1); mma_bf(acc[m], a2, b2, b3);
                    }
                    if (elect()) mbar_arrive(bars + 8 * (BAR_X + 6 + sl));
                    if (++sl == 6) { sl = 0; ph ^= 1; }
                }
                const int cb = 28 * pass + 7 * (b - 128) + (warp >> 1), gg = (g >> 1) + 4 * q;
                uint32_t w[2];
                #pragma unroll
                for (int m = 0; m < 2; m++) {
                    float v = bf_round(q ? acc[m][2] : acc[m][0]); if (cb >= 27) v *= 0.5f; else if (cb >= 18) v += 1.f;
                    w[m] = max(pack_bf(v, __shfl_xor_sync(~0u, v, 4)), 1u);
                }
                if (q < 2 && !(g & 1)) {
                    const int qq = (warp & 1) * 2;
                    if (cb < 27) asm volatile("st.relaxed.gpu.global.v2.u32 [%0], {%1, %2};" :: "l"(p.scr->modc + 32 * cb + 4 * gg + qq), "r"(w[0]), "r"(w[1]) : "memory");
                    else if (cb < 36) { uint32_t* o = p.scr->modc + 896 + 32 * (cb - 27) + 8 * qq + gg; o[0] = w[0]; o[8] = w[1]; }
                }
                if (tid == 0 && pass == 0) PROFT(25);
                bar_sync(1, 448);
                if (tid == 0) { fence_async_g(); red_release(g_cnt + (CNT_NC + pass) * 32); }
                __syncwarp();
            }
            fence_async_s();
        }
        __syncthreads();
    } else {
        uint32_t ta[QA * 4];
        if (strip && (warp >> 2) == 2) {
            const int w = warp - 8;
            const uint32_t ra = sm + OFF_STRIP + (144 * w + (lane & 7) + 8 * (lane >> 4)) * 64, sw = (lane >> 1) & 3, ch = (lane >> 3) & 1;
            float acc[2][2][4] = {};
            mbar_wait(bars + 8 * (BAR_ST + w), 0);
            #pragma unroll
            for (int u = 0; u < 9; u++)
                #pragma unroll
                for (int m = 0; m < 2; m++) { uint32_t a[4]; ldsm4t(a, ra + u * 1024 + ((ch + 2 * m) ^ sw) * 16); mma_bf(acc[u & 1][m], a, sb[2 * u], sb[2 * u + 1]); }
            #define PICK(a_) ((q & 2) ? ((q & 1) ? a_[1][2] : a_[1][0]) : ((q & 1) ? a_[0][2] : a_[0][0]))
            sts32(sm + OFF_RED + ((8 * q + g) * 4 + w) * 4, __float_as_uint(PICK(acc[0]) + PICK(acc[1])));
            if (tid == 256) PROFT(0);
            bar_sync(10, 128);
            if (warp == 8) {
                mbar_wait(bars + 8 * BAR_TAB, 0);
                const uint4 v = lds128(sm + OFF_RED + lane * 16);
                float sum = bf_round((__uint_as_float(v.x) + __uint_as_float(v.y)) + (__uint_as_float(v.z) + __uint_as_float(v.w)));
                if (b >= 36) sum = bf_round(1.f + sum);
                st_relaxed(g_mod + b * 16 + (lane & 16) + (lane & 1) * 8 + ((lane & 15) >> 1), (fabsf(sum) < 8.f ? pack_h(0.f, sum) : __float_as_uint(sum) | 0x8000u) | ((lds32(sm + OFF_EPOCH) + 1) & 0x7FFFu));
                asm volatile("bar.arrive 11, 416;" ::: "memory");
                if (tid == 256) PROFT(1);
            }
        }
        mbar_wait(bars + 8 * BAR_TAB, 0);
        load_tab<QA>(ta, sm + OFF_TAB + lane * 16);
        epoch = lds32(sm + OFF_EPOCH);
        const uint32_t tag = (epoch + 1) & 0x7FFFu;
        auto w_prefetch = [&]() {
            if (warp >= 14 && elect()) asm volatile("cp.async.bulk.prefetch.L2.global [%0], 9248;" :: "l"((warp == 14 ? p.wr : p.wi) + b * 4624) : "memory");
            __syncwarp();
        };
        uint32_t nb[2][5];
        uint4 mv = make_uint4(tag, tag, tag, tag);
        const bool poller = warp < 8 || warp == 12;
        const int mc = warp < 8 ? tid : tid - 128, mst = (mc >> 2) % 36, midx = (mc < 144 ? 10 : 0) + 5 * ((mc >> 1) & 1) + (mst >> 3);
        const uint32_t* mp = g_mod + mc * 4;
        const uint32_t ma = sm + OFF_MODA + ((midx >> 2) * 32 + (mc & 1) * 16 + (mst & 3)) * 16 + (midx & 3) * 4 + ((mst >> 2) & 1) * 2;
        #define MOD_MISSING ((((mv.x ^ tag) | (mv.y ^ tag) | (mv.z ^ tag) | (mv.w ^ tag)) & 0x7FFFu) != 0)
        if (strip && (warp >> 2) != 2) bar_sync(11, 416);
        #pragma unroll
        for (int i = 0; i < 9; i++) one[i] = lds32(sm + OFF_TAB + (QA - 1) * 512 + i * 16 + 8);
        hb();
        mbar_wait(bars + 8 * (BAR_X + warp), 0);
        if (poller) mv = ldx128(mp);
        PROF0(28);
        #pragma unroll
        for (int i = 0; i < 9; i++) xw[i] = lds32(sm + OFF_STAGE + warp * 1152 + (32 * i + 8 * q + g) * 4);
        {
            float r, mr;
            ln_stats(xw, one, g, q, r, mr);
            #pragma unroll
            for (int pp = 0; pp < 5; pp++) {
                nb[0][pp] = pack_h(fmaf(bf_lo(xw[2 * pp]), r, mr), pp < 4 ? fmaf(bf_lo(xw[pp < 4 ? 2 * pp + 1 : 0]), r, mr) : 0.f);
                nb[1][pp] = pack_h(fmaf(bf_hi(xw[2 * pp]), r, mr), pp < 4 ? fmaf(bf_hi(xw[pp < 4 ? 2 * pp + 1 : 0]), r, mr) : 0.f);
            }
        }
        PROF0(2);
        w_prefetch();
        if (poller && MOD_MISSING) mv = ldx128(mp);
        if (warp < 8) {
            if (warp >= 4) sts16(sm + OFF_MODA + ((warp - 3) * 32 + lane) * 16 + (warp - 4) * 4 + 2, 0);
            const int k1 = tid & 15, s1 = tid >> 4;
            float s, c;
            __sincosf((float)(((k1 * (128 * s1 + b) + 1024) & 2047) - 1024) * (3.14159265358979f / 1024.f), &s, &c); s *= 0.25f; c *= 0.25f;
            const int rf = ((s1 >> 3) * 4 + (k1 >> 2)) * 2 + ((s1 >> 2) & 1), ri = ((k1 >> 3) * 4 + (s1 >> 2)) * 2 + ((k1 >> 2) & 1);
            const uint32_t af = sm + OFF_B3 + ((rf >> 2) * 32 + (k1 & 3) * 8 + (s1 & 3)) * 16 + (rf & 3) * 4;
            const uint32_t ai = sm + OFF_B3 + 2048 + ((ri >> 2) * 32 + (s1 & 3) * 8 + (k1 & 3)) * 16 + (ri & 3) * 4;
            sts32(af, pack_h(c, s)); sts32(af + 64, pack_h(-s, c)); sts32(ai, pack_h(c, -s)); sts32(ai + 64, pack_h(s, c));
        }
        if (poller) {
            #pragma unroll 1
            for (int it = 0; __any_sync(~0u, MOD_MISSING); it++) { if (MOD_MISSING) mv = ldx128(mp); hb(); if (it > SPIN_LIMIT) __trap(); }
            sts16(ma, mv.x >> 16); sts16(ma + 64, mv.y >> 16); sts16(ma + 128, mv.z >> 16); sts16(ma + 192, mv.w >> 16);
        }
        uint32_t redo = 0; asm volatile("" : "+r"(redo));
        #pragma unroll 1
        do { if (redo) {
            const uint32_t w[4] = {mv.x, mv.y, mv.z, mv.w}; float f[4]; uint32_t big = 0;
            #pragma unroll
            for (int e = 0; e < 4; e++) { f[e] = (w[e] & 0x8000u) ? bf_hi(w[e]) : __half2float(__ushort_as_half(w[e] >> 16)); big = max(big, __float_as_uint(f[e]) << 1 >> 24); }
            sts32(sm + OFF_HEXP + warp * 4, __reduce_max_sync(~0u, big));
            __syncthreads();
            hexp = min(__reduce_max_sync(~0u, lds32(sm + OFF_HEXP + (lane & 15) * 4)), 253u) - 127;
            const float sc = __uint_as_float((127 - hexp) << 23);
            if (poller) {
                #pragma unroll
                for (int e = 0; e < 4; e++) sts16(ma + 64 * e, pack_h(f[e] * sc, 0.f));
            }
            mv = make_uint4(0, 0, 0, 0);
          }
          redo = __syncthreads_or((mv.x | mv.y | mv.z | mv.w) & 0x8000u);
          asm volatile("" : "+r"(redo));
        } while (redo);
        PROF0(3);
        asm volatile("barrier.cluster.arrive.relaxed.aligned;" ::: "memory");
        if (warp >= 13 && elect()) {
            if (warp == 15) bulk_load(sm + OFF_TAB + QA * 512, p.tab->w + QA * 128, (QB + QC) * 512, bars + 8 * BAR_TAB2);
            else tma3(sm + OFF_WRAW + (warp - 13) * 14336, warp == 13 ? &tm_wr : &tm_wi, wc0 & ~7, 0, 0, bars + 8 * BAR_W);
        }
        __syncwarp();
        {
            uint32_t md[20];
            load_tab<5>(md, sm + OFF_MODA + lane * 16);
            #pragma unroll
            for (int v = 0; v < 2; v++)
                #pragma unroll
                for (int pp = 0; pp < 5; pp++) nb[v][pp] = hfma2(nb[v][pp], md[v * 5 + pp], md[10 + v * 5 + pp]);
        }
        uint32_t re[3][2], im[3][2];
        #pragma unroll
        for (int mt = 0; mt < 3; mt++)
            #pragma unroll
            for (int v = 0; v < 2; v++) {
                re[mt][v] = 0; im[mt][v] = 0;
                mma_h8(re[mt][v], im[mt][v], ta[24 + 2 * mt], ta[25 + 2 * mt], nb[v][4]);
                mma_h(re[mt][v], im[mt][v], ta[mt * 8], ta[mt * 8 + 1], ta[mt * 8 + 2], ta[mt * 8 + 3], nb[v][0], nb[v][1]);
                mma_h(re[mt][v], im[mt][v], ta[mt * 8 + 4], ta[mt * 8 + 5], ta[mt * 8 + 6], ta[mt * 8 + 7], nb[v][2], nb[v][3]);
                cmul_neg(re[mt][v], im[mt][v], ta[30 + (mt * 2 + v) * 2], ta[31 + (mt * 2 + v) * 2]);
            }
        const uint32_t srow = sm + OFF_SPEC + warp * (SPEC_P * 4);
        #pragma unroll
        for (int nt = 0; nt < 2; nt++) {
            uint32_t o[2][4];
            #pragma unroll
            for (int v = 0; v < 2; v++) {
                const uint32_t b0 = ta[42 + (v * 2 + nt) * 2], b1 = ta[43 + (v * 2 + nt) * 2];
                o[v][0] = o[v][1] = o[v][2] = o[v][3] = 0;
                mma_h(o[v][0], o[v][1], re[0][v], re[1][v], im[0][v], im[1][v], b0, b1);
                mma_h(o[v][2], o[v][3], re[2][0], re[2][1], im[2][0], im[2][1], b0, b1);
            }
            const uint32_t a = srow + (g + 72 * q + 36 * nt) * 4, a2 = srow + (288 - g - 72 * q - 36 * nt) * 4;
            sts32(a, hadd2(o[0][0], o[1][0])); sts32(a + 32, hadd2(o[0][1], o[1][1])); if (g < 3) sts32(a + 64, hadd2(o[0][2], o[1][3]));
            if (g > 0 || (q == 0 && nt == 0)) sts32(a2, hsub2(o[0][0], o[1][0]) ^ 0x80000000u);
            sts32(a2 - 32, hsub2(o[0][1], o[1][1]) ^ 0x80000000u); if (g < 2) sts32(a2 - 64, hsub2(o[0][2], o[1][3]) ^ 0x80000000u);
        }
        uint32_t b3[16];
        if (warp < 10) load_tab<4>(b3, sm + OFF_B3 + lane * 16);
        __syncthreads();
        t_st = clk32();
        PROF0(4);
        if (warp < 10) {
            uint4 V[4], o[4];
            #pragma unroll
            for (int u = 0; u < 4; u++) V[u] = lds128(scol + u * (16 * SPEC_P));
            radix16(V, b3, o);
            #pragma unroll
            for (int nt = 0; nt < 4; nt++) { o[nt].x |= 1u; if (warp < 9 || g < 2) stx128(tptr + nt * tstr, o[nt]); }
        }
        PROF0(5);
    }

    int role = 0;
    asm volatile("barrier.cluster.wait.aligned;" ::: "memory");
    if (warp >= 12) {
        const int t = tid - 384;
        if (warp == 14 && rank == 0) {
            uint32_t smid; asm volatile("mov.u32 %0, %%smid;" : "=r"(smid));
            const uint32_t tp = smid >> 1;
            uint32_t pr = tp < 32 ? (tp & 7) * 8 + (tp >> 3) : tp < 60 ? (1 + (tp - 32) % 7) * 8 + 4 + (tp - 32) / 7 : tp < 62 ? 4 + tp : tp < 66 ? tp - 58 : 0;
            #pragma unroll 1
            for (;;) {
                uint32_t old = 0; if (lane == 0) old = atomicExch(g_slot + pr, epoch + 1);
                if (!__any_sync(~0u, lane == 0 && old == epoch + 1)) break;
                pr = pr == 65 ? 0 : pr + 1;
            }
            if (lane < 2) asm volatile("st.async.weak.shared::cluster.mbarrier::complete_tx::bytes.u32 [%0], %1, [%2];" :: "r"(mapa(sm + OFF_MISC, lane)), "r"(pr), "r"(mapa(bars + 8 * BAR_ROLE, lane)) : "memory");
        }
        __syncwarp();
        if (t == 0) {
            asm volatile("prefetch.tensormap [%0];" :: "l"(&tm_w1a) : "memory");
            asm volatile("prefetch.tensormap [%0];" :: "l"(&tm_h3a) : "memory"); asm volatile("prefetch.tensormap [%0];" :: "l"(&tm_w1b) : "memory");
            asm volatile("prefetch.tensormap [%0];" :: "l"(&tm_h3b) : "memory"); asm volatile("prefetch.tensormap [%0];" :: "l"(&tm_w2) : "memory");
            asm volatile("prefetch.tensormap [%0];" :: "l"(&tm_o) : "memory"); asm volatile("prefetch.tensormap [%0];" :: "l"(&tm_h3s) : "memory");
        }
        __syncwarp();
        if (rowcta) {
            spin_until(t0 + NCP);
            uint4 v[2];
            v[1] = make_uint4(1, 1, 1, 1);
            #pragma unroll 1
            for (int it = 0;; it++) {
                v[0] = ldx128(p.scr->modc + 4 * t); if (t < 88) v[1] = ldx128(p.scr->modc + 512 + 4 * t);
                if (__all_sync(~0u, min(min(min(v[0].x, v[0].y), min(v[0].z, v[0].w)), min(min(v[1].x, v[1].y), min(v[1].z, v[1].w))) != 0)) break;
                __nanosleep(100); if (it > SPIN_LIMIT) __trap();
            }
            if (t < 72) { const uint32_t sc = ((127 + hexp) << 7) * 0x10001u;
                v[0] = make_uint4(bfma2(v[0].x, sc, 0x80008000u), bfma2(v[0].y, sc, 0x80008000u), bfma2(v[0].z, sc, 0x80008000u), bfma2(v[0].w, sc, 0x80008000u)); }
            #pragma unroll
            for (int u = 0; u < 2; u++) if (u == 0 || t < 88) {
                const uint32_t a = sm + OFF_MODC + (((t >> 5) + 4 * u) * 32 + 4 * (t & 7)) * 16 + ((t >> 3) & 3) * 4;
                sts32(a, v[u].x); sts32(a + 16, v[u].y); sts32(a + 32, v[u].z); sts32(a + 48, v[u].w);
            }
            __syncwarp();
            if (elect()) mbar_arrive(bars + 8 * BAR_NC);
            if (t == 0) PROFT(29);
        }
    } else if (rowcta && warp < 11) {
        const int nw = !(b & 1) ? 10 : (b & 7) == 7 ? 9 : 8;
        const int cm = (b >> 3) * 288 + (b & 7) * 32, cx = (b & 1) ? 4608 + 8 * (b >> 3) : (b >> 3) * 288 + 256 + 4 * (b & 7);
        auto load_in = [&]() {
            if (elect()) {
                mbar_expect(bars + 8 * BAR_XB, nw > 8 ? 20480 : 16384);
                tma2(sm + OFF_STAGE, &tm_t, cm, 0, bars + 8 * BAR_XB);
                if (nw > 8) tma2(sm + OFF_STX, &tm_tx, cx, 0, bars + 8 * BAR_XB);
            }
            __syncwarp();
        };
        if (warp == 10) { fence_async_s(); spin_until(t_st + X1D); load_in(); }
        uint32_t tb[QB * 4], wre[4][2], wim[4][2];
        if (warp < nw) {
            mbar_wait(bars + 8 * BAR_TAB2, 0);
            load_tab<QB>(tb, sm + OFF_TAB + QA * 512 + lane * 16);
            mbar_wait(bars + 8 * BAR_W, 0);
            const int off = wc0 & 7;
            const uint32_t wa = sm + OFF_WRAW + lane * 112 + ((off >> 1) + 2 * warp) * 4, sh = (off & 1) * 16;
            #pragma unroll
            for (int c = 0; c < 2; c++)
                #pragma unroll
                for (int h = 0; h < 2; h++) {
                    uint32_t y[2][2];
                    #pragma unroll
                    for (int e = 0; e < 2; e++) {
                        const uint32_t a = wa + c * 14336 + (h + 2 * e) * 3584, x0 = lds32(a), x1 = lds32(a + 4), x2 = lds32(a + 8);
                        y[e][0] = __funnelshift_r(x0, x1, sh); y[e][1] = __funnelshift_r(x1, x2, sh);
                    }
                    #pragma unroll
                    for (int x = 0; x < 4; x++) {
                        const uint32_t v = (x & 1) ? pack_h(bf_hi(y[0][x >> 1]), bf_hi(y[1][x >> 1])) : pack_h(bf_lo(y[0][x >> 1]), bf_lo(y[1][x >> 1]));
                        if (c) wim[x][h] = v; else wre[x][h] = v;
                    }
                }
        }
        const uint32_t ca = warp < 8 ? sm + OFF_STAGE + lane * 128 + (warp ^ (lane & 7)) * 16 : sm + OFF_STX + lane * 32 + ((warp ^ g) & 1) * 16, cs = warp < 8 ? 4096 : 1024;
        uint32_t V[4][4];
        #pragma unroll 1
        for (int it = 0;; it++) {
            mbar_wait(bars + 8 * BAR_XB, it & 1);
            uint32_t ok = 1;
            if (warp < nw) {
                #pragma unroll
                for (int u = 0; u < 4; u++) { uint4 t4 = lds128(ca + u * cs); V[u][0] = t4.x; V[u][1] = t4.y; V[u][2] = t4.z; V[u][3] = t4.w; ok &= t4.x; }
            }
            asm volatile("{.reg .pred p; setp.ne.u32 p, %0, 0; bar.red.and.pred p, 1, 352, p; selp.u32 %0, 1, 0, p;}" : "+r"(ok) :: "memory");
            if (ok) break;
            if (warp == 10) { load_in(); hb(); }
            if (it > SPIN_LIMIT / 64) __trap();
        }
        PROF0(7);
        if (warp < nw) {
            uint32_t zr[4][2], zi[4][2];
            #pragma unroll
            for (int x = 0; x < 4; x++) {
                uint32_t er = 0, ei = 0, or_ = 0, oi = 0;
                mma_h(er, ei, tb[0], tb[1], tb[2], tb[3], V[0][x], V[1][x]);
                mma_h(or_, oi, tb[4], tb[5], tb[6], tb[7], V[2][x], V[3][x]);
                uint32_t r0 = hadd2(er, or_), r1 = hsub2(er, or_), i0 = hadd2(ei, oi), i1 = hsub2(ei, oi);
                cmul_neg(r0, i0, tb[8], tb[9]); cmul_neg(r1, i1, tb[10], tb[11]);
                uint32_t xr0 = 0, xr1 = 0, xi0 = 0, xi1 = 0;
                mma_h(xr0, xr1, r0, r1, i0, i1, tb[12], tb[13]);
                mma_h(xi0, xi1, r0, r1, i0, i1, tb[14], tb[15]);
                cmul_pos(xr0, xi0, wre[x][0], wim[x][0]); cmul_pos(xr1, xi1, wre[x][1], wim[x][1]);
                r0 = 0; i0 = 0; r1 = 0; i1 = 0;
                mma_h(r0, i0, tb[12], tb[13], tb[14], tb[15], xr0, xi0);
                mma_h(r1, i1, tb[12], tb[13], tb[14], tb[15], xr1, xi1);
                cmul_pos(r0, i0, tb[16], tb[17]); cmul_pos(r1, i1, tb[18], tb[19]);
                zr[x][0] = hadd2(r0, r1); zr[x][1] = hsub2(r0, r1); zi[x][0] = hadd2(i0, i1); zi[x][1] = hsub2(i0, i1);
            }
            #pragma unroll
            for (int nt = 0; nt < 4; nt++) {
                uint4 o = make_uint4(0, 0, 0, 0);
                const int h = nt >> 1;
                mma_h(o.x, o.y, zr[0][h], zr[1][h], zi[0][h], zi[1][h], tb[20 + 2 * nt], tb[21 + 2 * nt]);
                mma_h(o.z, o.w, zr[2][h], zr[3][h], zi[2][h], zi[3][h], tb[20 + 2 * nt], tb[21 + 2 * nt]);
                o.x &= ~1u;
                sts128(ca + nt * cs, o);
            }
        }
        fence_async_s();
        bar_sync(1, 352);
        t_st = clk32();
        PROF0(8);
        if (warp == 10 && elect()) {
            asm volatile("cp.async.bulk.tensor.2d.global.shared::cta.bulk_group [%0, {%2, %3}], [%1];" :: "l"(&tm_t), "r"(sm + OFF_STAGE), "r"(cm), "r"(0) : "memory");
            if (nw > 8) asm volatile("cp.async.bulk.tensor.2d.global.shared::cta.bulk_group [%0, {%2, %3}], [%1];" :: "l"(&tm_tx), "r"(sm + OFF_STX), "r"(cx), "r"(0) : "memory");
            asm volatile("cp.async.bulk.commit_group;" ::: "memory");
            asm volatile("cp.async.bulk.wait_group.read 0;" ::: "memory");
        }
        __syncwarp();
    }

    if (warp >= 10) { mbar_wait(bars + 8 * BAR_ROLE, 0); role = __shfl_sync(~0u, lds32(sm + OFF_MISC), 0); fence_async_s(); }
    auto first_a = [&]() {
        if (warp >= 10 && role < 64 && elect()) {
            const int it = warp - 10, hi = it >= 3; const bool p2 = it - 3 * hi == 2;
            tma4(sm + OFF_A + it * A_BYTES, p2 ? &tm_w1b : &tm_w1a, 0, 0, p2 ? 64 * rank + 8 * hi : 4 * (it - hi),
                 9 * (role >> 3) + (p2 ? 8 : (role & 4) + 2 * rank), bars + 8 * (BAR_FULL + it));
        }
        __syncwarp();
    };
    if (!rowcta) first_a();
    else {
        uint32_t tc[20], md[28];
        mbar_wait(bars + 8 * BAR_TAB2, 0);
        load_tab<5>(tc, sm + OFF_TAB + (QA + QB) * 512 + lane * 16);
        bool md_early = warp >= 10;
        if (md_early) { mbar_wait(bars + 8 * BAR_NC, 0); load_tab<7>(md, sm + OFF_MODC + lane * 16); }
        if (warp < 10) {
            uint32_t b3[16];
            load_tab<4>(b3, sm + OFF_B3 + 2048 + lane * 16);
            uint4 V[4], o[4];
            const bool tact = warp < 9 || g == 0;
            spin_until(t_st + X2D);
            #pragma unroll
            for (int u = 0; u < 4; u++) { V[u] = make_uint4(0, 0, 0, 0); if (tact) V[u] = ldx128(tptr + u * tstr); }
            md_early = __any_sync(~0u, mbar_test(bars + 8 * BAR_NC, 0));
            if (md_early) load_tab<7>(md, sm + OFF_MODC + lane * 16);
            #pragma unroll 1
            for (int it = 0; __any_sync(~0u, (V[0].x | V[1].x | V[2].x | V[3].x) & 1u); it++) {
                #pragma unroll
                for (int u = 0; u < 4; u++) if (V[u].x & 1u) V[u] = ldx128(tptr + u * tstr);
                hb();
                if (it > SPIN_LIMIT) __trap();
            }
            PROF0(10);
            radix16(V, b3, o);
            if (tact) {
                #pragma unroll
                for (int nt = 0; nt < 4; nt++) sts128(scol + nt * (16 * SPEC_P), o[nt]);
            }
        }
        __syncthreads();
        PROF0(11);
        first_a();
        const uint32_t srow = sm + OFF_SPEC + warp * (SPEC_P * 4);
        uint32_t re[2][3], im[2][3];
        #pragma unroll
        for (int mt = 0; mt < 3; mt++) {
            const uint32_t a = srow + (g + 72 * q + 8 * mt) * 4, a2 = srow + (288 - g - 72 * q - 8 * mt) * 4;
            const uint32_t z0 = lds32(a), z1 = lds32(a + 144), z2 = lds32(a2), z3 = lds32(a2 - 144);
            #pragma unroll
            for (int m2 = 0; m2 < 2; m2++) {
                re[m2][mt] = 0; im[m2][mt] = 0;
                const uint32_t sg = m2 ? 0x3C00BC00u : 0xBC003C00u;
                mma_h(re[m2][mt], im[m2][mt], tc[m2 * 4], tc[m2 * 4 + 1], tc[m2 * 4 + 2], tc[m2 * 4 + 3], hfma2(z2, sg, z0), hfma2(z3, sg, z1));
                cmul_pos(re[m2][mt], im[m2][mt], tc[8 + (m2 * 3 + mt) * 2], tc[9 + (m2 * 3 + mt) * 2]);
            }
        }
        float y[20];
        WG_FENCE();
        #pragma unroll
        for (int mt = 0; mt < 3; mt++)
            wgmma40_rs(y, re[0][mt], re[1][mt], im[0][mt], im[1][mt], desc_lo(OFF_TAB + (QA + QB + 5) * 512 + mt * 1280, 128), mt);
        WG_COMMIT();
        if (!md_early) { mbar_wait(bars + 8 * BAR_NC, 0); load_tab<7>(md, sm + OFF_MODC + lane * 16); }
        WG_WAIT(0);
        #pragma unroll
        for (int i = 0; i < 9; i++) xw[i] = bfma2(md[i], pack_bf(y[4 * (i >> 1) + (i & 1)], y[4 * (i >> 1) + 2 + (i & 1)]), xw[i]);
        float r, mr;
        ln_stats(xw, one, g, q, r, mr);
        uint32_t r2 = pack_bf(r, r), m2 = pack_bf(mr, mr);
        #pragma unroll
        for (int i = 0; i < 9; i++) {
            sts32(sm + OFF_X1 + warp * 1152 + (32 * i + 8 * q + g) * 4, xw[i]);
            xw[i] = bfma2(bfma2(xw[i], r2, m2), md[18 + i], md[9 + i]);
        }
        ln_stats(xw, one, g, q, r, mr);
        r2 = pack_bf(r, r); m2 = pack_bf(mr, mr);
        {
            const int n7 = 2 * q + (g >> 2);
            const uint32_t a = sm + OFF_STAGE + (warp >> 3) * 9216 + n7 * 128 + ((warp & 7) ^ n7) * 16 + (g & 3) * 4;
            #pragma unroll
            for (int i = 0; i < 9; i++) sts32(a + i * 1024, bfma2(xw[i], r2, m2));
        }
        fence_async_s();
        __syncthreads();
        PROF0(12);
        if (tid == 0) {
            asm volatile("cp.async.bulk.tensor.4d.global.shared::cta.bulk_group [%0, {%2, %2, %2, %3}], [%1];" :: "l"(&tm_h3s), "r"(sm + OFF_STAGE), "r"(0), "r"(b) : "memory");
            asm volatile("cp.async.bulk.commit_group;" ::: "memory");
        }
    }
    if (!rowcta) __syncthreads();
    else {
        if (tid == 0) { asm volatile("cp.async.bulk.wait_group 0;" ::: "memory"); fence_async_g(); red_release(g_cnt + CNT_H3 * 32); }
        PROF0(13);
        if (warp == 15) {
            __nanosleep(X1DELAY);
            #pragma unroll 1
            for (int r = 0; r < 16; r++) {
                if (lane == 0) asm volatile("cp.async.bulk.global.shared::cta.bulk_group [%0], [%1], 1152;" :: "l"(p.out + (size_t)(b + 128 * r) * D_), "r"(sm + OFF_X1 + r * 1152) : "memory");
                const uint32_t t1 = clk32();
                #pragma unroll 1
                while (__any_sync(~0u, (int)(clk32() - t1) < X1PACE)) __nanosleep(50);
            }
            if (lane == 0) {
                asm volatile("cp.async.bulk.commit_group;" ::: "memory");
                asm volatile("cp.async.bulk.wait_group 0;" ::: "memory");
                if (role < 64) mbar_arrive_remote(mapa(bars + 8 * BAR_HOLD, rank ^ 1));
                fence_async_g(); red_release(g_cnt + CNT_X1 * 32);
            }
        }
    }
    role = __shfl_sync(~0u, lds32(sm + OFF_MISC), 0);
    if ((sm & 0xFFFFFFu) != SM0) __trap();
    if (role >= 64) { if (warp == 0) PROFDUMP(); return; }

    const int gi = role >> 3, dt = role & 3, c2 = (role >> 2) & 1;
    const int wg = warp >> 2, wi = warp & 3;
    if (wg == 3) {
        uint32_t so = 0, eph = 1;
        #define RING_STEP(BYTES, OFF, ISSUE) do { \
            mbar_wait(bars + 8 * BAR_EMPTY + so, eph); \
            if (elect()) { const uint32_t fb = bars + 8 * BAR_FULL + so, dst = sm + (OFF) + so * ((BYTES) / 8); mbar_expect(fb, BYTES); ISSUE; } \
            so += 8; if (so == 8 * NST) { so = 0; eph ^= 1; } } while (0)
        const uint32_t kbt = g2_kb(lane, rank, gi, c2) | (g2_kb(32 + (lane & 3), rank, gi, c2) << 8);
        #define KB(n_) ((__shfl_sync(~0u, kbt, (n_) & 31) >> (((n_) >> 2) & 8)) & 255)
        if (warp == 12) {
            eph = 0;
            const int fb1 = 9 * gi + 4 * c2 + 2 * rank, sb2 = 4 * gi + 2 * c2;
            int pft = dt, pfj = 4 * (PF0 + PFS * dt);
            #pragma unroll 1
            for (int j = 16; j < 128; j += 4) {
                RING_STEP(A_BYTES, OFF_A, tma4(dst, &tm_w1a, 0, 0, j, fb1, fb));
                if (j < 64) { if (j & 4) RING_STEP(A_BYTES, OFF_A, tma4(dst, &tm_w1b, 0, 0, 64 * rank + j - 4, 9 * gi + 8, fb)); }
                if (__any_sync(~0u, j == pfj && pft < PFN)) {
                    const int kb = KB(pft); pft += 4; pfj += 16 * PFS;
                    if (elect()) asm volatile("cp.async.bulk.prefetch.tensor.3d.L2.global [%0, {%1, %2, %3}];" :: "l"(&tm_w2), "r"(0), "r"(64 * kb), "r"(sb2) : "memory");
                }
            }
            #pragma unroll 1
            for (int n = 0; n < 36; n++) {
                const int kb = KB(n);
                RING_STEP(A_BYTES, OFF_A, tma3(dst, &tm_w2, 0, 64 * kb, sb2, fb));
            }
        } else if (warp == 13) {
            const uint32_t e1 = __shfl_sync(~0u, epoch + 1, 0);
            fence_async_s();
            wait_count<0>(g_cnt + CNT_H3 * 32, e1 * 128);
            fence_async_g();
            if (lane == 0) PROFT(14);
            #pragma unroll 1
            for (int j = 0; j < 128; j += 4) {
                RING_STEP(B_BYTES, OFF_B, tma3(dst, &tm_h3a, 0, 18 * dt, j, fb));
                if (j < 64 && (j & 4)) RING_STEP(B_BYTES, OFF_B, tma3(dst, &tm_h3b, 0, 18 * dt + 9 * c2, 64 * rank + j - 4, fb));
            }
            int n = 0;
            #pragma unroll 1
            for (int cls = 0; cls < 3; cls++) {
                mbar_wait(bars + 8 * (BAR_UOK + cls), 0);
                fence_async_g();
                if (cls == 1 && lane == 0) PROFT(19);
                if (cls == 0 && lane == 0) PROFT(22);
                static_assert((IT_G2 + 4) % NST != NST - 1, "no wrap at the skipped stage");
                if (cls == 1) { n++; so += 8; }
                #pragma unroll 1
                for (; n < (cls == 0 ? 4 : cls == 1 ? 21 : 36); n++) {
                    const int kb = KB(n);
                    RING_STEP(B_BYTES, OFF_B, bulk_load(dst, g_U + (kb * 4 + dt) * 1152, B_BYTES, fb));
                }
            }
            if (role == 0 && rank == 0 && lane == 0) st_relaxed(g_cnt + CNT_EPOCH * 32, e1);
        } else if (warp == 15) {
            if (!rowcta && elect()) mbar_arrive_remote(mapa(bars + 8 * BAR_HOLD, rank ^ 1));
            __syncwarp();
            bar_sync(6, 160);
            if (elect()) mbar_arrive(bars + 8 * (BAR_FULL + (IT_G2 + 4) % NST));
            __syncwarp();
            mbar_wait(bars + 8 * BAR_W1GO, 0);
            if (elect()) {
                char* dst = (char*)(g_U + ((9 * gi + 4 * c2 + 2 * rank + 1) * 4 + dt) * 1152);
                #pragma unroll 1
                for (int i = 0; i < W1N; i++) {
                    asm volatile("cp.async.bulk.global.shared::cta.bulk_group [%0], [%1], %2;" :: "l"(dst + i * (18432 / W1N)), "r"(sm + OFF_X1 + i * (18432 / W1N)), "n"(18432 / W1N) : "memory");
                    const uint32_t t1 = clk32(); while ((int)(clk32() - t1) < W1P) {}
                }
                asm volatile("cp.async.bulk.commit_group;" ::: "memory");
                asm volatile("cp.async.bulk.wait_group 0;" ::: "memory");
                fence_async_g(); red_release(g_cnt + (CNT_U + 16) * 32);
                #pragma unroll 1
                for (int n = 0; n < 4; n++) { __nanosleep(300); tma2(sm + OFF_X1 + n * 4608, &tm_o, 144 * dt, 256 * gi + 128 * c2 + 64 * (rank ^ 1) + 16 * n, bars + 8 * BAR_XT); }
            }
        } else {
            const uint32_t e1 = epoch + 1;
            if (lane == 0) {
                __nanosleep(4000);
                wait_count<200>(g_cnt + CNT_NC * 32, e1 * 4); wait_count<200>(g_cnt + (CNT_NC + 1) * 32, e1 * 2);
                fence_async_g();
                mbar_expect(bars + 8 * BAR_GB, 1152);
                bulk_load(sm + OFF_GB, p.scr->modc + 896, 1152, bars + 8 * BAR_GB);
                wait_count<200>(g_cnt + CNT_X1 * 32, e1 * 128);
                if (role * 2 + rank < 108) {
                    uint4* z = (uint4*)p.scr->modc + (role * 2 + rank) * 2; z[0] = z[1] = make_uint4(0, 0, 0, 0);
                }
                wait_count<50>(g_cnt + (CNT_U + dt * 2 + rank) * 32, e1 * 16);
                mbar_arrive(bars + 8 * BAR_UOK);
            }
            __syncwarp();
            bar_sync(4, 160);
            if (lane == 0) {
                fence_async_g(); red_release(g_cnt + (CNT_U + 8) * 32);
                PROFT(17);
                wait_count<0>(g_cnt + (CNT_U + 8) * 32, e1 * 128);
                mbar_arrive(bars + 8 * (BAR_UOK + 1));
                __nanosleep(1000);
                wait_count<100>(g_cnt + (CNT_U + 16) * 32, e1 * 128);
                mbar_arrive(bars + 8 * (BAR_UOK + 2));
            }
        }
    } else if (wg == 2) {
        float d0[36];
        const float bias = bf_lo(ldg_nc16(p.b1 + 576 * gi + 512 + 16 * wi + g + 8 * rank));
        #pragma unroll 1
        for (int it = 0; it < 200 && !__any_sync(~0u, mbar_test(bars + 8 * BAR_FULL, 0)); it++) { hb(); __nanosleep(100); }
        const bool lead = wi == 0 && elect();
        #pragma unroll 1
        for (int i = 0; i < 8; i++) {
            const uint32_t s = P2S + 3 * (i & 1);
            mbar_wait(bars + 8 * BAR_FULL + 8 * s, (i >> 1) & 1);
            const uint32_t da = desc_lo(OFF_A, 8192) + s * (A_BYTES / 16), db = desc_lo(OFF_B, 128) + s * (B_BYTES / 16);
            WG_FENCE();
            wgmma72(d0, da, db, i);
            #pragma unroll
            for (int k = 1; k < 9; k++) {
                if (k == P2K) asm volatile("{.reg .pred p; setp.ne.u32 p, %1, 0; @p mbarrier.arrive.shared::cta.b64 _, [%0];}" :: "r"(bars + 8 * (BAR_P2N + (i & 1))), "r"((uint32_t)lead) : "memory");
                if (k < 8) wgmma72(d0, da + k * 128, db + k * 144, 1);
            }
            WG_COMMIT();
            WG_WAIT(0);
            if (lead) mbar_arrive_n(bars + 8 * BAR_EMPTY + 8 * s, 2);
        }
        if (lead) PROFT(18);
        const uint32_t slot = sm + OFF_P2R + (tid & 127) * 16, ra = mapa(slot, rank ^ 1), rb = mapa(bars + 8 * BAR_P2R, rank ^ 1);
        float sv[18];
        #pragma unroll
        for (int i = 0; i < 18; i++) { const float lo = d0[4 * (i >> 1) + (i & 1)], hi = d0[4 * (i >> 1) + 2 + (i & 1)];
            sv[i] = rank ? lo : hi; d0[4 * (i >> 1) + (i & 1)] = (rank ? hi : lo) + bias; }
        mbar_wait(bars + 8 * BAR_HOLD, 0);
        #pragma unroll
        for (int i = 0; i < 4; i++)
            asm volatile("st.async.weak.shared::cluster.mbarrier::complete_tx::bytes.v4.f32 [%0], {%1,%2,%3,%4}, [%5];"
                :: "r"(ra + i * 2048), "f"(sv[4 * i]), "f"(sv[4 * i + 1]), "f"(sv[4 * i + 2]), "f"(sv[4 * i + 3]), "r"(rb) : "memory");
        asm volatile("st.async.weak.shared::cluster.mbarrier::complete_tx::bytes.v2.f32 [%0], {%1,%2}, [%3];" :: "r"(ra + 8192), "f"(sv[16]), "f"(sv[17]), "r"(rb) : "memory");
        mbar_wait(bars + 8 * BAR_P2R, 0);
        #pragma unroll
        for (int i = 0; i < 5; i++) {
            const uint4 v = lds128(slot + i * 2048);
            d0[8 * i] += __uint_as_float(v.x); d0[8 * i + 1] += __uint_as_float(v.y);
            if (i < 4) { d0[8 * i + 4] += __uint_as_float(v.z); d0[8 * i + 5] += __uint_as_float(v.w); }
        }
        asm volatile("bar.arrive 5, 256;" ::: "memory");
        gelu_store<0>(d0, (char*)(g_U + ((9 * gi + 8) * 4 + dt) * 1152) + wi * 4608 + rank * 2304 + c2 * 1152 + g * 16, q);
        bar_sync(8, 128);
        if (lead) { fence_async_g(); red_release(g_cnt + (CNT_U + dt * 2 + (gi >> 2)) * 32); PROFT(26); }
    } else {
        float d[72];
        const bool lead = wi == 0 && elect();
        const uint32_t da0 = desc_lo(OFF_A, 8192) + wg * 512;
        const bool owner = (uint32_t)wg == rank;
        const int srow = 256 * gi + 128 * c2 + 64 * wg + 16 * wi;
        const uint32_t b2w0 = ldg_nc16(p.b2 + srow + g), b2w1 = ldg_nc16(p.b2 + srow + g + 8);
        const int fr = 576 * gi + 256 * c2 + 128 * rank + 64 * wg + 16 * wi + g;
        const float bias0 = bf_lo(ldg_nc16(p.b1 + fr)), bias1 = bf_lo(ldg_nc16(p.b1 + fr + 8));
        {
            #pragma unroll
            for (int i = 0; i < 72; i++) d[i] = (i & 2) ? bias1 : bias0;
            constexpr uint32_t db1 = desc_lo(OFF_B, 128);
            static_assert(IT_G2 - LEAD1 == 6 * NST && IT_P1 == 4 * NST && P2S == 2, "loop structure");
            #define REL(s_) if (lead) mbar_arrive(bars + 8 * (BAR_EMPTY + (s_)))
            mma_block<DHI_H3, 0>(d, bars, da0, db1, 0);
            #pragma unroll 1
            for (int c = 0; c < 4; c++) {
                const uint32_t ph = c & 1;
                mma_block<DHI_H3, 1>(d, bars, da0, db1, ph); REL(0);
                mbar_wait(bars + 8 * (P2K ? BAR_P2N : BAR_FULL + 2), ph);
                mma_block<DHI_H3, 3>(d, bars, da0, db1, ph); REL(1);
                mma_block<DHI_H3, 4>(d, bars, da0, db1, ph); REL(3);
                mbar_wait(bars + 8 * (P2K ? BAR_P2N + 1 : BAR_FULL + 5), ph);
                mma_block<DHI_H3, 0>(d, bars, da0, db1, ph ^ 1); REL(4);
            }
            #pragma unroll 1
            for (uint32_t ph = 0; ph < 2; ph++) {
                mma_block<DHI_H3, 1>(d, bars, da0, db1, ph); REL(0);
                mma_block<DHI_H3, 2>(d, bars, da0, db1, ph); REL(1);
                mma_block<DHI_H3, 3>(d, bars, da0, db1, ph); REL(2);
                mma_block<DHI_H3, 4>(d, bars, da0, db1, ph); REL(3);
                mma_block<DHI_H3, 5>(d, bars, da0, db1, ph); REL(4);
                const bool pause = ph && wg == 1;
                if (pause) { WG_WAIT(0); REL(5); bar_sync(9, 256); }
                mma_block<DHI_H3, 0>(d, bars, da0, db1, ph ^ 1); if (!pause) REL(5);
            }
            #pragma unroll
            for (int i = IT_G2 - LEAD1 + 1; i < IT_G2; i++) {
                mbar_wait(bars + 8 * (BAR_FULL + i % NST), (i / NST) & 1);
                WG_FENCE();
                #pragma unroll
                for (int k = 0; k < 4; k++) {
                    if (i == IT_G2 - 1 && k == HOK1) WG_COMMIT();
                    wgmma144<DHI_H3>(d, da0 + (i % NST) * (A_BYTES / 16) + k * 128, db1 + (i % NST) * (B_BYTES / 16) + k * 288, 1);
                }
                WG_COMMIT();
                if (i == IT_G2 - 1 && HOK1 < 4) WG_WAIT(2); else WG_WAIT(1);
                REL((i - 1) % NST);
            }
            if (wg == 0) { WG_WAIT(1); asm volatile("bar.arrive 9, 256;" ::: "memory"); }
            WG_WAIT(0);
            if (lead) mbar_arrive(bars + 8 * (BAR_EMPTY + (IT_G2 - 1) % NST));
            PROF0(16);
            if (wg == 1) bar_sync(5, 256);
            char* const ub = (wg == 0 ? (char*)(g_U + ((9 * gi + 4 * c2 + 2 * rank) * 4 + dt) * 1152) : (char*)__cvta_shared_to_generic(sm + OFF_X1)) + wi * 4608 + g * 16;
            gelu_store<0>(d, ub, q); gelu_store<2>(d, ub + 2304, q); gelu_store<36>(d, ub + 1152, q); gelu_store<38>(d, ub + 3456, q);
            PROF0(27);
            if (wg == 0) asm volatile("bar.arrive 4, 160;" ::: "memory");
            else { fence_async_s(); asm volatile("bar.arrive 6, 160;" ::: "memory"); }
        }
        constexpr uint32_t db0 = desc_lo(OFF_B, 2304);
        const bool keep = role < 0;
        constexpr int IT_L = IT_END - NST;
        #pragma unroll
        for (int i = IT_G2; i <= IT_G2 + W1S; i++) {
            const uint32_t db = db0 + (i == IT_G2 + 4 ? OFF_X1 - OFF_B : (i % NST) * B_BYTES) / 16;
            mbar_wait(bars + 8 * (BAR_FULL + i % NST), (i / NST) & 1);
            WG_FENCE();
            #pragma unroll
            for (int k = 0; k < 4; k++) wgmma144<DHI_U>(d, da0 + (i % NST) * (A_BYTES / 16) + k * 128, db + k * 288, i > IT_G2 || k > 0 || keep);
            WG_COMMIT();
            if (i > IT_G2) { WG_WAIT(1); if (lead) mbar_arrive(bars + 8 * (BAR_EMPTY + (i - 1) % NST)); }
        }
        if (lead) mbar_arrive(bars + 8 * BAR_W1GO);
        const uint32_t ga0 = sm + OFF_GB + (144 * dt + 8 * q) * 2, tile = sm + OFF_X1 + wi * 4608, to = g * 288 + q * 16;
        #define QOFF(i_) (((i_) >> 2) * 2304 + 144 * (((i_) >> 1) & 1) + 64 * ((i_) & 1))
        #define SOFF(k_) (((k_) >> 1) * 2304 + 144 * ((k_) & 1) + 128 - 12 * q)
        #define DIDX(i_, k_) ((i_) < 8 ? 36 * (((i_) >> 1) & 1) + 16 * ((i_) & 1) + 4 * (k_) + 2 * ((i_) >> 2) : 36 * ((k_) & 1) + 32 + 2 * ((k_) >> 1))
        #define FIN(k_, f_) bfma2(g4.f_, pack_bf(d[DIDX(i, k_)], d[DIDX(i, k_) + 1]), xq[i].f_)
        uint4 xq[9];
        auto load_g = [&](int i) { uint4 r; if (i < 4) r = lds128(ga0 + QOFF(i)); else { r.x = r.z = lds32(ga0 + SOFF(0)); r.y = r.w = lds32(ga0 + SOFF(1)); } return r; };
        static_assert(W1S == 5 && (IT_G2 + 6) % NST == 4 && ((IT_G2 + 6) / NST) % 2 == 1 && IT_L == IT_G2 + 30, "loop structure");
        #pragma unroll 1
        for (int c = 0; c < 4; c++) {
            const uint32_t ph = c & 1, xa = tile + to; const bool xl = c == 3 && !owner;
            mma_block<DHI_U, 4>(d, bars, da0, db0, ph ^ 1); REL(3);
            mma_block<DHI_U, 5>(d, bars, da0, db0, ph ^ 1); REL(4);
            mma_block<DHI_U, 0>(d, bars, da0, db0, ph); REL(5);
            if (xl) { mbar_wait(bars + 8 * BAR_XT, 0); xq[0] = lds128(xa + QOFF(0)); xq[4] = lds128(xa + QOFF(4)); xq[1] = lds128(xa + QOFF(1)); }
            mma_block<DHI_U, 1>(d, bars, da0, db0, ph); REL(0);
            if (xl) { xq[5] = lds128(xa + QOFF(5)); xq[2] = lds128(xa + QOFF(2)); xq[6] = lds128(xa + QOFF(6)); }
            mma_block<DHI_U, 2>(d, bars, da0, db0, ph); REL(1);
            if (xl) { xq[3] = lds128(xa + QOFF(3)); xq[7] = lds128(xa + QOFF(7));
                      xq[8] = make_uint4(lds32(xa + SOFF(0)), lds32(xa + SOFF(1)), lds32(xa + SOFF(2)), lds32(xa + SOFF(3))); }
            mma_block<DHI_U, 3>(d, bars, da0, db0, ph); REL(2);
        }
        if (!owner && elect()) mbar_arrive_remote(mapa(bars + 8 * BAR_DONE, rank ^ 1));
        if (owner) { WG_WAIT(0); if (lead) mbar_arrive(bars + 8 * (BAR_EMPTY + (IT_L - 1) % NST)); bar_sync(7, 256); }
        #pragma unroll
        for (int i = IT_L; i < IT_END; i++) {
            mbar_wait(bars + 8 * (BAR_FULL + i % NST), (i / NST) & 1);
            WG_FENCE();
            #pragma unroll
            for (int k = 0; k < 4; k++) {
                if (i == IT_END - 1 && k == HOK) WG_COMMIT();
                wgmma144<DHI_U>(d, da0 + (i % NST) * (A_BYTES / 16) + k * 128, db0 + (i % NST) * (B_BYTES / 16) + k * 288, 1);
            }
            WG_COMMIT();
            if (i == IT_L) { WG_WAIT(1); if (lead && !owner) mbar_arrive(bars + 8 * (BAR_EMPTY + (IT_L - 1) % NST)); }
        }
        PROF0(9);
        mbar_wait(bars + 8 * BAR_GB, 0);
        if (!owner) {
            const uint32_t ra = mapa(tile + lane * 16, rank ^ 1), rb = mapa(bars + 8 * BAR_RECV, rank ^ 1);
            mbar_wait(bars + 8 * BAR_DONE, 0);
            uint4 gn = load_g(0);
            WG_WAIT(1);
            asm volatile("bar.arrive 7, 256;" ::: "memory");
            WG_WAIT(0);
            #pragma unroll
            for (int i = 0; i < 72; i++) d[i] = fmaf(bf_lo((i & 2) ? b2w1 : b2w0), 2.f, d[i]);
            #pragma unroll
            for (int j = 0; j < 5; j++) {
                const uint4 g4 = gn;
                if (j < 4) gn = load_g(j + 1);
                #pragma unroll
                for (int i = j < 4 ? j : 8; i < 9; i += 4) if (i < 8 || j == 4)
                    asm volatile("st.async.weak.shared::cluster.mbarrier::complete_tx::bytes.v4.b32 [%0], {%1,%2,%3,%4}, [%5];"
                        :: "r"(ra + i * 512), "r"(FIN(0, x)), "r"(FIN(1, y)), "r"(FIN(2, z)), "r"(FIN(3, w)), "r"(rb) : "memory");
            }
            PROF0(6);
            if (warp == 0) PROFDUMP();
            return;
        }
        PROF0(24);
        mbar_wait(bars + 8 * BAR_RECV, 0);
        #pragma unroll
        for (int i = 0; i < 9; i++) xq[i] = lds128(tile + lane * 16 + i * 512);
        uint4 gn = load_g(0);
        WG_WAIT(0);
        __syncwarp();
        PROF0(21);
        #pragma unroll
        for (int j = 0; j < 5; j++) {
            const uint4 g4 = gn;
            if (j < 4) gn = load_g(j + 1);
            #pragma unroll
            for (int i = j < 4 ? j : 8; i < 9; i += 4) if (i < 8 || j == 4) {
                const uint4 o = make_uint4(FIN(0, x), FIN(1, y), FIN(2, z), FIN(3, w));
                if (i < 8) sts128(tile + to + QOFF(i), o);
                else { sts32(tile + to + SOFF(0), o.x); sts32(tile + to + SOFF(1), o.y); sts32(tile + to + SOFF(2), o.z); sts32(tile + to + SOFF(3), o.w); }
            }
        }
        fence_async_s();
        __syncwarp();
        if (elect()) {
            asm volatile("cp.async.bulk.tensor.2d.global.shared::cta.bulk_group [%0, {%2, %3}], [%1];" :: "l"(&tm_o), "r"(tile), "r"(144 * dt), "r"(srow) : "memory");
            asm volatile("cp.async.bulk.commit_group;" ::: "memory");
            asm volatile("cp.async.bulk.wait_group.read 0;" ::: "memory");
        }
        PROF0(23);
        if (warp == 0) { __syncwarp(); PROFDUMP(); }
    }
}

typedef CUresult (*EncodeFn)(CUtensorMap*, CUtensorMapDataType, cuuint32_t, void*, const cuuint64_t*, const cuuint64_t*, const cuuint32_t*,
                             const cuuint32_t*, CUtensorMapInterleave, CUtensorMapSwizzle, CUtensorMapL2promotion, CUtensorMapFloatOOBfill);

void encode(EncodeFn fn, CUtensorMap* m, CUtensorMapDataType dt, int rank, const void* ptr, const cuuint64_t* dims, const cuuint64_t* strides,
            const cuuint32_t* box, CUtensorMapSwizzle sw, CUtensorMapL2promotion promo = CU_TENSOR_MAP_L2_PROMOTION_L2_128B) {
    const cuuint32_t es[5] = {1, 1, 1, 1, 1};
    fn(m, dt, rank, (void*)ptr, dims, strides, box, es, CU_TENSOR_MAP_INTERLEAVE_NONE, sw, promo, CU_TENSOR_MAP_FLOAT_OOB_FILL_NONE);
}

}

extern "C" void kernel_launch(void* const* d_in, const int* in_sizes, int n_in, void* d_out, int out_size) {
    (void)in_sizes; (void)n_in; (void)out_size;
    Params p;
    p.x = (const uint16_t*)d_in[0]; p.wr = (const uint16_t*)d_in[1]; p.wi = (const uint16_t*)d_in[2];
    p.w1 = (const uint16_t*)d_in[4]; p.b1 = (const uint16_t*)d_in[5]; p.w2 = (const uint16_t*)d_in[6]; p.b2 = (const uint16_t*)d_in[7];
    p.c = (const uint16_t*)d_in[8]; p.wmod = (const uint16_t*)d_in[9]; p.out = (uint16_t*)d_out;

    void* fnp = nullptr; cudaDriverEntryPointQueryResult qr;
    cudaGetDriverEntryPoint("cuTensorMapEncodeTiled", &fnp, cudaEnableDefault, &qr);
    EncodeFn fn = (EncodeFn)fnp;
    cudaGetSymbolAddress((void**)&p.scr, g_scr); cudaGetSymbolAddress((void**)&p.tab, g_tab);
    void* h3p = p.scr->h3;
    CUtensorMap tw1a, tw1b, tw2, th3a, th3b, twr, twi, twm, tt, ttx, to, th3s, tws;
    {
        const cuuint64_t dims[4] = {64, 16, 128, 72}, st[3] = {128ull * F_ * 2, (cuuint64_t)F_ * 2, 128};
        const cuuint32_t ba[4] = {64, 16, 4, 2}, bb[4] = {64, 16, 8, 1};
        encode(fn, &tw1a, CU_TENSOR_MAP_DATA_TYPE_BFLOAT16, 4, p.w1, dims, st, ba, CU_TENSOR_MAP_SWIZZLE_128B);
        encode(fn, &tw1b, CU_TENSOR_MAP_DATA_TYPE_BFLOAT16, 4, p.w1, dims, st, bb, CU_TENSOR_MAP_SWIZZLE_128B);
    }
    {
        const cuuint64_t dims[3] = {64, F_, 32}, st[2] = {(cuuint64_t)S_ * 2, 128};
        const cuuint32_t bx[3] = {64, 64, 2};
        encode(fn, &tw2, CU_TENSOR_MAP_DATA_TYPE_BFLOAT16, 3, p.w2, dims, st, bx, CU_TENSOR_MAP_SWIZZLE_128B);
    }
    {
        const cuuint64_t dims[3] = {64, 72, 128}, st[2] = {256, 18432};
        const cuuint32_t ba[3] = {64, 18, 4}, bb[3] = {64, 9, 8};
        encode(fn, &th3a, CU_TENSOR_MAP_DATA_TYPE_UINT32, 3, h3p, dims, st, ba, CU_TENSOR_MAP_SWIZZLE_NONE);
        encode(fn, &th3b, CU_TENSOR_MAP_DATA_TYPE_UINT32, 3, h3p, dims, st, bb, CU_TENSOR_MAP_SWIZZLE_NONE);
    }
    {
        const cuuint64_t dims[4] = {32, 72, 2, 128}, st[3] = {256, 128, 18432};
        const cuuint32_t bx[4] = {32, 72, 2, 1};
        encode(fn, &th3s, CU_TENSOR_MAP_DATA_TYPE_UINT32, 4, h3p, dims, st, bx, CU_TENSOR_MAP_SWIZZLE_128B, CU_TENSOR_MAP_L2_PROMOTION_NONE);
    }
    {
        const cuuint64_t dims[3] = {4624, 4, 32}, st[2] = {9248 * 32, 9248};
        const cuuint32_t bx[3] = {56, 4, 32};
        encode(fn, &twr, CU_TENSOR_MAP_DATA_TYPE_BFLOAT16, 3, p.wr, dims, st, bx, CU_TENSOR_MAP_SWIZZLE_NONE);
        encode(fn, &twi, CU_TENSOR_MAP_DATA_TYPE_BFLOAT16, 3, p.wi, dims, st, bx, CU_TENSOR_MAP_SWIZZLE_NONE);
    }
    {
        const cuuint64_t dims[2] = {3456, 576}, st[1] = {6912};
        const cuuint32_t bx[2] = {32, 144};
        encode(fn, &tws, CU_TENSOR_MAP_DATA_TYPE_BFLOAT16, 2, p.wmod, dims, st, bx, CU_TENSOR_MAP_SWIZZLE_64B);
    }
    {
        const cuuint64_t dims[3] = {64, 576, 54}, st[2] = {6912, 128};
        const cuuint32_t bx[3] = {64, 32, 7};
        encode(fn, &twm, CU_TENSOR_MAP_DATA_TYPE_BFLOAT16, 3, p.wmod, dims, st, bx, CU_TENSOR_MAP_SWIZZLE_128B);
    }
    {
        const cuuint64_t dims[2] = {TP, 128}, st[1] = {TP * 4};
        const cuuint32_t ba[2] = {32, 128}, bb[2] = {8, 128};
        encode(fn, &tt, CU_TENSOR_MAP_DATA_TYPE_UINT32, 2, p.scr->T, dims, st, ba, CU_TENSOR_MAP_SWIZZLE_128B, CU_TENSOR_MAP_L2_PROMOTION_NONE);
        encode(fn, &ttx, CU_TENSOR_MAP_DATA_TYPE_UINT32, 2, p.scr->T, dims, st, bb, CU_TENSOR_MAP_SWIZZLE_32B, CU_TENSOR_MAP_L2_PROMOTION_NONE);
    }
    {
        const cuuint64_t dims[2] = {D_, S_}, st[1] = {D_ * 2};
        const cuuint32_t bx[2] = {144, 16};
        encode(fn, &to, CU_TENSOR_MAP_DATA_TYPE_BFLOAT16, 2, p.out, dims, st, bx, CU_TENSOR_MAP_SWIZZLE_NONE, CU_TENSOR_MAP_L2_PROMOTION_NONE);
    }
    cudaFuncSetAttribute(fused_kernel, cudaFuncAttributeMaxDynamicSharedMemorySize, SMEM_BYTES);
    cudaLaunchConfig_t cfg = {};
    cfg.gridDim = dim3(NCTA); cfg.blockDim = dim3(NTHR); cfg.dynamicSmemBytes = SMEM_BYTES; cfg.stream = cudaStreamPerThread;
    cudaLaunchAttribute at[1];
    at[0].id = cudaLaunchAttributeClusterDimension; at[0].val.clusterDim.x = 2; at[0].val.clusterDim.y = 1; at[0].val.clusterDim.z = 1;
    cfg.attrs = at; cfg.numAttrs = 1;
    int nclusters = 0;
    cudaOccupancyMaxActiveClusters(&nclusters, fused_kernel, &cfg);
    at[0].id = cudaLaunchAttributeCooperative; at[0].val.cooperative = 1;
    cfg.numAttrs = nclusters * 2 >= NCTA ? 0 : 1;
    cudaLaunchKernelEx(&cfg, fused_kernel, p, tw1a, tw1b, tw2, th3a, th3b, twr, twi, twm, tt, ttx, to, th3s, tws);
}
```

```cpp
#include <cuda_runtime.h>
#include <cuda_bf16.h>
#include <cuda_fp16.h>
#include <cuda.h>
#include <stdint.h>

namespace {

constexpr int S_ = 2048, D_ = 576, F_ = 4608;
constexpr int NCTA = 132, NTHR = 512;
constexpr int TP = 4736;
constexpr int SPEC_P = 296;
constexpr int NST = 6;
constexpr int A_BYTES = 16384, B_BYTES = 18432;
constexpr int IT_P1 = 24, IT_G2 = 40, IT_END = 76;
constexpr int SPIN_LIMIT = 1 << 22;
#define X2D 1350
constexpr int P2S = 2;
#define LEAD1 4
#define W1N 8
#define W1P 100
#define W1S 5
#define XDELAY 1100
#define HOK 2
#define HOK1 2
#define NCP 10800
#define P2K 4
#define RP1 2
#define RPX 1
#define SLP 64
#define X1D 2100
#define PF0 4
#define PFS 3
#define PFN 9
#define X1DELAY 2000
#define X1PACE 400

constexpr int OFF_A = 0;
constexpr int OFF_B = NST * A_BYTES;
constexpr int OFF_P = OFF_B + NST * B_BYTES;
constexpr int OFF_BAR = OFF_P;
constexpr int OFF_EPOCH = OFF_P + 480;
constexpr int OFF_MISC = OFF_P + 496;
constexpr int OFF_GB = OFF_P + 512;
constexpr int OFF_P2R = OFF_P + 1664;
constexpr int OFF_X1 = OFF_P2R;
constexpr int OFF_PROF = OFF_X1 + 18432;
constexpr int SMEM_BYTES = OFF_PROF + 512;
constexpr int QA = 13, QB = 7, QC = 13;
constexpr int TAB_BYTES = (QA + QB + QC) * 512;
constexpr int OFF_STAGE = OFF_B;
constexpr int OFF_STX = OFF_STAGE + 16384;
constexpr int OFF_TAB = OFF_STAGE + 20480;
constexpr int OFF_SPEC = OFF_TAB + TAB_BYTES;
constexpr int OFF_WRAW = OFF_SPEC + 19072;
constexpr int OFF_B3 = OFF_WRAW + 28672;
constexpr int OFF_MODA = OFF_B3 + 4096;
constexpr int OFF_MODC = OFF_MODA + 2560;
constexpr int OFF_RED = OFF_MODC + 3584;
constexpr int OFF_HEXP = OFF_RED + 512;
constexpr int OFF_SILU = OFF_RED + 1536;
static_assert(OFF_SILU + 1152 <= OFF_P && 6 * 28672 <= OFF_B3, "scratch overflow");
constexpr int OFF_STRIP = OFF_A;
static_assert(OFF_WRAW % 128 == 0 && OFF_STAGE % 128 == 0 && OFF_STX % 128 == 0, "align");
constexpr int BAR_FULL = 0, BAR_EMPTY = 6, BAR_TAB = 12, BAR_W = 13, BAR_P2N = 14, BAR_P2R = 16,
              BAR_XT = 17, BAR_RECV = 18, BAR_ROLE = 19, BAR_NC = 20, BAR_TAB2 = 21, BAR_XB = 22, BAR_GB = 23, BAR_HOLD = 24, BAR_W1GO = 25, BAR_UOK = 26, BAR_DONE = 30, BAR_X = 31, BAR_ST = 47;

struct Cos1152 { double c[1152]; };
constexpr double cx_cos(double x) { double t = 1, s = 1; for (int i = 1; i < 14; i++) { t *= -x * x / ((2 * i - 1) * (2 * i)); s += t; } return s; }
constexpr Cos1152 make_cos() {
    Cos1152 r{};
    for (int i = 0; i <= 288; i++) {
        double v = (i == 288) ? 0.0 : cx_cos(3.14159265358979323846 * 2.0 * i / 1152.0);
        r.c[i] = v; r.c[576 - i] = -v; r.c[576 + i] = -v; r.c[(1152 - i) % 1152] = v;
    }
    return r;
}
constexpr uint32_t cx_f2h(double v) {
    uint32_t s = v < 0 ? 0x8000u : 0u; double a = v < 0 ? -v : v;
    if (a < 1e-9) return 0;
    int e = 0;
    while (a >= 2.0) { a *= 0.5; e++; }
    while (a < 1.0 && e > -14) { a *= 2.0; e--; }
    double m = a * 1024.0; uint32_t mi = (uint32_t)m; double fr = m - mi;
    if (fr > 0.5 || (fr == 0.5 && (mi & 1))) mi++;
    return s | (uint32_t)(((e + 14) << 10) + mi);
}
struct Tab { uint32_t w[(QA + QB + QC) * 128]; };
constexpr Tab make_tab() {
    Tab t{};
    Cos1152 ct = make_cos();
    auto C = [&](int num, int den) { return ct.c[(num % den) * (1152 / den)]; };
    auto Sn = [&](int num, int den) { return ct.c[((num % den) * (1152 / den) + 864) % 1152]; };
    auto put = [&](int q0, int idx, int lane, double lo, double hi) { t.w[((q0 + idx / 4) * 32 + lane) * 4 + idx % 4] = cx_f2h(lo) | (cx_f2h(hi) << 16); };
    for (int lane = 0; lane < 32; lane++) {
        const int g = lane >> 2, q = lane & 3;
        for (int mt = 0; mt < 3; mt++) {
            const int ka = 8 * mt + g;
            for (int r = 0; r < 10; r++) {
                const int im = r & 1, i0 = (r >> 1) * 2;
                double v[2] = {0, 0};
                for (int e = 0; e < 2; e++) { int i = i0 + e, d1 = 4 * i + q; if (i < 9 && ka <= 18) v[e] = (im ? -Sn(ka * d1, 36) : C(ka * d1, 36)) / 8; }
                put(0, r < 8 ? mt * 8 + r : 16 + 2 * mt + r, lane, v[0], v[1]);
            }
            for (int v = 0; v < 2; v++) {
                const int d2 = 4 * q + v;
                put(0, 30 + (mt * 2 + v) * 2, lane, C(ka * d2, 576) * 4 / 3, C(ka * (d2 + 2), 576) * 4 / 3);
                put(0, 31 + (mt * 2 + v) * 2, lane, Sn(ka * d2, 576) * 4 / 3, Sn(ka * (d2 + 2), 576) * 4 / 3);
            }
        }
        for (int v = 0; v < 2; v++) for (int nt = 0; nt < 2; nt++) {
            const int kb = 2 * (g >> 1) + nt, part = g & 1;
            double b0[2] = {0, 0}, b1[2] = {0, 0};
            for (int e = 0; e < 2; e++) { int d2 = 4 * q + 2 * e + v; double c = C(kb * d2, 16) / 4, s = Sn(kb * d2, 16) / 4;
                b0[e] = part ? -s : c; b1[e] = part ? c : s; }
            put(0, 42 + (v * 2 + nt) * 2, lane, b0[0], b0[1]); put(0, 43 + (v * 2 + nt) * 2, lane, b1[0], b1[1]);
        }
        t.w[((QA - 1) * 32 + lane) * 4 + 2] = 0x3F803F80u;
        for (int par = 0; par < 2; par++) for (int a = 0; a < 4; a++) {
            const int ja = 2 * (q + 4 * (a >> 1)) + par; const double c = C(g * ja, 16) / 4, s = Sn(g * ja, 16) / 4;
            put(QA, par * 4 + a, lane, (a & 1) ? -s : c, (a & 1) ? c : s);
        }
        for (int h = 0; h < 2; h++) {
            put(QA, 8 + 2 * h, lane, C((g + 8 * h) * (2 * q), 128) / 2, C((g + 8 * h) * (2 * q + 1), 128) / 2);
            put(QA, 9 + 2 * h, lane, Sn((g + 8 * h) * (2 * q), 128) / 2, Sn((g + 8 * h) * (2 * q + 1), 128) / 2);
            put(QA, 16 + 2 * h, lane, C(g * (8 * h + 2 * q), 128), C(g * (8 * h + 2 * q + 1), 128));
            put(QA, 17 + 2 * h, lane, Sn(g * (8 * h + 2 * q), 128), Sn(g * (8 * h + 2 * q + 1), 128));
        }
        put(QA, 12, lane, C(g * 2 * q, 8) / 2, C(g * (2 * q + 1), 8) / 2);
        put(QA, 15, lane, C(g * 2 * q, 8) / 2, C(g * (2 * q + 1), 8) / 2);
        put(QA, 13, lane, Sn(g * 2 * q, 8) / 2, Sn(g * (2 * q + 1), 8) / 2);
        put(QA, 14, lane, -Sn(g * 2 * q, 8) / 2, -Sn(g * (2 * q + 1), 8) / 2);
        for (int u = 0; u < 4; u++) {
            const int ja = 2 * ((g >> 1) + 4 * (u & 1)) + (u >> 1), part = g & 1; double b0[2] = {0, 0}, b1[2] = {0, 0};
            for (int e = 0; e < 2; e++) { int ka = 2 * q + e; double c = C(ja * ka, 16) / 4, s = Sn(ja * ka, 16) / 4;
                b0[e] = part ? s : c; b1[e] = part ? c : -s; }
            put(QA, 20 + u * 2, lane, b0[0], b0[1]); put(QA, 21 + u * 2, lane, b1[0], b1[1]);
        }
        for (int m2 = 0; m2 < 2; m2++) {
            const int d2 = 2 * g + m2;
            for (int a = 0; a < 4; a++) {
                const int kb = 2 * q + (a >> 1); const double c = C(d2 * kb, 16) / 4, s = Sn(d2 * kb, 16) / 4;
                put(QA + QB, m2 * 4 + a, lane, (a & 1) ? s : c, (a & 1) ? c : -s);
            }
            for (int mt = 0; mt < 3; mt++) {
                const int ka = 8 * mt + 2 * q;
                put(QA + QB, 8 + (m2 * 3 + mt) * 2, lane, C(ka * d2, 576) * 4 / 3, C((ka + 1) * d2, 576) * 4 / 3);
                put(QA + QB, 9 + (m2 * 3 + mt) * 2, lane, Sn(ka * d2, 576) * 4 / 3, Sn((ka + 1) * d2, 576) * 4 / 3);
            }
        }
        for (int mt = 0; mt < 3; mt++) for (int nt = 0; nt < 5; nt++) {
            const int i = 2 * nt + (g & 1), d1 = 4 * i + (g >> 1); double b0[2] = {0, 0}, b1[2] = {0, 0};
            for (int e = 0; e < 2; e++) { int ka = 8 * mt + 2 * q + e;
                if (ka <= 18 && i < 9) { double wt = (ka == 0 || ka == 18) ? 0.125 : 0.25; b0[e] = wt * C(ka * d1, 36); b1[e] = -wt * Sn(ka * d1, 36); } }
            const int o = (QA + QB + 5) * 128 + (mt * 5 + nt) * 64 + lane;
            t.w[o] = cx_f2h(b0[0]) | (cx_f2h(b0[1]) << 16); t.w[o + 32] = cx_f2h(b1[0]) | (cx_f2h(b1[1]) << 16);
        }
    }
    return t;
}
__device__ __align__(128) const Tab g_tab = make_tab();

struct Scratch {
    uint32_t cnt[30 * 32];
    uint32_t slot[96];
    uint32_t mod[2304];
    uint32_t modc[896 + 288];
    uint32_t T[128 * TP];
    uint4 h3[128 * 1152];
    uint4 U[72 * 4 * 1152];
};
__device__ __align__(1024) Scratch g_scr;
#define g_cnt (p.scr->cnt)
#define g_slot (p.scr->slot)
#define g_mod (p.scr->mod)
#define g_T (p.scr->T)
#define g_h3 (p.scr->h3)
#define g_U (p.scr->U)
constexpr int CNT_EPOCH = 0, CNT_H3 = 1, CNT_X1 = 26, CNT_NC = 27, CNT_U = 2;
#define PROFT(i) do {} while (0)
#define PROFDUMP() do {} while (0)
#define PROF0(i) do {} while (0)

__device__ __forceinline__ void mbar_init(uint32_t bar, uint32_t cnt) { asm volatile("mbarrier.init.shared::cta.b64 [%0], %1;" :: "r"(bar), "r"(cnt) : "memory"); }
__device__ __forceinline__ void mbar_expect(uint32_t bar, uint32_t bytes) { asm volatile("mbarrier.arrive.expect_tx.shared::cta.b64 _, [%0], %1;" :: "r"(bar), "r"(bytes) : "memory"); }
__device__ __forceinline__ void mbar_arrive(uint32_t bar) { asm volatile("mbarrier.arrive.shared::cta.b64 _, [%0];" :: "r"(bar) : "memory"); }
__device__ __forceinline__ void mbar_arrive_n(uint32_t bar, uint32_t n) { asm volatile("mbarrier.arrive.shared::cta.b64 _, [%0], %1;" :: "r"(bar), "r"(n) : "memory"); }
__device__ __forceinline__ void mbar_arrive_remote(uint32_t rbar) { asm volatile("mbarrier.arrive.relaxed.cluster.shared::cluster.b64 _, [%0];" :: "r"(rbar) : "memory"); }
__device__ __forceinline__ void mbar_wait(uint32_t bar, uint32_t parity) {
    asm volatile("{.reg .pred p; .reg .u32 c;\n"
        "mbarrier.try_wait.parity.shared::cta.b64 p, [%0], %1;\n@p bra.uni DONE;\nmov.u32 c, 0;\n"
        "LOOP: mbarrier.try_wait.parity.shared::cta.b64 p, [%0], %1;\n@p bra.uni DONE;\n"
        "add.u32 c, c, 1;\nsetp.lt.u32 p, c, %2;\n@p bra.uni LOOP;\ntrap;\nDONE:}" :: "r"(bar), "r"(parity), "n"(SPIN_LIMIT) : "memory");
}
__device__ __forceinline__ bool mbar_test(uint32_t bar, uint32_t parity) {
    uint32_t ok; asm volatile("{.reg .pred p; mbarrier.test_wait.parity.shared::cta.b64 p, [%1], %2; selp.u32 %0, 1, 0, p;}" : "=r"(ok) : "r"(bar), "r"(parity) : "memory"); return ok; }
__device__ __forceinline__ uint32_t mapa(uint32_t a, uint32_t rank) { uint32_t r; asm("mapa.shared::cluster.u32 %0, %1, %2;" : "=r"(r) : "r"(a), "r"(rank)); return r; }
__device__ __forceinline__ uint32_t clk32() { uint32_t r; asm volatile("mov.u32 %0, %%clock;" : "=r"(r)); return r; }
__device__ __forceinline__ void hb() {
    asm volatile("{.reg .b32 a, b; .reg .pred p; mma.sync.aligned.m16n8k8.row.col.f16.f16.f16.f16 {a, b}, {%0,%0}, {%0}, {%0,%0};\n"
                 "setp.ne.u32 p, a, 0; @p trap;}" :: "r"(0));
}
__device__ __forceinline__ void spin_until(uint32_t t) {
    #pragma unroll 1
    while (__any_sync(~0u, (int)(clk32() - t) < -SLP * 4)) { __nanosleep(SLP); hb(); }
    #pragma unroll 1
    while (__any_sync(~0u, (int)(clk32() - t) < 0)) {}
}
__device__ __forceinline__ bool elect() { uint32_t r; asm volatile("{.reg .pred p; elect.sync _|p, 0xffffffff; selp.u32 %0, 1, 0, p;}" : "=r"(r)); return r; }
__device__ __forceinline__ void bar_sync(int id, int n) { asm volatile("bar.sync %0, %1;" :: "r"(id), "r"(n) : "memory"); }
__device__ __forceinline__ void bulk_load(uint32_t dst, const void* src, uint32_t bytes, uint32_t bar) {
    asm volatile("cp.async.bulk.shared::cluster.global.mbarrier::complete_tx::bytes [%0], [%1], %2, [%3];" :: "r"(dst), "l"(src), "r"(bytes), "r"(bar) : "memory"); }
__device__ __forceinline__ void tma2(uint32_t dst, const CUtensorMap* m, int c0, int c1, uint32_t bar) {
    asm volatile("cp.async.bulk.tensor.2d.shared::cluster.global.mbarrier::complete_tx::bytes [%0], [%1, {%3, %4}], [%2];" :: "r"(dst), "l"(m), "r"(bar), "r"(c0), "r"(c1) : "memory"); }
__device__ __forceinline__ void tma3(uint32_t dst, const CUtensorMap* m, int c0, int c1, int c2, uint32_t bar) {
    asm volatile("cp.async.bulk.tensor.3d.shared::cluster.global.mbarrier::complete_tx::bytes [%0], [%1, {%3, %4, %5}], [%2];" :: "r"(dst), "l"(m), "r"(bar), "r"(c0), "r"(c1), "r"(c2) : "memory"); }
__device__ __forceinline__ void tma4(uint32_t dst, const CUtensorMap* m, int c0, int c1, int c2, int c3, uint32_t bar) {
    asm volatile("cp.async.bulk.tensor.4d.shared::cluster.global.mbarrier::complete_tx::bytes [%0], [%1, {%3, %4, %5, %6}], [%2];" :: "r"(dst), "l"(m), "r"(bar), "r"(c0), "r"(c1), "r"(c2), "r"(c3) : "memory"); }
__device__ __forceinline__ void fence_async_g() { asm volatile("fence.proxy.async.global;" ::: "memory"); }
__device__ __forceinline__ void fence_async_s() { asm volatile("fence.proxy.async.shared::cta;" ::: "memory"); }
__device__ __forceinline__ uint4 lds128(uint32_t a) { uint4 v; asm volatile("ld.shared.v4.u32 {%0,%1,%2,%3}, [%4];" : "=r"(v.x), "=r"(v.y), "=r"(v.z), "=r"(v.w) : "r"(a) : "memory"); return v; }
__device__ __forceinline__ uint32_t lds32(uint32_t a) { uint32_t v; asm volatile("ld.shared.u32 %0, [%1];" : "=r"(v) : "r"(a) : "memory"); return v; }
__device__ __forceinline__ void sts128(uint32_t a, uint4 v) { asm volatile("st.shared.v4.u32 [%0], {%1,%2,%3,%4};" :: "r"(a), "r"(v.x), "r"(v.y), "r"(v.z), "r"(v.w) : "memory"); }
__device__ __forceinline__ void sts32(uint32_t a, uint32_t v) { asm volatile("st.shared.u32 [%0], %1;" :: "r"(a), "r"(v) : "memory"); }
__device__ __forceinline__ void sts16(uint32_t a, uint32_t v) { asm volatile("st.shared.u16 [%0], %1;" :: "r"(a), "h"((uint16_t)v) : "memory"); }
__device__ __forceinline__ uint4 ldx128(const void* p) {
    uint4 v; asm volatile("{.reg .b128 t; .reg .b64 a, b; ld.relaxed.gpu.global.b128 t, [%4]; mov.b128 {a, b}, t; mov.b64 {%0,%1}, a; mov.b64 {%2,%3}, b;}"
        : "=r"(v.x), "=r"(v.y), "=r"(v.z), "=r"(v.w) : "l"(p) : "memory"); return v; }
__device__ __forceinline__ void stx128(void* p, uint4 v) {
    asm volatile("{.reg .b128 t; .reg .b64 a, b; mov.b64 a, {%1,%2}; mov.b64 b, {%3,%4}; mov.b128 t, {a, b}; st.relaxed.gpu.global.b128 [%0], t;}"
        :: "l"(p), "r"(v.x), "r"(v.y), "r"(v.z), "r"(v.w) : "memory"); }
__device__ __forceinline__ uint32_t ld_acquire(const uint32_t* p) { uint32_t v; asm volatile("ld.acquire.gpu.global.u32 %0, [%1];" : "=r"(v) : "l"(p) : "memory"); return v; }
__device__ __forceinline__ void st_relaxed(uint32_t* p, uint32_t v) { asm volatile("st.relaxed.gpu.global.u32 [%0], %1;" :: "l"(p), "r"(v) : "memory"); }
__device__ __forceinline__ void red_release(uint32_t* p) { asm volatile("red.release.gpu.global.add.u32 [%0], 1;" :: "l"(p) : "memory"); }
template <int SLEEP> __device__ __forceinline__ void wait_count(const uint32_t* p, uint32_t target) {
    int it = 0; while ((int)(ld_acquire(p) - target) < 0) { if (SLEEP) __nanosleep(SLEEP); if (++it > SPIN_LIMIT) __trap(); }
}
__device__ __forceinline__ uint32_t ldg_nc32(const void* p) { uint32_t v; asm volatile("ld.global.nc.L1::no_allocate.u32 %0, [%1];" : "=r"(v) : "l"(p)); return v; }
__device__ __forceinline__ uint32_t ldg_nc16(const void* p) { uint16_t v; asm volatile("ld.global.nc.u16 %0, [%1];" : "=h"(v) : "l"(p)); return v; }
__device__ __forceinline__ float bf_lo(uint32_t w) { return __uint_as_float(w << 16); }
__device__ __forceinline__ float bf_hi(uint32_t w) { return __uint_as_float(w & 0xFFFF0000u); }
__device__ __forceinline__ uint32_t pack_bf(float lo, float hi) { uint32_t r; asm("cvt.rn.bf16x2.f32 %0, %1, %2;" : "=r"(r) : "f"(hi), "f"(lo)); return r; }
__device__ __forceinline__ uint32_t pack_h(float lo, float hi) { uint32_t r; asm("cvt.rn.f16x2.f32 %0, %1, %2;" : "=r"(r) : "f"(hi), "f"(lo)); return r; }
__device__ __forceinline__ float bf_round(float v) { return bf_lo(pack_bf(v, 0.f)); }
__device__ __forceinline__ uint32_t hmul2(uint32_t a, uint32_t b) { uint32_t r; asm("mul.rn.f16x2 %0, %1, %2;" : "=r"(r) : "r"(a), "r"(b)); return r; }
__device__ __forceinline__ uint32_t hfma2(uint32_t a, uint32_t b, uint32_t c) { uint32_t r; asm("fma.rn.f16x2 %0, %1, %2, %3;" : "=r"(r) : "r"(a), "r"(b), "r"(c)); return r; }
__device__ __forceinline__ uint32_t hfms2(uint32_t a, uint32_t b, uint32_t c) { uint32_t r; asm("{.reg .b32 t; neg.f16x2 t, %3; fma.rn.f16x2 %0, %1, %2, t;}" : "=r"(r) : "r"(a), "r"(b), "r"(c)); return r; }
__device__ __forceinline__ uint32_t hadd2(uint32_t a, uint32_t b) { uint32_t r; asm("add.rn.f16x2 %0, %1, %2;" : "=r"(r) : "r"(a), "r"(b)); return r; }
__device__ __forceinline__ uint32_t hsub2(uint32_t a, uint32_t b) { uint32_t r; asm("sub.rn.f16x2 %0, %1, %2;" : "=r"(r) : "r"(a), "r"(b)); return r; }
__device__ __forceinline__ void cmul_neg(uint32_t& re, uint32_t& im, uint32_t c, uint32_t s) { uint32_t a = hfma2(re, c, hmul2(im, s)), b = hfms2(im, c, hmul2(re, s)); re = a; im = b; }
__device__ __forceinline__ void cmul_pos(uint32_t& re, uint32_t& im, uint32_t c, uint32_t s) { uint32_t a = hfms2(re, c, hmul2(im, s)), b = hfma2(im, c, hmul2(re, s)); re = a; im = b; }
__device__ __forceinline__ void mma_h(uint32_t& d0, uint32_t& d1, uint32_t a0, uint32_t a1, uint32_t a2, uint32_t a3, uint32_t b0, uint32_t b1) {
    asm("mma.sync.aligned.m16n8k16.row.col.f16.f16.f16.f16 {%0,%1}, {%2,%3,%4,%5}, {%6,%7}, {%0,%1};" : "+r"(d0), "+r"(d1) : "r"(a0), "r"(a1), "r"(a2), "r"(a3), "r"(b0), "r"(b1)); }
__device__ __forceinline__ void mma_h8(uint32_t& d0, uint32_t& d1, uint32_t a0, uint32_t a1, uint32_t b0) {
    asm("mma.sync.aligned.m16n8k8.row.col.f16.f16.f16.f16 {%0,%1}, {%2,%3}, {%4}, {%0,%1};" : "+r"(d0), "+r"(d1) : "r"(a0), "r"(a1), "r"(b0)); }
template <int NQ> __device__ __forceinline__ void load_tab(uint32_t (&r)[NQ * 4], uint32_t addr) {
    #pragma unroll
    for (int i = 0; i < NQ; i++) { uint4 v = lds128(addr + i * 512); r[4 * i] = v.x; r[4 * i + 1] = v.y; r[4 * i + 2] = v.z; r[4 * i + 3] = v.w; }
}
__device__ __forceinline__ float gelu2(float x) {
    float t = x * fmaf(x * x, 0.044715f * 0.7978845608028654f, 0.7978845608028654f), th;
    asm volatile("tanh.approx.f32 %0, %1;" : "=f"(th) : "f"(t));
    return fmaf(x, th, x);
}
constexpr uint32_t SM0 = 1024;
__device__ __forceinline__ constexpr uint32_t desc_lo(uint32_t off, uint32_t lbo) { return ((SM0 + off) >> 4) | ((lbo >> 4) << 16); }
constexpr uint32_t DHI_A = (1024 >> 4) | (1u << 30), DHI_H3 = 256 >> 4, DHI_U = 128 >> 4;
#define WG_FENCE() asm volatile("wgmma.fence.sync.aligned;" ::: "memory")
#define WG_COMMIT() asm volatile("wgmma.commit_group.sync.aligned;" ::: "memory")
#define WG_WAIT(n) asm volatile("wgmma.wait_group.sync.aligned %0;" :: "n"(n) : "memory")
#define R4(b) "+f"(d[b]), "+f"(d[b + 1]), "+f"(d[b + 2]), "+f"(d[b + 3])
#define R12(b) R4(b), R4(b + 4), R4(b + 8)
#define R36(b) R12(b), R12(b + 12), R12(b + 24)
template <uint32_t BHI> __device__ __forceinline__ void wgmma144(float (&d)[72], uint32_t da, uint32_t db, int acc) {
    asm volatile("{.reg .pred p; .reg .b64 a, b; setp.ne.b32 p, %74, 0; mov.b64 a, {%72, %75}; mov.b64 b, {%73, %76};\n"
        "wgmma.mma_async.sync.aligned.m64n144k16.f32.bf16.bf16 {%0,%1,%2,%3,%4,%5,%6,%7,%8,%9,%10,%11,%12,%13,%14,%15,%16,%17,%18,%19,%20,%21,%22,%23,"
        "%24,%25,%26,%27,%28,%29,%30,%31,%32,%33,%34,%35,%36,%37,%38,%39,%40,%41,%42,%43,%44,%45,%46,%47,"
        "%48,%49,%50,%51,%52,%53,%54,%55,%56,%57,%58,%59,%60,%61,%62,%63,%64,%65,%66,%67,%68,%69,%70,%71}, a, b, p, 1, 1, 1, 1;}\n"
        : R36(0), R36(36) : "r"(da), "r"(db), "r"(acc), "n"(DHI_A), "n"(BHI));
}
__device__ __forceinline__ void wgmma40_rs(float (&d)[20], uint32_t a0, uint32_t a1, uint32_t a2, uint32_t a3, uint32_t db, int acc) {
    asm volatile("{.reg .pred p; .reg .b64 b; setp.ne.b32 p, %25, 0; mov.b64 b, {%24, %26};\n"
        "wgmma.mma_async.sync.aligned.m64n40k16.f32.f16.f16 {%0,%1,%2,%3,%4,%5,%6,%7,%8,%9,%10,%11,%12,%13,%14,%15,%16,%17,%18,%19}, {%20,%21,%22,%23}, b, p, 1, 1, 0;}\n"
        : R12(0), R4(12), R4(16) : "r"(a0), "r"(a1), "r"(a2), "r"(a3), "r"(db), "r"(acc), "n"(DHI_H3));
}
__device__ __forceinline__ void wgmma72(float (&d)[36], uint32_t da, uint32_t db, int acc) {
    asm volatile("{.reg .pred p; .reg .b64 a, b; setp.ne.b32 p, %38, 0; mov.b64 a, {%36, %39}; mov.b64 b, {%37, %40};\n"
        "wgmma.mma_async.sync.aligned.m64n72k16.f32.bf16.bf16 {%0,%1,%2,%3,%4,%5,%6,%7,%8,%9,%10,%11,%12,%13,%14,%15,%16,%17,%18,%19,%20,%21,%22,%23,"
        "%24,%25,%26,%27,%28,%29,%30,%31,%32,%33,%34,%35}, a, b, p, 1, 1, 1, 1;}\n"
        : R36(0) : "r"(da), "r"(db), "r"(acc), "n"(DHI_A), "n"(DHI_H3));
}

__device__ __forceinline__ int g2_kb(int n, int kh, int gi, int c2) {
    if (n < 4) return 36 * kh + 9 * n + 8;
    if (n == 4) return 9 * gi + 4 * c2 + 2 * kh + 1;
    const int w = n > 20, m = n - (w ? 19 : 5);
    return 9 * ((gi * w + (m >> 1)) & 7) + 4 * (n == 35 ? 1 - c2 : m & 1) + 2 * kh + w;
}

template <uint32_t BHI, int S> __device__ __forceinline__ void mma_block(float (&d)[72], uint32_t bars, uint32_t da0, uint32_t db0, uint32_t ph) {
    mbar_wait(bars + 8 * (BAR_FULL + S), ph);
    WG_FENCE();
    #pragma unroll
    for (int k = 0; k < 4; k++) wgmma144<BHI>(d, da0 + S * (A_BYTES / 16) + k * 128, db0 + S * (B_BYTES / 16) + k * 288, 1);
    WG_COMMIT();
    WG_WAIT(1);
}

struct Params {
    const uint16_t *wmod, *c, *x;
    Scratch* scr;
    const Tab* tab;
    const uint16_t *wr, *wi, *w1, *b1, *w2, *b2;
    uint16_t* out;
};

__device__ __forceinline__ void mma_bf(float (&d)[4], const uint32_t (&a)[4], uint32_t b0, uint32_t b1) {
    asm("mma.sync.aligned.m16n8k16.row.col.f32.bf16.bf16.f32 {%0,%1,%2,%3}, {%4,%5,%6,%7}, {%8,%9}, {%0,%1,%2,%3};"
        : "+f"(d[0]), "+f"(d[1]), "+f"(d[2]), "+f"(d[3]) : "r"(a[0]), "r"(a[1]), "r"(a[2]), "r"(a[3]), "r"(b0), "r"(b1)); }
__device__ __forceinline__ void ldsm4t(uint32_t (&a)[4], uint32_t addr) {
    asm volatile("ldmatrix.sync.aligned.m8n8.x4.trans.shared.b16 {%0,%1,%2,%3}, [%4];" : "=r"(a[0]), "=r"(a[1]), "=r"(a[2]), "=r"(a[3]) : "r"(addr) : "memory"); }
__device__ __forceinline__ void ln_stats(const uint32_t (&w)[9], const uint32_t (&one)[9], int g, int q, float& r, float& mr) {
    float c[2][4] = {};
    #pragma unroll
    for (int p = 0; p < 9; p++)
        asm("mma.sync.aligned.m16n8k8.row.col.f32.bf16.bf16.f32 {%0,%1,%2,%3}, {%4,%5}, {%4}, {%0,%1,%2,%3};"
            : "+f"(c[p & 1][0]), "+f"(c[p & 1][1]), "+f"(c[p & 1][2]), "+f"(c[p & 1][3]) : "r"(w[p]), "r"(one[p]));
    const float t = (g & 1) ? c[0][1] + c[1][1] : c[0][0] + c[1][0];
    float s1 = (c[0][2] + c[1][2]) + (c[0][3] + c[1][3]), s2 = __shfl_sync(~0u, t, 9 * q) + __shfl_sync(~0u, t, 9 * q + 4);
    #pragma unroll
    for (int o = 1; o < 4; o <<= 1) { s1 += __shfl_xor_sync(~0u, s1, o); s2 += __shfl_xor_sync(~0u, s2, o); }
    const float m = s1 * (1.f / D_);
    asm("rsqrt.approx.ftz.f32 %0, %1;" : "=f"(r) : "f"(fmaxf(fmaf(s2, 1.f / D_, -m * m), 0.f) + 1e-5f));
    mr = -m * r;
}
__device__ __forceinline__ float silu(float v) { return __fdividef(v, 1.f + __expf(-v)); }
__device__ __forceinline__ uint32_t bfma2(uint32_t a, uint32_t b, uint32_t c) { uint32_t r; asm("fma.rn.bf16x2 %0, %1, %2, %3;" : "=r"(r) : "r"(a), "r"(b), "r"(c)); return r; }
__device__ __forceinline__ void radix16(const uint4 (&V)[4], const uint32_t (&B)[16], uint4 (&o)[4]) {
    #pragma unroll
    for (int nt = 0; nt < 4; nt++) o[nt] = make_uint4(0, 0, 0, 0);
    #pragma unroll
    for (int u = 0; u < 4; u++)
        #pragma unroll
        for (int nt = 0; nt < 4; nt++) {
            const uint32_t b = B[((u >> 1) * 4 + nt) * 2 + (u & 1)];
            mma_h8(o[nt].x, o[nt].y, V[u].x, V[u].y, b); mma_h8(o[nt].z, o[nt].w, V[u].z, V[u].w, b);
        }
}
template <int OFF, int N> __device__ __forceinline__ void gelu_store(const float (&d)[N], char* p, int q) {
    uint32_t w[9];
    #pragma unroll
    for (int blk = 0; blk < 9; blk++) w[blk] = pack_bf(gelu2(d[OFF + 4 * blk]), gelu2(d[OFF + 4 * blk + 1]));
    asm volatile("st.v4.u32 [%0], {%1,%2,%3,%4};" :: "l"(p + q * 128), "r"(w[0]), "r"(w[1]), "r"(w[2]), "r"(w[3]) : "memory");
    asm volatile("st.v4.u32 [%0+512], {%1,%2,%3,%4};" :: "l"(p + q * 128), "r"(w[4]), "r"(w[5]), "r"(w[6]), "r"(w[7]) : "memory");
    asm volatile("st.u32 [%0+1024], %1;" :: "l"(p + q * 4), "r"(w[8]) : "memory");
}

__global__ void __cluster_dims__(2, 1, 1) __launch_bounds__(NTHR, 1)
fused_kernel(const Params p,
             const __grid_constant__ CUtensorMap tm_w1a, const __grid_constant__ CUtensorMap tm_w1b, const __grid_constant__ CUtensorMap tm_w2,
             const __grid_constant__ CUtensorMap tm_h3a, const __grid_constant__ CUtensorMap tm_h3b,
             const __grid_constant__ CUtensorMap tm_wr, const __grid_constant__ CUtensorMap tm_wi, const __grid_constant__ CUtensorMap tm_wm,
             const __grid_constant__ CUtensorMap tm_t, const __grid_constant__ CUtensorMap tm_tx, const __grid_constant__ CUtensorMap tm_o,
             const __grid_constant__ CUtensorMap tm_h3s, const __grid_constant__ CUtensorMap tm_ws)
{
    extern __shared__ __align__(1024) char smem_raw[];
    const uint32_t t0 = clk32();
    const uint32_t sm = __shfl_sync(~0u, ((uint32_t)__cvta_generic_to_shared(smem_raw) + 1023u) & ~1023u, 0);
    const int tid = threadIdx.x, warp = __shfl_sync(~0u, tid >> 5, 0), lane = tid & 31, g = lane >> 2, q = lane & 3;
    const int b = blockIdx.x;
    const uint32_t rank = b & 1;
    const uint32_t bars = sm + OFF_BAR;
    const bool rowcta = b < 128;

    auto nc_issue = [&](int st, uint32_t sl) {
        const int pass = st >= 18;
        mbar_expect(bars + 8 * (BAR_X + sl), 28672);
        tma3(sm + sl * 28672, &tm_wm, 0, 32 * (st - 18 * pass), 18 + 28 * pass + 7 * (b - 128), bars + 8 * (BAR_X + sl));
    };
    uint32_t epoch;
    const bool strip = b < 72 && !(b & 1);
    const bool sil = (warp >> 2) == 2 && lane < 24 && (strip || !rowcta);
    uint32_t cw[3];
    if (elect()) {
        mbar_init(bars + 8 * (BAR_X + warp), rowcta || warp < 6 ? 1 : 14);
        if (warp >= 12) {
            if (strip) { const uint32_t sb = bars + 8 * (BAR_ST + warp - 12);
                mbar_init(sb, 1); mbar_expect(sb, 9216); tma2(sm + OFF_STRIP + (warp - 12) * 9216, &tm_ws, 16 * b, 144 * (warp - 12), sb); }
        } else if (warp == 7) {
            mbar_init(bars + 8 * BAR_TAB, 1); mbar_expect(bars + 8 * BAR_TAB, rowcta ? QA * 512 + 16 : 16);
            bulk_load(sm + OFF_EPOCH, g_cnt + CNT_EPOCH * 32, 16, bars + 8 * BAR_TAB);
            if (rowcta) bulk_load(sm + OFF_TAB, p.tab, QA * 512, bars + 8 * BAR_TAB);
        } else if (b + 132 * warp < 576) {
            asm volatile("cp.async.bulk.prefetch.L2.global [%0], 2304;" :: "l"(p.wmod + (b + 132 * warp) * 3456) : "memory");
        }
    }
    if (sil) {
        #pragma unroll
        for (int u = 0; u < 3; u++) cw[u] = ldg_nc32(p.c + 144 * (warp - 8) + 48 * u + 2 * lane);
    }
    if (warp == 6) hb();
    __syncthreads();
    if (!rowcta) { if (warp < 6 && elect()) nc_issue(warp, warp); }
    if (warp == 5 || warp == 6) {
        if (elect()) {
            if (warp == 5) {
                for (int i = BAR_W; i < BAR_X; i++) mbar_init(bars + 8 * i, i == BAR_DONE || i == BAR_NC ? 4 : i == BAR_W1GO ? 2 : 1);
                mbar_expect(bars + 8 * BAR_W, 28672); mbar_expect(bars + 8 * BAR_TAB2, (QB + QC) * 512);
                mbar_expect(bars + 8 * BAR_ROLE, 4); mbar_expect(bars + 8 * BAR_P2R, 9216); mbar_expect(bars + 8 * BAR_RECV, 18432); mbar_expect(bars + 8 * BAR_XT, 18432);
            } else {
                for (int i = 0; i < 2 * NST; i++) mbar_init(bars + 8 * i, 2);
                for (int i = 0; i < NST; i++) mbar_expect(bars + 8 * (BAR_FULL + i), A_BYTES);
            }
            asm volatile("fence.mbarrier_init.release.cluster;" ::: "memory");
        }
    } else if (warp >= 12 && elect())
        asm volatile("prefetch.tensormap [%0];" :: "l"(warp == 12 ? &tm_wr : warp == 13 ? &tm_wi : warp == 14 ? &tm_t : &tm_tx) : "memory");
    uint32_t sb[18];
    if ((warp >> 2) == 2) {
        if (sil) {
            #pragma unroll
            for (int u = 0; u < 3; u++) sts32(sm + OFF_SILU + (72 * (warp - 8) + 24 * u + lane) * 4, pack_bf(silu(bf_lo(cw[u])), silu(bf_hi(cw[u]))));
        }
        __syncwarp();
        if (strip) {
            #pragma unroll
            for (int u = 0; u < 18; u++) sb[u] = lds32(sm + OFF_SILU + (72 * (warp - 8) + 4 * u + q) * 4);
        }
    }
    if (rowcta && elect()) {
        if (XDELAY) while ((int)(clk32() - t0) < XDELAY) {}
        mbar_expect(bars + 8 * (BAR_X + warp), 1152);
        bulk_load(sm + OFF_STAGE + warp * 1152, p.x + (size_t)(b + 128 * warp) * D_, 1152, bars + 8 * (BAR_X + warp));
    }
    __syncwarp();
    hb();

    const int trow = 4 * (b & 7) + ((b >> 4) & 3) + 64 * ((b >> 3) & 1) + 32 * (b >> 6);
    uint32_t* const tptr = g_T + (size_t)trow * TP + (warp < 9 ? q * 288 + 32 * warp : 4608 + 8 * q) + 4 * g;
    const int tstr = warp < 9 ? 1152 : 32;
    const uint32_t scol = sm + OFF_SPEC + (q * SPEC_P + (warp < 8 ? 72 * (warp >> 1) + 40 * (warp & 1) + 4 * g : warp == 8 ? 72 * (g >> 1) + 32 + 4 * (g & 1) : 288 + 4 * g)) * 4;
    const int wc0 = (b >> 3) * 289 + 72 * ((b & 7) >> 1) + 40 * (b & 1);

    uint32_t xw[9], one[9], t_st = t0, hexp = 0;
    if (!rowcta) {
        const int nst = b < 130 ? 36 : 18;
        __syncthreads();
        asm volatile("barrier.cluster.arrive.relaxed.aligned;" ::: "memory");
        mbar_wait(bars + 8 * BAR_TAB, 0);
        epoch = lds32(sm + OFF_EPOCH);
        if (warp == 14) {
            uint32_t sl = 0, ph = 0;
            #pragma unroll 1
            for (int st = 6; st < nst; st++) {
                mbar_wait(bars + 8 * (BAR_X + 6 + sl), ph);
                if (elect()) nc_issue(st, sl);
                if (++sl == 6) { sl = 0; ph ^= 1; }
            }
        } else if (warp < 14) {
            uint32_t sl = 0, ph = 0;
            const uint32_t ad0 = sm + (warp >> 1) * 4096 + ((lane & 7) + 8 * (lane >> 4)) * 128, ch = (warp & 1) * 4 + ((lane >> 3) & 1);
            #pragma unroll 1
            for (int pass = 0; pass * 18 < nst; pass++) {
                float acc[2][4] = {};
                #pragma unroll 1
                for (int st = 0; st < 18; st++) {
                    const uint32_t sa = sm + OFF_SILU + (16 * st + q) * 4;
                    const uint32_t b0 = lds32(sa), b1 = lds32(sa + 16), b2 = lds32(sa + 32), b3 = lds32(sa + 48);
                    mbar_wait(bars + 8 * (BAR_X + sl), ph);
                    #pragma unroll
                    for (int m = 0; m < 2; m++) {
                        uint32_t a[4], a2[4];
                        const uint32_t ad = ad0 + sl * 28672 + ((ch + 2 * m) ^ (lane & 7)) * 16;
                        ldsm4t(a, ad); ldsm4t(a2, ad + 2048);
                        mma_bf(acc[m], a, b0, b1); mma_bf(acc[m], a2, b2, b3);
                    }
                    if (elect()) mbar_arrive(bars + 8 * (BAR_X + 6 + sl));
                    if (++sl == 6) { sl = 0; ph ^= 1; }
                }
                const int cb = 28 * pass + 7 * (b - 128) + (warp >> 1), gg = (g >> 1) + 4 * q;
                uint32_t w[2];
                #pragma unroll
                for (int m = 0; m < 2; m++) {
                    float v = bf_round(q ? acc[m][2] : acc[m][0]); if (cb >= 27) v *= 0.5f; else if (cb >= 18) v += 1.f;
                    w[m] = max(pack_bf(v, __shfl_xor_sync(~0u, v, 4)), 1u);
                }
                if (q < 2 && !(g & 1)) {
                    const int qq = (warp & 1) * 2;
                    if (cb < 27) asm volatile("st.relaxed.gpu.global.v2.u32 [%0], {%1, %2};" :: "l"(p.scr->modc + 32 * cb + 4 * gg + qq), "r"(w[0]), "r"(w[1]) : "memory");
                    else if (cb < 36) { uint32_t* o = p.scr->modc + 896 + 32 * (cb - 27) + 8 * qq + gg; o[0] = w[0]; o[8] = w[1]; }
                }
                if (tid == 0 && pass == 0) PROFT(25);
                bar_sync(1, 448);
                if (tid == 0) { fence_async_g(); red_release(g_cnt + (CNT_NC + pass) * 32); }
                __syncwarp();
            }
            fence_async_s();
        }
        __syncthreads();
    } else {
        uint32_t ta[QA * 4];
        if (strip && (warp >> 2) == 2) {
            const int w = warp - 8;
            const uint32_t ra = sm + OFF_STRIP + (144 * w + (lane & 7) + 8 * (lane >> 4)) * 64, sw = (lane >> 1) & 3, ch = (lane >> 3) & 1;
            float acc[2][2][4] = {};
            mbar_wait(bars + 8 * (BAR_ST + w), 0);
            #pragma unroll
            for (int u = 0; u < 9; u++)
                #pragma unroll
                for (int m = 0; m < 2; m++) { uint32_t a[4]; ldsm4t(a, ra + u * 1024 + ((ch + 2 * m) ^ sw) * 16); mma_bf(acc[u & 1][m], a, sb[2 * u], sb[2 * u + 1]); }
            #define PICK(a_) ((q & 2) ? ((q & 1) ? a_[1][2] : a_[1][0]) : ((q & 1) ? a_[0][2] : a_[0][0]))
            sts32(sm + OFF_RED + ((8 * q + g) * 4 + w) * 4, __float_as_uint(PICK(acc[0]) + PICK(acc[1])));
            if (tid == 256) PROFT(0);
            bar_sync(10, 128);
            if (warp == 8) {
                mbar_wait(bars + 8 * BAR_TAB, 0);
                const uint4 v = lds128(sm + OFF_RED + lane * 16);
                float sum = bf_round((__uint_as_float(v.x) + __uint_as_float(v.y)) + (__uint_as_float(v.z) + __uint_as_float(v.w)));
                if (b >= 36) sum = bf_round(1.f + sum);
                st_relaxed(g_mod + b * 16 + (lane & 16) + (lane & 1) * 8 + ((lane & 15) >> 1), (fabsf(sum) < 8.f ? pack_h(0.f, sum) : __float_as_uint(sum) | 0x8000u) | ((lds32(sm + OFF_EPOCH) + 1) & 0x7FFFu));
                asm volatile("bar.arrive 11, 416;" ::: "memory");
                if (tid == 256) PROFT(1);
            }
        }
        mbar_wait(bars + 8 * BAR_TAB, 0);
        load_tab<QA>(ta, sm + OFF_TAB + lane * 16);
        epoch = lds32(sm + OFF_EPOCH);
        const uint32_t tag = (epoch + 1) & 0x7FFFu;
        auto w_prefetch = [&]() {
            if (warp >= 14 && elect()) asm volatile("cp.async.bulk.prefetch.L2.global [%0], 9248;" :: "l"((warp == 14 ? p.wr : p.wi) + b * 4624) : "memory");
            __syncwarp();
        };
        uint32_t nb[2][5];
        uint4 mv = make_uint4(tag, tag, tag, tag);
        const bool poller = warp < 8 || warp == 12;
        const int mc = warp < 8 ? tid : tid - 128, mst = (mc >> 2) % 36, midx = (mc < 144 ? 10 : 0) + 5 * ((mc >> 1) & 1) + (mst >> 3);
        const uint32_t* mp = g_mod + mc * 4;
        const uint32_t ma = sm + OFF_MODA + ((midx >> 2) * 32 + (mc & 1) * 16 + (mst & 3)) * 16 + (midx & 3) * 4 + ((mst >> 2) & 1) * 2;
        #define MOD_MISSING ((((mv.x ^ tag) | (mv.y ^ tag) | (mv.z ^ tag) | (mv.w ^ tag)) & 0x7FFFu) != 0)
        if (strip && (warp >> 2) != 2) bar_sync(11, 416);
        #pragma unroll
        for (int i = 0; i < 9; i++) one[i] = lds32(sm + OFF_TAB + (QA - 1) * 512 + i * 16 + 8);
        hb();
        mbar_wait(bars + 8 * (BAR_X + warp), 0);
        if (poller) mv = ldx128(mp);
        PROF0(28);
        #pragma unroll
        for (int i = 0; i < 9; i++) xw[i] = lds32(sm + OFF_STAGE + warp * 1152 + (32 * i + 8 * q + g) * 4);
        {
            float r, mr;
            ln_stats(xw, one, g, q, r, mr);
            #pragma unroll
            for (int pp = 0; pp < 5; pp++) {
                nb[0][pp] = pack_h(fmaf(bf_lo(xw[2 * pp]), r, mr), pp < 4 ? fmaf(bf_lo(xw[pp < 4 ? 2 * pp + 1 : 0]), r, mr) : 0.f);
                nb[1][pp] = pack_h(fmaf(bf_hi(xw[2 * pp]), r, mr), pp < 4 ? fmaf(bf_hi(xw[pp < 4 ? 2 * pp + 1 : 0]), r, mr) : 0.f);
            }
        }
        PROF0(2);
        w_prefetch();
        if (poller && MOD_MISSING) mv = ldx128(mp);
        if (warp < 8) {
            if (warp >= 4) sts16(sm + OFF_MODA + ((warp - 3) * 32 + lane) * 16 + (warp - 4) * 4 + 2, 0);
            const int k1 = tid & 15, s1 = tid >> 4;
            float s, c;
            __sincosf((float)(((k1 * (128 * s1 + b) + 1024) & 2047) - 1024) * (3.14159265358979f / 1024.f), &s, &c); s *= 0.25f; c *= 0.25f;
            const int rf = ((s1 >> 3) * 4 + (k1 >> 2)) * 2 + ((s1 >> 2) & 1), ri = ((k1 >> 3) * 4 + (s1 >> 2)) * 2 + ((k1 >> 2) & 1);
            const uint32_t af = sm + OFF_B3 + ((rf >> 2) * 32 + (k1 & 3) * 8 + (s1 & 3)) * 16 + (rf & 3) * 4;
            const uint32_t ai = sm + OFF_B3 + 2048 + ((ri >> 2) * 32 + (s1 & 3) * 8 + (k1 & 3)) * 16 + (ri & 3) * 4;
            sts32(af, pack_h(c, s)); sts32(af + 64, pack_h(-s, c)); sts32(ai, pack_h(c, -s)); sts32(ai + 64, pack_h(s, c));
        }
        if (poller) {
            #pragma unroll 1
            for (int it = 0; __any_sync(~0u, MOD_MISSING); it++) { if (MOD_MISSING) mv = ldx128(mp); hb(); if (it > SPIN_LIMIT) __trap(); }
            sts16(ma, mv.x >> 16); sts16(ma + 64, mv.y >> 16); sts16(ma + 128, mv.z >> 16); sts16(ma + 192, mv.w >> 16);
        }
        uint32_t redo = 0; asm volatile("" : "+r"(redo));
        #pragma unroll 1
        do { if (redo) {
            const uint32_t w[4] = {mv.x, mv.y, mv.z, mv.w}; float f[4]; uint32_t big = 0;
            #pragma unroll
            for (int e = 0; e < 4; e++) { f[e] = (w[e] & 0x8000u) ? bf_hi(w[e]) : __half2float(__ushort_as_half(w[e] >> 16)); big = max(big, __float_as_uint(f[e]) << 1 >> 24); }
            sts32(sm + OFF_HEXP + warp * 4, __reduce_max_sync(~0u, big));
            __syncthreads();
            hexp = min(__reduce_max_sync(~0u, lds32(sm + OFF_HEXP + (lane & 15) * 4)), 253u) - 127;
            const float sc = __uint_as_float((127 - hexp) << 23);
            if (poller) {
                #pragma unroll
                for (int e = 0; e < 4; e++) sts16(ma + 64 * e, pack_h(f[e] * sc, 0.f));
            }
            mv = make_uint4(0, 0, 0, 0);
          }
          redo = __syncthreads_or((mv.x | mv.y | mv.z | mv.w) & 0x8000u);
          asm volatile("" : "+r"(redo));
        } while (redo);
        PROF0(3);
        asm volatile("barrier.cluster.arrive.relaxed.aligned;" ::: "memory");
        if (warp >= 13 && elect()) {
            if (warp == 15) bulk_load(sm + OFF_TAB + QA * 512, p.tab->w + QA * 128, (QB + QC) * 512, bars + 8 * BAR_TAB2);
            else tma3(sm + OFF_WRAW + (warp - 13) * 14336, warp == 13 ? &tm_wr : &tm_wi, wc0 & ~7, 0, 0, bars + 8 * BAR_W);
        }
        __syncwarp();
        {
            uint32_t md[20];
            load_tab<5>(md, sm + OFF_MODA + lane * 16);
            #pragma unroll
            for (int v = 0; v < 2; v++)
                #pragma unroll
                for (int pp = 0; pp < 5; pp++) nb[v][pp] = hfma2(nb[v][pp], md[v * 5 + pp], md[10 + v * 5 + pp]);
        }
        uint32_t re[3][2], im[3][2];
        #pragma unroll
        for (int mt = 0; mt < 3; mt++)
            #pragma unroll
            for (int v = 0; v < 2; v++) {
                re[mt][v] = 0; im[mt][v] = 0;
                mma_h8(re[mt][v], im[mt][v], ta[24 + 2 * mt], ta[25 + 2 * mt], nb[v][4]);
                mma_h(re[mt][v], im[mt][v], ta[mt * 8], ta[mt * 8 + 1], ta[mt * 8 + 2], ta[mt * 8 + 3], nb[v][0], nb[v][1]);
                mma_h(re[mt][v], im[mt][v], ta[mt * 8 + 4], ta[mt * 8 + 5], ta[mt * 8 + 6], ta[mt * 8 + 7], nb[v][2], nb[v][3]);
                cmul_neg(re[mt][v], im[mt][v], ta[30 + (mt * 2 + v) * 2], ta[31 + (mt * 2 + v) * 2]);
            }
        const uint32_t srow = sm + OFF_SPEC + warp * (SPEC_P * 4);
        #pragma unroll
        for (int nt = 0; nt < 2; nt++) {
            uint32_t o[2][4];
            #pragma unroll
            for (int v = 0; v < 2; v++) {
                const uint32_t b0 = ta[42 + (v * 2 + nt) * 2], b1 = ta[43 + (v * 2 + nt) * 2];
                o[v][0] = o[v][1] = o[v][2] = o[v][3] = 0;
                mma_h(o[v][0], o[v][1], re[0][v], re[1][v], im[0][v], im[1][v], b0, b1);
                mma_h(o[v][2], o[v][3], re[2][0], re[2][1], im[2][0], im[2][1], b0, b1);
            }
            const uint32_t a = srow + (g + 72 * q + 36 * nt) * 4, a2 = srow + (288 - g - 72 * q - 36 * nt) * 4;
            sts32(a, hadd2(o[0][0], o[1][0])); sts32(a + 32, hadd2(o[0][1], o[1][1])); if (g < 3) sts32(a + 64, hadd2(o[0][2], o[1][3]));
            if (g > 0 || (q == 0 && nt == 0)) sts32(a2, hsub2(o[0][0], o[1][0]) ^ 0x80000000u);
            sts32(a2 - 32, hsub2(o[0][1], o[1][1]) ^ 0x80000000u); if (g < 2) sts32(a2 - 64, hsub2(o[0][2], o[1][3]) ^ 0x80000000u);
        }
        uint32_t b3[16];
        if (warp < 10) load_tab<4>(b3, sm + OFF_B3 + lane * 16);
        __syncthreads();
        t_st = clk32();
        PROF0(4);
        if (warp < 10) {
            uint4 V[4], o[4];
            #pragma unroll
            for (int u = 0; u < 4; u++) V[u] = lds128(scol + u * (16 * SPEC_P));
            radix16(V, b3, o);
            #pragma unroll
            for (int nt = 0; nt < 4; nt++) { o[nt].x |= 1u; if (warp < 9 || g < 2) stx128(tptr + nt * tstr, o[nt]); }
        }
        PROF0(5);
    }

    int role = 0;
    asm volatile("barrier.cluster.wait.aligned;" ::: "memory");
    if (warp >= 12) {
        const int t = tid - 384;
        if (warp == 14 && rank == 0) {
            uint32_t smid; asm volatile("mov.u32 %0, %%smid;" : "=r"(smid));
            const uint32_t tp = smid >> 1;
            uint32_t pr = tp < 32 ? (tp & 7) * 8 + (tp >> 3) : tp < 60 ? (1 + (tp - 32) % 7) * 8 + 4 + (tp - 32) / 7 : tp < 62 ? 4 + tp : tp < 66 ? tp - 58 : 0;
            #pragma unroll 1
            for (;;) {
                uint32_t old = 0; if (lane == 0) old = atomicExch(g_slot + pr, epoch + 1);
                if (!__any_sync(~0u, lane == 0 && old == epoch + 1)) break;
                pr = pr == 65 ? 0 : pr + 1;
            }
            if (lane < 2) asm volatile("st.async.weak.shared::cluster.mbarrier::complete_tx::bytes.u32 [%0], %1, [%2];" :: "r"(mapa(sm + OFF_MISC, lane)), "r"(pr), "r"(mapa(bars + 8 * BAR_ROLE, lane)) : "memory");
        }
        __syncwarp();
        if (t == 0) {
            asm volatile("prefetch.tensormap [%0];" :: "l"(&tm_w1a) : "memory");
            asm volatile("prefetch.tensormap [%0];" :: "l"(&tm_h3a) : "memory"); asm volatile("prefetch.tensormap [%0];" :: "l"(&tm_w1b) : "memory");
            asm volatile("prefetch.tensormap [%0];" :: "l"(&tm_h3b) : "memory"); asm volatile("prefetch.tensormap [%0];" :: "l"(&tm_w2) : "memory");
            asm volatile("prefetch.tensormap [%0];" :: "l"(&tm_o) : "memory"); asm volatile("prefetch.tensormap [%0];" :: "l"(&tm_h3s) : "memory");
        }
        __syncwarp();
        if (rowcta) {
            spin_until(t0 + NCP);
            uint4 v[2];
            v[1] = make_uint4(1, 1, 1, 1);
            #pragma unroll 1
            for (int it = 0;; it++) {
                v[0] = ldx128(p.scr->modc + 4 * t); if (t < 88) v[1] = ldx128(p.scr->modc + 512 + 4 * t);
                if (__all_sync(~0u, min(min(min(v[0].x, v[0].y), min(v[0].z, v[0].w)), min(min(v[1].x, v[1].y), min(v[1].z, v[1].w))) != 0)) break;
                __nanosleep(100); if (it > SPIN_LIMIT) __trap();
            }
            if (t < 72) { const uint32_t sc = ((127 + hexp) << 7) * 0x10001u;
                v[0] = make_uint4(bfma2(v[0].x, sc, 0x80008000u), bfma2(v[0].y, sc, 0x80008000u), bfma2(v[0].z, sc, 0x80008000u), bfma2(v[0].w, sc, 0x80008000u)); }
            #pragma unroll
            for (int u = 0; u < 2; u++) if (u == 0 || t < 88) {
                const uint32_t a = sm + OFF_MODC + (((t >> 5) + 4 * u) * 32 + 4 * (t & 7)) * 16 + ((t >> 3) & 3) * 4;
                sts32(a, v[u].x); sts32(a + 16, v[u].y); sts32(a + 32, v[u].z); sts32(a + 48, v[u].w);
            }
            __syncwarp();
            if (elect()) mbar_arrive(bars + 8 * BAR_NC);
            if (t == 0) PROFT(29);
        }
    } else if (rowcta && warp < 11) {
        const int nw = !(b & 1) ? 10 : (b & 7) == 7 ? 9 : 8;
        const int cm = (b >> 3) * 288 + (b & 7) * 32, cx = (b & 1) ? 4608 + 8 * (b >> 3) : (b >> 3) * 288 + 256 + 4 * (b & 7);
        auto load_in = [&]() {
            if (elect()) {
                mbar_expect(bars + 8 * BAR_XB, nw > 8 ? 20480 : 16384);
                tma2(sm + OFF_STAGE, &tm_t, cm, 0, bars + 8 * BAR_XB);
                if (nw > 8) tma2(sm + OFF_STX, &tm_tx, cx, 0, bars + 8 * BAR_XB);
            }
            __syncwarp();
        };
        if (warp == 10) { fence_async_s(); spin_until(t_st + X1D); load_in(); }
        uint32_t tb[QB * 4], wre[4][2], wim[4][2];
        if (warp < nw) {
            mbar_wait(bars + 8 * BAR_TAB2, 0);
            load_tab<QB>(tb, sm + OFF_TAB + QA * 512 + lane * 16);
            mbar_wait(bars + 8 * BAR_W, 0);
            const int off = wc0 & 7;
            const uint32_t wa = sm + OFF_WRAW + lane * 112 + ((off >> 1) + 2 * warp) * 4, sh = (off & 1) * 16;
            #pragma unroll
            for (int c = 0; c < 2; c++)
                #pragma unroll
                for (int h = 0; h < 2; h++) {
                    uint32_t y[2][2];
                    #pragma unroll
                    for (int e = 0; e < 2; e++) {
                        const uint32_t a = wa + c * 14336 + (h + 2 * e) * 3584, x0 = lds32(a), x1 = lds32(a + 4), x2 = lds32(a + 8);
                        y[e][0] = __funnelshift_r(x0, x1, sh); y[e][1] = __funnelshift_r(x1, x2, sh);
                    }
                    #pragma unroll
                    for (int x = 0; x < 4; x++) {
                        const uint32_t v = (x & 1) ? pack_h(bf_hi(y[0][x >> 1]), bf_hi(y[1][x >> 1])) : pack_h(bf_lo(y[0][x >> 1]), bf_lo(y[1][x >> 1]));
                        if (c) wim[x][h] = v; else wre[x][h] = v;
                    }
                }
        }
        const uint32_t ca = warp < 8 ? sm + OFF_STAGE + lane * 128 + (warp ^ (lane & 7)) * 16 : sm + OFF_STX + lane * 32 + ((warp ^ g) & 1) * 16, cs = warp < 8 ? 4096 : 1024;
        uint32_t V[4][4];
        #pragma unroll 1
        for (int it = 0;; it++) {
            mbar_wait(bars + 8 * BAR_XB, it & 1);
            uint32_t ok = 1;
            if (warp < nw) {
                #pragma unroll
                for (int u = 0; u < 4; u++) { uint4 t4 = lds128(ca + u * cs); V[u][0] = t4.x; V[u][1] = t4.y; V[u][2] = t4.z; V[u][3] = t4.w; ok &= t4.x; }
            }
            asm volatile("{.reg .pred p; setp.ne.u32 p, %0, 0; bar.red.and.pred p, 1, 352, p; selp.u32 %0, 1, 0, p;}" : "+r"(ok) :: "memory");
            if (ok) break;
            if (warp == 10) { load_in(); hb(); }
            if (it > SPIN_LIMIT / 64) __trap();
        }
        PROF0(7);
        if (warp < nw) {
            uint32_t zr[4][2], zi[4][2];
            #pragma unroll
            for (int x = 0; x < 4; x++) {
                uint32_t er = 0, ei = 0, or_ = 0, oi = 0;
                mma_h(er, ei, tb[0], tb[1], tb[2], tb[3], V[0][x], V[1][x]);
                mma_h(or_, oi, tb[4], tb[5], tb[6], tb[7], V[2][x], V[3][x]);
                uint32_t r0 = hadd2(er, or_), r1 = hsub2(er, or_), i0 = hadd2(ei, oi), i1 = hsub2(ei, oi);
                cmul_neg(r0, i0, tb[8], tb[9]); cmul_neg(r1, i1, tb[10], tb[11]);
                uint32_t xr0 = 0, xr1 = 0, xi0 = 0, xi1 = 0;
                mma_h(xr0, xr1, r0, r1, i0, i1, tb[12], tb[13]);
                mma_h(xi0, xi1, r0, r1, i0, i1, tb[14], tb[15]);
                cmul_pos(xr0, xi0, wre[x][0], wim[x][0]); cmul_pos(xr1, xi1, wre[x][1], wim[x][1]);
                r0 = 0; i0 = 0; r1 = 0; i1 = 0;
                mma_h(r0, i0, tb[12], tb[13], tb[14], tb[15], xr0, xi0);
                mma_h(r1, i1, tb[12], tb[13], tb[14], tb[15], xr1, xi1);
                cmul_pos(r0, i0, tb[16], tb[17]); cmul_pos(r1, i1, tb[18], tb[19]);
                zr[x][0] = hadd2(r0, r1); zr[x][1] = hsub2(r0, r1); zi[x][0] = hadd2(i0, i1); zi[x][1] = hsub2(i0, i1);
            }
            #pragma unroll
            for (int nt = 0; nt < 4; nt++) {
                uint4 o = make_uint4(0, 0, 0, 0);
                const int h = nt >> 1;
                mma_h(o.x, o.y, zr[0][h], zr[1][h], zi[0][h], zi[1][h], tb[20 + 2 * nt], tb[21 + 2 * nt]);
                mma_h(o.z, o.w, zr[2][h], zr[3][h], zi[2][h], zi[3][h], tb[20 + 2 * nt], tb[21 + 2 * nt]);
                o.x &= ~1u;
                sts128(ca + nt * cs, o);
            }
        }
        fence_async_s();
        bar_sync(1, 352);
        t_st = clk32();
        PROF0(8);
        if (warp == 10 && elect()) {
            asm volatile("cp.async.bulk.tensor.2d.global.shared::cta.bulk_group [%0, {%2, %3}], [%1];" :: "l"(&tm_t), "r"(sm + OFF_STAGE), "r"(cm), "r"(0) : "memory");
            if (nw > 8) asm volatile("cp.async.bulk.tensor.2d.global.shared::cta.bulk_group [%0, {%2, %3}], [%1];" :: "l"(&tm_tx), "r"(sm + OFF_STX), "r"(cx), "r"(0) : "memory");
            asm volatile("cp.async.bulk.commit_group;" ::: "memory");
            asm volatile("cp.async.bulk.wait_group.read 0;" ::: "memory");
        }
        __syncwarp();
    }

    if (warp >= 10) { mbar_wait(bars + 8 * BAR_ROLE, 0); role = __shfl_sync(~0u, lds32(sm + OFF_MISC), 0); fence_async_s(); }
    auto first_a = [&]() {
        if (warp >= 10 && role < 64 && elect()) {
            const int it = warp - 10, hi = it >= 3; const bool p2 = it - 3 * hi == 2;
            tma4(sm + OFF_A + it * A_BYTES, p2 ? &tm_w1b : &tm_w1a, 0, 0, p2 ? 64 * rank + 8 * hi : 4 * (it - hi),
                 9 * (role >> 3) + (p2 ? 8 : (role & 4) + 2 * rank), bars + 8 * (BAR_FULL + it));
        }
        __syncwarp();
    };
    if (!rowcta) first_a();
    else {
        uint32_t tc[20], md[28];
        mbar_wait(bars + 8 * BAR_TAB2, 0);
        load_tab<5>(tc, sm + OFF_TAB + (QA + QB) * 512 + lane * 16);
        bool md_early = warp >= 10;
        if (md_early) { mbar_wait(bars + 8 * BAR_NC, 0); load_tab<7>(md, sm + OFF_MODC + lane * 16); }
        if (warp < 10) {
            uint32_t b3[16];
            load_tab<4>(b3, sm + OFF_B3 + 2048 + lane * 16);
            uint4 V[4], o[4];
            const bool tact = warp < 9 || g == 0;
            spin_until(t_st + X2D);
            #pragma unroll
            for (int u = 0; u < 4; u++) { V[u] = make_uint4(0, 0, 0, 0); if (tact) V[u] = ldx128(tptr + u * tstr); }
            md_early = __any_sync(~0u, mbar_test(bars + 8 * BAR_NC, 0));
            if (md_early) load_tab<7>(md, sm + OFF_MODC + lane * 16);
            #pragma unroll 1
            for (int it = 0; __any_sync(~0u, (V[0].x | V[1].x | V[2].x | V[3].x) & 1u); it++) {
                #pragma unroll
                for (int u = 0; u < 4; u++) if (V[u].x & 1u) V[u] = ldx128(tptr + u * tstr);
                hb();
                if (it > SPIN_LIMIT) __trap();
            }
            PROF0(10);
            radix16(V, b3, o);
            if (tact) {
                #pragma unroll
                for (int nt = 0; nt < 4; nt++) sts128(scol + nt * (16 * SPEC_P), o[nt]);
            }
        }
        __syncthreads();
        PROF0(11);
        first_a();
        const uint32_t srow = sm + OFF_SPEC + warp * (SPEC_P * 4);
        uint32_t re[2][3], im[2][3];
        #pragma unroll
        for (int mt = 0; mt < 3; mt++) {
            const uint32_t a = srow + (g + 72 * q + 8 * mt) * 4, a2 = srow + (288 - g - 72 * q - 8 * mt) * 4;
            const uint32_t z0 = lds32(a), z1 = lds32(a + 144), z2 = lds32(a2), z3 = lds32(a2 - 144);
            #pragma unroll
            for (int m2 = 0; m2 < 2; m2++) {
                re[m2][mt] = 0; im[m2][mt] = 0;
                const uint32_t sg = m2 ? 0x3C00BC00u : 0xBC003C00u;
                mma_h(re[m2][mt], im[m2][mt], tc[m2 * 4], tc[m2 * 4 + 1], tc[m2 * 4 + 2], tc[m2 * 4 + 3], hfma2(z2, sg, z0), hfma2(z3, sg, z1));
                cmul_pos(re[m2][mt], im[m2][mt], tc[8 + (m2 * 3 + mt) * 2], tc[9 + (m2 * 3 + mt) * 2]);
            }
        }
        float y[20];
        WG_FENCE();
        #pragma unroll
        for (int mt = 0; mt < 3; mt++)
            wgmma40_rs(y, re[0][mt], re[1][mt], im[0][mt], im[1][mt], desc_lo(OFF_TAB + (QA + QB + 5) * 512 + mt * 1280, 128), mt);
        WG_COMMIT();
        if (!md_early) { mbar_wait(bars + 8 * BAR_NC, 0); load_tab<7>(md, sm + OFF_MODC + lane * 16); }
        WG_WAIT(0);
        #pragma unroll
        for (int i = 0; i < 9; i++) xw[i] = bfma2(md[i], pack_bf(y[4 * (i >> 1) + (i & 1)], y[4 * (i >> 1) + 2 + (i & 1)]), xw[i]);
        float r, mr;
        ln_stats(xw, one, g, q, r, mr);
        uint32_t r2 = pack_bf(r, r), m2 = pack_bf(mr, mr);
        #pragma unroll
        for (int i = 0; i < 9; i++) {
            sts32(sm + OFF_X1 + warp * 1152 + (32 * i + 8 * q + g) * 4, xw[i]);
            xw[i] = bfma2(bfma2(xw[i], r2, m2), md[18 + i], md[9 + i]);
        }
        ln_stats(xw, one, g, q, r, mr);
        r2 = pack_bf(r, r); m2 = pack_bf(mr, mr);
        {
            const int n7 = 2 * q + (g >> 2);
            const uint32_t a = sm + OFF_STAGE + (warp >> 3) * 9216 + n7 * 128 + ((warp & 7) ^ n7) * 16 + (g & 3) * 4;
            #pragma unroll
            for (int i = 0; i < 9; i++) sts32(a + i * 1024, bfma2(xw[i], r2, m2));
        }
        fence_async_s();
        __syncthreads();
        PROF0(12);
        if (tid == 0) {
            asm volatile("cp.async.bulk.tensor.4d.global.shared::cta.bulk_group [%0, {%2, %2, %2, %3}], [%1];" :: "l"(&tm_h3s), "r"(sm + OFF_STAGE), "r"(0), "r"(b) : "memory");
            asm volatile("cp.async.bulk.commit_group;" ::: "memory");
        }
    }
    if (!rowcta) __syncthreads();
    else {
        if (tid == 0) { asm volatile("cp.async.bulk.wait_group 0;" ::: "memory"); fence_async_g(); red_release(g_cnt + CNT_H3 * 32); }
        PROF0(13);
        if (warp == 15) {
            __nanosleep(X1DELAY);
            #pragma unroll 1
            for (int r = 0; r < 16; r++) {
                if (lane == 0) asm volatile("cp.async.bulk.global.shared::cta.bulk_group [%0], [%1], 1152;" :: "l"(p.out + (size_t)(b + 128 * r) * D_), "r"(sm + OFF_X1 + r * 1152) : "memory");
                const uint32_t t1 = clk32();
                #pragma unroll 1
                while (__any_sync(~0u, (int)(clk32() - t1) < X1PACE)) __nanosleep(50);
            }
            if (lane == 0) {
                asm volatile("cp.async.bulk.commit_group;" ::: "memory");
                asm volatile("cp.async.bulk.wait_group 0;" ::: "memory");
                if (role < 64) mbar_arrive_remote(mapa(bars + 8 * BAR_HOLD, rank ^ 1));
                fence_async_g(); red_release(g_cnt + CNT_X1 * 32);
            }
        }
    }
    role = __shfl_sync(~0u, lds32(sm + OFF_MISC), 0);
    if ((sm & 0xFFFFFFu) != SM0) __trap();
    if (role >= 64) { if (warp == 0) PROFDUMP(); return; }

    const int gi = role >> 3, dt = role & 3, c2 = (role >> 2) & 1;
    const int wg = warp >> 2, wi = warp & 3;
    if (wg == 3) {
        uint32_t so = 0, eph = 1;
        #define RING_STEP(BYTES, OFF, ISSUE) do { \
            mbar_wait(bars + 8 * BAR_EMPTY + so, eph); \
            if (elect()) { const uint32_t fb = bars + 8 * BAR_FULL + so, dst = sm + (OFF) + so * ((BYTES) / 8); mbar_expect(fb, BYTES); ISSUE; } \
            so += 8; if (so == 8 * NST) { so = 0; eph ^= 1; } } while (0)
        const uint32_t kbt = g2_kb(lane, rank, gi, c2) | (g2_kb(32 + (lane & 3), rank, gi, c2) << 8);
        #define KB(n_) ((__shfl_sync(~0u, kbt, (n_) & 31) >> (((n_) >> 2) & 8)) & 255)
        if (warp == 12) {
            eph = 0;
            const int fb1 = 9 * gi + 4 * c2 + 2 * rank, sb2 = 4 * gi + 2 * c2;
            int pft = dt, pfj = 4 * (PF0 + PFS * dt);
            #pragma unroll 1
            for (int j = 16; j < 128; j += 4) {
                RING_STEP(A_BYTES, OFF_A, tma4(dst, &tm_w1a, 0, 0, j, fb1, fb));
                if (j < 64) { if (j & 4) RING_STEP(A_BYTES, OFF_A, tma4(dst, &tm_w1b, 0, 0, 64 * rank + j - 4, 9 * gi + 8, fb)); }
                if (RP1 && __any_sync(~0u, (j & 12) == 4 * dt && j + 4 * RP1 < 128) && elect())
                    asm volatile("cp.async.bulk.prefetch.tensor.4d.L2.global [%0, {%1, %1, %2, %3}];" :: "l"(&tm_w1a), "r"(0), "r"(j + 4 * RP1), "r"(fb1) : "memory");
                if (RPX && __any_sync(~0u, (j & 4) == 0 && j + 8 * RPX < 64 && ((j >> 3) & 7) == (role & 7)) && elect())
                    asm volatile("cp.async.bulk.prefetch.tensor.4d.L2.global [%0, {%1, %1, %2, %3}];" :: "l"(&tm_w1b), "r"(0), "r"(64 * (int)rank + j + 8 * RPX), "r"(9 * gi + 8) : "memory");
                if (__any_sync(~0u, j == pfj && pft < PFN)) {
                    const int kb = KB(pft); pft += 4; pfj += 16 * PFS;
                    if (elect()) asm volatile("cp.async.bulk.prefetch.tensor.3d.L2.global [%0, {%1, %2, %3}];" :: "l"(&tm_w2), "r"(0), "r"(64 * kb), "r"(sb2) : "memory");
                }
            }
            #pragma unroll 1
            for (int n = 0; n < 36; n++) {
                const int kb = KB(n);
                RING_STEP(A_BYTES, OFF_A, tma3(dst, &tm_w2, 0, 64 * kb, sb2, fb));
            }
        } else if (warp == 13) {
            const uint32_t e1 = __shfl_sync(~0u, epoch + 1, 0);
            fence_async_s();
            wait_count<0>(g_cnt + CNT_H3 * 32, e1 * 128);
            fence_async_g();
            if (lane == 0) PROFT(14);
            #pragma unroll 1
            for (int j = 0; j < 128; j += 4) {
                RING_STEP(B_BYTES, OFF_B, tma3(dst, &tm_h3a, 0, 18 * dt, j, fb));
                if (j < 64 && (j & 4)) RING_STEP(B_BYTES, OFF_B, tma3(dst, &tm_h3b, 0, 18 * dt + 9 * c2, 64 * rank + j - 4, fb));
            }
            int n = 0;
            #pragma unroll 1
            for (int cls = 0; cls < 3; cls++) {
                mbar_wait(bars + 8 * (BAR_UOK + cls), 0);
                fence_async_g();
                if (cls == 1 && lane == 0) PROFT(19);
                if (cls == 0 && lane == 0) PROFT(22);
                static_assert((IT_G2 + 4) % NST != NST - 1, "no wrap at the skipped stage");
                if (cls == 1) { n++; so += 8; }
                #pragma unroll 1
                for (; n < (cls == 0 ? 4 : cls == 1 ? 21 : 36); n++) {
                    const int kb = KB(n);
                    RING_STEP(B_BYTES, OFF_B, bulk_load(dst, g_U + (kb * 4 + dt) * 1152, B_BYTES, fb));
                }
            }
            if (role == 0 && rank == 0 && lane == 0) st_relaxed(g_cnt + CNT_EPOCH * 32, e1);
        } else if (warp == 15) {
            if (!rowcta && elect()) mbar_arrive_remote(mapa(bars + 8 * BAR_HOLD, rank ^ 1));
            __syncwarp();
            bar_sync(6, 160);
            if (elect()) mbar_arrive(bars + 8 * (BAR_FULL + (IT_G2 + 4) % NST));
            __syncwarp();
            mbar_wait(bars + 8 * BAR_W1GO, 0);
            if (elect()) {
                char* dst = (char*)(g_U + ((9 * gi + 4 * c2 + 2 * rank + 1) * 4 + dt) * 1152);
                #pragma unroll 1
                for (int i = 0; i < W1N; i++) {
                    asm volatile("cp.async.bulk.global.shared::cta.bulk_group [%0], [%1], %2;" :: "l"(dst + i * (18432 / W1N)), "r"(sm + OFF_X1 + i * (18432 / W1N)), "n"(18432 / W1N) : "memory");
                    const uint32_t t1 = clk32(); while ((int)(clk32() - t1) < W1P) {}
                }
                asm volatile("cp.async.bulk.commit_group;" ::: "memory");
                asm volatile("cp.async.bulk.wait_group 0;" ::: "memory");
                fence_async_g(); red_release(g_cnt + (CNT_U + 16) * 32);
                #pragma unroll 1
                for (int n = 0; n < 4; n++) { __nanosleep(300); tma2(sm + OFF_X1 + n * 4608, &tm_o, 144 * dt, 256 * gi + 128 * c2 + 64 * (rank ^ 1) + 16 * n, bars + 8 * BAR_XT); }
            }
        } else {
            const uint32_t e1 = epoch + 1;
            if (lane == 0) {
                __nanosleep(4000);
                wait_count<200>(g_cnt + CNT_NC * 32, e1 * 4); wait_count<200>(g_cnt + (CNT_NC + 1) * 32, e1 * 2);
                fence_async_g();
                mbar_expect(bars + 8 * BAR_GB, 1152);
                bulk_load(sm + OFF_GB, p.scr->modc + 896, 1152, bars + 8 * BAR_GB);
                wait_count<200>(g_cnt + CNT_X1 * 32, e1 * 128);
                if (role * 2 + rank < 108) {
                    uint4* z = (uint4*)p.scr->modc + (role * 2 + rank) * 2; z[0] = z[1] = make_uint4(0, 0, 0, 0);
                }
                wait_count<50>(g_cnt + (CNT_U + dt * 2 + rank) * 32, e1 * 16);
                mbar_arrive(bars + 8 * BAR_UOK);
            }
            __syncwarp();
            bar_sync(4, 160);
            if (lane == 0) {
                fence_async_g(); red_release(g_cnt + (CNT_U + 8) * 32);
                PROFT(17);
                wait_count<0>(g_cnt + (CNT_U + 8) * 32, e1 * 128);
                mbar_arrive(bars + 8 * (BAR_UOK + 1));
                __nanosleep(1000);
                wait_count<100>(g_cnt + (CNT_U + 16) * 32, e1 * 128);
                mbar_arrive(bars + 8 * (BAR_UOK + 2));
            }
        }
    } else if (wg == 2) {
        float d0[36];
        const float bias = bf_lo(ldg_nc16(p.b1 + 576 * gi + 512 + 16 * wi + g + 8 * rank));
        #pragma unroll 1
        for (int it = 0; it < 200 && !__any_sync(~0u, mbar_test(bars + 8 * BAR_FULL, 0)); it++) { hb(); __nanosleep(100); }
        const bool lead = wi == 0 && elect();
        #pragma unroll 1
        for (int i = 0; i < 8; i++) {
            const uint32_t s = P2S + 3 * (i & 1);
            mbar_wait(bars + 8 * BAR_FULL + 8 * s, (i >> 1) & 1);
            const uint32_t da = desc_lo(OFF_A, 8192) + s * (A_BYTES / 16), db = desc_lo(OFF_B, 128) + s * (B_BYTES / 16);
            WG_FENCE();
            wgmma72(d0, da, db, i);
            #pragma unroll
            for (int k = 1; k < 9; k++) {
                if (k == P2K) asm volatile("{.reg .pred p; setp.ne.u32 p, %1, 0; @p mbarrier.arrive.shared::cta.b64 _, [%0];}" :: "r"(bars + 8 * (BAR_P2N + (i & 1))), "r"((uint32_t)lead) : "memory");
                if (k < 8) wgmma72(d0, da + k * 128, db + k * 144, 1);
            }
            WG_COMMIT();
            WG_WAIT(0);
            if (lead) mbar_arrive_n(bars + 8 * BAR_EMPTY + 8 * s, 2);
        }
        if (lead) PROFT(18);
        const uint32_t slot = sm + OFF_P2R + (tid & 127) * 16, ra = mapa(slot, rank ^ 1), rb = mapa(bars + 8 * BAR_P2R, rank ^ 1);
        float sv[18];
        #pragma unroll
        for (int i = 0; i < 18; i++) { const float lo = d0[4 * (i >> 1) + (i & 1)], hi = d0[4 * (i >> 1) + 2 + (i & 1)];
            sv[i] = rank ? lo : hi; d0[4 * (i >> 1) + (i & 1)] = (rank ? hi : lo) + bias; }
        mbar_wait(bars + 8 * BAR_HOLD, 0);
        #pragma unroll
        for (int i = 0; i < 4; i++)
            asm volatile("st.async.weak.shared::cluster.mbarrier::complete_tx::bytes.v4.f32 [%0], {%1,%2,%3,%4}, [%5];"
                :: "r"(ra + i * 2048), "f"(sv[4 * i]), "f"(sv[4 * i + 1]), "f"(sv[4 * i + 2]), "f"(sv[4 * i + 3]), "r"(rb) : "memory");
        asm volatile("st.async.weak.shared::cluster.mbarrier::complete_tx::bytes.v2.f32 [%0], {%1,%2}, [%3];" :: "r"(ra + 8192), "f"(sv[16]), "f"(sv[17]), "r"(rb) : "memory");
        mbar_wait(bars + 8 * BAR_P2R, 0);
        #pragma unroll
        for (int i = 0; i < 5; i++) {
            const uint4 v = lds128(slot + i * 2048);
            d0[8 * i] += __uint_as_float(v.x); d0[8 * i + 1] += __uint_as_float(v.y);
            if (i < 4) { d0[8 * i + 4] += __uint_as_float(v.z); d0[8 * i + 5] += __uint_as_float(v.w); }
        }
        asm volatile("bar.arrive 5, 256;" ::: "memory");
        gelu_store<0>(d0, (char*)(g_U + ((9 * gi + 8) * 4 + dt) * 1152) + wi * 4608 + rank * 2304 + c2 * 1152 + g * 16, q);
        bar_sync(8, 128);
        if (lead) { fence_async_g(); red_release(g_cnt + (CNT_U + dt * 2 + (gi >> 2)) * 32); PROFT(26); }
    } else {
        float d[72];
        const bool lead = wi == 0 && elect();
        const uint32_t da0 = desc_lo(OFF_A, 8192) + wg * 512;
        const bool owner = (uint32_t)wg == rank;
        const int srow = 256 * gi + 128 * c2 + 64 * wg + 16 * wi;
        const uint32_t b2w0 = ldg_nc16(p.b2 + srow + g), b2w1 = ldg_nc16(p.b2 + srow + g + 8);
        const int fr = 576 * gi + 256 * c2 + 128 * rank + 64 * wg + 16 * wi + g;
        const float bias0 = bf_lo(ldg_nc16(p.b1 + fr)), bias1 = bf_lo(ldg_nc16(p.b1 + fr + 8));
        {
            #pragma unroll
            for (int i = 0; i < 72; i++) d[i] = (i & 2) ? bias1 : bias0;
            constexpr uint32_t db1 = desc_lo(OFF_B, 128);
            static_assert(IT_G2 - LEAD1 == 6 * NST && IT_P1 == 4 * NST && P2S == 2, "loop structure");
            #define REL(s_) if (lead) mbar_arrive(bars + 8 * (BAR_EMPTY + (s_)))
            mma_block<DHI_H3, 0>(d, bars, da0, db1, 0);
            #pragma unroll 1
            for (int c = 0; c < 4; c++) {
                const uint32_t ph = c & 1;
                mma_block<DHI_H3, 1>(d, bars, da0, db1, ph); REL(0);
                mbar_wait(bars + 8 * (P2K ? BAR_P2N : BAR_FULL + 2), ph);
                mma_block<DHI_H3, 3>(d, bars, da0, db1, ph); REL(1);
                mma_block<DHI_H3, 4>(d, bars, da0, db1, ph); REL(3);
                mbar_wait(bars + 8 * (P2K ? BAR_P2N + 1 : BAR_FULL + 5), ph);
                mma_block<DHI_H3, 0>(d, bars, da0, db1, ph ^ 1); REL(4);
            }
            #pragma unroll 1
            for (uint32_t ph = 0; ph < 2; ph++) {
                mma_block<DHI_H3, 1>(d, bars, da0, db1, ph); REL(0);
                mma_block<DHI_H3, 2>(d, bars, da0, db1, ph); REL(1);
                mma_block<DHI_H3, 3>(d, bars, da0, db1, ph); REL(2);
                mma_block<DHI_H3, 4>(d, bars, da0, db1, ph); REL(3);
                mma_block<DHI_H3, 5>(d, bars, da0, db1, ph); REL(4);
                const bool pause = ph && wg == 1;
                if (pause) { WG_WAIT(0); REL(5); bar_sync(9, 256); }
                mma_block<DHI_H3, 0>(d, bars, da0, db1, ph ^ 1); if (!pause) REL(5);
            }
            #pragma unroll
            for (int i = IT_G2 - LEAD1 + 1; i < IT_G2; i++) {
                mbar_wait(bars + 8 * (BAR_FULL + i % NST), (i / NST) & 1);
                WG_FENCE();
                #pragma unroll
                for (int k = 0; k < 4; k++) {
                    if (i == IT_G2 - 1 && k == HOK1) WG_COMMIT();
                    wgmma144<DHI_H3>(d, da0 + (i % NST) * (A_BYTES / 16) + k * 128, db1 + (i % NST) * (B_BYTES / 16) + k * 288, 1);
                }
                WG_COMMIT();
                if (i == IT_G2 - 1 && HOK1 < 4) WG_WAIT(2); else WG_WAIT(1);
                REL((i - 1) % NST);
            }
            if (wg == 0) { WG_WAIT(1); asm volatile("bar.arrive 9, 256;" ::: "memory"); }
            WG_WAIT(0);
            if (lead) mbar_arrive(bars + 8 * (BAR_EMPTY + (IT_G2 - 1) % NST));
            PROF0(16);
            if (wg == 1) bar_sync(5, 256);
            char* const ub = (wg == 0 ? (char*)(g_U + ((9 * gi + 4 * c2 + 2 * rank) * 4 + dt) * 1152) : (char*)__cvta_shared_to_generic(sm + OFF_X1)) + wi * 4608 + g * 16;
            gelu_store<0>(d, ub, q); gelu_store<2>(d, ub + 2304, q); gelu_store<36>(d, ub + 1152, q); gelu_store<38>(d, ub + 3456, q);
            PROF0(27);
            if (wg == 0) asm volatile("bar.arrive 4, 160;" ::: "memory");
            else { fence_async_s(); asm volatile("bar.arrive 6, 160;" ::: "memory"); }
        }
        constexpr uint32_t db0 = desc_lo(OFF_B, 2304);
        const bool keep = role < 0;
        constexpr int IT_L = IT_END - NST;
        #pragma unroll
        for (int i = IT_G2; i <= IT_G2 + W1S; i++) {
            const uint32_t db = db0 + (i == IT_G2 + 4 ? OFF_X1 - OFF_B : (i % NST) * B_BYTES) / 16;
            mbar_wait(bars + 8 * (BAR_FULL + i % NST), (i / NST) & 1);
            WG_FENCE();
            #pragma unroll
            for (int k = 0; k < 4; k++) wgmma144<DHI_U>(d, da0 + (i % NST) * (A_BYTES / 16) + k * 128, db + k * 288, i > IT_G2 || k > 0 || keep);
            WG_COMMIT();
            if (i > IT_G2) { WG_WAIT(1); if (lead) mbar_arrive(bars + 8 * (BAR_EMPTY + (i - 1) % NST)); }
        }
        if (lead) mbar_arrive(bars + 8 * BAR_W1GO);
        const uint32_t ga0 = sm + OFF_GB + (144 * dt + 8 * q) * 2, tile = sm + OFF_X1 + wi * 4608, to = g * 288 + q * 16;
        #define QOFF(i_) (((i_) >> 2) * 2304 + 144 * (((i_) >> 1) & 1) + 64 * ((i_) & 1))
        #define SOFF(k_) (((k_) >> 1) * 2304 + 144 * ((k_) & 1) + 128 - 12 * q)
        #define DIDX(i_, k_) ((i_) < 8 ? 36 * (((i_) >> 1) & 1) + 16 * ((i_) & 1) + 4 * (k_) + 2 * ((i_) >> 2) : 36 * ((k_) & 1) + 32 + 2 * ((k_) >> 1))
        #define FIN(k_, f_) bfma2(g4.f_, pack_bf(d[DIDX(i, k_)], d[DIDX(i, k_) + 1]), xq[i].f_)
        uint4 xq[9];
        auto load_g = [&](int i) { uint4 r; if (i < 4) r = lds128(ga0 + QOFF(i)); else { r.x = r.z = lds32(ga0 + SOFF(0)); r.y = r.w = lds32(ga0 + SOFF(1)); } return r; };
        static_assert(W1S == 5 && (IT_G2 + 6) % NST == 4 && ((IT_G2 + 6) / NST) % 2 == 1 && IT_L == IT_G2 + 30, "loop structure");
        #pragma unroll 1
        for (int c = 0; c < 4; c++) {
            const uint32_t ph = c & 1, xa = tile + to; const bool xl = c == 3 && !owner;
            mma_block<DHI_U, 4>(d, bars, da0, db0, ph ^ 1); REL(3);
            mma_block<DHI_U, 5>(d, bars, da0, db0, ph ^ 1); REL(4);
            mma_block<DHI_U, 0>(d, bars, da0, db0, ph); REL(5);
            if (xl) { mbar_wait(bars + 8 * BAR_XT, 0); xq[0] = lds128(xa + QOFF(0)); xq[4] = lds128(xa + QOFF(4)); xq[1] = lds128(xa + QOFF(1)); }
            mma_block<DHI_U, 1>(d, bars, da0, db0, ph); REL(0);
            if (xl) { xq[5] = lds128(xa + QOFF(5)); xq[2] = lds128(xa + QOFF(2)); xq[6] = lds128(xa + QOFF(6)); }
            mma_block<DHI_U, 2>(d, bars, da0, db0, ph); REL(1);
            if (xl) { xq[3] = lds128(xa + QOFF(3)); xq[7] = lds128(xa + QOFF(7));
                      xq[8] = make_uint4(lds32(xa + SOFF(0)), lds32(xa + SOFF(1)), lds32(xa + SOFF(2)), lds32(xa + SOFF(3))); }
            mma_block<DHI_U, 3>(d, bars, da0, db0, ph); REL(2);
        }
        if (!owner && elect()) mbar_arrive_remote(mapa(bars + 8 * BAR_DONE, rank ^ 1));
        if (owner) { WG_WAIT(0); if (lead) mbar_arrive(bars + 8 * (BAR_EMPTY + (IT_L - 1) % NST)); bar_sync(7, 256); }
        #pragma unroll
        for (int i = IT_L; i < IT_END; i++) {
            mbar_wait(bars + 8 * (BAR_FULL + i % NST), (i / NST) & 1);
            WG_FENCE();
            #pragma unroll
            for (int k = 0; k < 4; k++) {
                if (i == IT_END - 1 && k == HOK) WG_COMMIT();
                wgmma144<DHI_U>(d, da0 + (i % NST) * (A_BYTES / 16) + k * 128, db0 + (i % NST) * (B_BYTES / 16) + k * 288, 1);
            }
            WG_COMMIT();
            if (i == IT_L) { WG_WAIT(1); if (lead && !owner) mbar_arrive(bars + 8 * (BAR_EMPTY + (IT_L - 1) % NST)); }
        }
        PROF0(9);
        mbar_wait(bars + 8 * BAR_GB, 0);
        if (!owner) {
            const uint32_t ra = mapa(tile + lane * 16, rank ^ 1), rb = mapa(bars + 8 * BAR_RECV, rank ^ 1);
            mbar_wait(bars + 8 * BAR_DONE, 0);
            uint4 gn = load_g(0);
            WG_WAIT(1);
            asm volatile("bar.arrive 7, 256;" ::: "memory");
            WG_WAIT(0);
            #pragma unroll
            for (int i = 0; i < 72; i++) d[i] = fmaf(bf_lo((i & 2) ? b2w1 : b2w0), 2.f, d[i]);
            #pragma unroll
            for (int j = 0; j < 5; j++) {
                const uint4 g4 = gn;
                if (j < 4) gn = load_g(j + 1);
                #pragma unroll
                for (int i = j < 4 ? j : 8; i < 9; i += 4) if (i < 8 || j == 4)
                    asm volatile("st.async.weak.shared::cluster.mbarrier::complete_tx::bytes.v4.b32 [%0], {%1,%2,%3,%4}, [%5];"
                        :: "r"(ra + i * 512), "r"(FIN(0, x)), "r"(FIN(1, y)), "r"(FIN(2, z)), "r"(FIN(3, w)), "r"(rb) : "memory");
            }
            PROF0(6);
            if (warp == 0) PROFDUMP();
            return;
        }
        PROF0(24);
        mbar_wait(bars + 8 * BAR_RECV, 0);
        #pragma unroll
        for (int i = 0; i < 9; i++) xq[i] = lds128(tile + lane * 16 + i * 512);
        uint4 gn = load_g(0);
        WG_WAIT(0);
        __syncwarp();
        PROF0(21);
        #pragma unroll
        for (int j = 0; j < 5; j++) {
            const uint4 g4 = gn;
            if (j < 4) gn = load_g(j + 1);
            #pragma unroll
            for (int i = j < 4 ? j : 8; i < 9; i += 4) if (i < 8 || j == 4) {
                const uint4 o = make_uint4(FIN(0, x), FIN(1, y), FIN(2, z), FIN(3, w));
                if (i < 8) sts128(tile + to + QOFF(i), o);
                else { sts32(tile + to + SOFF(0), o.x); sts32(tile + to + SOFF(1), o.y); sts32(tile + to + SOFF(2), o.z); sts32(tile + to + SOFF(3), o.w); }
            }
        }
        fence_async_s();
        __syncwarp();
        if (elect()) {
            asm volatile("cp.async.bulk.tensor.2d.global.shared::cta.bulk_group [%0, {%2, %3}], [%1];" :: "l"(&tm_o), "r"(tile), "r"(144 * dt), "r"(srow) : "memory");
            asm volatile("cp.async.bulk.commit_group;" ::: "memory");
            asm volatile("cp.async.bulk.wait_group.read 0;" ::: "memory");
        }
        PROF0(23);
        if (warp == 0) { __syncwarp(); PROFDUMP(); }
    }
}

typedef CUresult (*EncodeFn)(CUtensorMap*, CUtensorMapDataType, cuuint32_t, void*, const cuuint64_t*, const cuuint64_t*, const cuuint32_t*,
                             const cuuint32_t*, CUtensorMapInterleave, CUtensorMapSwizzle, CUtensorMapL2promotion, CUtensorMapFloatOOBfill);

void encode(EncodeFn fn, CUtensorMap* m, CUtensorMapDataType dt, int rank, const void* ptr, const cuuint64_t* dims, const cuuint64_t* strides,
            const cuuint32_t* box, CUtensorMapSwizzle sw, CUtensorMapL2promotion promo = CU_TENSOR_MAP_L2_PROMOTION_L2_128B) {
    const cuuint32_t es[5] = {1, 1, 1, 1, 1};
    fn(m, dt, rank, (void*)ptr, dims, strides, box, es, CU_TENSOR_MAP_INTERLEAVE_NONE, sw, promo, CU_TENSOR_MAP_FLOAT_OOB_FILL_NONE);
}

}

extern "C" void kernel_launch(void* const* d_in, const int* in_sizes, int n_in, void* d_out, int out_size) {
    (void)in_sizes; (void)n_in; (void)out_size;
    Params p;
    p.x = (const uint16_t*)d_in[0]; p.wr = (const uint16_t*)d_in[1]; p.wi = (const uint16_t*)d_in[2];
    p.w1 = (const uint16_t*)d_in[4]; p.b1 = (const uint16_t*)d_in[5]; p.w2 = (const uint16_t*)d_in[6]; p.b2 = (const uint16_t*)d_in[7];
    p.c = (const uint16_t*)d_in[8]; p.wmod = (const uint16_t*)d_in[9]; p.out = (uint16_t*)d_out;

    void* fnp = nullptr; cudaDriverEntryPointQueryResult qr;
    cudaGetDriverEntryPoint("cuTensorMapEncodeTiled", &fnp, cudaEnableDefault, &qr);
    EncodeFn fn = (EncodeFn)fnp;
    cudaGetSymbolAddress((void**)&p.scr, g_scr); cudaGetSymbolAddress((void**)&p.tab, g_tab);
    void* h3p = p.scr->h3;
    CUtensorMap tw1a, tw1b, tw2, th3a, th3b, twr, twi, twm, tt, ttx, to, th3s, tws;
    {
        const cuuint64_t dims[4] = {64, 16, 128, 72}, st[3] = {128ull * F_ * 2, (cuuint64_t)F_ * 2, 128};
        const cuuint32_t ba[4] = {64, 16, 4, 2}, bb[4] = {64, 16, 8, 1};
        encode(fn, &tw1a, CU_TENSOR_MAP_DATA_TYPE_BFLOAT16, 4, p.w1, dims, st, ba, CU_TENSOR_MAP_SWIZZLE_128B);
        encode(fn, &tw1b, CU_TENSOR_MAP_DATA_TYPE_BFLOAT16, 4, p.w1, dims, st, bb, CU_TENSOR_MAP_SWIZZLE_128B);
    }
    {
        const cuuint64_t dims[3] = {64, F_, 32}, st[2] = {(cuuint64_t)S_ * 2, 128};
        const cuuint32_t bx[3] = {64, 64, 2};
        encode(fn, &tw2, CU_TENSOR_MAP_DATA_TYPE_BFLOAT16, 3, p.w2, dims, st, bx, CU_TENSOR_MAP_SWIZZLE_128B);
    }
    {
        const cuuint64_t dims[3] = {64, 72, 128}, st[2] = {256, 18432};
        const cuuint32_t ba[3] = {64, 18, 4}, bb[3] = {64, 9, 8};
        encode(fn, &th3a, CU_TENSOR_MAP_DATA_TYPE_UINT32, 3, h3p, dims, st, ba, CU_TENSOR_MAP_SWIZZLE_NONE);
        encode(fn, &th3b, CU_TENSOR_MAP_DATA_TYPE_UINT32, 3, h3p, dims, st, bb, CU_TENSOR_MAP_SWIZZLE_NONE);
    }
    {
        const cuuint64_t dims[4] = {32, 72, 2, 128}, st[3] = {256, 128, 18432};
        const cuuint32_t bx[4] = {32, 72, 2, 1};
        encode(fn, &th3s, CU_TENSOR_MAP_DATA_TYPE_UINT32, 4, h3p, dims, st, bx, CU_TENSOR_MAP_SWIZZLE_128B, CU_TENSOR_MAP_L2_PROMOTION_NONE);
    }
    {
        const cuuint64_t dims[3] = {4624, 4, 32}, st[2] = {9248 * 32, 9248};
        const cuuint32_t bx[3] = {56, 4, 32};
        encode(fn, &twr, CU_TENSOR_MAP_DATA_TYPE_BFLOAT16, 3, p.wr, dims, st, bx, CU_TENSOR_MAP_SWIZZLE_NONE);
        encode(fn, &twi, CU_TENSOR_MAP_DATA_TYPE_BFLOAT16, 3, p.wi, dims, st, bx, CU_TENSOR_MAP_SWIZZLE_NONE);
    }
    {
        const cuuint64_t dims[2] = {3456, 576}, st[1] = {6912};
        const cuuint32_t bx[2] = {32, 144};
        encode(fn, &tws, CU_TENSOR_MAP_DATA_TYPE_BFLOAT16, 2, p.wmod, dims, st, bx, CU_TENSOR_MAP_SWIZZLE_64B);
    }
    {
        const cuuint64_t dims[3] = {64, 576, 54}, st[2] = {6912, 128};
        const cuuint32_t bx[3] = {64, 32, 7};
        encode(fn, &twm, CU_TENSOR_MAP_DATA_TYPE_BFLOAT16, 3, p.wmod, dims, st, bx, CU_TENSOR_MAP_SWIZZLE_128B);
    }
    {
        const cuuint64_t dims[2] = {TP, 128}, st[1] = {TP * 4};
        const cuuint32_t ba[2] = {32, 128}, bb[2] = {8, 128};
        encode(fn, &tt, CU_TENSOR_MAP_DATA_TYPE_UINT32, 2, p.scr->T, dims, st, ba, CU_TENSOR_MAP_SWIZZLE_128B, CU_TENSOR_MAP_L2_PROMOTION_NONE);
        encode(fn, &ttx, CU_TENSOR_MAP_DATA_TYPE_UINT32, 2, p.scr->T, dims, st, bb, CU_TENSOR_MAP_SWIZZLE_32B, CU_TENSOR_MAP_L2_PROMOTION_NONE);
    }
    {
        const cuuint64_t dims[2] = {D_, S_}, st[1] = {D_ * 2};
        const cuuint32_t bx[2] = {144, 16};
        encode(fn, &to, CU_TENSOR_MAP_DATA_TYPE_BFLOAT16, 2, p.out, dims, st, bx, CU_TENSOR_MAP_SWIZZLE_NONE, CU_TENSOR_MAP_L2_PROMOTION_NONE);
    }
    cudaFuncSetAttribute(fused_kernel, cudaFuncAttributeMaxDynamicSharedMemorySize, SMEM_BYTES);
    cudaLaunchConfig_t cfg = {};
    cfg.gridDim = dim3(NCTA); cfg.blockDim = dim3(NTHR); cfg.dynamicSmemBytes = SMEM_BYTES; cfg.stream = cudaStreamPerThread;
    cudaLaunchAttribute at[1];
    at[0].id = cudaLaunchAttributeClusterDimension; at[0].val.clusterDim.x = 2; at[0].val.clusterDim.y = 1; at[0].val.clusterDim.z = 1;
    cfg.attrs = at; cfg.numAttrs = 1;
    int nclusters = 0;
    cudaOccupancyMaxActiveClusters(&nclusters, fused_kernel, &cfg);
    at[0].id = cudaLaunchAttributeCooperative; at[0].val.cooperative = 1;
    cfg.numAttrs = nclusters * 2 >= NCTA ? 0 : 1;
    cudaLaunchKernelEx(&cfg, fused_kernel, p, tw1a, tw1b, tw2, th3a, th3b, twr, twi, twm, tt, ttx, to, th3s, tws);
}
```

```cpp
#include <cuda_runtime.h>
#include <cuda_bf16.h>
#include <cuda_fp16.h>
#include <cuda.h>
#include <stdint.h>

namespace {

constexpr int S_ = 2048, D_ = 576, F_ = 4608;
constexpr int NCTA = 132, NTHR = 512;
constexpr int TP = 4736;
constexpr int SPEC_P = 296;
constexpr int NST = 6;
constexpr int A_BYTES = 16384, B_BYTES = 18432;
constexpr int IT_P1 = 24, IT_G2 = 40, IT_END = 76;
constexpr int SPIN_LIMIT = 1 << 22;
#define X2D 1350
constexpr int P2S = 2;
#define LEAD1 4
#define W1N 8
#define W1P 100
#define W1S 5
#define XDELAY 1100
#define HOK 2
#define HOK1 2
#define NCP 10800
#define P2K 4
#define RP1 2
#define RPX 1
#define SLP 64
#define X1D 2100
#define PF0 4
#define PFS 3
#define PFN 9
#define X1DELAY 2000
#define X1PACE 400

constexpr int OFF_A = 0;
constexpr int OFF_B = NST * A_BYTES;
constexpr int OFF_P = OFF_B + NST * B_BYTES;
constexpr int OFF_BAR = OFF_P;
constexpr int OFF_EPOCH = OFF_P + 480;
constexpr int OFF_MISC = OFF_P + 496;
constexpr int OFF_GB = OFF_P + 512;
constexpr int OFF_P2R = OFF_P + 1664;
constexpr int OFF_X1 = OFF_P2R;
constexpr int OFF_PROF = OFF_X1 + 18432;
constexpr int SMEM_BYTES = OFF_PROF + 512;
constexpr int QA = 13, QB = 7, QC = 13;
constexpr int TAB_BYTES = (QA + QB + QC) * 512;
constexpr int OFF_STAGE = OFF_B;
constexpr int OFF_STX = OFF_STAGE + 16384;
constexpr int OFF_TAB = OFF_STAGE + 20480;
constexpr int OFF_SPEC = OFF_TAB + TAB_BYTES;
constexpr int OFF_WRAW = OFF_SPEC + 19072;
constexpr int OFF_B3 = OFF_WRAW + 28672;
constexpr int OFF_MODA = OFF_B3 + 4096;
constexpr int OFF_MODC = OFF_MODA + 2560;
constexpr int OFF_RED = OFF_MODC + 3584;
constexpr int OFF_HEXP = OFF_RED + 512;
constexpr int OFF_SILU = OFF_RED + 1536;
static_assert(OFF_SILU + 1152 <= OFF_P && 6 * 28672 <= OFF_B3, "scratch overflow");
constexpr int OFF_STRIP = OFF_A;
static_assert(OFF_WRAW % 128 == 0 && OFF_STAGE % 128 == 0 && OFF_STX % 128 == 0, "align");
constexpr int BAR_FULL = 0, BAR_EMPTY = 6, BAR_TAB = 12, BAR_W = 13, BAR_P2N = 14, BAR_P2R = 16,
              BAR_XT = 17, BAR_RECV = 18, BAR_ROLE = 19, BAR_NC = 20, BAR_TAB2 = 21, BAR_XB = 22, BAR_GB = 23, BAR_HOLD = 24, BAR_W1GO = 25, BAR_UOK = 26, BAR_DONE = 30, BAR_X = 31, BAR_ST = 47;

struct Cos1152 { double c[1152]; };
constexpr double cx_cos(double x) { double t = 1, s = 1; for (int i = 1; i < 14; i++) { t *= -x * x / ((2 * i - 1) * (2 * i)); s += t; } return s; }
constexpr Cos1152 make_cos() {
    Cos1152 r{};
    for (int i = 0; i <= 288; i++) {
        double v = (i == 288) ? 0.0 : cx_cos(3.14159265358979323846 * 2.0 * i / 1152.0);
        r.c[i] = v; r.c[576 - i] = -v; r.c[576 + i] = -v; r.c[(1152 - i) % 1152] = v;
    }
    return r;
}
constexpr uint32_t cx_f2h(double v) {
    uint32_t s = v < 0 ? 0x8000u : 0u; double a = v < 0 ? -v : v;
    if (a < 1e-9) return 0;
    int e = 0;
    while (a >= 2.0) { a *= 0.5; e++; }
    while (a < 1.0 && e > -14) { a *= 2.0; e--; }
    double m = a * 1024.0; uint32_t mi = (uint32_t)m; double fr = m - mi;
    if (fr > 0.5 || (fr == 0.5 && (mi & 1))) mi++;
    return s | (uint32_t)(((e + 14) << 10) + mi);
}
struct Tab { uint32_t w[(QA + QB + QC) * 128]; };
constexpr Tab make_tab() {
    Tab t{};
    Cos1152 ct = make_cos();
    auto C = [&](int num, int den) { return ct.c[(num % den) * (1152 / den)]; };
    auto Sn = [&](int num, int den) { return ct.c[((num % den) * (1152 / den) + 864) % 1152]; };
    auto put = [&](int q0, int idx, int lane, double lo, double hi) { t.w[((q0 + idx / 4) * 32 + lane) * 4 + idx % 4] = cx_f2h(lo) | (cx_f2h(hi) << 16); };
    for (int lane = 0; lane < 32; lane++) {
        const int g = lane >> 2, q = lane & 3;
        for (int mt = 0; mt < 3; mt++) {
            const int ka = 8 * mt + g;
            for (int r = 0; r < 10; r++) {
                const int im = r & 1, i0 = (r >> 1) * 2;
                double v[2] = {0, 0};
                for (int e = 0; e < 2; e++) { int i = i0 + e, d1 = 4 * i + q; if (i < 9 && ka <= 18) v[e] = (im ? -Sn(ka * d1, 36) : C(ka * d1, 36)) / 8; }
                put(0, r < 8 ? mt * 8 + r : 16 + 2 * mt + r, lane, v[0], v[1]);
            }
            for (int v = 0; v < 2; v++) {
                const int d2 = 4 * q + v;
                put(0, 30 + (mt * 2 + v) * 2, lane, C(ka * d2, 576) * 4 / 3, C(ka * (d2 + 2), 576) * 4 / 3);
                put(0, 31 + (mt * 2 + v) * 2, lane, Sn(ka * d2, 576) * 4 / 3, Sn(ka * (d2 + 2), 576) * 4 / 3);
            }
        }
        for (int v = 0; v < 2; v++) for (int nt = 0; nt < 2; nt++) {
            const int kb = 2 * (g >> 1) + nt, part = g & 1;
            double b0[2] = {0, 0}, b1[2] = {0, 0};
            for (int e = 0; e < 2; e++) { int d2 = 4 * q + 2 * e + v; double c = C(kb * d2, 16) / 4, s = Sn(kb * d2, 16) / 4;
                b0[e] = part ? -s : c; b1[e] = part ? c : s; }
            put(0, 42 + (v * 2 + nt) * 2, lane, b0[0], b0[1]); put(0, 43 + (v * 2 + nt) * 2, lane, b1[0], b1[1]);
        }
        t.w[((QA - 1) * 32 + lane) * 4 + 2] = 0x3F803F80u;
        for (int par = 0; par < 2; par++) for (int a = 0; a < 4; a++) {
            const int ja = 2 * (q + 4 * (a >> 1)) + par; const double c = C(g * ja, 16) / 4, s = Sn(g * ja, 16) / 4;
            put(QA, par * 4 + a, lane, (a & 1) ? -s : c, (a & 1) ? c : s);
        }
        for (int h = 0; h < 2; h++) {
            put(QA, 8 + 2 * h, lane, C((g + 8 * h) * (2 * q), 128) / 2, C((g + 8 * h) * (2 * q + 1), 128) / 2);
            put(QA, 9 + 2 * h, lane, Sn((g + 8 * h) * (2 * q), 128) / 2, Sn((g + 8 * h) * (2 * q + 1), 128) / 2);
            put(QA, 16 + 2 * h, lane, C(g * (8 * h + 2 * q), 128), C(g * (8 * h + 2 * q + 1), 128));
            put(QA, 17 + 2 * h, lane, Sn(g * (8 * h + 2 * q), 128), Sn(g * (8 * h + 2 * q + 1), 128));
        }
        put(QA, 12, lane, C(g * 2 * q, 8) / 2, C(g * (2 * q + 1), 8) / 2);
        put(QA, 15, lane, C(g * 2 * q, 8) / 2, C(g * (2 * q + 1), 8) / 2);
        put(QA, 13, lane, Sn(g * 2 * q, 8) / 2, Sn(g * (2 * q + 1), 8) / 2);
        put(QA, 14, lane, -Sn(g * 2 * q, 8) / 2, -Sn(g * (2 * q + 1), 8) / 2);
        for (int u = 0; u < 4; u++) {
            const int ja = 2 * ((g >> 1) + 4 * (u & 1)) + (u >> 1), part = g & 1; double b0[2] = {0, 0}, b1[2] = {0, 0};
            for (int e = 0; e < 2; e++) { int ka = 2 * q + e; double c = C(ja * ka, 16) / 4, s = Sn(ja * ka, 16) / 4;
                b0[e] = part ? s : c; b1[e] = part ? c : -s; }
            put(QA, 20 + u * 2, lane, b0[0], b0[1]); put(QA, 21 + u * 2, lane, b1[0], b1[1]);
        }
        for (int m2 = 0; m2 < 2; m2++) {
            const int d2 = 2 * g + m2;
            for (int a = 0; a < 4; a++) {
                const int kb = 2 * q + (a >> 1); const double c = C(d2 * kb, 16) / 4, s = Sn(d2 * kb, 16) / 4;
                put(QA + QB, m2 * 4 + a, lane, (a & 1) ? s : c, (a & 1) ? c : -s);
            }
            for (int mt = 0; mt < 3; mt++) {
                const int ka = 8 * mt + 2 * q;
                put(QA + QB, 8 + (m2 * 3 + mt) * 2, lane, C(ka * d2, 576) * 4 / 3, C((ka + 1) * d2, 576) * 4 / 3);
                put(QA + QB, 9 + (m2 * 3 + mt) * 2, lane, Sn(ka * d2, 576) * 4 / 3, Sn((ka + 1) * d2, 576) * 4 / 3);
            }
        }
        for (int mt = 0; mt < 3; mt++) for (int nt = 0; nt < 5; nt++) {
            const int i = 2 * nt + (g & 1), d1 = 4 * i + (g >> 1); double b0[2] = {0, 0}, b1[2] = {0, 0};
            for (int e = 0; e < 2; e++) { int ka = 8 * mt + 2 * q + e;
                if (ka <= 18 && i < 9) { double wt = (ka == 0 || ka == 18) ? 0.125 : 0.25; b0[e] = wt * C(ka * d1, 36); b1[e] = -wt * Sn(ka * d1, 36); } }
            const int o = (QA + QB + 5) * 128 + (mt * 5 + nt) * 64 + lane;
            t.w[o] = cx_f2h(b0[0]) | (cx_f2h(b0[1]) << 16); t.w[o + 32] = cx_f2h(b1[0]) | (cx_f2h(b1[1]) << 16);
        }
    }
    return t;
}
__device__ __align__(128) const Tab g_tab = make_tab();

struct Scratch {
    uint32_t cnt[30 * 32];
    uint32_t slot[96];
    uint32_t mod[2304];
    uint32_t modc[896 + 288];
    uint32_t T[128 * TP];
    uint4 h3[128 * 1152];
    uint4 U[72 * 4 * 1152];
};
__device__ __align__(1024) Scratch g_scr;
#define g_cnt (p.scr->cnt)
#define g_slot (p.scr->slot)
#define g_mod (p.scr->mod)
#define g_T (p.scr->T)
#define g_h3 (p.scr->h3)
#define g_U (p.scr->U)
constexpr int CNT_EPOCH = 0, CNT_H3 = 1, CNT_X1 = 26, CNT_NC = 27, CNT_U = 2;
#define PROFT(i) do {} while (0)
#define PROFDUMP() do {} while (0)
#define PROF0(i) do {} while (0)

__device__ __forceinline__ void mbar_init(uint32_t bar, uint32_t cnt) { asm volatile("mbarrier.init.shared::cta.b64 [%0], %1;" :: "r"(bar), "r"(cnt) : "memory"); }
__device__ __forceinline__ void mbar_expect(uint32_t bar, uint32_t bytes) { asm volatile("mbarrier.arrive.expect_tx.shared::cta.b64 _, [%0], %1;" :: "r"(bar), "r"(bytes) : "memory"); }
__device__ __forceinline__ void mbar_arrive(uint32_t bar) { asm volatile("mbarrier.arrive.shared::cta.b64 _, [%0];" :: "r"(bar) : "memory"); }
__device__ __forceinline__ void mbar_arrive_n(uint32_t bar, uint32_t n) { asm volatile("mbarrier.arrive.shared::cta.b64 _, [%0], %1;" :: "r"(bar), "r"(n) : "memory"); }
__device__ __forceinline__ void mbar_arrive_remote(uint32_t rbar) { asm volatile("mbarrier.arrive.relaxed.cluster.shared::cluster.b64 _, [%0];" :: "r"(rbar) : "memory"); }
__device__ __forceinline__ void mbar_wait(uint32_t bar, uint32_t parity) {
    asm volatile("{.reg .pred p; .reg .u32 c;\n"
        "mbarrier.try_wait.parity.shared::cta.b64 p, [%0], %1;\n@p bra.uni DONE;\nmov.u32 c, 0;\n"
        "LOOP: mbarrier.try_wait.parity.shared::cta.b64 p, [%0], %1;\n@p bra.uni DONE;\n"
        "add.u32 c, c, 1;\nsetp.lt.u32 p, c, %2;\n@p bra.uni LOOP;\ntrap;\nDONE:}" :: "r"(bar), "r"(parity), "n"(SPIN_LIMIT) : "memory");
}
__device__ __forceinline__ bool mbar_test(uint32_t bar, uint32_t parity) {
    uint32_t ok; asm volatile("{.reg .pred p; mbarrier.test_wait.parity.shared::cta.b64 p, [%1], %2; selp.u32 %0, 1, 0, p;}" : "=r"(ok) : "r"(bar), "r"(parity) : "memory"); return ok; }
__device__ __forceinline__ uint32_t mapa(uint32_t a, uint32_t rank) { uint32_t r; asm("mapa.shared::cluster.u32 %0, %1, %2;" : "=r"(r) : "r"(a), "r"(rank)); return r; }
__device__ __forceinline__ uint32_t clk32() { uint32_t r; asm volatile("mov.u32 %0, %%clock;" : "=r"(r)); return r; }
__device__ __forceinline__ void hb() {
    asm volatile("{.reg .b32 a, b; .reg .pred p; mma.sync.aligned.m16n8k8.row.col.f16.f16.f16.f16 {a, b}, {%0,%0}, {%0}, {%0,%0};\n"
                 "setp.ne.u32 p, a, 0; @p trap;}" :: "r"(0));
}
__device__ __forceinline__ void spin_until(uint32_t t) {
    #pragma unroll 1
    while (__any_sync(~0u, (int)(clk32() - t) < -SLP * 4)) { __nanosleep(SLP); hb(); }
    #pragma unroll 1
    while (__any_sync(~0u, (int)(clk32() - t) < 0)) {}
}
__device__ __forceinline__ bool elect() { uint32_t r; asm volatile("{.reg .pred p; elect.sync _|p, 0xffffffff; selp.u32 %0, 1, 0, p;}" : "=r"(r)); return r; }
__device__ __forceinline__ void bar_sync(int id, int n) { asm volatile("bar.sync %0, %1;" :: "r"(id), "r"(n) : "memory"); }
__device__ __forceinline__ void bulk_load(uint32_t dst, const void* src, uint32_t bytes, uint32_t bar) {
    asm volatile("cp.async.bulk.shared::cluster.global.mbarrier::complete_tx::bytes [%0], [%1], %2, [%3];" :: "r"(dst), "l"(src), "r"(bytes), "r"(bar) : "memory"); }
__device__ __forceinline__ void tma2(uint32_t dst, const CUtensorMap* m, int c0, int c1, uint32_t bar) {
    asm volatile("cp.async.bulk.tensor.2d.shared::cluster.global.mbarrier::complete_tx::bytes [%0], [%1, {%3, %4}], [%2];" :: "r"(dst), "l"(m), "r"(bar), "r"(c0), "r"(c1) : "memory"); }
__device__ __forceinline__ void tma3(uint32_t dst, const CUtensorMap* m, int c0, int c1, int c2, uint32_t bar) {
    asm volatile("cp.async.bulk.tensor.3d.shared::cluster.global.mbarrier::complete_tx::bytes [%0], [%1, {%3, %4, %5}], [%2];" :: "r"(dst), "l"(m), "r"(bar), "r"(c0), "r"(c1), "r"(c2) : "memory"); }
__device__ __forceinline__ void tma4(uint32_t dst, const CUtensorMap* m, int c0, int c1, int c2, int c3, uint32_t bar) {
    asm volatile("cp.async.bulk.tensor.4d.shared::cluster.global.mbarrier::complete_tx::bytes [%0], [%1, {%3, %4, %5, %6}], [%2];" :: "r"(dst), "l"(m), "r"(bar), "r"(c0), "r"(c1), "r"(c2), "r"(c3) : "memory"); }
__device__ __forceinline__ void fence_async_g() { asm volatile("fence.proxy.async.global;" ::: "memory"); }
__device__ __forceinline__ void fence_async_s() { asm volatile("fence.proxy.async.shared::cta;" ::: "memory"); }
__device__ __forceinline__ uint4 lds128(uint32_t a) { uint4 v; asm volatile("ld.shared.v4.u32 {%0,%1,%2,%3}, [%4];" : "=r"(v.x), "=r"(v.y), "=r"(v.z), "=r"(v.w) : "r"(a) : "memory"); return v; }
__device__ __forceinline__ uint32_t lds32(uint32_t a) { uint32_t v; asm volatile("ld.shared.u32 %0, [%1];" : "=r"(v) : "r"(a) : "memory"); return v; }
__device__ __forceinline__ void sts128(uint32_t a, uint4 v) { asm volatile("st.shared.v4.u32 [%0], {%1,%2,%3,%4};" :: "r"(a), "r"(v.x), "r"(v.y), "r"(v.z), "r"(v.w) : "memory"); }
__device__ __forceinline__ void sts32(uint32_t a, uint32_t v) { asm volatile("st.shared.u32 [%0], %1;" :: "r"(a), "r"(v) : "memory"); }
__device__ __forceinline__ void sts16(uint32_t a, uint32_t v) { asm volatile("st.shared.u16 [%0], %1;" :: "r"(a), "h"((uint16_t)v) : "memory"); }
__device__ __forceinline__ uint4 ldx128(const void* p) {
    uint4 v; asm volatile("{.reg .b128 t; .reg .b64 a, b; ld.relaxed.gpu.global.b128 t, [%4]; mov.b128 {a, b}, t; mov.b64 {%0,%1}, a; mov.b64 {%2,%3}, b;}"
        : "=r"(v.x), "=r"(v.y), "=r"(v.z), "=r"(v.w) : "l"(p) : "memory"); return v; }
__device__ __forceinline__ void stx128(void* p, uint4 v) {
    asm volatile("{.reg .b128 t; .reg .b64 a, b; mov.b64 a, {%1,%2}; mov.b64 b, {%3,%4}; mov.b128 t, {a, b}; st.relaxed.gpu.global.b128 [%0], t;}"
        :: "l"(p), "r"(v.x), "r"(v.y), "r"(v.z), "r"(v.w) : "memory"); }
__device__ __forceinline__ uint32_t ld_acquire(const uint32_t* p) { uint32_t v; asm volatile("ld.acquire.gpu.global.u32 %0, [%1];" : "=r"(v) : "l"(p) : "memory"); return v; }
__device__ __forceinline__ void st_relaxed(uint32_t* p, uint32_t v) { asm volatile("st.relaxed.gpu.global.u32 [%0], %1;" :: "l"(p), "r"(v) : "memory"); }
__device__ __forceinline__ void red_release(uint32_t* p) { asm volatile("red.release.gpu.global.add.u32 [%0], 1;" :: "l"(p) : "memory"); }
template <int SLEEP> __device__ __forceinline__ void wait_count(const uint32_t* p, uint32_t target) {
    int it = 0; while ((int)(ld_acquire(p) - target) < 0) { if (SLEEP) __nanosleep(SLEEP); if (++it > SPIN_LIMIT) __trap(); }
}
__device__ __forceinline__ uint32_t ldg_nc32(const void* p) { uint32_t v; asm volatile("ld.global.nc.L1::no_allocate.u32 %0, [%1];" : "=r"(v) : "l"(p)); return v; }
__device__ __forceinline__ uint32_t ldg_nc16(const void* p) { uint16_t v; asm volatile("ld.global.nc.u16 %0, [%1];" : "=h"(v) : "l"(p)); return v; }
__device__ __forceinline__ float bf_lo(uint32_t w) { return __uint_as_float(w << 16); }
__device__ __forceinline__ float bf_hi(uint32_t w) { return __uint_as_float(w & 0xFFFF0000u); }
__device__ __forceinline__ uint32_t pack_bf(float lo, float hi) { uint32_t r; asm("cvt.rn.bf16x2.f32 %0, %1, %2;" : "=r"(r) : "f"(hi), "f"(lo)); return r; }
__device__ __forceinline__ uint32_t pack_h(float lo, float hi) { uint32_t r; asm("cvt.rn.f16x2.f32 %0, %1, %2;" : "=r"(r) : "f"(hi), "f"(lo)); return r; }
__device__ __forceinline__ float bf_round(float v) { return bf_lo(pack_bf(v, 0.f)); }
__device__ __forceinline__ uint32_t hmul2(uint32_t a, uint32_t b) { uint32_t r; asm("mul.rn.f16x2 %0, %1, %2;" : "=r"(r) : "r"(a), "r"(b)); return r; }
__device__ __forceinline__ uint32_t hfma2(uint32_t a, uint32_t b, uint32_t c) { uint32_t r; asm("fma.rn.f16x2 %0, %1, %2, %3;" : "=r"(r) : "r"(a), "r"(b), "r"(c)); return r; }
__device__ __forceinline__ uint32_t hfms2(uint32_t a, uint32_t b, uint32_t c) { uint32_t r; asm("{.reg .b32 t; neg.f16x2 t, %3; fma.rn.f16x2 %0, %1, %2, t;}" : "=r"(r) : "r"(a), "r"(b), "r"(c)); return r; }
__device__ __forceinline__ uint32_t hadd2(uint32_t a, uint32_t b) { uint32_t r; asm("add.rn.f16x2 %0, %1, %2;" : "=r"(r) : "r"(a), "r"(b)); return r; }
__device__ __forceinline__ uint32_t hsub2(uint32_t a, uint32_t b) { uint32_t r; asm("sub.rn.f16x2 %0, %1, %2;" : "=r"(r) : "r"(a), "r"(b)); return r; }
__device__ __forceinline__ void cmul_neg(uint32_t& re, uint32_t& im, uint32_t c, uint32_t s) { uint32_t a = hfma2(re, c, hmul2(im, s)), b = hfms2(im, c, hmul2(re, s)); re = a; im = b; }
__device__ __forceinline__ void cmul_pos(uint32_t& re, uint32_t& im, uint32_t c, uint32_t s) { uint32_t a = hfms2(re, c, hmul2(im, s)), b = hfma2(im, c, hmul2(re, s)); re = a; im = b; }
__device__ __forceinline__ void mma_h(uint32_t& d0, uint32_t& d1, uint32_t a0, uint32_t a1, uint32_t a2, uint32_t a3, uint32_t b0, uint32_t b1) {
    asm("mma.sync.aligned.m16n8k16.row.col.f16.f16.f16.f16 {%0,%1}, {%2,%3,%4,%5}, {%6,%7}, {%0,%1};" : "+r"(d0), "+r"(d1) : "r"(a0), "r"(a1), "r"(a2), "r"(a3), "r"(b0), "r"(b1)); }
__device__ __forceinline__ void mma_h8(uint32_t& d0, uint32_t& d1, uint32_t a0, uint32_t a1, uint32_t b0) {
    asm("mma.sync.aligned.m16n8k8.row.col.f16.f16.f16.f16 {%0,%1}, {%2,%3}, {%4}, {%0,%1};" : "+r"(d0), "+r"(d1) : "r"(a0), "r"(a1), "r"(b0)); }
template <int NQ> __device__ __forceinline__ void load_tab(uint32_t (&r)[NQ * 4], uint32_t addr) {
    #pragma unroll
    for (int i = 0; i < NQ; i++) { uint4 v = lds128(addr + i * 512); r[4 * i] = v.x; r[4 * i + 1] = v.y; r[4 * i + 2] = v.z; r[4 * i + 3] = v.w; }
}
__device__ __forceinline__ float gelu2(float x) {
    float t = x * fmaf(x * x, 0.044715f * 0.7978845608028654f, 0.7978845608028654f), th;
    asm volatile("tanh.approx.f32 %0, %1;" : "=f"(th) : "f"(t));
    return fmaf(x, th, x);
}
constexpr uint32_t SM0 = 1024;
__device__ __forceinline__ constexpr uint32_t desc_lo(uint32_t off, uint32_t lbo) { return ((SM0 + off) >> 4) | ((lbo >> 4) << 16); }
constexpr uint32_t DHI_A = (1024 >> 4) | (1u << 30), DHI_H3 = 256 >> 4, DHI_U = 128 >> 4;
#define WG_FENCE() asm volatile("wgmma.fence.sync.aligned;" ::: "memory")
#define WG_COMMIT() asm volatile("wgmma.commit_group.sync.aligned;" ::: "memory")
#define WG_WAIT(n) asm volatile("wgmma.wait_group.sync.aligned %0;" :: "n"(n) : "memory")
#define R4(b) "+f"(d[b]), "+f"(d[b + 1]), "+f"(d[b + 2]), "+f"(d[b + 3])
#define R12(b) R4(b), R4(b + 4), R4(b + 8)
#define R36(b) R12(b), R12(b + 12), R12(b + 24)
template <uint32_t BHI> __device__ __forceinline__ void wgmma144(float (&d)[72], uint32_t da, uint32_t db, int acc) {
    asm volatile("{.reg .pred p; .reg .b64 a, b; setp.ne.b32 p, %74, 0; mov.b64 a, {%72, %75}; mov.b64 b, {%73, %76};\n"
        "wgmma.mma_async.sync.aligned.m64n144k16.f32.bf16.bf16 {%0,%1,%2,%3,%4,%5,%6,%7,%8,%9,%10,%11,%12,%13,%14,%15,%16,%17,%18,%19,%20,%21,%22,%23,"
        "%24,%25,%26,%27,%28,%29,%30,%31,%32,%33,%34,%35,%36,%37,%38,%39,%40,%41,%42,%43,%44,%45,%46,%47,"
        "%48,%49,%50,%51,%52,%53,%54,%55,%56,%57,%58,%59,%60,%61,%62,%63,%64,%65,%66,%67,%68,%69,%70,%71}, a, b, p, 1, 1, 1, 1;}\n"
        : R36(0), R36(36) : "r"(da), "r"(db), "r"(acc), "n"(DHI_A), "n"(BHI));
}
__device__ __forceinline__ void wgmma40_rs(float (&d)[20], uint32_t a0, uint32_t a1, uint32_t a2, uint32_t a3, uint32_t db, int acc) {
    asm volatile("{.reg .pred p; .reg .b64 b; setp.ne.b32 p, %25, 0; mov.b64 b, {%24, %26};\n"
        "wgmma.mma_async.sync.aligned.m64n40k16.f32.f16.f16 {%0,%1,%2,%3,%4,%5,%6,%7,%8,%9,%10,%11,%12,%13,%14,%15,%16,%17,%18,%19}, {%20,%21,%22,%23}, b, p, 1, 1, 0;}\n"
        : R12(0), R4(12), R4(16) : "r"(a0), "r"(a1), "r"(a2), "r"(a3), "r"(db), "r"(acc), "n"(DHI_H3));
}
__device__ __forceinline__ void wgmma72(float (&d)[36], uint32_t da, uint32_t db, int acc) {
    asm volatile("{.reg .pred p; .reg .b64 a, b; setp.ne.b32 p, %38, 0; mov.b64 a, {%36, %39}; mov.b64 b, {%37, %40};\n"
        "wgmma.mma_async.sync.aligned.m64n72k16.f32.bf16.bf16 {%0,%1,%2,%3,%4,%5,%6,%7,%8,%9,%10,%11,%12,%13,%14,%15,%16,%17,%18,%19,%20,%21,%22,%23,"
        "%24,%25,%26,%27,%28,%29,%30,%31,%32,%33,%34,%35}, a, b, p, 1, 1, 1, 1;}\n"
        : R36(0) : "r"(da), "r"(db), "r"(acc), "n"(DHI_A), "n"(DHI_H3));
}

__device__ __forceinline__ int g2_kb(int n, int kh, int gi, int c2) {
    if (n < 4) return 36 * kh + 9 * n + 8;
    if (n == 4) return 9 * gi + 4 * c2 + 2 * kh + 1;
    const int w = n > 20, m = n - (w ? 19 : 5);
    return 9 * ((gi * w + (m >> 1)) & 7) + 4 * (n == 35 ? 1 - c2 : m & 1) + 2 * kh + w;
}

template <uint32_t BHI, int S> __device__ __forceinline__ void mma_block(float (&d)[72], uint32_t bars, uint32_t da0, uint32_t db0, uint32_t ph) {
    mbar_wait(bars + 8 * (BAR_FULL + S), ph);
    WG_FENCE();
    #pragma unroll
    for (int k = 0; k < 4; k++) wgmma144<BHI>(d, da0 + S * (A_BYTES / 16) + k * 128, db0 + S * (B_BYTES / 16) + k * 288, 1);
    WG_COMMIT();
    WG_WAIT(1);
}

struct Params {
    const uint16_t *wmod, *c, *x;
    Scratch* scr;
    const Tab* tab;
    const uint16_t *wr, *wi, *w1, *b1, *w2, *b2;
    uint16_t* out;
};

__device__ __forceinline__ void mma_bf(float (&d)[4], const uint32_t (&a)[4], uint32_t b0, uint32_t b1) {
    asm("mma.sync.aligned.m16n8k16.row.col.f32.bf16.bf16.f32 {%0,%1,%2,%3}, {%4,%5,%6,%7}, {%8,%9}, {%0,%1,%2,%3};"
        : "+f"(d[0]), "+f"(d[1]), "+f"(d[2]), "+f"(d[3]) : "r"(a[0]), "r"(a[1]), "r"(a[2]), "r"(a[3]), "r"(b0), "r"(b1)); }
__device__ __forceinline__ void ldsm4t(uint32_t (&a)[4], uint32_t addr) {
    asm volatile("ldmatrix.sync.aligned.m8n8.x4.trans.shared.b16 {%0,%1,%2,%3}, [%4];" : "=r"(a[0]), "=r"(a[1]), "=r"(a[2]), "=r"(a[3]) : "r"(addr) : "memory"); }
__device__ __forceinline__ void ln_stats(const uint32_t (&w)[9], const uint32_t (&one)[9], int g, int q, float& r, float& mr) {
    float c[2][4] = {};
    #pragma unroll
    for (int p = 0; p < 9; p++)
        asm("mma.sync.aligned.m16n8k8.row.col.f32.bf16.bf16.f32 {%0,%1,%2,%3}, {%4,%5}, {%4}, {%0,%1,%2,%3};"
            : "+f"(c[p & 1][0]), "+f"(c[p & 1][1]), "+f"(c[p & 1][2]), "+f"(c[p & 1][3]) : "r"(w[p]), "r"(one[p]));
    const float t = (g & 1) ? c[0][1] + c[1][1] : c[0][0] + c[1][0];
    float s1 = (c[0][2] + c[1][2]) + (c[0][3] + c[1][3]), s2 = __shfl_sync(~0u, t, 9 * q) + __shfl_sync(~0u, t, 9 * q + 4);
    #pragma unroll
    for (int o = 1; o < 4; o <<= 1) { s1 += __shfl_xor_sync(~0u, s1, o); s2 += __shfl_xor_sync(~0u, s2, o); }
    const float m = s1 * (1.f / D_);
    asm("rsqrt.approx.ftz.f32 %0, %1;" : "=f"(r) : "f"(fmaxf(fmaf(s2, 1.f / D_, -m * m), 0.f) + 1e-5f));
    mr = -m * r;
}
__device__ __forceinline__ float silu(float v) { return __fdividef(v, 1.f + __expf(-v)); }
__device__ __forceinline__ uint32_t bfma2(uint32_t a, uint32_t b, uint32_t c) { uint32_t r; asm("fma.rn.bf16x2 %0, %1, %2, %3;" : "=r"(r) : "r"(a), "r"(b), "r"(c)); return r; }
__device__ __forceinline__ void radix16(const uint4 (&V)[4], const uint32_t (&B)[16], uint4 (&o)[4]) {
    #pragma unroll
    for (int nt = 0; nt < 4; nt++) o[nt] = make_uint4(0, 0, 0, 0);
    #pragma unroll
    for (int u = 0; u < 4; u++)
        #pragma unroll
        for (int nt = 0; nt < 4; nt++) {
            const uint32_t b = B[((u >> 1) * 4 + nt) * 2 + (u & 1)];
            mma_h8(o[nt].x, o[nt].y, V[u].x, V[u].y, b); mma_h8(o[nt].z, o[nt].w, V[u].z, V[u].w, b);
        }
}
template <int OFF, int N> __device__ __forceinline__ void gelu_store(const float (&d)[N], char* p, int q) {
    uint32_t w[9];
    #pragma unroll
    for (int blk = 0; blk < 9; blk++) w[blk] = pack_bf(gelu2(d[OFF + 4 * blk]), gelu2(d[OFF + 4 * blk + 1]));
    asm volatile("st.v4.u32 [%0], {%1,%2,%3,%4};" :: "l"(p + q * 128), "r"(w[0]), "r"(w[1]), "r"(w[2]), "r"(w[3]) : "memory");
    asm volatile("st.v4.u32 [%0+512], {%1,%2,%3,%4};" :: "l"(p + q * 128), "r"(w[4]), "r"(w[5]), "r"(w[6]), "r"(w[7]) : "memory");
    asm volatile("st.u32 [%0+1024], %1;" :: "l"(p + q * 4), "r"(w[8]) : "memory");
}

__global__ void __cluster_dims__(2, 1, 1) __launch_bounds__(NTHR, 1)
fused_kernel(const Params p,
             const __grid_constant__ CUtensorMap tm_w1a, const __grid_constant__ CUtensorMap tm_w1b, const __grid_constant__ CUtensorMap tm_w2,
             const __grid_constant__ CUtensorMap tm_h3a, const __grid_constant__ CUtensorMap tm_h3b,
             const __grid_constant__ CUtensorMap tm_wr, const __grid_constant__ CUtensorMap tm_wi, const __grid_constant__ CUtensorMap tm_wm,
             const __grid_constant__ CUtensorMap tm_t, const __grid_constant__ CUtensorMap tm_tx, const __grid_constant__ CUtensorMap tm_o,
             const __grid_constant__ CUtensorMap tm_h3s, const __grid_constant__ CUtensorMap tm_ws)
{
    extern __shared__ __align__(1024) char smem_raw[];
    const uint32_t t0 = clk32();
    const uint32_t sm = __shfl_sync(~0u, ((uint32_t)__cvta_generic_to_shared(smem_raw) + 1023u) & ~1023u, 0);
    const int tid = threadIdx.x, warp = __shfl_sync(~0u, tid >> 5, 0), lane = tid & 31, g = lane >> 2, q = lane & 3;
    const int b = blockIdx.x;
    const uint32_t rank = b & 1;
    const uint32_t bars = sm + OFF_BAR;
    const bool rowcta = b < 128;

    auto nc_issue = [&](int st, uint32_t sl) {
        const int pass = st >= 18;
        mbar_expect(bars + 8 * (BAR_X + sl), 28672);
        tma3(sm + sl * 28672, &tm_wm, 0, 32 * (st - 18 * pass), 18 + 28 * pass + 7 * (b - 128), bars + 8 * (BAR_X + sl));
    };
    uint32_t epoch;
    const bool strip = b < 72 && !(b & 1);
    const bool sil = (warp >> 2) == 2 && lane < 24 && (strip || !rowcta);
    uint32_t cw[3];
    if (elect()) {
        mbar_init(bars + 8 * (BAR_X + warp), rowcta || warp < 6 ? 1 : 14);
        if (warp >= 12) {
            if (strip) { const uint32_t sb = bars + 8 * (BAR_ST + warp - 12);
                mbar_init(sb, 1); mbar_expect(sb, 9216); tma2(sm + OFF_STRIP + (warp - 12) * 9216, &tm_ws, 16 * b, 144 * (warp - 12), sb); }
        } else if (warp == 7) {
            mbar_init(bars + 8 * BAR_TAB, 1); mbar_expect(bars + 8 * BAR_TAB, rowcta ? QA * 512 + 16 : 16);
            bulk_load(sm + OFF_EPOCH, g_cnt + CNT_EPOCH * 32, 16, bars + 8 * BAR_TAB);
            if (rowcta) bulk_load(sm + OFF_TAB, p.tab, QA * 512, bars + 8 * BAR_TAB);
        } else if (b + 132 * warp < 576) {
            asm volatile("cp.async.bulk.prefetch.L2.global [%0], 2304;" :: "l"(p.wmod + (b + 132 * warp) * 3456) : "memory");
        }
    }
    if (sil) {
        #pragma unroll
        for (int u = 0; u < 3; u++) cw[u] = ldg_nc32(p.c + 144 * (warp - 8) + 48 * u + 2 * lane);
    }
    if (warp == 6) hb();
    __syncthreads();
    if (!rowcta) { if (warp < 6 && elect()) nc_issue(warp, warp); }
    if (warp == 5 || warp == 6) {
        if (elect()) {
            if (warp == 5) {
                for (int i = BAR_W; i < BAR_X; i++) mbar_init(bars + 8 * i, i == BAR_DONE || i == BAR_NC ? 4 : i == BAR_W1GO ? 2 : 1);
                mbar_expect(bars + 8 * BAR_W, 28672); mbar_expect(bars + 8 * BAR_TAB2, (QB + QC) * 512);
                mbar_expect(bars + 8 * BAR_ROLE, 4); mbar_expect(bars + 8 * BAR_P2R, 9216); mbar_expect(bars + 8 * BAR_RECV, 18432); mbar_expect(bars + 8 * BAR_XT, 18432);
            } else {
                for (int i = 0; i < 2 * NST; i++) mbar_init(bars + 8 * i, 2);
                for (int i = 0; i < NST; i++) mbar_expect(bars + 8 * (BAR_FULL + i), A_BYTES);
            }
            asm volatile("fence.mbarrier_init.release.cluster;" ::: "memory");
        }
    } else if (warp >= 12 && elect())
        asm volatile("prefetch.tensormap [%0];" :: "l"(warp == 12 ? &tm_wr : warp == 13 ? &tm_wi : warp == 14 ? &tm_t : &tm_tx) : "memory");
    uint32_t sb[18];
    if ((warp >> 2) == 2) {
        if (sil) {
            #pragma unroll
            for (int u = 0; u < 3; u++) sts32(sm + OFF_SILU + (72 * (warp - 8) + 24 * u + lane) * 4, pack_bf(silu(bf_lo(cw[u])), silu(bf_hi(cw[u]))));
        }
        __syncwarp();
        if (strip) {
            #pragma unroll
            for (int u = 0; u < 18; u++) sb[u] = lds32(sm + OFF_SILU + (72 * (warp - 8) + 4 * u + q) * 4);
        }
    }
    if (rowcta && elect()) {
        if (XDELAY) while ((int)(clk32() - t0) < XDELAY) {}
        mbar_expect(bars + 8 * (BAR_X + warp), 1152);
        bulk_load(sm + OFF_STAGE + warp * 1152, p.x + (size_t)(b + 128 * warp) * D_, 1152, bars + 8 * (BAR_X + warp));
    }
    __syncwarp();
    hb();

    const int trow = 4 * (b & 7) + ((b >> 4) & 3) + 64 * ((b >> 3) & 1) + 32 * (b >> 6);
    uint32_t* const tptr = g_T + (size_t)trow * TP + (warp < 9 ? q * 288 + 32 * warp : 4608 + 8 * q) + 4 * g;
    const int tstr = warp < 9 ? 1152 : 32;
    const uint32_t scol = sm + OFF_SPEC + (q * SPEC_P + (warp < 8 ? 72 * (warp >> 1) + 40 * (warp & 1) + 4 * g : warp == 8 ? 72 * (g >> 1) + 32 + 4 * (g & 1) : 288 + 4 * g)) * 4;
    const int wc0 = (b >> 3) * 289 + 72 * ((b & 7) >> 1) + 40 * (b & 1);

    uint32_t xw[9], one[9], t_st = t0, hexp = 0;
    if (!rowcta) {
        const int nst = b < 130 ? 36 : 18;
        __syncthreads();
        asm volatile("barrier.cluster.arrive.relaxed.aligned;" ::: "memory");
        mbar_wait(bars + 8 * BAR_TAB, 0);
        epoch = lds32(sm + OFF_EPOCH);
        if (warp == 14) {
            uint32_t sl = 0, ph = 0;
            #pragma unroll 1
            for (int st = 6; st < nst; st++) {
                mbar_wait(bars + 8 * (BAR_X + 6 + sl), ph);
                if (elect()) nc_issue(st, sl);
                if (++sl == 6) { sl = 0; ph ^= 1; }
            }
        } else if (warp < 14) {
            uint32_t sl = 0, ph = 0;
            const uint32_t ad0 = sm + (warp >> 1) * 4096 + ((lane & 7) + 8 * (lane >> 4)) * 128, ch = (warp & 1) * 4 + ((lane >> 3) & 1);
            #pragma unroll 1
            for (int pass = 0; pass * 18 < nst; pass++) {
                float acc[2][4] = {};
                #pragma unroll 1
                for (int st = 0; st < 18; st++) {
                    const uint32_t sa = sm + OFF_SILU + (16 * st + q) * 4;
                    const uint32_t b0 = lds32(sa), b1 = lds32(sa + 16), b2 = lds32(sa + 32), b3 = lds32(sa + 48);
                    mbar_wait(bars + 8 * (BAR_X + sl), ph);
                    #pragma unroll
                    for (int m = 0; m < 2; m++) {
                        uint32_t a[4], a2[4];
                        const uint32_t ad = ad0 + sl * 28672 + ((ch + 2 * m) ^ (lane & 7)) * 16;
                        ldsm4t(a, ad); ldsm4t(a2, ad + 2048);
                        mma_bf(acc[m], a, b0, b1); mma_bf(acc[m], a2, b2, b3);
                    }
                    if (elect()) mbar_arrive(bars + 8 * (BAR_X + 6 + sl));
                    if (++sl == 6) { sl = 0; ph ^= 1; }
                }
                const int cb = 28 * pass + 7 * (b - 128) + (warp >> 1), gg = (g >> 1) + 4 * q;
                uint32_t w[2];
                #pragma unroll
                for (int m = 0; m < 2; m++) {
                    float v = bf_round(q ? acc[m][2] : acc[m][0]); if (cb >= 27) v *= 0.5f; else if (cb >= 18) v += 1.f;
                    w[m] = max(pack_bf(v, __shfl_xor_sync(~0u, v, 4)), 1u);
                }
                if (q < 2 && !(g & 1)) {
                    const int qq = (warp & 1) * 2;
                    if (cb < 27) asm volatile("st.relaxed.gpu.global.v2.u32 [%0], {%1, %2};" :: "l"(p.scr->modc + 32 * cb + 4 * gg + qq), "r"(w[0]), "r"(w[1]) : "memory");
                    else if (cb < 36) { uint32_t* o = p.scr->modc + 896 + 32 * (cb - 27) + 8 * qq + gg; o[0] = w[0]; o[8] = w[1]; }
                }
                if (tid == 0 && pass == 0) PROFT(25);
                bar_sync(1, 448);
                if (tid == 0) { fence_async_g(); red_release(g_cnt + (CNT_NC + pass) * 32); }
                __syncwarp();
            }
            fence_async_s();
        }
        __syncthreads();
    } else {
        uint32_t ta[QA * 4];
        if (strip && (warp >> 2) == 2) {
            const int w = warp - 8;
            const uint32_t ra = sm + OFF_STRIP + (144 * w + (lane & 7) + 8 * (lane >> 4)) * 64, sw = (lane >> 1) & 3, ch = (lane >> 3) & 1;
            float acc[2][2][4] = {};
            mbar_wait(bars + 8 * (BAR_ST + w), 0);
            #pragma unroll
            for (int u = 0; u < 9; u++)
                #pragma unroll
                for (int m = 0; m < 2; m++) { uint32_t a[4]; ldsm4t(a, ra + u * 1024 + ((ch + 2 * m) ^ sw) * 16); mma_bf(acc[u & 1][m], a, sb[2 * u], sb[2 * u + 1]); }
            #define PICK(a_) ((q & 2) ? ((q & 1) ? a_[1][2] : a_[1][0]) : ((q & 1) ? a_[0][2] : a_[0][0]))
            sts32(sm + OFF_RED + ((8 * q + g) * 4 + w) * 4, __float_as_uint(PICK(acc[0]) + PICK(acc[1])));
            if (tid == 256) PROFT(0);
            bar_sync(10, 128);
            if (warp == 8) {
                mbar_wait(bars + 8 * BAR_TAB, 0);
                const uint4 v = lds128(sm + OFF_RED + lane * 16);
                float sum = bf_round((__uint_as_float(v.x) + __uint_as_float(v.y)) + (__uint_as_float(v.z) + __uint_as_float(v.w)));
                if (b >= 36) sum = bf_round(1.f + sum);
                st_relaxed(g_mod + b * 16 + (lane & 16) + (lane & 1) * 8 + ((lane & 15) >> 1), (fabsf(sum) < 8.f ? pack_h(0.f, sum) : __float_as_uint(sum) | 0x8000u) | ((lds32(sm + OFF_EPOCH) + 1) & 0x7FFFu));
                asm volatile("bar.arrive 11, 416;" ::: "memory");
                if (tid == 256) PROFT(1);
            }
        }
        mbar_wait(bars + 8 * BAR_TAB, 0);
        load_tab<QA>(ta, sm + OFF_TAB + lane * 16);
        epoch = lds32(sm + OFF_EPOCH);
        const uint32_t tag = (epoch + 1) & 0x7FFFu;
        auto w_prefetch = [&]() {
            if (warp >= 14 && elect()) asm volatile("cp.async.bulk.prefetch.L2.global [%0], 9248;" :: "l"((warp == 14 ? p.wr : p.wi) + b * 4624) : "memory");
            __syncwarp();
        };
        uint32_t nb[2][5];
        uint4 mv = make_uint4(tag, tag, tag, tag);
        const bool poller = warp < 8 || warp == 12;
        const int mc = warp < 8 ? tid : tid - 128, mst = (mc >> 2) % 36, midx = (mc < 144 ? 10 : 0) + 5 * ((mc >> 1) & 1) + (mst >> 3);
        const uint32_t* mp = g_mod + mc * 4;
        const uint32_t ma = sm + OFF_MODA + ((midx >> 2) * 32 + (mc & 1) * 16 + (mst & 3)) * 16 + (midx & 3) * 4 + ((mst >> 2) & 1) * 2;
        #define MOD_MISSING ((((mv.x ^ tag) | (mv.y ^ tag) | (mv.z ^ tag) | (mv.w ^ tag)) & 0x7FFFu) != 0)
        if (strip && (warp >> 2) != 2) bar_sync(11, 416);
        #pragma unroll
        for (int i = 0; i < 9; i++) one[i] = lds32(sm + OFF_TAB + (QA - 1) * 512 + i * 16 + 8);
        hb();
        mbar_wait(bars + 8 * (BAR_X + warp), 0);
        if (poller) mv = ldx128(mp);
        PROF0(28);
        #pragma unroll
        for (int i = 0; i < 9; i++) xw[i] = lds32(sm + OFF_STAGE + warp * 1152 + (32 * i + 8 * q + g) * 4);
        {
            float r, mr;
            ln_stats(xw, one, g, q, r, mr);
            #pragma unroll
            for (int pp = 0; pp < 5; pp++) {
                nb[0][pp] = pack_h(fmaf(bf_lo(xw[2 * pp]), r, mr), pp < 4 ? fmaf(bf_lo(xw[pp < 4 ? 2 * pp + 1 : 0]), r, mr) : 0.f);
                nb[1][pp] = pack_h(fmaf(bf_hi(xw[2 * pp]), r, mr), pp < 4 ? fmaf(bf_hi(xw[pp < 4 ? 2 * pp + 1 : 0]), r, mr) : 0.f);
            }
        }
        PROF0(2);
        w_prefetch();
        if (poller && MOD_MISSING) mv = ldx128(mp);
        if (warp < 8) {
            if (warp >= 4) sts16(sm + OFF_MODA + ((warp - 3) * 32 + lane) * 16 + (warp - 4) * 4 + 2, 0);
            const int k1 = tid & 15, s1 = tid >> 4;
            float s, c;
            __sincosf((float)(((k1 * (128 * s1 + b) + 1024) & 2047) - 1024) * (3.14159265358979f / 1024.f), &s, &c); s *= 0.25f; c *= 0.25f;
            const int rf = ((s1 >> 3) * 4 + (k1 >> 2)) * 2 + ((s1 >> 2) & 1), ri = ((k1 >> 3) * 4 + (s1 >> 2)) * 2 + ((k1 >> 2) & 1);
            const uint32_t af = sm + OFF_B3 + ((rf >> 2) * 32 + (k1 & 3) * 8 + (s1 & 3)) * 16 + (rf & 3) * 4;
            const uint32_t ai = sm + OFF_B3 + 2048 + ((ri >> 2) * 32 + (s1 & 3) * 8 + (k1 & 3)) * 16 + (ri & 3) * 4;
            sts32(af, pack_h(c, s)); sts32(af + 64, pack_h(-s, c)); sts32(ai, pack_h(c, -s)); sts32(ai + 64, pack_h(s, c));
        }
        if (poller) {
            #pragma unroll 1
            for (int it = 0; __any_sync(~0u, MOD_MISSING); it++) { if (MOD_MISSING) mv = ldx128(mp); hb(); if (it > SPIN_LIMIT) __trap(); }
            sts16(ma, mv.x >> 16); sts16(ma + 64, mv.y >> 16); sts16(ma + 128, mv.z >> 16); sts16(ma + 192, mv.w >> 16);
        }
        uint32_t redo = 0; asm volatile("" : "+r"(redo));
        #pragma unroll 1
        do { if (redo) {
            const uint32_t w[4] = {mv.x, mv.y, mv.z, mv.w}; float f[4]; uint32_t big = 0;
            #pragma unroll
            for (int e = 0; e < 4; e++) { f[e] = (w[e] & 0x8000u) ? bf_hi(w[e]) : __half2float(__ushort_as_half(w[e] >> 16)); big = max(big, __float_as_uint(f[e]) << 1 >> 24); }
            sts32(sm + OFF_HEXP + warp * 4, __reduce_max_sync(~0u, big));
            __syncthreads();
            hexp = min(__reduce_max_sync(~0u, lds32(sm + OFF_HEXP + (lane & 15) * 4)), 253u) - 127;
            const float sc = __uint_as_float((127 - hexp) << 23);
            if (poller) {
                #pragma unroll
                for (int e = 0; e < 4; e++) sts16(ma + 64 * e, pack_h(f[e] * sc, 0.f));
            }
            mv = make_uint4(0, 0, 0, 0);
          }
          redo = __syncthreads_or((mv.x | mv.y | mv.z | mv.w) & 0x8000u);
          asm volatile("" : "+r"(redo));
        } while (redo);
        PROF0(3);
        asm volatile("barrier.cluster.arrive.relaxed.aligned;" ::: "memory");
        if (warp >= 13 && elect()) {
            if (warp == 15) bulk_load(sm + OFF_TAB + QA * 512, p.tab->w + QA * 128, (QB + QC) * 512, bars + 8 * BAR_TAB2);
            else tma3(sm + OFF_WRAW + (warp - 13) * 14336, warp == 13 ? &tm_wr : &tm_wi, wc0 & ~7, 0, 0, bars + 8 * BAR_W);
        }
        __syncwarp();
        {
            uint32_t md[20];
            load_tab<5>(md, sm + OFF_MODA + lane * 16);
            #pragma unroll
            for (int v = 0; v < 2; v++)
                #pragma unroll
                for (int pp = 0; pp < 5; pp++) nb[v][pp] = hfma2(nb[v][pp], md[v * 5 + pp], md[10 + v * 5 + pp]);
        }
        uint32_t re[3][2], im[3][2];
        #pragma unroll
        for (int mt = 0; mt < 3; mt++)
            #pragma unroll
            for (int v = 0; v < 2; v++) {
                re[mt][v] = 0; im[mt][v] = 0;
                mma_h8(re[mt][v], im[mt][v], ta[24 + 2 * mt], ta[25 + 2 * mt], nb[v][4]);
                mma_h(re[mt][v], im[mt][v], ta[mt * 8], ta[mt * 8 + 1], ta[mt * 8 + 2], ta[mt * 8 + 3], nb[v][0], nb[v][1]);
                mma_h(re[mt][v], im[mt][v], ta[mt * 8 + 4], ta[mt * 8 + 5], ta[mt * 8 + 6], ta[mt * 8 + 7], nb[v][2], nb[v][3]);
                cmul_neg(re[mt][v], im[mt][v], ta[30 + (mt * 2 + v) * 2], ta[31 + (mt * 2 + v) * 2]);
            }
        const uint32_t srow = sm + OFF_SPEC + warp * (SPEC_P * 4);
        #pragma unroll
        for (int nt = 0; nt < 2; nt++) {
            uint32_t o[2][4];
            #pragma unroll
            for (int v = 0; v < 2; v++) {
                const uint32_t b0 = ta[42 + (v * 2 + nt) * 2], b1 = ta[43 + (v * 2 + nt) * 2];
                o[v][0] = o[v][1] = o[v][2] = o[v][3] = 0;
                mma_h(o[v][0], o[v][1], re[0][v], re[1][v], im[0][v], im[1][v], b0, b1);
                mma_h(o[v][2], o[v][3], re[2][0], re[2][1], im[2][0], im[2][1], b0, b1);
            }
            const uint32_t a = srow + (g + 72 * q + 36 * nt) * 4, a2 = srow + (288 - g - 72 * q - 36 * nt) * 4;
            sts32(a, hadd2(o[0][0], o[1][0])); sts32(a + 32, hadd2(o[0][1], o[1][1])); if (g < 3) sts32(a + 64, hadd2(o[0][2], o[1][3]));
            if (g > 0 || (q == 0 && nt == 0)) sts32(a2, hsub2(o[0][0], o[1][0]) ^ 0x80000000u);
            sts32(a2 - 32, hsub2(o[0][1], o[1][1]) ^ 0x80000000u); if (g < 2) sts32(a2 - 64, hsub2(o[0][2], o[1][3]) ^ 0x80000000u);
        }
        uint32_t b3[16];
        if (warp < 10) load_tab<4>(b3, sm + OFF_B3 + lane * 16);
        __syncthreads();
        t_st = clk32();
        PROF0(4);
        if (warp < 10) {
            uint4 V[4], o[4];
            #pragma unroll
            for (int u = 0; u < 4; u++) V[u] = lds128(scol + u * (16 * SPEC_P));
            radix16(V, b3, o);
            #pragma unroll
            for (int nt = 0; nt < 4; nt++) { o[nt].x |= 1u; if (warp < 9 || g < 2) stx128(tptr + nt * tstr, o[nt]); }
        }
        PROF0(5);
    }

    int role = 0;
    asm volatile("barrier.cluster.wait.aligned;" ::: "memory");
    if (warp >= 12) {
        const int t = tid - 384;
        if (warp == 14 && rank == 0) {
            uint32_t smid; asm volatile("mov.u32 %0, %%smid;" : "=r"(smid));
            const uint32_t tp = smid >> 1;
            uint32_t pr = tp < 32 ? (tp & 7) * 8 + (tp >> 3) : tp < 60 ? (1 + (tp - 32) % 7) * 8 + 4 + (tp - 32) / 7 : tp < 62 ? 4 + tp : tp < 66 ? tp - 58 : 0;
            #pragma unroll 1
            for (;;) {
                uint32_t old = 0; if (lane == 0) old = atomicExch(g_slot + pr, epoch + 1);
                if (!__any_sync(~0u, lane == 0 && old == epoch + 1)) break;
                pr = pr == 65 ? 0 : pr + 1;
            }
            if (lane < 2) asm volatile("st.async.weak.shared::cluster.mbarrier::complete_tx::bytes.u32 [%0], %1, [%2];" :: "r"(mapa(sm + OFF_MISC, lane)), "r"(pr), "r"(mapa(bars + 8 * BAR_ROLE, lane)) : "memory");
        }
        __syncwarp();
        if (t == 0) {
            asm volatile("prefetch.tensormap [%0];" :: "l"(&tm_w1a) : "memory");
            asm volatile("prefetch.tensormap [%0];" :: "l"(&tm_h3a) : "memory"); asm volatile("prefetch.tensormap [%0];" :: "l"(&tm_w1b) : "memory");
            asm volatile("prefetch.tensormap [%0];" :: "l"(&tm_h3b) : "memory"); asm volatile("prefetch.tensormap [%0];" :: "l"(&tm_w2) : "memory");
            asm volatile("prefetch.tensormap [%0];" :: "l"(&tm_o) : "memory"); asm volatile("prefetch.tensormap [%0];" :: "l"(&tm_h3s) : "memory");
        }
        __syncwarp();
        if (rowcta) {
            spin_until(t0 + NCP);
            uint4 v[2];
            v[1] = make_uint4(1, 1, 1, 1);
            #pragma unroll 1
            for (int it = 0;; it++) {
                v[0] = ldx128(p.scr->modc + 4 * t); if (t < 88) v[1] = ldx128(p.scr->modc + 512 + 4 * t);
                if (__all_sync(~0u, min(min(min(v[0].x, v[0].y), min(v[0].z, v[0].w)), min(min(v[1].x, v[1].y), min(v[1].z, v[1].w))) != 0)) break;
                __nanosleep(100); if (it > SPIN_LIMIT) __trap();
            }
            if (t < 72) { const uint32_t sc = ((127 + hexp) << 7) * 0x10001u;
                v[0] = make_uint4(bfma2(v[0].x, sc, 0x80008000u), bfma2(v[0].y, sc, 0x80008000u), bfma2(v[0].z, sc, 0x80008000u), bfma2(v[0].w, sc, 0x80008000u)); }
            #pragma unroll
            for (int u = 0; u < 2; u++) if (u == 0 || t < 88) {
                const uint32_t a = sm + OFF_MODC + (((t >> 5) + 4 * u) * 32 + 4 * (t & 7)) * 16 + ((t >> 3) & 3) * 4;
                sts32(a, v[u].x); sts32(a + 16, v[u].y); sts32(a + 32, v[u].z); sts32(a + 48, v[u].w);
            }
            __syncwarp();
            if (elect()) mbar_arrive(bars + 8 * BAR_NC);
            if (t == 0) PROFT(29);
        }
    } else if (rowcta && warp < 11) {
        const int nw = !(b & 1) ? 10 : (b & 7) == 7 ? 9 : 8;
        const int cm = (b >> 3) * 288 + (b & 7) * 32, cx = (b & 1) ? 4608 + 8 * (b >> 3) : (b >> 3) * 288 + 256 + 4 * (b & 7);
        auto load_in = [&]() {
            if (elect()) {
                mbar_expect(bars + 8 * BAR_XB, nw > 8 ? 20480 : 16384);
                tma2(sm + OFF_STAGE, &tm_t, cm, 0, bars + 8 * BAR_XB);
                if (nw > 8) tma2(sm + OFF_STX, &tm_tx, cx, 0, bars + 8 * BAR_XB);
            }
            __syncwarp();
        };
        if (warp == 10) { fence_async_s(); spin_until(t_st + X1D); load_in(); }
        uint32_t tb[QB * 4], wre[4][2], wim[4][2];
        if (warp < nw) {
            mbar_wait(bars + 8 * BAR_TAB2, 0);
            load_tab<QB>(tb, sm + OFF_TAB + QA * 512 + lane * 16);
            mbar_wait(bars + 8 * BAR_W, 0);
            const int off = wc0 & 7;
            const uint32_t wa = sm + OFF_WRAW + lane * 112 + ((off >> 1) + 2 * warp) * 4, sh = (off & 1) * 16;
            #pragma unroll
            for (int c = 0; c < 2; c++)
                #pragma unroll
                for (int h = 0; h < 2; h++) {
                    uint32_t y[2][2];
                    #pragma unroll
                    for (int e = 0; e < 2; e++) {
                        const uint32_t a = wa + c * 14336 + (h + 2 * e) * 3584, x0 = lds32(a), x1 = lds32(a + 4), x2 = lds32(a + 8);
                        y[e][0] = __funnelshift_r(x0, x1, sh); y[e][1] = __funnelshift_r(x1, x2, sh);
                    }
                    #pragma unroll
                    for (int x = 0; x < 4; x++) {
                        const uint32_t v = (x & 1) ? pack_h(bf_hi(y[0][x >> 1]), bf_hi(y[1][x >> 1])) : pack_h(bf_lo(y[0][x >> 1]), bf_lo(y[1][x >> 1]));
                        if (c) wim[x][h] = v; else wre[x][h] = v;
                    }
                }
        }
        const uint32_t ca = warp < 8 ? sm + OFF_STAGE + lane * 128 + (warp ^ (lane & 7)) * 16 : sm + OFF_STX + lane * 32 + ((warp ^ g) & 1) * 16, cs = warp < 8 ? 4096 : 1024;
        uint32_t V[4][4];
        #pragma unroll 1
        for (int it = 0;; it++) {
            mbar_wait(bars + 8 * BAR_XB, it & 1);
            uint32_t ok = 1;
            if (warp < nw) {
                #pragma unroll
                for (int u = 0; u < 4; u++) { uint4 t4 = lds128(ca + u * cs); V[u][0] = t4.x; V[u][1] = t4.y; V[u][2] = t4.z; V[u][3] = t4.w; ok &= t4.x; }
            }
            asm volatile("{.reg .pred p; setp.ne.u32 p, %0, 0; bar.red.and.pred p, 1, 352, p; selp.u32 %0, 1, 0, p;}" : "+r"(ok) :: "memory");
            if (ok) break;
            if (warp == 10) { load_in(); hb(); }
            if (it > SPIN_LIMIT / 64) __trap();
        }
        PROF0(7);
        if (warp < nw) {
            uint32_t zr[4][2], zi[4][2];
            #pragma unroll
            for (int x = 0; x < 4; x++) {
                uint32_t er = 0, ei = 0, or_ = 0, oi = 0;
                mma_h(er, ei, tb[0], tb[1], tb[2], tb[3], V[0][x], V[1][x]);
                mma_h(or_, oi, tb[4], tb[5], tb[6], tb[7], V[2][x], V[3][x]);
                uint32_t r0 = hadd2(er, or_), r1 = hsub2(er, or_), i0 = hadd2(ei, oi), i1 = hsub2(ei, oi);
                cmul_neg(r0, i0, tb[8], tb[9]); cmul_neg(r1, i1, tb[10], tb[11]);
                uint32_t xr0 = 0, xr1 = 0, xi0 = 0, xi1 = 0;
                mma_h(xr0, xr1, r0, r1, i0, i1, tb[12], tb[13]);
                mma_h(xi0, xi1, r0, r1, i0, i1, tb[14], tb[15]);
                cmul_pos(xr0, xi0, wre[x][0], wim[x][0]); cmul_pos(xr1, xi1, wre[x][1], wim[x][1]);
                r0 = 0; i0 = 0; r1 = 0; i1 = 0;
                mma_h(r0, i0, tb[12], tb[13], tb[14], tb[15], xr0, xi0);
                mma_h(r1, i1, tb[12], tb[13], tb[14], tb[15], xr1, xi1);
                cmul_pos(r0, i0, tb[16], tb[17]); cmul_pos(r1, i1, tb[18], tb[19]);
                zr[x][0] = hadd2(r0, r1); zr[x][1] = hsub2(r0, r1); zi[x][0] = hadd2(i0, i1); zi[x][1] = hsub2(i0, i1);
            }
            #pragma unroll
            for (int nt = 0; nt < 4; nt++) {
                uint4 o = make_uint4(0, 0, 0, 0);
                const int h = nt >> 1;
                mma_h(o.x, o.y, zr[0][h], zr[1][h], zi[0][h], zi[1][h], tb[20 + 2 * nt], tb[21 + 2 * nt]);
                mma_h(o.z, o.w, zr[2][h], zr[3][h], zi[2][h], zi[3][h], tb[20 + 2 * nt], tb[21 + 2 * nt]);
                o.x &= ~1u;
                sts128(ca + nt * cs, o);
            }
        }
        fence_async_s();
        bar_sync(1, 352);
        t_st = clk32();
        PROF0(8);
        if (warp == 10 && elect()) {
            asm volatile("cp.async.bulk.tensor.2d.global.shared::cta.bulk_group [%0, {%2, %3}], [%1];" :: "l"(&tm_t), "r"(sm + OFF_STAGE), "r"(cm), "r"(0) : "memory");
            if (nw > 8) asm volatile("cp.async.bulk.tensor.2d.global.shared::cta.bulk_group [%0, {%2, %3}], [%1];" :: "l"(&tm_tx), "r"(sm + OFF_STX), "r"(cx), "r"(0) : "memory");
            asm volatile("cp.async.bulk.commit_group;" ::: "memory");
            asm volatile("cp.async.bulk.wait_group.read 0;" ::: "memory");
        }
        __syncwarp();
    }

    if (warp >= 10) { mbar_wait(bars + 8 * BAR_ROLE, 0); role = __shfl_sync(~0u, lds32(sm + OFF_MISC), 0); fence_async_s(); }
    auto first_a = [&]() {
        if (warp >= 10 && role < 64 && elect()) {
            const int it = warp - 10, hi = it >= 3; const bool p2 = it - 3 * hi == 2;
            tma4(sm + OFF_A + it * A_BYTES, p2 ? &tm_w1b : &tm_w1a, 0, 0, p2 ? 64 * rank + 8 * hi : 4 * (it - hi),
                 9 * (role >> 3) + (p2 ? 8 : (role & 4) + 2 * rank), bars + 8 * (BAR_FULL + it));
        }
        __syncwarp();
    };
    if (!rowcta) first_a();
    else {
        uint32_t tc[20], md[28];
        mbar_wait(bars + 8 * BAR_TAB2, 0);
        load_tab<5>(tc, sm + OFF_TAB + (QA + QB) * 512 + lane * 16);
        bool md_early = warp >= 10;
        if (md_early) { mbar_wait(bars + 8 * BAR_NC, 0); load_tab<7>(md, sm + OFF_MODC + lane * 16); }
        if (warp < 10) {
            uint32_t b3[16];
            load_tab<4>(b3, sm + OFF_B3 + 2048 + lane * 16);
            uint4 V[4], o[4];
            const bool tact = warp < 9 || g == 0;
            spin_until(t_st + X2D);
            #pragma unroll
            for (int u = 0; u < 4; u++) { V[u] = make_uint4(0, 0, 0, 0); if (tact) V[u] = ldx128(tptr + u * tstr); }
            md_early = __any_sync(~0u, mbar_test(bars + 8 * BAR_NC, 0));
            if (md_early) load_tab<7>(md, sm + OFF_MODC + lane * 16);
            #pragma unroll 1
            for (int it = 0; __any_sync(~0u, (V[0].x | V[1].x | V[2].x | V[3].x) & 1u); it++) {
                #pragma unroll
                for (int u = 0; u < 4; u++) if (V[u].x & 1u) V[u] = ldx128(tptr + u * tstr);
                hb();
                if (it > SPIN_LIMIT) __trap();
            }
            PROF0(10);
            radix16(V, b3, o);
            if (tact) {
                #pragma unroll
                for (int nt = 0; nt < 4; nt++) sts128(scol + nt * (16 * SPEC_P), o[nt]);
            }
        }
        __syncthreads();
        PROF0(11);
        first_a();
        const uint32_t srow = sm + OFF_SPEC + warp * (SPEC_P * 4);
        uint32_t re[2][3], im[2][3];
        #pragma unroll
        for (int mt = 0; mt < 3; mt++) {
            const uint32_t a = srow + (g + 72 * q + 8 * mt) * 4, a2 = srow + (288 - g - 72 * q - 8 * mt) * 4;
            const uint32_t z0 = lds32(a), z1 = lds32(a + 144), z2 = lds32(a2), z3 = lds32(a2 - 144);
            #pragma unroll
            for (int m2 = 0; m2 < 2; m2++) {
                re[m2][mt] = 0; im[m2][mt] = 0;
                const uint32_t sg = m2 ? 0x3C00BC00u : 0xBC003C00u;
                mma_h(re[m2][mt], im[m2][mt], tc[m2 * 4], tc[m2 * 4 + 1], tc[m2 * 4 + 2], tc[m2 * 4 + 3], hfma2(z2, sg, z0), hfma2(z3, sg, z1));
                cmul_pos(re[m2][mt], im[m2][mt], tc[8 + (m2 * 3 + mt) * 2], tc[9 + (m2 * 3 + mt) * 2]);
            }
        }
        float y[20];
        WG_FENCE();
        #pragma unroll
        for (int mt = 0; mt < 3; mt++)
            wgmma40_rs(y, re[0][mt], re[1][mt], im[0][mt], im[1][mt], desc_lo(OFF_TAB + (QA + QB + 5) * 512 + mt * 1280, 128), mt);
        WG_COMMIT();
        if (!md_early) { mbar_wait(bars + 8 * BAR_NC, 0); load_tab<7>(md, sm + OFF_MODC + lane * 16); }
        WG_WAIT(0);
        #pragma unroll
        for (int i = 0; i < 9; i++) xw[i] = bfma2(md[i], pack_bf(y[4 * (i >> 1) + (i & 1)], y[4 * (i >> 1) + 2 + (i & 1)]), xw[i]);
        float r, mr;
        ln_stats(xw, one, g, q, r, mr);
        uint32_t r2 = pack_bf(r, r), m2 = pack_bf(mr, mr);
        #pragma unroll
        for (int i = 0; i < 9; i++) {
            sts32(sm + OFF_X1 + warp * 1152 + (32 * i + 8 * q + g) * 4, xw[i]);
            xw[i] = bfma2(bfma2(xw[i], r2, m2), md[18 + i], md[9 + i]);
        }
        ln_stats(xw, one, g, q, r, mr);
        r2 = pack_bf(r, r); m2 = pack_bf(mr, mr);
        {
            const int n7 = 2 * q + (g >> 2);
            const uint32_t a = sm + OFF_STAGE + (warp >> 3) * 9216 + n7 * 128 + ((warp & 7) ^ n7) * 16 + (g & 3) * 4;
            #pragma unroll
            for (int i = 0; i < 9; i++) sts32(a + i * 1024, bfma2(xw[i], r2, m2));
        }
        fence_async_s();
        __syncthreads();
        PROF0(12);
        if (tid == 0) {
            asm volatile("cp.async.bulk.tensor.4d.global.shared::cta.bulk_group [%0, {%2, %2, %2, %3}], [%1];" :: "l"(&tm_h3s), "r"(sm + OFF_STAGE), "r"(0), "r"(b) : "memory");
            asm volatile("cp.async.bulk.commit_group;" ::: "memory");
        }
    }
    if (!rowcta) __syncthreads();
    else {
        if (tid == 0) { asm volatile("cp.async.bulk.wait_group 0;" ::: "memory"); fence_async_g(); red_release(g_cnt + CNT_H3 * 32); }
        PROF0(13);
        if (warp == 15) {
            __nanosleep(X1DELAY);
            #pragma unroll 1
            for (int r = 0; r < 16; r++) {
                if (lane == 0) asm volatile("cp.async.bulk.global.shared::cta.bulk_group [%0], [%1], 1152;" :: "l"(p.out + (size_t)(b + 128 * r) * D_), "r"(sm + OFF_X1 + r * 1152) : "memory");
                const uint32_t t1 = clk32();
                #pragma unroll 1
                while (__any_sync(~0u, (int)(clk32() - t1) < X1PACE)) __nanosleep(50);
            }
            if (lane == 0) {
                asm volatile("cp.async.bulk.commit_group;" ::: "memory");
                asm volatile("cp.async.bulk.wait_group 0;" ::: "memory");
                if (role < 64) mbar_arrive_remote(mapa(bars + 8 * BAR_HOLD, rank ^ 1));
                fence_async_g(); red_release(g_cnt + CNT_X1 * 32);
            }
        }
    }
    role = __shfl_sync(~0u, lds32(sm + OFF_MISC), 0);
    if ((sm & 0xFFFFFFu) != SM0) __trap();
    if (role >= 64) { if (warp == 0) PROFDUMP(); return; }

    const int gi = role >> 3, dt = role & 3, c2 = (role >> 2) & 1;
    const int wg = warp >> 2, wi = warp & 3;
    if (wg == 3) {
        uint32_t so = 0, eph = 1;
        #define RING_STEP(BYTES, OFF, ISSUE) do { \
            mbar_wait(bars + 8 * BAR_EMPTY + so, eph); \
            if (elect()) { const uint32_t fb = bars + 8 * BAR_FULL + so, dst = sm + (OFF) + so * ((BYTES) / 8); mbar_expect(fb, BYTES); ISSUE; } \
            so += 8; if (so == 8 * NST) { so = 0; eph ^= 1; } } while (0)
        const uint32_t kbm = warp == 12 ? 64 : 4 * B_BYTES, kba = warp == 12 ? 0 : dt * B_BYTES;
        const uint32_t kb0 = g2_kb(lane, rank, gi, c2) * kbm + kba, kb1 = g2_kb(32 + (lane & 3), rank, gi, c2) * kbm + kba;
        #define KB(n_) __shfl_sync(~0u, (n_) < 32 ? kb0 : kb1, (n_) & 31)
        if (warp == 12) {
            eph = 0;
            const int fb1 = 9 * gi + 4 * c2 + 2 * rank, sb2 = 4 * gi + 2 * c2;
            int pft = dt, pfj = 4 * (PF0 + PFS * dt);
            #pragma unroll 1
            for (int j = 16; j < 128; j += 4) {
                RING_STEP(A_BYTES, OFF_A, tma4(dst, &tm_w1a, 0, 0, j, fb1, fb));
                if (j < 64) { if (j & 4) RING_STEP(A_BYTES, OFF_A, tma4(dst, &tm_w1b, 0, 0, 64 * rank + j - 4, 9 * gi + 8, fb)); }
                if (RP1 && __any_sync(~0u, (j & 12) == 4 * dt && j + 4 * RP1 < 128) && elect())
                    asm volatile("cp.async.bulk.prefetch.tensor.4d.L2.global [%0, {%1, %1, %2, %3}];" :: "l"(&tm_w1a), "r"(0), "r"(j + 4 * RP1), "r"(fb1) : "memory");
                if (RPX && __any_sync(~0u, (j & 4) == 0 && j + 8 * RPX < 64 && ((j >> 3) & 7) == (role & 7)) && elect())
                    asm volatile("cp.async.bulk.prefetch.tensor.4d.L2.global [%0, {%1, %1, %2, %3}];" :: "l"(&tm_w1b), "r"(0), "r"(64 * (int)rank + j + 8 * RPX), "r"(9 * gi + 8) : "memory");
                if (__any_sync(~0u, j == pfj && pft < PFN)) {
                    const int kb = KB(pft); pft += 4; pfj += 16 * PFS;
                    if (elect()) asm volatile("cp.async.bulk.prefetch.tensor.3d.L2.global [%0, {%1, %2, %3}];" :: "l"(&tm_w2), "r"(0), "r"(kb), "r"(sb2) : "memory");
                }
            }
            #pragma unroll 1
            for (int n = 0; n < 36; n++) {
                const int kb = KB(n);
                RING_STEP(A_BYTES, OFF_A, tma3(dst, &tm_w2, 0, kb, sb2, fb));
            }
        } else if (warp == 13) {
            const uint32_t e1 = __shfl_sync(~0u, epoch + 1, 0);
            fence_async_s();
            if (lane == 0) mbar_expect(bars + 8 * BAR_FULL, B_BYTES);
            wait_count<0>(g_cnt + CNT_H3 * 32, e1 * 128); fence_async_g();
            if (elect()) tma3(sm + OFF_B, &tm_h3a, 0, 18 * dt, 0, bars + 8 * BAR_FULL);
            so = 8;
            if (lane == 0) PROFT(14);
            #pragma unroll 1
            for (int j = 4; j < 128; j += 4) {
                RING_STEP(B_BYTES, OFF_B, tma3(dst, &tm_h3a, 0, 18 * dt, j, fb));
                if (j < 64 && (j & 4)) RING_STEP(B_BYTES, OFF_B, tma3(dst, &tm_h3b, 0, 18 * dt + 9 * c2, 64 * rank + j - 4, fb));
            }
            mbar_wait(bars + 8 * BAR_UOK, 0); fence_async_g();
            if (lane == 0) PROFT(22);
            #pragma unroll 1
            for (int n = 0; n < 4; n++) { const uint32_t o = KB(n); RING_STEP(B_BYTES, OFF_B, bulk_load(dst, (const char*)g_U + o, B_BYTES, fb)); }
            {
                constexpr int S5 = (IT_G2 + 5) % NST; static_assert(S5 > 0 && S5 < NST - 1, "no wrap");
                const char* src = (const char*)g_U + KB(5);
                mbar_wait(bars + 8 * (BAR_EMPTY + S5), eph);
                if (lane == 0) mbar_expect(bars + 8 * (BAR_FULL + S5), B_BYTES);
                mbar_wait(bars + 8 * (BAR_UOK + 1), 0);
                wait_count<0>(g_cnt + (CNT_U + 8) * 32, e1 * 128); fence_async_g();
                if (elect()) bulk_load(sm + OFF_B + S5 * B_BYTES, src, B_BYTES, bars + 8 * (BAR_FULL + S5));
                so = 8 * (S5 + 1);
                if (lane == 0) PROFT(19);
            }
            #pragma unroll 1
            for (int n = 6; n < 36; n++) {
                const uint32_t o = KB(n);
                if (n == 21) { mbar_wait(bars + 8 * (BAR_UOK + 2), 0); fence_async_g(); }
                RING_STEP(B_BYTES, OFF_B, bulk_load(dst, (const char*)g_U + o, B_BYTES, fb));
            }
            if (role == 0 && rank == 0 && lane == 0) st_relaxed(g_cnt + CNT_EPOCH * 32, e1);
        } else if (warp == 15) {
            if (!rowcta && elect()) mbar_arrive_remote(mapa(bars + 8 * BAR_HOLD, rank ^ 1));
            __syncwarp();
            bar_sync(6, 160);
            if (elect()) mbar_arrive(bars + 8 * (BAR_FULL + (IT_G2 + 4) % NST));
            __syncwarp();
            mbar_wait(bars + 8 * BAR_W1GO, 0);
            if (elect()) {
                char* dst = (char*)(g_U + ((9 * gi + 4 * c2 + 2 * rank + 1) * 4 + dt) * 1152);
                #pragma unroll 1
                for (int i = 0; i < W1N; i++) {
                    asm volatile("cp.async.bulk.global.shared::cta.bulk_group [%0], [%1], %2;" :: "l"(dst + i * (18432 / W1N)), "r"(sm + OFF_X1 + i * (18432 / W1N)), "n"(18432 / W1N) : "memory");
                    const uint32_t t1 = clk32(); while ((int)(clk32() - t1) < W1P) {}
                }
                asm volatile("cp.async.bulk.commit_group;" ::: "memory");
                asm volatile("cp.async.bulk.wait_group 0;" ::: "memory");
                fence_async_g(); red_release(g_cnt + (CNT_U + 16) * 32);
                #pragma unroll 1
                for (int n = 0; n < 4; n++) { __nanosleep(300); tma2(sm + OFF_X1 + n * 4608, &tm_o, 144 * dt, 256 * gi + 128 * c2 + 64 * (rank ^ 1) + 16 * n, bars + 8 * BAR_XT); }
            }
        } else {
            const uint32_t e1 = epoch + 1;
            if (lane == 0) {
                __nanosleep(4000);
                wait_count<200>(g_cnt + CNT_NC * 32, e1 * 4); wait_count<200>(g_cnt + (CNT_NC + 1) * 32, e1 * 2);
                fence_async_g();
                mbar_expect(bars + 8 * BAR_GB, 1152);
                bulk_load(sm + OFF_GB, p.scr->modc + 896, 1152, bars + 8 * BAR_GB);
                wait_count<200>(g_cnt + CNT_X1 * 32, e1 * 128);
                if (role * 2 + rank < 108) {
                    uint4* z = (uint4*)p.scr->modc + (role * 2 + rank) * 2; z[0] = z[1] = make_uint4(0, 0, 0, 0);
                }
                wait_count<50>(g_cnt + (CNT_U + dt * 2 + rank) * 32, e1 * 16);
                mbar_arrive(bars + 8 * BAR_UOK);
            }
            __syncwarp();
            bar_sync(4, 160);
            if (lane == 0) {
                fence_async_g(); red_release(g_cnt + (CNT_U + 8) * 32);
                PROFT(17);
                mbar_arrive(bars + 8 * (BAR_UOK + 1));
                __nanosleep(2000);
                wait_count<100>(g_cnt + (CNT_U + 16) * 32, e1 * 128);
                mbar_arrive(bars + 8 * (BAR_UOK + 2));
            }
        }
    } else if (wg == 2) {
        float d0[36];
        const float bias = bf_lo(ldg_nc16(p.b1 + 576 * gi + 512 + 16 * wi + g + 8 * rank));
        #pragma unroll 1
        for (int it = 0; it < 200 && !__any_sync(~0u, mbar_test(bars + 8 * BAR_FULL, 0)); it++) { hb(); __nanosleep(100); }
        const bool lead = wi == 0 && elect();
        #pragma unroll 1
        for (int i = 0; i < 8; i++) {
            const uint32_t s = P2S + 3 * (i & 1);
            mbar_wait(bars + 8 * BAR_FULL + 8 * s, (i >> 1) & 1);
            const uint32_t da = desc_lo(OFF_A, 8192) + s * (A_BYTES / 16), db = desc_lo(OFF_B, 128) + s * (B_BYTES / 16);
            WG_FENCE();
            wgmma72(d0, da, db, i);
            #pragma unroll
            for (int k = 1; k < 9; k++) {
                if (k == P2K) asm volatile("{.reg .pred p; setp.ne.u32 p, %1, 0; @p mbarrier.arrive.shared::cta.b64 _, [%0];}" :: "r"(bars + 8 * (BAR_P2N + (i & 1))), "r"((uint32_t)lead) : "memory");
                if (k < 8) wgmma72(d0, da + k * 128, db + k * 144, 1);
            }
            WG_COMMIT();
            WG_WAIT(0);
            if (lead) mbar_arrive_n(bars + 8 * BAR_EMPTY + 8 * s, 2);
        }
        if (lead) PROFT(18);
        const uint32_t slot = sm + OFF_P2R + (tid & 127) * 16, ra = mapa(slot, rank ^ 1), rb = mapa(bars + 8 * BAR_P2R, rank ^ 1);
        float sv[18];
        #pragma unroll
        for (int i = 0; i < 18; i++) { const float lo = d0[4 * (i >> 1) + (i & 1)], hi = d0[4 * (i >> 1) + 2 + (i & 1)];
            sv[i] = rank ? lo : hi; d0[4 * (i >> 1) + (i & 1)] = (rank ? hi : lo) + bias; }
        mbar_wait(bars + 8 * BAR_HOLD, 0);
        #pragma unroll
        for (int i = 0; i < 4; i++)
            asm volatile("st.async.weak.shared::cluster.mbarrier::complete_tx::bytes.v4.f32 [%0], {%1,%2,%3,%4}, [%5];"
                :: "r"(ra + i * 2048), "f"(sv[4 * i]), "f"(sv[4 * i + 1]), "f"(sv[4 * i + 2]), "f"(sv[4 * i + 3]), "r"(rb) : "memory");
        asm volatile("st.async.weak.shared::cluster.mbarrier::complete_tx::bytes.v2.f32 [%0], {%1,%2}, [%3];" :: "r"(ra + 8192), "f"(sv[16]), "f"(sv[17]), "r"(rb) : "memory");
        mbar_wait(bars + 8 * BAR_P2R, 0);
        #pragma unroll
        for (int i = 0; i < 5; i++) {
            const uint4 v = lds128(slot + i * 2048);
            d0[8 * i] += __uint_as_float(v.x); d0[8 * i + 1] += __uint_as_float(v.y);
            if (i < 4) { d0[8 * i + 4] += __uint_as_float(v.z); d0[8 * i + 5] += __uint_as_float(v.w); }
        }
        asm volatile("bar.arrive 5, 256;" ::: "memory");
        gelu_store<0>(d0, (char*)(g_U + ((9 * gi + 8) * 4 + dt) * 1152) + wi * 4608 + rank * 2304 + c2 * 1152 + g * 16, q);
        bar_sync(8, 128);
        if (lead) { fence_async_g(); red_release(g_cnt + (CNT_U + dt * 2 + (gi >> 2)) * 32); PROFT(26); }
    } else {
        float d[72];
        const bool lead = wi == 0 && elect();
        const uint32_t da0 = desc_lo(OFF_A, 8192) + wg * 512;
        const bool owner = (uint32_t)wg == rank;
        const int srow = 256 * gi + 128 * c2 + 64 * wg + 16 * wi;
        const uint32_t b2w0 = ldg_nc16(p.b2 + srow + g), b2w1 = ldg_nc16(p.b2 + srow + g + 8);
        const int fr = 576 * gi + 256 * c2 + 128 * rank + 64 * wg + 16 * wi + g;
        const float bias0 = bf_lo(ldg_nc16(p.b1 + fr)), bias1 = bf_lo(ldg_nc16(p.b1 + fr + 8));
        {
            #pragma unroll
            for (int i = 0; i < 72; i++) d[i] = (i & 2) ? bias1 : bias0;
            constexpr uint32_t db1 = desc_lo(OFF_B, 128);
            static_assert(IT_G2 - LEAD1 == 6 * NST && IT_P1 == 4 * NST && P2S == 2, "loop structure");
            #define REL(s_) if (lead) mbar_arrive(bars + 8 * (BAR_EMPTY + (s_)))
            mma_block<DHI_H3, 0>(d, bars, da0, db1, 0);
            #pragma unroll 1
            for (int c = 0; c < 4; c++) {
                const uint32_t ph = c & 1;
                mma_block<DHI_H3, 1>(d, bars, da0, db1, ph); REL(0);
                mbar_wait(bars + 8 * (P2K ? BAR_P2N : BAR_FULL + 2), ph);
                mma_block<DHI_H3, 3>(d, bars, da0, db1, ph); REL(1);
                mma_block<DHI_H3, 4>(d, bars, da0, db1, ph); REL(3);
                mbar_wait(bars + 8 * (P2K ? BAR_P2N + 1 : BAR_FULL + 5), ph);
                mma_block<DHI_H3, 0>(d, bars, da0, db1, ph ^ 1); REL(4);
            }
            #pragma unroll 1
            for (uint32_t ph = 0; ph < 2; ph++) {
                mma_block<DHI_H3, 1>(d, bars, da0, db1, ph); REL(0);
                mma_block<DHI_H3, 2>(d, bars, da0, db1, ph); REL(1);
                mma_block<DHI_H3, 3>(d, bars, da0, db1, ph); REL(2);
                mma_block<DHI_H3, 4>(d, bars, da0, db1, ph); REL(3);
                mma_block<DHI_H3, 5>(d, bars, da0, db1, ph); REL(4);
                const bool pause = ph && wg == 1;
                if (pause) { WG_WAIT(0); REL(5); bar_sync(9, 256); }
                mma_block<DHI_H3, 0>(d, bars, da0, db1, ph ^ 1); if (!pause) REL(5);
            }
            #pragma unroll
            for (int i = IT_G2 - LEAD1 + 1; i < IT_G2; i++) {
                mbar_wait(bars + 8 * (BAR_FULL + i % NST), (i / NST) & 1);
                WG_FENCE();
                #pragma unroll
                for (int k = 0; k < 4; k++) {
                    if (i == IT_G2 - 1 && k == HOK1) WG_COMMIT();
                    wgmma144<DHI_H3>(d, da0 + (i % NST) * (A_BYTES / 16) + k * 128, db1 + (i % NST) * (B_BYTES / 16) + k * 288, 1);
                }
                WG_COMMIT();
                if (i == IT_G2 - 1 && HOK1 < 4) WG_WAIT(2); else WG_WAIT(1);
                REL((i - 1) % NST);
            }
            if (wg == 0) { WG_WAIT(1); asm volatile("bar.arrive 9, 256;" ::: "memory"); }
            WG_WAIT(0);
            if (lead) mbar_arrive(bars + 8 * (BAR_EMPTY + (IT_G2 - 1) % NST));
            PROF0(16);
            if (wg == 1) bar_sync(5, 256);
            char* const ub = (wg == 0 ? (char*)(g_U + ((9 * gi + 4 * c2 + 2 * rank) * 4 + dt) * 1152) : (char*)__cvta_shared_to_generic(sm + OFF_X1)) + wi * 4608 + g * 16;
            gelu_store<0>(d, ub, q); gelu_store<2>(d, ub + 2304, q); gelu_store<36>(d, ub + 1152, q); gelu_store<38>(d, ub + 3456, q);
            PROF0(27);
            if (wg == 0) asm volatile("bar.arrive 4, 160;" ::: "memory");
            else { fence_async_s(); asm volatile("bar.arrive 6, 160;" ::: "memory"); }
        }
        constexpr uint32_t db0 = desc_lo(OFF_B, 2304);
        const bool keep = role < 0;
        constexpr int IT_L = IT_END - NST;
        #pragma unroll
        for (int i = IT_G2; i <= IT_G2 + W1S; i++) {
            const uint32_t db = db0 + (i == IT_G2 + 4 ? OFF_X1 - OFF_B : (i % NST) * B_BYTES) / 16;
            mbar_wait(bars + 8 * (BAR_FULL + i % NST), (i / NST) & 1);
            WG_FENCE();
            #pragma unroll
            for (int k = 0; k < 4; k++) wgmma144<DHI_U>(d, da0 + (i % NST) * (A_BYTES / 16) + k * 128, db + k * 288, i > IT_G2 || k > 0 || keep);
            WG_COMMIT();
            if (i > IT_G2) { WG_WAIT(1); if (lead) mbar_arrive(bars + 8 * (BAR_EMPTY + (i - 1) % NST)); }
        }
        if (lead) mbar_arrive(bars + 8 * BAR_W1GO);
        const uint32_t ga0 = sm + OFF_GB + (144 * dt + 8 * q) * 2, tile = sm + OFF_X1 + wi * 4608, to = g * 288 + q * 16;
        #define QOFF(i_) (((i_) >> 2) * 2304 + 144 * (((i_) >> 1) & 1) + 64 * ((i_) & 1))
        #define SOFF(k_) (((k_) >> 1) * 2304 + 144 * ((k_) & 1) + 128 - 12 * q)
        #define DIDX(i_, k_) ((i_) < 8 ? 36 * (((i_) >> 1) & 1) + 16 * ((i_) & 1) + 4 * (k_) + 2 * ((i_) >> 2) : 36 * ((k_) & 1) + 32 + 2 * ((k_) >> 1))
        #define FIN(k_, f_) bfma2(g4.f_, pack_bf(d[DIDX(i, k_)], d[DIDX(i, k_) + 1]), xq[i].f_)
        uint4 xq[9];
        auto load_g = [&](int i) { uint4 r; if (i < 4) r = lds128(ga0 + QOFF(i)); else { r.x = r.z = lds32(ga0 + SOFF(0)); r.y = r.w = lds32(ga0 + SOFF(1)); } return r; };
        static_assert(W1S == 5 && (IT_G2 + 6) % NST == 4 && ((IT_G2 + 6) / NST) % 2 == 1 && IT_L == IT_G2 + 30, "loop structure");
        #pragma unroll 1
        for (int c = 0; c < 4; c++) {
            const uint32_t ph = c & 1, xa = tile + to; const bool xl = c == 3 && !owner;
            mma_block<DHI_U, 4>(d, bars, da0, db0, ph ^ 1); REL(3);
            mma_block<DHI_U, 5>(d, bars, da0, db0, ph ^ 1); REL(4);
            mma_block<DHI_U, 0>(d, bars, da0, db0, ph); REL(5);
            if (xl) { mbar_wait(bars + 8 * BAR_XT, 0); xq[0] = lds128(xa + QOFF(0)); xq[4] = lds128(xa + QOFF(4)); xq[1] = lds128(xa + QOFF(1)); }
            mma_block<DHI_U, 1>(d, bars, da0, db0, ph); REL(0);
            if (xl) { xq[5] = lds128(xa + QOFF(5)); xq[2] = lds128(xa + QOFF(2)); xq[6] = lds128(xa + QOFF(6)); }
            mma_block<DHI_U, 2>(d, bars, da0, db0, ph); REL(1);
            if (xl) { xq[3] = lds128(xa + QOFF(3)); xq[7] = lds128(xa + QOFF(7));
                      xq[8] = make_uint4(lds32(xa + SOFF(0)), lds32(xa + SOFF(1)), lds32(xa + SOFF(2)), lds32(xa + SOFF(3))); }
            mma_block<DHI_U, 3>(d, bars, da0, db0, ph); REL(2);
        }
        if (!owner && elect()) mbar_arrive_remote(mapa(bars + 8 * BAR_DONE, rank ^ 1));
        if (owner) { WG_WAIT(0); if (lead) mbar_arrive(bars + 8 * (BAR_EMPTY + (IT_L - 1) % NST)); bar_sync(7, 256); }
        #pragma unroll
        for (int i = IT_L; i < IT_END; i++) {
            mbar_wait(bars + 8 * (BAR_FULL + i % NST), (i / NST) & 1);
            WG_FENCE();
            #pragma unroll
            for (int k = 0; k < 4; k++) {
                if (i == IT_END - 1 && k == HOK) WG_COMMIT();
                wgmma144<DHI_U>(d, da0 + (i % NST) * (A_BYTES / 16) + k * 128, db0 + (i % NST) * (B_BYTES / 16) + k * 288, 1);
            }
            WG_COMMIT();
            if (i == IT_L) { WG_WAIT(1); if (lead && !owner) mbar_arrive(bars + 8 * (BAR_EMPTY + (IT_L - 1) % NST)); }
        }
        PROF0(9);
        mbar_wait(bars + 8 * BAR_GB, 0);
        if (!owner) {
            const uint32_t ra = mapa(tile + lane * 16, rank ^ 1), rb = mapa(bars + 8 * BAR_RECV, rank ^ 1);
            mbar_wait(bars + 8 * BAR_DONE, 0);
            uint4 gn = load_g(0);
            WG_WAIT(1);
            asm volatile("bar.arrive 7, 256;" ::: "memory");
            WG_WAIT(0);
            #pragma unroll
            for (int i = 0; i < 72; i++) d[i] = fmaf(bf_lo((i & 2) ? b2w1 : b2w0), 2.f, d[i]);
            #pragma unroll
            for (int j = 0; j < 5; j++) {
                const uint4 g4 = gn;
                if (j < 4) gn = load_g(j + 1);
                #pragma unroll
                for (int i = j < 4 ? j : 8; i < 9; i += 4) if (i < 8 || j == 4)
                    asm volatile("st.async.weak.shared::cluster.mbarrier::complete_tx::bytes.v4.b32 [%0], {%1,%2,%3,%4}, [%5];"
                        :: "r"(ra + i * 512), "r"(FIN(0, x)), "r"(FIN(1, y)), "r"(FIN(2, z)), "r"(FIN(3, w)), "r"(rb) : "memory");
            }
            PROF0(6);
            if (warp == 0) PROFDUMP();
            return;
        }
        PROF0(24);
        mbar_wait(bars + 8 * BAR_RECV, 0);
        #pragma unroll
        for (int i = 0; i < 9; i++) xq[i] = lds128(tile + lane * 16 + i * 512);
        uint4 gn = load_g(0);
        WG_WAIT(0);
        __syncwarp();
        PROF0(21);
        #pragma unroll
        for (int j = 0; j < 5; j++) {
            const uint4 g4 = gn;
            if (j < 4) gn = load_g(j + 1);
            #pragma unroll
            for (int i = j < 4 ? j : 8; i < 9; i += 4) if (i < 8 || j == 4) {
                const uint4 o = make_uint4(FIN(0, x), FIN(1, y), FIN(2, z), FIN(3, w));
                if (i < 8) sts128(tile + to + QOFF(i), o);
                else { sts32(tile + to + SOFF(0), o.x); sts32(tile + to + SOFF(1), o.y); sts32(tile + to + SOFF(2), o.z); sts32(tile + to + SOFF(3), o.w); }
            }
        }
        fence_async_s();
        __syncwarp();
        if (elect()) {
            asm volatile("cp.async.bulk.tensor.2d.global.shared::cta.bulk_group [%0, {%2, %3}], [%1];" :: "l"(&tm_o), "r"(tile), "r"(144 * dt), "r"(srow) : "memory");
            asm volatile("cp.async.bulk.commit_group;" ::: "memory");
            asm volatile("cp.async.bulk.wait_group.read 0;" ::: "memory");
        }
        PROF0(23);
        if (warp == 0) { __syncwarp(); PROFDUMP(); }
    }
}

typedef CUresult (*EncodeFn)(CUtensorMap*, CUtensorMapDataType, cuuint32_t, void*, const cuuint64_t*, const cuuint64_t*, const cuuint32_t*,
                             const cuuint32_t*, CUtensorMapInterleave, CUtensorMapSwizzle, CUtensorMapL2promotion, CUtensorMapFloatOOBfill);

void encode(EncodeFn fn, CUtensorMap* m, CUtensorMapDataType dt, int rank, const void* ptr, const cuuint64_t* dims, const cuuint64_t* strides,
            const cuuint32_t* box, CUtensorMapSwizzle sw, CUtensorMapL2promotion promo = CU_TENSOR_MAP_L2_PROMOTION_L2_128B) {
    const cuuint32_t es[5] = {1, 1, 1, 1, 1};
    fn(m, dt, rank, (void*)ptr, dims, strides, box, es, CU_TENSOR_MAP_INTERLEAVE_NONE, sw, promo, CU_TENSOR_MAP_FLOAT_OOB_FILL_NONE);
}

}

extern "C" void kernel_launch(void* const* d_in, const int* in_sizes, int n_in, void* d_out, int out_size) {
    (void)in_sizes; (void)n_in; (void)out_size;
    Params p;
    p.x = (const uint16_t*)d_in[0]; p.wr = (const uint16_t*)d_in[1]; p.wi = (const uint16_t*)d_in[2];
    p.w1 = (const uint16_t*)d_in[4]; p.b1 = (const uint16_t*)d_in[5]; p.w2 = (const uint16_t*)d_in[6]; p.b2 = (const uint16_t*)d_in[7];
    p.c = (const uint16_t*)d_in[8]; p.wmod = (const uint16_t*)d_in[9]; p.out = (uint16_t*)d_out;

    void* fnp = nullptr; cudaDriverEntryPointQueryResult qr;
    cudaGetDriverEntryPoint("cuTensorMapEncodeTiled", &fnp, cudaEnableDefault, &qr);
    EncodeFn fn = (EncodeFn)fnp;
    cudaGetSymbolAddress((void**)&p.scr, g_scr); cudaGetSymbolAddress((void**)&p.tab, g_tab);
    void* h3p = p.scr->h3;
    CUtensorMap tw1a, tw1b, tw2, th3a, th3b, twr, twi, twm, tt, ttx, to, th3s, tws;
    {
        const cuuint64_t dims[4] = {64, 16, 128, 72}, st[3] = {128ull * F_ * 2, (cuuint64_t)F_ * 2, 128};
        const cuuint32_t ba[4] = {64, 16, 4, 2}, bb[4] = {64, 16, 8, 1};
        encode(fn, &tw1a, CU_TENSOR_MAP_DATA_TYPE_BFLOAT16, 4, p.w1, dims, st, ba, CU_TENSOR_MAP_SWIZZLE_128B);
        encode(fn, &tw1b, CU_TENSOR_MAP_DATA_TYPE_BFLOAT16, 4, p.w1, dims, st, bb, CU_TENSOR_MAP_SWIZZLE_128B);
    }
    {
        const cuuint64_t dims[3] = {64, F_, 32}, st[2] = {(cuuint64_t)S_ * 2, 128};
        const cuuint32_t bx[3] = {64, 64, 2};
        encode(fn, &tw2, CU_TENSOR_MAP_DATA_TYPE_BFLOAT16, 3, p.w2, dims, st, bx, CU_TENSOR_MAP_SWIZZLE_128B);
    }
    {
        const cuuint64_t dims[3] = {64, 72, 128}, st[2] = {256, 18432};
        const cuuint32_t ba[3] = {64, 18, 4}, bb[3] = {64, 9, 8};
        encode(fn, &th3a, CU_TENSOR_MAP_DATA_TYPE_UINT32, 3, h3p, dims, st, ba, CU_TENSOR_MAP_SWIZZLE_NONE);
        encode(fn, &th3b, CU_TENSOR_MAP_DATA_TYPE_UINT32, 3, h3p, dims, st, bb, CU_TENSOR_MAP_SWIZZLE_NONE);
    }
    {
        const cuuint64_t dims[4] = {32, 72, 2, 128}, st[3] = {256, 128, 18432};
        const cuuint32_t bx[4] = {32, 72, 2, 1};
        encode(fn, &th3s, CU_TENSOR_MAP_DATA_TYPE_UINT32, 4, h3p, dims, st, bx, CU_TENSOR_MAP_SWIZZLE_128B, CU_TENSOR_MAP_L2_PROMOTION_NONE);
    }
    {
        const cuuint64_t dims[3] = {4624, 4, 32}, st[2] = {9248 * 32, 9248};
        const cuuint32_t bx[3] = {56, 4, 32};
        encode(fn, &twr, CU_TENSOR_MAP_DATA_TYPE_BFLOAT16, 3, p.wr, dims, st, bx, CU_TENSOR_MAP_SWIZZLE_NONE);
        encode(fn, &twi, CU_TENSOR_MAP_DATA_TYPE_BFLOAT16, 3, p.wi, dims, st, bx, CU_TENSOR_MAP_SWIZZLE_NONE);
    }
    {
        const cuuint64_t dims[2] = {3456, 576}, st[1] = {6912};
        const cuuint32_t bx[2] = {32, 144};
        encode(fn, &tws, CU_TENSOR_MAP_DATA_TYPE_BFLOAT16, 2, p.wmod, dims, st, bx, CU_TENSOR_MAP_SWIZZLE_64B);
    }
    {
        const cuuint64_t dims[3] = {64, 576, 54}, st[2] = {6912, 128};
        const cuuint32_t bx[3] = {64, 32, 7};
        encode(fn, &twm, CU_TENSOR_MAP_DATA_TYPE_BFLOAT16, 3, p.wmod, dims, st, bx, CU_TENSOR_MAP_SWIZZLE_128B);
    }
    {
        const cuuint64_t dims[2] = {TP, 128}, st[1] = {TP * 4};
        const cuuint32_t ba[2] = {32, 128}, bb[2] = {8, 128};
        encode(fn, &tt, CU_TENSOR_MAP_DATA_TYPE_UINT32, 2, p.scr->T, dims, st, ba, CU_TENSOR_MAP_SWIZZLE_128B, CU_TENSOR_MAP_L2_PROMOTION_NONE);
        encode(fn, &ttx, CU_TENSOR_MAP_DATA_TYPE_UINT32, 2, p.scr->T, dims, st, bb, CU_TENSOR_MAP_SWIZZLE_32B, CU_TENSOR_MAP_L2_PROMOTION_NONE);
    }
    {
        const cuuint64_t dims[2] = {D_, S_}, st[1] = {D_ * 2};
        const cuuint32_t bx[2] = {144, 16};
        encode(fn, &to, CU_TENSOR_MAP_DATA_TYPE_BFLOAT16, 2, p.out, dims, st, bx, CU_TENSOR_MAP_SWIZZLE_NONE, CU_TENSOR_MAP_L2_PROMOTION_NONE);
    }
    cudaFuncSetAttribute(fused_kernel, cudaFuncAttributeMaxDynamicSharedMemorySize, SMEM_BYTES);
    cudaLaunchConfig_t cfg = {};
    cfg.gridDim = dim3(NCTA); cfg.blockDim = dim3(NTHR); cfg.dynamicSmemBytes = SMEM_BYTES; cfg.stream = cudaStreamPerThread;
    cudaLaunchAttribute at[1];
    at[0].id = cudaLaunchAttributeClusterDimension; at[0].val.clusterDim.x = 2; at[0].val.clusterDim.y = 1; at[0].val.clusterDim.z = 1;
    cfg.attrs = at; cfg.numAttrs = 1;
    int nclusters = 0;
    cudaOccupancyMaxActiveClusters(&nclusters, fused_kernel, &cfg);
    at[0].id = cudaLaunchAttributeCooperative; at[0].val.cooperative = 1;
    cfg.numAttrs = nclusters * 2 >= NCTA ? 0 : 1;
    cudaLaunchKernelEx(&cfg, fused_kernel, p, tw1a, tw1b, tw2, th3a, th3b, twr, twi, twm, tt, ttx, to, th3s, tws);
}
```

```cpp
#include <cuda_runtime.h>
#include <cuda_bf16.h>
#include <cuda_fp16.h>
#include <cuda.h>
#include <stdint.h>

namespace {

constexpr int S_ = 2048, D_ = 576, F_ = 4608;
constexpr int NCTA = 132, NTHR = 512;
constexpr int TP = 4736;
constexpr int SPEC_P = 296;
constexpr int NST = 6;
constexpr int A_BYTES = 16384, B_BYTES = 18432;
constexpr int IT_P1 = 24, IT_G2 = 40, IT_END = 76;
constexpr int SPIN_LIMIT = 1 << 22;
#define X2D 1350
constexpr int P2S = 2;
#define LEAD1 4
#define W1N 8
#define W1P 100
#define W1S 5
#define XDELAY 1100
#define HOK 2
#define HOK1 2
#define NCP 11300
#define P2K 4
#define RP1 2
#define RPX 1
#define SLP 64
#define X1D 2100
#define PF0 4
#define PFS 3
#define PFN 9
#define X1DELAY 2000
#define X1PACE 400

constexpr int OFF_A = 0;
constexpr int OFF_B = NST * A_BYTES;
constexpr int OFF_P = OFF_B + NST * B_BYTES;
constexpr int OFF_BAR = OFF_P;
constexpr int OFF_EPOCH = OFF_P + 480;
constexpr int OFF_MISC = OFF_P + 496;
constexpr int OFF_GB = OFF_P + 512;
constexpr int OFF_P2R = OFF_P + 1664;
constexpr int OFF_X1 = OFF_P2R;
constexpr int OFF_PROF = OFF_X1 + 18432;
constexpr int SMEM_BYTES = OFF_PROF + 512;
constexpr int QA = 13, QB = 7, QC = 13;
constexpr int TAB_BYTES = (QA + QB + QC) * 512;
constexpr int OFF_STAGE = OFF_B;
constexpr int OFF_STX = OFF_STAGE + 16384;
constexpr int OFF_TAB = OFF_STAGE + 20480;
constexpr int OFF_SPEC = OFF_TAB + TAB_BYTES;
constexpr int OFF_WRAW = OFF_SPEC + 19072;
constexpr int OFF_B3 = OFF_WRAW + 28672;
constexpr int OFF_MODA = OFF_B3 + 4096;
constexpr int OFF_MODC = OFF_MODA + 2560;
constexpr int OFF_RED = OFF_MODC + 3584;
constexpr int OFF_HEXP = OFF_RED + 512;
constexpr int OFF_SILU = OFF_RED + 1536;
static_assert(OFF_SILU + 1152 <= OFF_P && 6 * 28672 <= OFF_B3, "scratch overflow");
constexpr int OFF_STRIP = OFF_A;
static_assert(OFF_WRAW % 128 == 0 && OFF_STAGE % 128 == 0 && OFF_STX % 128 == 0, "align");
constexpr int BAR_FULL = 0, BAR_EMPTY = 6, BAR_TAB = 12, BAR_W = 13, BAR_P2N = 14, BAR_P2R = 16,
              BAR_XT = 17, BAR_RECV = 18, BAR_ROLE = 19, BAR_NC = 20, BAR_TAB2 = 21, BAR_XB = 22, BAR_GB = 23, BAR_HOLD = 24, BAR_W1GO = 25, BAR_UOK = 26, BAR_DONE = 30, BAR_X = 31, BAR_ST = 47;

struct Cos1152 { double c[1152]; };
constexpr double cx_cos(double x) { double t = 1, s = 1; for (int i = 1; i < 14; i++) { t *= -x * x / ((2 * i - 1) * (2 * i)); s += t; } return s; }
constexpr Cos1152 make_cos() {
    Cos1152 r{};
    for (int i = 0; i <= 288; i++) {
        double v = (i == 288) ? 0.0 : cx_cos(3.14159265358979323846 * 2.0 * i / 1152.0);
        r.c[i] = v; r.c[576 - i] = -v; r.c[576 + i] = -v; r.c[(1152 - i) % 1152] = v;
    }
    return r;
}
constexpr uint32_t cx_f2h(double v) {
    uint32_t s = v < 0 ? 0x8000u : 0u; double a = v < 0 ? -v : v;
    if (a < 1e-9) return 0;
    int e = 0;
    while (a >= 2.0) { a *= 0.5; e++; }
    while (a < 1.0 && e > -14) { a *= 2.0; e--; }
    double m = a * 1024.0; uint32_t mi = (uint32_t)m; double fr = m - mi;
    if (fr > 0.5 || (fr == 0.5 && (mi & 1))) mi++;
    return s | (uint32_t)(((e + 14) << 10) + mi);
}
struct Tab { uint32_t w[(QA + QB + QC) * 128]; };
constexpr Tab make_tab() {
    Tab t{};
    Cos1152 ct = make_cos();
    auto C = [&](int num, int den) { return ct.c[(num % den) * (1152 / den)]; };
    auto Sn = [&](int num, int den) { return ct.c[((num % den) * (1152 / den) + 864) % 1152]; };
    auto put = [&](int q0, int idx, int lane, double lo, double hi) { t.w[((q0 + idx / 4) * 32 + lane) * 4 + idx % 4] = cx_f2h(lo) | (cx_f2h(hi) << 16); };
    for (int lane = 0; lane < 32; lane++) {
        const int g = lane >> 2, q = lane & 3;
        for (int mt = 0; mt < 3; mt++) {
            const int ka = 8 * mt + g;
            for (int r = 0; r < 10; r++) {
                const int im = r & 1, i0 = (r >> 1) * 2;
                double v[2] = {0, 0};
                for (int e = 0; e < 2; e++) { int i = i0 + e, d1 = 4 * i + q; if (i < 9 && ka <= 18) v[e] = (im ? -Sn(ka * d1, 36) : C(ka * d1, 36)) / 8; }
                put(0, r < 8 ? mt * 8 + r : 16 + 2 * mt + r, lane, v[0], v[1]);
            }
            for (int v = 0; v < 2; v++) {
                const int d2 = 4 * q + v;
                put(0, 30 + (mt * 2 + v) * 2, lane, C(ka * d2, 576) * 4 / 3, C(ka * (d2 + 2), 576) * 4 / 3);
                put(0, 31 + (mt * 2 + v) * 2, lane, Sn(ka * d2, 576) * 4 / 3, Sn(ka * (d2 + 2), 576) * 4 / 3);
            }
        }
        for (int v = 0; v < 2; v++) for (int nt = 0; nt < 2; nt++) {
            const int kb = 2 * (g >> 1) + nt, part = g & 1;
            double b0[2] = {0, 0}, b1[2] = {0, 0};
            for (int e = 0; e < 2; e++) { int d2 = 4 * q + 2 * e + v; double c = C(kb * d2, 16) / 4, s = Sn(kb * d2, 16) / 4;
                b0[e] = part ? -s : c; b1[e] = part ? c : s; }
            put(0, 42 + (v * 2 + nt) * 2, lane, b0[0], b0[1]); put(0, 43 + (v * 2 + nt) * 2, lane, b1[0], b1[1]);
        }
        t.w[((QA - 1) * 32 + lane) * 4 + 2] = 0x3F803F80u;
        for (int par = 0; par < 2; par++) for (int a = 0; a < 4; a++) {
            const int ja = 2 * (q + 4 * (a >> 1)) + par; const double c = C(g * ja, 16) / 4, s = Sn(g * ja, 16) / 4;
            put(QA, par * 4 + a, lane, (a & 1) ? -s : c, (a & 1) ? c : s);
        }
        for (int h = 0; h < 2; h++) {
            put(QA, 8 + 2 * h, lane, C((g + 8 * h) * (2 * q), 128) / 2, C((g + 8 * h) * (2 * q + 1), 128) / 2);
            put(QA, 9 + 2 * h, lane, Sn((g + 8 * h) * (2 * q), 128) / 2, Sn((g + 8 * h) * (2 * q + 1), 128) / 2);
            put(QA, 16 + 2 * h, lane, C(g * (8 * h + 2 * q), 128), C(g * (8 * h + 2 * q + 1), 128));
            put(QA, 17 + 2 * h, lane, Sn(g * (8 * h + 2 * q), 128), Sn(g * (8 * h + 2 * q + 1), 128));
        }
        put(QA, 12, lane, C(g * 2 * q, 8) / 2, C(g * (2 * q + 1), 8) / 2);
        put(QA, 15, lane, C(g * 2 * q, 8) / 2, C(g * (2 * q + 1), 8) / 2);
        put(QA, 13, lane, Sn(g * 2 * q, 8) / 2, Sn(g * (2 * q + 1), 8) / 2);
        put(QA, 14, lane, -Sn(g * 2 * q, 8) / 2, -Sn(g * (2 * q + 1), 8) / 2);
        for (int u = 0; u < 4; u++) {
            const int ja = 2 * ((g >> 1) + 4 * (u & 1)) + (u >> 1), part = g & 1; double b0[2] = {0, 0}, b1[2] = {0, 0};
            for (int e = 0; e < 2; e++) { int ka = 2 * q + e; double c = C(ja * ka, 16) / 4, s = Sn(ja * ka, 16) / 4;
                b0[e] = part ? s : c; b1[e] = part ? c : -s; }
            put(QA, 20 + u * 2, lane, b0[0], b0[1]); put(QA, 21 + u * 2, lane, b1[0], b1[1]);
        }
        for (int m2 = 0; m2 < 2; m2++) {
            const int d2 = 2 * g + m2;
            for (int a = 0; a < 4; a++) {
                const int kb = 2 * q + (a >> 1); const double c = C(d2 * kb, 16) / 4, s = Sn(d2 * kb, 16) / 4;
                put(QA + QB, m2 * 4 + a, lane, (a & 1) ? s : c, (a & 1) ? c : -s);
            }
            for (int mt = 0; mt < 3; mt++) {
                const int ka = 8 * mt + 2 * q;
                put(QA + QB, 8 + (m2 * 3 + mt) * 2, lane, C(ka * d2, 576) * 4 / 3, C((ka + 1) * d2, 576) * 4 / 3);
                put(QA + QB, 9 + (m2 * 3 + mt) * 2, lane, Sn(ka * d2, 576) * 4 / 3, Sn((ka + 1) * d2, 576) * 4 / 3);
            }
        }
        for (int mt = 0; mt < 3; mt++) for (int nt = 0; nt < 5; nt++) {
            const int i = 2 * nt + (g & 1), d1 = 4 * i + (g >> 1); double b0[2] = {0, 0}, b1[2] = {0, 0};
            for (int e = 0; e < 2; e++) { int ka = 8 * mt + 2 * q + e;
                if (ka <= 18 && i < 9) { double wt = (ka == 0 || ka == 18) ? 0.125 : 0.25; b0[e] = wt * C(ka * d1, 36); b1[e] = -wt * Sn(ka * d1, 36); } }
            const int o = (QA + QB + 5) * 128 + (mt * 5 + nt) * 64 + lane;
            t.w[o] = cx_f2h(b0[0]) | (cx_f2h(b0[1]) << 16); t.w[o + 32] = cx_f2h(b1[0]) | (cx_f2h(b1[1]) << 16);
        }
    }
    return t;
}
__device__ __align__(128) const Tab g_tab = make_tab();

struct Scratch {
    uint32_t cnt[30 * 32];
    uint32_t slot[96];
    uint32_t mod[2304];
    uint32_t modc[896 + 288];
    uint32_t T[128 * TP];
    uint4 h3[128 * 1152];
    uint4 U[72 * 4 * 1152];
};
__device__ __align__(1024) Scratch g_scr;
#define g_cnt (p.scr->cnt)
#define g_slot (p.scr->slot)
#define g_mod (p.scr->mod)
#define g_T (p.scr->T)
#define g_h3 (p.scr->h3)
#define g_U (p.scr->U)
constexpr int CNT_EPOCH = 0, CNT_H3 = 1, CNT_X1 = 26, CNT_NC = 27, CNT_U = 2;
#define PROFT(i) do {} while (0)
#define PROFDUMP() do {} while (0)
#define PROF0(i) do {} while (0)

__device__ __forceinline__ void mbar_init(uint32_t bar, uint32_t cnt) { asm volatile("mbarrier.init.shared::cta.b64 [%0], %1;" :: "r"(bar), "r"(cnt) : "memory"); }
__device__ __forceinline__ void mbar_expect(uint32_t bar, uint32_t bytes) { asm volatile("mbarrier.arrive.expect_tx.shared::cta.b64 _, [%0], %1;" :: "r"(bar), "r"(bytes) : "memory"); }
__device__ __forceinline__ void mbar_arrive(uint32_t bar) { asm volatile("mbarrier.arrive.shared::cta.b64 _, [%0];" :: "r"(bar) : "memory"); }
__device__ __forceinline__ void mbar_arrive_n(uint32_t bar, uint32_t n) { asm volatile("mbarrier.arrive.shared::cta.b64 _, [%0], %1;" :: "r"(bar), "r"(n) : "memory"); }
__device__ __forceinline__ void mbar_arrive_remote(uint32_t rbar) { asm volatile("mbarrier.arrive.relaxed.cluster.shared::cluster.b64 _, [%0];" :: "r"(rbar) : "memory"); }
__device__ __forceinline__ void mbar_wait(uint32_t bar, uint32_t parity) {
    asm volatile("{.reg .pred p; .reg .u32 c;\n"
        "mbarrier.try_wait.parity.shared::cta.b64 p, [%0], %1;\n@p bra.uni DONE;\nmov.u32 c, 0;\n"
        "LOOP: mbarrier.try_wait.parity.shared::cta.b64 p, [%0], %1;\n@p bra.uni DONE;\n"
        "add.u32 c, c, 1;\nsetp.lt.u32 p, c, %2;\n@p bra.uni LOOP;\ntrap;\nDONE:}" :: "r"(bar), "r"(parity), "n"(SPIN_LIMIT) : "memory");
}
__device__ __forceinline__ bool mbar_test(uint32_t bar, uint32_t parity) {
    uint32_t ok; asm volatile("{.reg .pred p; mbarrier.test_wait.parity.shared::cta.b64 p, [%1], %2; selp.u32 %0, 1, 0, p;}" : "=r"(ok) : "r"(bar), "r"(parity) : "memory"); return ok; }
__device__ __forceinline__ uint32_t mapa(uint32_t a, uint32_t rank) { uint32_t r; asm("mapa.shared::cluster.u32 %0, %1, %2;" : "=r"(r) : "r"(a), "r"(rank)); return r; }
__device__ __forceinline__ uint32_t clk32() { uint32_t r; asm volatile("mov.u32 %0, %%clock;" : "=r"(r)); return r; }
__device__ __forceinline__ void hb() {
    asm volatile("{.reg .b32 a, b; .reg .pred p; mma.sync.aligned.m16n8k8.row.col.f16.f16.f16.f16 {a, b}, {%0,%0}, {%0}, {%0,%0};\n"
                 "setp.ne.u32 p, a, 0; @p trap;}" :: "r"(0));
}
__device__ __forceinline__ void spin_until(uint32_t t) {
    #pragma unroll 1
    while (__any_sync(~0u, (int)(clk32() - t) < -SLP * 4)) { __nanosleep(SLP); hb(); }
    #pragma unroll 1
    while (__any_sync(~0u, (int)(clk32() - t) < 0)) {}
}
__device__ __forceinline__ bool elect() { uint32_t r; asm volatile("{.reg .pred p; elect.sync _|p, 0xffffffff; selp.u32 %0, 1, 0, p;}" : "=r"(r)); return r; }
__device__ __forceinline__ void bar_sync(int id, int n) { asm volatile("bar.sync %0, %1;" :: "r"(id), "r"(n) : "memory"); }
__device__ __forceinline__ void bulk_load(uint32_t dst, const void* src, uint32_t bytes, uint32_t bar) {
    asm volatile("cp.async.bulk.shared::cluster.global.mbarrier::complete_tx::bytes [%0], [%1], %2, [%3];" :: "r"(dst), "l"(src), "r"(bytes), "r"(bar) : "memory"); }
__device__ __forceinline__ void tma2(uint32_t dst, const CUtensorMap* m, int c0, int c1, uint32_t bar) {
    asm volatile("cp.async.bulk.tensor.2d.shared::cluster.global.mbarrier::complete_tx::bytes [%0], [%1, {%3, %4}], [%2];" :: "r"(dst), "l"(m), "r"(bar), "r"(c0), "r"(c1) : "memory"); }
__device__ __forceinline__ void tma3(uint32_t dst, const CUtensorMap* m, int c0, int c1, int c2, uint32_t bar) {
    asm volatile("cp.async.bulk.tensor.3d.shared::cluster.global.mbarrier::complete_tx::bytes [%0], [%1, {%3, %4, %5}], [%2];" :: "r"(dst), "l"(m), "r"(bar), "r"(c0), "r"(c1), "r"(c2) : "memory"); }
__device__ __forceinline__ void tma4(uint32_t dst, const CUtensorMap* m, int c0, int c1, int c2, int c3, uint32_t bar) {
    asm volatile("cp.async.bulk.tensor.4d.shared::cluster.global.mbarrier::complete_tx::bytes [%0], [%1, {%3, %4, %5, %6}], [%2];" :: "r"(dst), "l"(m), "r"(bar), "r"(c0), "r"(c1), "r"(c2), "r"(c3) : "memory"); }
__device__ __forceinline__ void fence_async_g() { asm volatile("fence.proxy.async.global;" ::: "memory"); }
__device__ __forceinline__ void fence_async_s() { asm volatile("fence.proxy.async.shared::cta;" ::: "memory"); }
__device__ __forceinline__ uint4 lds128(uint32_t a) { uint4 v; asm volatile("ld.shared.v4.u32 {%0,%1,%2,%3}, [%4];" : "=r"(v.x), "=r"(v.y), "=r"(v.z), "=r"(v.w) : "r"(a) : "memory"); return v; }
__device__ __forceinline__ uint32_t lds32(uint32_t a) { uint32_t v; asm volatile("ld.shared.u32 %0, [%1];" : "=r"(v) : "r"(a) : "memory"); return v; }
__device__ __forceinline__ void sts128(uint32_t a, uint4 v) { asm volatile("st.shared.v4.u32 [%0], {%1,%2,%3,%4};" :: "r"(a), "r"(v.x), "r"(v.y), "r"(v.z), "r"(v.w) : "memory"); }
__device__ __forceinline__ void sts32(uint32_t a, uint32_t v) { asm volatile("st.shared.u32 [%0], %1;" :: "r"(a), "r"(v) : "memory"); }
__device__ __forceinline__ void sts16(uint32_t a, uint32_t v) { asm volatile("st.shared.u16 [%0], %1;" :: "r"(a), "h"((uint16_t)v) : "memory"); }
__device__ __forceinline__ uint4 ldx128(const void* p) {
    uint4 v; asm volatile("{.reg .b128 t; .reg .b64 a, b; ld.relaxed.gpu.global.b128 t, [%4]; mov.b128 {a, b}, t; mov.b64 {%0,%1}, a; mov.b64 {%2,%3}, b;}"
        : "=r"(v.x), "=r"(v.y), "=r"(v.z), "=r"(v.w) : "l"(p) : "memory"); return v; }
__device__ __forceinline__ void stx128(void* p, uint4 v) {
    asm volatile("{.reg .b128 t; .reg .b64 a, b; mov.b64 a, {%1,%2}; mov.b64 b, {%3,%4}; mov.b128 t, {a, b}; st.relaxed.gpu.global.b128 [%0], t;}"
        :: "l"(p), "r"(v.x), "r"(v.y), "r"(v.z), "r"(v.w) : "memory"); }
__device__ __forceinline__ uint32_t ld_acquire(const uint32_t* p) { uint32_t v; asm volatile("ld.acquire.gpu.global.u32 %0, [%1];" : "=r"(v) : "l"(p) : "memory"); return v; }
__device__ __forceinline__ void st_relaxed(uint32_t* p, uint32_t v) { asm volatile("st.relaxed.gpu.global.u32 [%0], %1;" :: "l"(p), "r"(v) : "memory"); }
__device__ __forceinline__ void red_release(uint32_t* p) { asm volatile("red.release.gpu.global.add.u32 [%0], 1;" :: "l"(p) : "memory"); }
template <int SLEEP> __device__ __forceinline__ void wait_count(const uint32_t* p, uint32_t target) {
    int it = 0; while ((int)(ld_acquire(p) - target) < 0) { if (SLEEP) __nanosleep(SLEEP); if (++it > SPIN_LIMIT) __trap(); }
}
__device__ __forceinline__ uint32_t ldg_nc32(const void* p) { uint32_t v; asm volatile("ld.global.nc.L1::no_allocate.u32 %0, [%1];" : "=r"(v) : "l"(p)); return v; }
__device__ __forceinline__ uint32_t ldg_nc16(const void* p) { uint16_t v; asm volatile("ld.global.nc.u16 %0, [%1];" : "=h"(v) : "l"(p)); return v; }
__device__ __forceinline__ float bf_lo(uint32_t w) { return __uint_as_float(w << 16); }
__device__ __forceinline__ float bf_hi(uint32_t w) { return __uint_as_float(w & 0xFFFF0000u); }
__device__ __forceinline__ uint32_t pack_bf(float lo, float hi) { uint32_t r; asm("cvt.rn.bf16x2.f32 %0, %1, %2;" : "=r"(r) : "f"(hi), "f"(lo)); return r; }
__device__ __forceinline__ uint32_t pack_h(float lo, float hi) { uint32_t r; asm("cvt.rn.f16x2.f32 %0, %1, %2;" : "=r"(r) : "f"(hi), "f"(lo)); return r; }
__device__ __forceinline__ float bf_round(float v) { return bf_lo(pack_bf(v, 0.f)); }
__device__ __forceinline__ uint32_t hmul2(uint32_t a, uint32_t b) { uint32_t r; asm("mul.rn.f16x2 %0, %1, %2;" : "=r"(r) : "r"(a), "r"(b)); return r; }
__device__ __forceinline__ uint32_t hfma2(uint32_t a, uint32_t b, uint32_t c) { uint32_t r; asm("fma.rn.f16x2 %0, %1, %2, %3;" : "=r"(r) : "r"(a), "r"(b), "r"(c)); return r; }
__device__ __forceinline__ uint32_t hfms2(uint32_t a, uint32_t b, uint32_t c) { uint32_t r; asm("{.reg .b32 t; neg.f16x2 t, %3; fma.rn.f16x2 %0, %1, %2, t;}" : "=r"(r) : "r"(a), "r"(b), "r"(c)); return r; }
__device__ __forceinline__ uint32_t hadd2(uint32_t a, uint32_t b) { uint32_t r; asm("add.rn.f16x2 %0, %1, %2;" : "=r"(r) : "r"(a), "r"(b)); return r; }
__device__ __forceinline__ uint32_t hsub2(uint32_t a, uint32_t b) { uint32_t r; asm("sub.rn.f16x2 %0, %1, %2;" : "=r"(r) : "r"(a), "r"(b)); return r; }
__device__ __forceinline__ void cmul_neg(uint32_t& re, uint32_t& im, uint32_t c, uint32_t s) { uint32_t a = hfma2(re, c, hmul2(im, s)), b = hfms2(im, c, hmul2(re, s)); re = a; im = b; }
__device__ __forceinline__ void cmul_pos(uint32_t& re, uint32_t& im, uint32_t c, uint32_t s) { uint32_t a = hfms2(re, c, hmul2(im, s)), b = hfma2(im, c, hmul2(re, s)); re = a; im = b; }
__device__ __forceinline__ void mma_h(uint32_t& d0, uint32_t& d1, uint32_t a0, uint32_t a1, uint32_t a2, uint32_t a3, uint32_t b0, uint32_t b1) {
    asm("mma.sync.aligned.m16n8k16.row.col.f16.f16.f16.f16 {%0,%1}, {%2,%3,%4,%5}, {%6,%7}, {%0,%1};" : "+r"(d0), "+r"(d1) : "r"(a0), "r"(a1), "r"(a2), "r"(a3), "r"(b0), "r"(b1)); }
__device__ __forceinline__ void mma_h8(uint32_t& d0, uint32_t& d1, uint32_t a0, uint32_t a1, uint32_t b0) {
    asm("mma.sync.aligned.m16n8k8.row.col.f16.f16.f16.f16 {%0,%1}, {%2,%3}, {%4}, {%0,%1};" : "+r"(d0), "+r"(d1) : "r"(a0), "r"(a1), "r"(b0)); }
template <int NQ> __device__ __forceinline__ void load_tab(uint32_t (&r)[NQ * 4], uint32_t addr) {
    #pragma unroll
    for (int i = 0; i < NQ; i++) { uint4 v = lds128(addr + i * 512); r[4 * i] = v.x; r[4 * i + 1] = v.y; r[4 * i + 2] = v.z; r[4 * i + 3] = v.w; }
}
__device__ __forceinline__ float gelu2(float x) {
    float t = x * fmaf(x * x, 0.044715f * 0.7978845608028654f, 0.7978845608028654f), th;
    asm volatile("tanh.approx.f32 %0, %1;" : "=f"(th) : "f"(t));
    return fmaf(x, th, x);
}
constexpr uint32_t SM0 = 1024;
__device__ __forceinline__ constexpr uint32_t desc_lo(uint32_t off, uint32_t lbo) { return ((SM0 + off) >> 4) | ((lbo >> 4) << 16); }
constexpr uint32_t DHI_A = (1024 >> 4) | (1u << 30), DHI_H3 = 256 >> 4, DHI_U = 128 >> 4;
#define WG_FENCE() asm volatile("wgmma.fence.sync.aligned;" ::: "memory")
#define WG_COMMIT() asm volatile("wgmma.commit_group.sync.aligned;" ::: "memory")
#define WG_WAIT(n) asm volatile("wgmma.wait_group.sync.aligned %0;" :: "n"(n) : "memory")
#define R4(b) "+f"(d[b]), "+f"(d[b + 1]), "+f"(d[b + 2]), "+f"(d[b + 3])
#define R12(b) R4(b), R4(b + 4), R4(b + 8)
#define R36(b) R12(b), R12(b + 12), R12(b + 24)
template <uint32_t BHI> __device__ __forceinline__ void wgmma144(float (&d)[72], uint32_t da, uint32_t db, int acc) {
    asm volatile("{.reg .pred p; .reg .b64 a, b; setp.ne.b32 p, %74, 0; mov.b64 a, {%72, %75}; mov.b64 b, {%73, %76};\n"
        "wgmma.mma_async.sync.aligned.m64n144k16.f32.bf16.bf16 {%0,%1,%2,%3,%4,%5,%6,%7,%8,%9,%10,%11,%12,%13,%14,%15,%16,%17,%18,%19,%20,%21,%22,%23,"
        "%24,%25,%26,%27,%28,%29,%30,%31,%32,%33,%34,%35,%36,%37,%38,%39,%40,%41,%42,%43,%44,%45,%46,%47,"
        "%48,%49,%50,%51,%52,%53,%54,%55,%56,%57,%58,%59,%60,%61,%62,%63,%64,%65,%66,%67,%68,%69,%70,%71}, a, b, p, 1, 1, 1, 1;}\n"
        : R36(0), R36(36) : "r"(da), "r"(db), "r"(acc), "n"(DHI_A), "n"(BHI));
}
__device__ __forceinline__ void wgmma40_rs(float (&d)[20], uint32_t a0, uint32_t a1, uint32_t a2, uint32_t a3, uint32_t db, int acc) {
    asm volatile("{.reg .pred p; .reg .b64 b; setp.ne.b32 p, %25, 0; mov.b64 b, {%24, %26};\n"
        "wgmma.mma_async.sync.aligned.m64n40k16.f32.f16.f16 {%0,%1,%2,%3,%4,%5,%6,%7,%8,%9,%10,%11,%12,%13,%14,%15,%16,%17,%18,%19}, {%20,%21,%22,%23}, b, p, 1, 1, 0;}\n"
        : R12(0), R4(12), R4(16) : "r"(a0), "r"(a1), "r"(a2), "r"(a3), "r"(db), "r"(acc), "n"(DHI_H3));
}
__device__ __forceinline__ void wgmma72(float (&d)[36], uint32_t da, uint32_t db, int acc) {
    asm volatile("{.reg .pred p; .reg .b64 a, b; setp.ne.b32 p, %38, 0; mov.b64 a, {%36, %39}; mov.b64 b, {%37, %40};\n"
        "wgmma.mma_async.sync.aligned.m64n72k16.f32.bf16.bf16 {%0,%1,%2,%3,%4,%5,%6,%7,%8,%9,%10,%11,%12,%13,%14,%15,%16,%17,%18,%19,%20,%21,%22,%23,"
        "%24,%25,%26,%27,%28,%29,%30,%31,%32,%33,%34,%35}, a, b, p, 1, 1, 1, 1;}\n"
        : R36(0) : "r"(da), "r"(db), "r"(acc), "n"(DHI_A), "n"(DHI_H3));
}

__device__ __forceinline__ int g2_kb(int n, int kh, int gi, int c2) {
    if (n < 4) return 36 * kh + 9 * n + 8;
    if (n == 4) return 9 * gi + 4 * c2 + 2 * kh + 1;
    const int w = n > 20, m = n - (w ? 19 : 5);
    return 9 * ((gi * w + (m >> 1)) & 7) + 4 * (n == 35 ? 1 - c2 : m & 1) + 2 * kh + w;
}

template <uint32_t BHI, int S> __device__ __forceinline__ void mma_block(float (&d)[72], uint32_t bars, uint32_t da0, uint32_t db0, uint32_t ph) {
    mbar_wait(bars + 8 * (BAR_FULL + S), ph);
    WG_FENCE();
    #pragma unroll
    for (int k = 0; k < 4; k++) wgmma144<BHI>(d, da0 + S * (A_BYTES / 16) + k * 128, db0 + S * (B_BYTES / 16) + k * 288, 1);
    WG_COMMIT();
    WG_WAIT(1);
}

struct Params {
    const uint16_t *wmod, *c, *x;
    Scratch* scr;
    const Tab* tab;
    const uint16_t *wr, *wi, *w1, *b1, *w2, *b2;
    uint16_t* out;
};

__device__ __forceinline__ void mma_bf(float (&d)[4], const uint32_t (&a)[4], uint32_t b0, uint32_t b1) {
    asm("mma.sync.aligned.m16n8k16.row.col.f32.bf16.bf16.f32 {%0,%1,%2,%3}, {%4,%5,%6,%7}, {%8,%9}, {%0,%1,%2,%3};"
        : "+f"(d[0]), "+f"(d[1]), "+f"(d[2]), "+f"(d[3]) : "r"(a[0]), "r"(a[1]), "r"(a[2]), "r"(a[3]), "r"(b0), "r"(b1)); }
__device__ __forceinline__ void ldsm4t(uint32_t (&a)[4], uint32_t addr) {
    asm volatile("ldmatrix.sync.aligned.m8n8.x4.trans.shared.b16 {%0,%1,%2,%3}, [%4];" : "=r"(a[0]), "=r"(a[1]), "=r"(a[2]), "=r"(a[3]) : "r"(addr) : "memory"); }
__device__ __forceinline__ void ln_stats(const uint32_t (&w)[9], const uint32_t (&one)[9], int g, int q, float& r, float& mr) {
    float c[2][4] = {};
    #pragma unroll
    for (int p = 0; p < 9; p++)
        asm("mma.sync.aligned.m16n8k8.row.col.f32.bf16.bf16.f32 {%0,%1,%2,%3}, {%4,%5}, {%4}, {%0,%1,%2,%3};"
            : "+f"(c[p & 1][0]), "+f"(c[p & 1][1]), "+f"(c[p & 1][2]), "+f"(c[p & 1][3]) : "r"(w[p]), "r"(one[p]));
    const float t = (g & 1) ? c[0][1] + c[1][1] : c[0][0] + c[1][0];
    float s1 = (c[0][2] + c[1][2]) + (c[0][3] + c[1][3]), s2 = __shfl_sync(~0u, t, 9 * q) + __shfl_sync(~0u, t, 9 * q + 4);
    #pragma unroll
    for (int o = 1; o < 4; o <<= 1) { s1 += __shfl_xor_sync(~0u, s1, o); s2 += __shfl_xor_sync(~0u, s2, o); }
    const float m = s1 * (1.f / D_);
    asm("rsqrt.approx.ftz.f32 %0, %1;" : "=f"(r) : "f"(fmaxf(fmaf(s2, 1.f / D_, -m * m), 0.f) + 1e-5f));
    mr = -m * r;
}
__device__ __forceinline__ float silu(float v) { return __fdividef(v, 1.f + __expf(-v)); }
__device__ __forceinline__ uint32_t bfma2(uint32_t a, uint32_t b, uint32_t c) { uint32_t r; asm("fma.rn.bf16x2 %0, %1, %2, %3;" : "=r"(r) : "r"(a), "r"(b), "r"(c)); return r; }
__device__ __forceinline__ void radix16(const uint4 (&V)[4], const uint32_t (&B)[16], uint4 (&o)[4]) {
    #pragma unroll
    for (int nt = 0; nt < 4; nt++) o[nt] = make_uint4(0, 0, 0, 0);
    #pragma unroll
    for (int u = 0; u < 4; u++)
        #pragma unroll
        for (int nt = 0; nt < 4; nt++) {
            const uint32_t b = B[((u >> 1) * 4 + nt) * 2 + (u & 1)];
            mma_h8(o[nt].x, o[nt].y, V[u].x, V[u].y, b); mma_h8(o[nt].z, o[nt].w, V[u].z, V[u].w, b);
        }
}
template <int OFF, int N> __device__ __forceinline__ void gelu_store(const float (&d)[N], char* p, int q) {
    uint32_t w[9];
    #pragma unroll
    for (int blk = 0; blk < 9; blk++) w[blk] = pack_bf(gelu2(d[OFF + 4 * blk]), gelu2(d[OFF + 4 * blk + 1]));
    asm volatile("st.v4.u32 [%0], {%1,%2,%3,%4};" :: "l"(p + q * 128), "r"(w[0]), "r"(w[1]), "r"(w[2]), "r"(w[3]) : "memory");
    asm volatile("st.v4.u32 [%0+512], {%1,%2,%3,%4};" :: "l"(p + q * 128), "r"(w[4]), "r"(w[5]), "r"(w[6]), "r"(w[7]) : "memory");
    asm volatile("st.u32 [%0+1024], %1;" :: "l"(p + q * 4), "r"(w[8]) : "memory");
}

__global__ void __cluster_dims__(2, 1, 1) __launch_bounds__(NTHR, 1)
fused_kernel(const Params p,
             const __grid_constant__ CUtensorMap tm_w1a, const __grid_constant__ CUtensorMap tm_w1b, const __grid_constant__ CUtensorMap tm_w2,
             const __grid_constant__ CUtensorMap tm_h3a, const __grid_constant__ CUtensorMap tm_h3b,
             const __grid_constant__ CUtensorMap tm_wr, const __grid_constant__ CUtensorMap tm_wi, const __grid_constant__ CUtensorMap tm_wm,
             const __grid_constant__ CUtensorMap tm_t, const __grid_constant__ CUtensorMap tm_tx, const __grid_constant__ CUtensorMap tm_o,
             const __grid_constant__ CUtensorMap tm_h3s, const __grid_constant__ CUtensorMap tm_ws)
{
    extern __shared__ __align__(1024) char smem_raw[];
    const uint32_t t0 = clk32();
    const uint32_t sm = __shfl_sync(~0u, ((uint32_t)__cvta_generic_to_shared(smem_raw) + 1023u) & ~1023u, 0);
    const int tid = threadIdx.x, warp = __shfl_sync(~0u, tid >> 5, 0), lane = tid & 31, g = lane >> 2, q = lane & 3;
    const int b = blockIdx.x;
    const uint32_t rank = b & 1;
    const uint32_t bars = sm + OFF_BAR;
    const bool rowcta = b < 128;

    auto nc_issue = [&](int st, uint32_t sl) {
        const int pass = st >= 18;
        mbar_expect(bars + 8 * (BAR_X + sl), 28672);
        tma3(sm + sl * 28672, &tm_wm, 0, 32 * (st - 18 * pass), 18 + 28 * pass + 7 * (b - 128), bars + 8 * (BAR_X + sl));
    };
    uint32_t epoch;
    const bool strip = b < 72 && !(b & 1);
    const bool sil = (warp >> 2) == 2 && lane < 24 && (strip || !rowcta);
    uint32_t cw[3];
    if (elect()) {
        mbar_init(bars + 8 * (BAR_X + warp), rowcta || warp < 6 ? 1 : 14);
        if (warp >= 12) {
            if (strip) { const uint32_t sb = bars + 8 * (BAR_ST + warp - 12);
                mbar_init(sb, 1); mbar_expect(sb, 9216); tma2(sm + OFF_STRIP + (warp - 12) * 9216, &tm_ws, 16 * b, 144 * (warp - 12), sb); }
        } else if (warp == 7) {
            mbar_init(bars + 8 * BAR_TAB, 1); mbar_expect(bars + 8 * BAR_TAB, rowcta ? QA * 512 + 16 : 16);
            bulk_load(sm + OFF_EPOCH, g_cnt + CNT_EPOCH * 32, 16, bars + 8 * BAR_TAB);
            if (rowcta) bulk_load(sm + OFF_TAB, p.tab, QA * 512, bars + 8 * BAR_TAB);
        } else if (b + 132 * warp < 576) {
            asm volatile("cp.async.bulk.prefetch.L2.global [%0], 2304;" :: "l"(p.wmod + (b + 132 * warp) * 3456) : "memory");
        }
    }
    if (sil) {
        #pragma unroll
        for (int u = 0; u < 3; u++) cw[u] = ldg_nc32(p.c + 144 * (warp - 8) + 48 * u + 2 * lane);
    }
    if (warp == 6) hb();
    __syncthreads();
    if (!rowcta) { if (warp < 6 && elect()) nc_issue(warp, warp); }
    if (warp == 5 || warp == 6) {
        if (elect()) {
            if (warp == 5) {
                for (int i = BAR_W; i < BAR_X; i++) mbar_init(bars + 8 * i, i == BAR_DONE || i == BAR_NC ? 4 : i == BAR_W1GO ? 2 : 1);
                mbar_expect(bars + 8 * BAR_W, 28672); mbar_expect(bars + 8 * BAR_TAB2, (QB + QC) * 512);
                mbar_expect(bars + 8 * BAR_ROLE, 4); mbar_expect(bars + 8 * BAR_P2R, 9216); mbar_expect(bars + 8 * BAR_RECV, 18432); mbar_expect(bars + 8 * BAR_XT, 18432);
            } else {
                for (int i = 0; i < 2 * NST; i++) mbar_init(bars + 8 * i, 2);
                for (int i = 0; i < NST; i++) mbar_expect(bars + 8 * (BAR_FULL + i), A_BYTES);
            }
            asm volatile("fence.mbarrier_init.release.cluster;" ::: "memory");
        }
    } else if (warp >= 12 && elect())
        asm volatile("prefetch.tensormap [%0];" :: "l"(warp == 12 ? &tm_wr : warp == 13 ? &tm_wi : warp == 14 ? &tm_t : &tm_tx) : "memory");
    uint32_t sb[18];
    if ((warp >> 2) == 2) {
        if (sil) {
            #pragma unroll
            for (int u = 0; u < 3; u++) sts32(sm + OFF_SILU + (72 * (warp - 8) + 24 * u + lane) * 4, pack_bf(silu(bf_lo(cw[u])), silu(bf_hi(cw[u]))));
        }
        __syncwarp();
        if (strip) {
            #pragma unroll
            for (int u = 0; u < 18; u++) sb[u] = lds32(sm + OFF_SILU + (72 * (warp - 8) + 4 * u + q) * 4);
        }
    }
    if (rowcta && elect()) {
        if (XDELAY) while ((int)(clk32() - t0) < XDELAY) {}
        mbar_expect(bars + 8 * (BAR_X + warp), 1152);
        bulk_load(sm + OFF_STAGE + warp * 1152, p.x + (size_t)(b + 128 * warp) * D_, 1152, bars + 8 * (BAR_X + warp));
    }
    __syncwarp();
    hb();

    const int trow = 4 * (b & 7) + ((b >> 4) & 3) + 64 * ((b >> 3) & 1) + 32 * (b >> 6);
    uint32_t* const tptr = g_T + (size_t)trow * TP + (warp < 9 ? q * 288 + 32 * warp : 4608 + 8 * q) + 4 * g;
    const int tstr = warp < 9 ? 1152 : 32;
    const uint32_t scol = sm + OFF_SPEC + (q * SPEC_P + (warp < 8 ? 72 * (warp >> 1) + 40 * (warp & 1) + 4 * g : warp == 8 ? 72 * (g >> 1) + 32 + 4 * (g & 1) : 288 + 4 * g)) * 4;
    const int wc0 = (b >> 3) * 289 + 72 * ((b & 7) >> 1) + 40 * (b & 1);

    uint32_t xw[9], one[9], t_st = t0, hexp = 0;
    if (!rowcta) {
        const int nst = b < 130 ? 36 : 18;
        __syncthreads();
        asm volatile("barrier.cluster.arrive.relaxed.aligned;" ::: "memory");
        mbar_wait(bars + 8 * BAR_TAB, 0);
        epoch = lds32(sm + OFF_EPOCH);
        if (warp == 14) {
            uint32_t sl = 0, ph = 0;
            #pragma unroll 1
            for (int st = 6; st < nst; st++) {
                mbar_wait(bars + 8 * (BAR_X + 6 + sl), ph);
                if (elect()) nc_issue(st, sl);
                if (++sl == 6) { sl = 0; ph ^= 1; }
            }
        } else if (warp < 14) {
            uint32_t sl = 0, ph = 0;
            const uint32_t ad0 = sm + (warp >> 1) * 4096 + ((lane & 7) + 8 * (lane >> 4)) * 128, ch = (warp & 1) * 4 + ((lane >> 3) & 1);
            #pragma unroll 1
            for (int pass = 0; pass * 18 < nst; pass++) {
                float acc[2][4] = {};
                #pragma unroll 1
                for (int st = 0; st < 18; st++) {
                    const uint32_t sa = sm + OFF_SILU + (16 * st + q) * 4;
                    const uint32_t b0 = lds32(sa), b1 = lds32(sa + 16), b2 = lds32(sa + 32), b3 = lds32(sa + 48);
                    mbar_wait(bars + 8 * (BAR_X + sl), ph);
                    #pragma unroll
                    for (int m = 0; m < 2; m++) {
                        uint32_t a[4], a2[4];
                        const uint32_t ad = ad0 + sl * 28672 + ((ch + 2 * m) ^ (lane & 7)) * 16;
                        ldsm4t(a, ad); ldsm4t(a2, ad + 2048);
                        mma_bf(acc[m], a, b0, b1); mma_bf(acc[m], a2, b2, b3);
                    }
                    if (elect()) mbar_arrive(bars + 8 * (BAR_X + 6 + sl));
                    if (++sl == 6) { sl = 0; ph ^= 1; }
                }
                const int cb = 28 * pass + 7 * (b - 128) + (warp >> 1), gg = (g >> 1) + 4 * q;
                uint32_t w[2];
                #pragma unroll
                for (int m = 0; m < 2; m++) {
                    float v = bf_round(q ? acc[m][2] : acc[m][0]); if (cb >= 27) v *= 0.5f; else if (cb >= 18) v += 1.f;
                    w[m] = max(pack_bf(v, __shfl_xor_sync(~0u, v, 4)), 1u);
                }
                if (q < 2 && !(g & 1)) {
                    const int qq = (warp & 1) * 2;
                    if (cb < 27) asm volatile("st.relaxed.gpu.global.v2.u32 [%0], {%1, %2};" :: "l"(p.scr->modc + 32 * cb + 8 * qq + 2 * gg), "r"(w[0]), "r"(w[1]) : "memory");
                    else if (cb < 36) { uint32_t* o = p.scr->modc + 896 + 32 * (cb - 27) + 8 * qq + gg; o[0] = w[0]; o[8] = w[1]; }
                }
                if (tid == 0 && pass == 0) PROFT(25);
                bar_sync(1, 448);
                if (tid == 0) { fence_async_g(); red_release(g_cnt + (CNT_NC + pass) * 32); }
                __syncwarp();
            }
            fence_async_s();
        }
        __syncthreads();
    } else {
        uint32_t ta[QA * 4];
        if (strip && (warp >> 2) == 2) {
            const int w = warp - 8;
            const uint32_t ra = sm + OFF_STRIP + (144 * w + (lane & 7) + 8 * (lane >> 4)) * 64, sw = (lane >> 1) & 3, ch = (lane >> 3) & 1;
            float acc[2][2][4] = {};
            mbar_wait(bars + 8 * (BAR_ST + w), 0);
            #pragma unroll
            for (int u = 0; u < 9; u++)
                #pragma unroll
                for (int m = 0; m < 2; m++) { uint32_t a[4]; ldsm4t(a, ra + u * 1024 + ((ch + 2 * m) ^ sw) * 16); mma_bf(acc[u & 1][m], a, sb[2 * u], sb[2 * u + 1]); }
            #define PICK(a_) ((q & 2) ? ((q & 1) ? a_[1][2] : a_[1][0]) : ((q & 1) ? a_[0][2] : a_[0][0]))
            sts32(sm + OFF_RED + ((8 * q + g) * 4 + w) * 4, __float_as_uint(PICK(acc[0]) + PICK(acc[1])));
            if (tid == 256) PROFT(0);
            bar_sync(10, 128);
            if (warp == 8) {
                mbar_wait(bars + 8 * BAR_TAB, 0);
                const uint4 v = lds128(sm + OFF_RED + lane * 16);
                float sum = bf_round((__uint_as_float(v.x) + __uint_as_float(v.y)) + (__uint_as_float(v.z) + __uint_as_float(v.w)));
                if (b >= 36) sum = bf_round(1.f + sum);
                st_relaxed(g_mod + b * 16 + (lane & 16) + (lane & 1) * 8 + ((lane & 15) >> 1), (fabsf(sum) < 8.f ? pack_h(0.f, sum) : __float_as_uint(sum) | 0x8000u) | ((lds32(sm + OFF_EPOCH) + 1) & 0x7FFFu));
                asm volatile("bar.arrive 11, 416;" ::: "memory");
                if (tid == 256) PROFT(1);
            }
        }
        mbar_wait(bars + 8 * BAR_TAB, 0);
        load_tab<QA>(ta, sm + OFF_TAB + lane * 16);
        epoch = lds32(sm + OFF_EPOCH);
        const uint32_t tag = (epoch + 1) & 0x7FFFu;
        auto w_prefetch = [&]() {
            if (warp >= 14 && elect()) asm volatile("cp.async.bulk.prefetch.L2.global [%0], 9248;" :: "l"((warp == 14 ? p.wr : p.wi) + b * 4624) : "memory");
            __syncwarp();
        };
        uint32_t nb[2][5];
        uint4 mv = make_uint4(tag, tag, tag, tag);
        const bool poller = warp < 8 || warp == 12;
        const int mc = warp < 8 ? tid : tid - 128, mst = (mc >> 2) % 36, midx = (mc < 144 ? 10 : 0) + 5 * ((mc >> 1) & 1) + (mst >> 3);
        const uint32_t* mp = g_mod + mc * 4;
        const uint32_t ma = sm + OFF_MODA + ((midx >> 2) * 32 + (mc & 1) * 16 + (mst & 3)) * 16 + (midx & 3) * 4 + ((mst >> 2) & 1) * 2;
        #define MOD_MISSING ((((mv.x ^ tag) | (mv.y ^ tag) | (mv.z ^ tag) | (mv.w ^ tag)) & 0x7FFFu) != 0)
        if (strip && (warp >> 2) != 2) bar_sync(11, 416);
        #pragma unroll
        for (int i = 0; i < 9; i++) one[i] = lds32(sm + OFF_TAB + (QA - 1) * 512 + i * 16 + 8);
        hb();
        mbar_wait(bars + 8 * (BAR_X + warp), 0);
        if (poller) mv = ldx128(mp);
        PROF0(28);
        #pragma unroll
        for (int i = 0; i < 9; i++) xw[i] = lds32(sm + OFF_STAGE + warp * 1152 + (32 * i + 8 * q + g) * 4);
        {
            float r, mr;
            ln_stats(xw, one, g, q, r, mr);
            #pragma unroll
            for (int pp = 0; pp < 5; pp++) {
                nb[0][pp] = pack_h(fmaf(bf_lo(xw[2 * pp]), r, mr), pp < 4 ? fmaf(bf_lo(xw[pp < 4 ? 2 * pp + 1 : 0]), r, mr) : 0.f);
                nb[1][pp] = pack_h(fmaf(bf_hi(xw[2 * pp]), r, mr), pp < 4 ? fmaf(bf_hi(xw[pp < 4 ? 2 * pp + 1 : 0]), r, mr) : 0.f);
            }
        }
        PROF0(2);
        w_prefetch();
        if (poller && MOD_MISSING) mv = ldx128(mp);
        if (warp < 8) {
            if (warp >= 4) sts16(sm + OFF_MODA + ((warp - 3) * 32 + lane) * 16 + (warp - 4) * 4 + 2, 0);
            const int k1 = tid & 15, s1 = tid >> 4;
            float s, c;
            __sincosf((float)(((k1 * (128 * s1 + b) + 1024) & 2047) - 1024) * (3.14159265358979f / 1024.f), &s, &c); s *= 0.25f; c *= 0.25f;
            const int rf = ((s1 >> 3) * 4 + (k1 >> 2)) * 2 + ((s1 >> 2) & 1), ri = ((k1 >> 3) * 4 + (s1 >> 2)) * 2 + ((k1 >> 2) & 1);
            const uint32_t af = sm + OFF_B3 + ((rf >> 2) * 32 + (k1 & 3) * 8 + (s1 & 3)) * 16 + (rf & 3) * 4;
            const uint32_t ai = sm + OFF_B3 + 2048 + ((ri >> 2) * 32 + (s1 & 3) * 8 + (k1 & 3)) * 16 + (ri & 3) * 4;
            sts32(af, pack_h(c, s)); sts32(af + 64, pack_h(-s, c)); sts32(ai, pack_h(c, -s)); sts32(ai + 64, pack_h(s, c));
        }
        if (poller) {
            #pragma unroll 1
            for (int it = 0; __any_sync(~0u, MOD_MISSING); it++) { if (MOD_MISSING) mv = ldx128(mp); hb(); if (it > SPIN_LIMIT) __trap(); }
            sts16(ma, mv.x >> 16); sts16(ma + 64, mv.y >> 16); sts16(ma + 128, mv.z >> 16); sts16(ma + 192, mv.w >> 16);
        }
        uint32_t redo = 0; asm volatile("" : "+r"(redo));
        #pragma unroll 1
        do { if (redo) {
            const uint32_t w[4] = {mv.x, mv.y, mv.z, mv.w}; float f[4]; uint32_t big = 0;
            #pragma unroll
            for (int e = 0; e < 4; e++) { f[e] = (w[e] & 0x8000u) ? bf_hi(w[e]) : __half2float(__ushort_as_half(w[e] >> 16)); big = max(big, __float_as_uint(f[e]) << 1 >> 24); }
            sts32(sm + OFF_HEXP + warp * 4, __reduce_max_sync(~0u, big));
            __syncthreads();
            hexp = min(__reduce_max_sync(~0u, lds32(sm + OFF_HEXP + (lane & 15) * 4)), 253u) - 127;
            const float sc = __uint_as_float((127 - hexp) << 23);
            if (poller) {
                #pragma unroll
                for (int e = 0; e < 4; e++) sts16(ma + 64 * e, pack_h(f[e] * sc, 0.f));
            }
            mv = make_uint4(0, 0, 0, 0);
          }
          redo = __syncthreads_or((mv.x | mv.y | mv.z | mv.w) & 0x8000u);
          asm volatile("" : "+r"(redo));
        } while (redo);
        PROF0(3);
        asm volatile("barrier.cluster.arrive.relaxed.aligned;" ::: "memory");
        if (warp >= 13 && elect()) {
            if (warp == 15) bulk_load(sm + OFF_TAB + QA * 512, p.tab->w + QA * 128, (QB + QC) * 512, bars + 8 * BAR_TAB2);
            else tma3(sm + OFF_WRAW + (warp - 13) * 14336, warp == 13 ? &tm_wr : &tm_wi, wc0 & ~7, 0, 0, bars + 8 * BAR_W);
        }
        __syncwarp();
        {
            uint32_t md[20];
            load_tab<5>(md, sm + OFF_MODA + lane * 16);
            #pragma unroll
            for (int v = 0; v < 2; v++)
                #pragma unroll
                for (int pp = 0; pp < 5; pp++) nb[v][pp] = hfma2(nb[v][pp], md[v * 5 + pp], md[10 + v * 5 + pp]);
        }
        uint32_t re[3][2], im[3][2];
        #pragma unroll
        for (int mt = 0; mt < 3; mt++)
            #pragma unroll
            for (int v = 0; v < 2; v++) {
                re[mt][v] = 0; im[mt][v] = 0;
                mma_h8(re[mt][v], im[mt][v], ta[24 + 2 * mt], ta[25 + 2 * mt], nb[v][4]);
                mma_h(re[mt][v], im[mt][v], ta[mt * 8], ta[mt * 8 + 1], ta[mt * 8 + 2], ta[mt * 8 + 3], nb[v][0], nb[v][1]);
                mma_h(re[mt][v], im[mt][v], ta[mt * 8 + 4], ta[mt * 8 + 5], ta[mt * 8 + 6], ta[mt * 8 + 7], nb[v][2], nb[v][3]);
                cmul_neg(re[mt][v], im[mt][v], ta[30 + (mt * 2 + v) * 2], ta[31 + (mt * 2 + v) * 2]);
            }
        const uint32_t srow = sm + OFF_SPEC + warp * (SPEC_P * 4);
        #pragma unroll
        for (int nt = 0; nt < 2; nt++) {
            uint32_t o[2][4];
            #pragma unroll
            for (int v = 0; v < 2; v++) {
                const uint32_t b0 = ta[42 + (v * 2 + nt) * 2], b1 = ta[43 + (v * 2 + nt) * 2];
                o[v][0] = o[v][1] = o[v][2] = o[v][3] = 0;
                mma_h(o[v][0], o[v][1], re[0][v], re[1][v], im[0][v], im[1][v], b0, b1);
                mma_h(o[v][2], o[v][3], re[2][0], re[2][1], im[2][0], im[2][1], b0, b1);
            }
            const uint32_t a = srow + (g + 72 * q + 36 * nt) * 4, a2 = srow + (288 - g - 72 * q - 36 * nt) * 4;
            sts32(a, hadd2(o[0][0], o[1][0])); sts32(a + 32, hadd2(o[0][1], o[1][1])); if (g < 3) sts32(a + 64, hadd2(o[0][2], o[1][3]));
            if (g > 0 || (q == 0 && nt == 0)) sts32(a2, hsub2(o[0][0], o[1][0]) ^ 0x80000000u);
            sts32(a2 - 32, hsub2(o[0][1], o[1][1]) ^ 0x80000000u); if (g < 2) sts32(a2 - 64, hsub2(o[0][2], o[1][3]) ^ 0x80000000u);
        }
        uint32_t b3[16];
        if (warp < 10) load_tab<4>(b3, sm + OFF_B3 + lane * 16);
        __syncthreads();
        if (warp == 10) t_st = clk32();
        PROF0(4);
        if (warp < 10) {
            uint4 V[4], o[4];
            #pragma unroll
            for (int u = 0; u < 4; u++) V[u] = lds128(scol + u * (16 * SPEC_P));
            radix16(V, b3, o);
            #pragma unroll
            for (int nt = 0; nt < 4; nt++) { o[nt].x |= 1u; if (warp < 9 || g < 2) stx128(tptr + nt * tstr, o[nt]); }
        }
        PROF0(5);
    }

    int role = 0;
    asm volatile("barrier.cluster.wait.aligned;" ::: "memory");
    if (warp >= 12) {
        const int t = tid - 384;
        if (warp == 14 && rank == 0) {
            uint32_t smid; asm volatile("mov.u32 %0, %%smid;" : "=r"(smid));
            const uint32_t tp = smid >> 1;
            uint32_t pr = tp < 32 ? (tp & 7) * 8 + (tp >> 3) : tp < 60 ? (1 + (tp - 32) % 7) * 8 + 4 + (tp - 32) / 7 : tp < 62 ? 4 + tp : tp < 66 ? tp - 58 : 0;
            #pragma unroll 1
            for (;;) {
                uint32_t old = 0; if (lane == 0) old = atomicExch(g_slot + pr, epoch + 1);
                if (!__any_sync(~0u, lane == 0 && old == epoch + 1)) break;
                pr = pr == 65 ? 0 : pr + 1;
            }
            if (lane < 2) asm volatile("st.async.weak.shared::cluster.mbarrier::complete_tx::bytes.u32 [%0], %1, [%2];" :: "r"(mapa(sm + OFF_MISC, lane)), "r"(pr), "r"(mapa(bars + 8 * BAR_ROLE, lane)) : "memory");
        }
        __syncwarp();
        if (t == 0) {
            asm volatile("prefetch.tensormap [%0];" :: "l"(&tm_w1a) : "memory");
            asm volatile("prefetch.tensormap [%0];" :: "l"(&tm_h3a) : "memory"); asm volatile("prefetch.tensormap [%0];" :: "l"(&tm_w1b) : "memory");
            asm volatile("prefetch.tensormap [%0];" :: "l"(&tm_h3b) : "memory"); asm volatile("prefetch.tensormap [%0];" :: "l"(&tm_w2) : "memory");
            asm volatile("prefetch.tensormap [%0];" :: "l"(&tm_o) : "memory"); asm volatile("prefetch.tensormap [%0];" :: "l"(&tm_h3s) : "memory");
        }
        __syncwarp();
        if (rowcta) {
            spin_until(t0 + NCP);
            uint4 v[2];
            v[1] = make_uint4(1, 1, 1, 1);
            #pragma unroll 1
            for (int it = 0;; it++) {
                v[0] = ldx128(p.scr->modc + 4 * t); if (t < 88) v[1] = ldx128(p.scr->modc + 512 + 4 * t);
                if (__all_sync(~0u, min(min(min(v[0].x, v[0].y), min(v[0].z, v[0].w)), min(min(v[1].x, v[1].y), min(v[1].z, v[1].w))) != 0)) break;
                __nanosleep(100); if (it > SPIN_LIMIT) __trap();
            }
            if (t < 72) { const uint32_t sc = ((127 + hexp) << 7) * 0x10001u;
                v[0] = make_uint4(bfma2(v[0].x, sc, 0x80008000u), bfma2(v[0].y, sc, 0x80008000u), bfma2(v[0].z, sc, 0x80008000u), bfma2(v[0].w, sc, 0x80008000u)); }
            #pragma unroll
            for (int u = 0; u < 2; u++) if (u == 0 || t < 88) {
                const uint32_t a = sm + OFF_MODC + (((t >> 5) + 4 * u) * 32 + 8 * (t & 3) + ((t >> 1) & 2)) * 16 + ((t >> 3) & 3) * 4;
                sts32(a, v[u].x); sts32(a + 16, v[u].y); sts32(a + 64, v[u].z); sts32(a + 80, v[u].w);
            }
            __syncwarp();
            if (elect()) mbar_arrive(bars + 8 * BAR_NC);
            if (t == 0) PROFT(29);
        }
    } else if (rowcta && warp < 11) {
        const int nw = !(b & 1) ? 10 : (b & 7) == 7 ? 9 : 8;
        const int cm = (b >> 3) * 288 + (b & 7) * 32, cx = (b & 1) ? 4608 + 8 * (b >> 3) : (b >> 3) * 288 + 256 + 4 * (b & 7);
        auto load_in = [&]() {
            if (elect()) {
                mbar_expect(bars + 8 * BAR_XB, nw > 8 ? 20480 : 16384);
                tma2(sm + OFF_STAGE, &tm_t, cm, 0, bars + 8 * BAR_XB);
                if (nw > 8) tma2(sm + OFF_STX, &tm_tx, cx, 0, bars + 8 * BAR_XB);
            }
            __syncwarp();
        };
        if (warp == 10) { fence_async_s(); spin_until(t_st + X1D); load_in(); }
        uint32_t tb[QB * 4], wre[4][2], wim[4][2];
        if (warp < nw) {
            mbar_wait(bars + 8 * BAR_TAB2, 0);
            load_tab<QB>(tb, sm + OFF_TAB + QA * 512 + lane * 16);
            mbar_wait(bars + 8 * BAR_W, 0);
            const int off = wc0 & 7;
            const uint32_t wa = sm + OFF_WRAW + lane * 112 + ((off >> 1) + 2 * warp) * 4, sh = (off & 1) * 16;
            #pragma unroll
            for (int c = 0; c < 2; c++)
                #pragma unroll
                for (int h = 0; h < 2; h++) {
                    uint32_t y[2][2];
                    #pragma unroll
                    for (int e = 0; e < 2; e++) {
                        const uint32_t a = wa + c * 14336 + (h + 2 * e) * 3584, x0 = lds32(a), x1 = lds32(a + 4), x2 = lds32(a + 8);
                        y[e][0] = __funnelshift_r(x0, x1, sh); y[e][1] = __funnelshift_r(x1, x2, sh);
                    }
                    #pragma unroll
                    for (int x = 0; x < 4; x++) {
                        const uint32_t v = (x & 1) ? pack_h(bf_hi(y[0][x >> 1]), bf_hi(y[1][x >> 1])) : pack_h(bf_lo(y[0][x >> 1]), bf_lo(y[1][x >> 1]));
                        if (c) wim[x][h] = v; else wre[x][h] = v;
                    }
                }
        }
        const uint32_t ca = warp < 8 ? sm + OFF_STAGE + lane * 128 + (warp ^ (lane & 7)) * 16 : sm + OFF_STX + lane * 32 + ((warp ^ g) & 1) * 16, cs = warp < 8 ? 4096 : 1024;
        uint32_t V[4][4];
        #pragma unroll 1
        for (int it = 0;; it++) {
            mbar_wait(bars + 8 * BAR_XB, it & 1);
            uint32_t ok = 1;
            if (warp < nw) {
                #pragma unroll
                for (int u = 0; u < 4; u++) { uint4 t4 = lds128(ca + u * cs); V[u][0] = t4.x; V[u][1] = t4.y; V[u][2] = t4.z; V[u][3] = t4.w; ok &= t4.x; }
            }
            asm volatile("{.reg .pred p; setp.ne.u32 p, %0, 0; bar.red.and.pred p, 1, 352, p; selp.u32 %0, 1, 0, p;}" : "+r"(ok) :: "memory");
            if (ok) break;
            if (warp == 10) { load_in(); hb(); }
            if (it > SPIN_LIMIT / 64) __trap();
        }
        PROF0(7);
        if (warp < nw) {
            uint32_t zr[4][2], zi[4][2];
            #pragma unroll
            for (int x = 0; x < 4; x++) {
                uint32_t er = 0, ei = 0, or_ = 0, oi = 0;
                mma_h(er, ei, tb[0], tb[1], tb[2], tb[3], V[0][x], V[1][x]);
                mma_h(or_, oi, tb[4], tb[5], tb[6], tb[7], V[2][x], V[3][x]);
                uint32_t r0 = hadd2(er, or_), r1 = hsub2(er, or_), i0 = hadd2(ei, oi), i1 = hsub2(ei, oi);
                cmul_neg(r0, i0, tb[8], tb[9]); cmul_neg(r1, i1, tb[10], tb[11]);
                uint32_t xr0 = 0, xr1 = 0, xi0 = 0, xi1 = 0;
                mma_h(xr0, xr1, r0, r1, i0, i1, tb[12], tb[13]);
                mma_h(xi0, xi1, r0, r1, i0, i1, tb[14], tb[15]);
                cmul_pos(xr0, xi0, wre[x][0], wim[x][0]); cmul_pos(xr1, xi1, wre[x][1], wim[x][1]);
                r0 = 0; i0 = 0; r1 = 0; i1 = 0;
                mma_h(r0, i0, tb[12], tb[13], tb[14], tb[15], xr0, xi0);
                mma_h(r1, i1, tb[12], tb[13], tb[14], tb[15], xr1, xi1);
                cmul_pos(r0, i0, tb[16], tb[17]); cmul_pos(r1, i1, tb[18], tb[19]);
                zr[x][0] = hadd2(r0, r1); zr[x][1] = hsub2(r0, r1); zi[x][0] = hadd2(i0, i1); zi[x][1] = hsub2(i0, i1);
            }
            #pragma unroll
            for (int nt = 0; nt < 4; nt++) {
                uint4 o = make_uint4(0, 0, 0, 0);
                const int h = nt >> 1;
                mma_h(o.x, o.y, zr[0][h], zr[1][h], zi[0][h], zi[1][h], tb[20 + 2 * nt], tb[21 + 2 * nt]);
                mma_h(o.z, o.w, zr[2][h], zr[3][h], zi[2][h], zi[3][h], tb[20 + 2 * nt], tb[21 + 2 * nt]);
                o.x &= ~1u;
                sts128(ca + nt * cs, o);
            }
        }
        fence_async_s();
        bar_sync(1, 352);
        if (warp < 10) t_st = clk32();
        PROF0(8);
        if (warp == 10 && elect()) {
            asm volatile("cp.async.bulk.tensor.2d.global.shared::cta.bulk_group [%0, {%2, %3}], [%1];" :: "l"(&tm_t), "r"(sm + OFF_STAGE), "r"(cm), "r"(0) : "memory");
            if (nw > 8) asm volatile("cp.async.bulk.tensor.2d.global.shared::cta.bulk_group [%0, {%2, %3}], [%1];" :: "l"(&tm_tx), "r"(sm + OFF_STX), "r"(cx), "r"(0) : "memory");
            asm volatile("cp.async.bulk.commit_group;" ::: "memory");
            asm volatile("cp.async.bulk.wait_group.read 0;" ::: "memory");
        }
        __syncwarp();
    }

    if (warp >= 10) { mbar_wait(bars + 8 * BAR_ROLE, 0); role = __shfl_sync(~0u, lds32(sm + OFF_MISC), 0); fence_async_s(); }
    auto first_a = [&]() {
        if (warp >= 10 && role < 64 && elect()) {
            const int it = warp - 10, hi = it >= 3; const bool p2 = it - 3 * hi == 2;
            tma4(sm + OFF_A + it * A_BYTES, p2 ? &tm_w1b : &tm_w1a, 0, 0, p2 ? 64 * rank + 8 * hi : 4 * (it - hi),
                 9 * (role >> 3) + (p2 ? 8 : (role & 4) + 2 * rank), bars + 8 * (BAR_FULL + it));
        }
        __syncwarp();
    };
    if (!rowcta) first_a();
    else {
        uint32_t tc[20], md[28];
        mbar_wait(bars + 8 * BAR_TAB2, 0);
        load_tab<5>(tc, sm + OFF_TAB + (QA + QB) * 512 + lane * 16);
        bool md_early = warp >= 10;
        if (md_early) { mbar_wait(bars + 8 * BAR_NC, 0); load_tab<7>(md, sm + OFF_MODC + lane * 16); }
        if (warp < 10) {
            uint32_t b3[16];
            load_tab<4>(b3, sm + OFF_B3 + 2048 + lane * 16);
            uint4 V[4], o[4];
            const bool tact = warp < 9 || g == 0;
            spin_until(t_st + X2D);
            #pragma unroll
            for (int u = 0; u < 4; u++) { V[u] = make_uint4(0, 0, 0, 0); if (tact) V[u] = ldx128(tptr + u * tstr); }
            md_early = __any_sync(~0u, mbar_test(bars + 8 * BAR_NC, 0));
            if (md_early) load_tab<7>(md, sm + OFF_MODC + lane * 16);
            #pragma unroll 1
            for (int it = 0; __any_sync(~0u, (V[0].x | V[1].x | V[2].x | V[3].x) & 1u); it++) {
                #pragma unroll
                for (int u = 0; u < 4; u++) if (V[u].x & 1u) V[u] = ldx128(tptr + u * tstr);
                hb();
                if (it > SPIN_LIMIT) __trap();
            }
            PROF0(10);
            radix16(V, b3, o);
            if (tact) {
                #pragma unroll
                for (int nt = 0; nt < 4; nt++) sts128(scol + nt * (16 * SPEC_P), o[nt]);
            }
        }
        __syncthreads();
        PROF0(11);
        first_a();
        const uint32_t srow = sm + OFF_SPEC + warp * (SPEC_P * 4);
        uint32_t re[2][3], im[2][3];
        #pragma unroll
        for (int mt = 0; mt < 3; mt++) {
            const uint32_t a = srow + (g + 72 * q + 8 * mt) * 4, a2 = srow + (288 - g - 72 * q - 8 * mt) * 4;
            const uint32_t z0 = lds32(a), z1 = lds32(a + 144), z2 = lds32(a2), z3 = lds32(a2 - 144);
            #pragma unroll
            for (int m2 = 0; m2 < 2; m2++) {
                re[m2][mt] = 0; im[m2][mt] = 0;
                const uint32_t sg = m2 ? 0x3C00BC00u : 0xBC003C00u;
                mma_h(re[m2][mt], im[m2][mt], tc[m2 * 4], tc[m2 * 4 + 1], tc[m2 * 4 + 2], tc[m2 * 4 + 3], hfma2(z2, sg, z0), hfma2(z3, sg, z1));
                cmul_pos(re[m2][mt], im[m2][mt], tc[8 + (m2 * 3 + mt) * 2], tc[9 + (m2 * 3 + mt) * 2]);
            }
        }
        float y[20];
        WG_FENCE();
        #pragma unroll
        for (int mt = 0; mt < 3; mt++)
            wgmma40_rs(y, re[0][mt], re[1][mt], im[0][mt], im[1][mt], desc_lo(OFF_TAB + (QA + QB + 5) * 512 + mt * 1280, 128), mt);
        WG_COMMIT();
        if (!md_early) { mbar_wait(bars + 8 * BAR_NC, 0); load_tab<7>(md, sm + OFF_MODC + lane * 16); }
        WG_WAIT(0);
        #pragma unroll
        for (int i = 0; i < 9; i++) xw[i] = bfma2(md[i], pack_bf(y[4 * (i >> 1) + (i & 1)], y[4 * (i >> 1) + 2 + (i & 1)]), xw[i]);
        float r, mr;
        ln_stats(xw, one, g, q, r, mr);
        uint32_t r2 = pack_bf(r, r), m2 = pack_bf(mr, mr);
        #pragma unroll
        for (int i = 0; i < 9; i++) {
            sts32(sm + OFF_X1 + warp * 1152 + (32 * i + 8 * q + g) * 4, xw[i]);
            xw[i] = bfma2(bfma2(xw[i], r2, m2), md[18 + i], md[9 + i]);
        }
        ln_stats(xw, one, g, q, r, mr);
        r2 = pack_bf(r, r); m2 = pack_bf(mr, mr);
        {
            const int n7 = 2 * q + (g >> 2);
            const uint32_t a = sm + OFF_STAGE + (warp >> 3) * 9216 + n7 * 128 + ((warp & 7) ^ n7) * 16 + (g & 3) * 4;
            #pragma unroll
            for (int i = 0; i < 9; i++) sts32(a + i * 1024, bfma2(xw[i], r2, m2));
        }
        fence_async_s();
        __syncthreads();
        PROF0(12);
        if (tid == 0) {
            asm volatile("cp.async.bulk.tensor.4d.global.shared::cta.bulk_group [%0, {%2, %2, %2, %3}], [%1];" :: "l"(&tm_h3s), "r"(sm + OFF_STAGE), "r"(0), "r"(b) : "memory");
            asm volatile("cp.async.bulk.commit_group;" ::: "memory");
        }
    }
    if (!rowcta) __syncthreads();
    else {
        if (tid == 0) { asm volatile("cp.async.bulk.wait_group 0;" ::: "memory"); fence_async_g(); red_release(g_cnt + CNT_H3 * 32); }
        PROF0(13);
        if (warp == 15) {
            __nanosleep(X1DELAY);
            #pragma unroll 1
            for (int r = 0; r < 16; r++) {
                if (lane == 0) asm volatile("cp.async.bulk.global.shared::cta.bulk_group [%0], [%1], 1152;" :: "l"(p.out + (size_t)(b + 128 * r) * D_), "r"(sm + OFF_X1 + r * 1152) : "memory");
                const uint32_t t1 = clk32();
                #pragma unroll 1
                while (__any_sync(~0u, (int)(clk32() - t1) < X1PACE)) __nanosleep(50);
            }
            if (lane == 0) {
                asm volatile("cp.async.bulk.commit_group;" ::: "memory");
                asm volatile("cp.async.bulk.wait_group 0;" ::: "memory");
                if (role < 64) mbar_arrive_remote(mapa(bars + 8 * BAR_HOLD, rank ^ 1));
                fence_async_g(); red_release(g_cnt + CNT_X1 * 32);
            }
        }
    }
    role = __shfl_sync(~0u, lds32(sm + OFF_MISC), 0);
    if ((sm & 0xFFFFFFu) != SM0) __trap();
    if (role >= 64) { if (warp == 0) PROFDUMP(); return; }

    const int gi = role >> 3, dt = role & 3, c2 = (role >> 2) & 1;
    const int wg = warp >> 2, wi = warp & 3;
    if (wg == 3) {
        uint32_t so = 0, eph = 1;
        #define RING_STEP(BYTES, OFF, ISSUE) do { \
            mbar_wait(bars + 8 * BAR_EMPTY + so, eph); \
            if (elect()) { const uint32_t fb = bars + 8 * BAR_FULL + so, dst = sm + (OFF) + so * ((BYTES) / 8); mbar_expect(fb, BYTES); ISSUE; } \
            so += 8; if (so == 8 * NST) { so = 0; eph ^= 1; } } while (0)
        const uint32_t kbm = warp == 12 ? 64 : 4 * B_BYTES, kba = warp == 12 ? 0 : dt * B_BYTES;
        const uint32_t kb0 = g2_kb(lane, rank, gi, c2) * kbm + kba, kb1 = g2_kb(32 + (lane & 3), rank, gi, c2) * kbm + kba;
        #define KB(n_) __shfl_sync(~0u, (n_) < 32 ? kb0 : kb1, (n_) & 31)
        if (warp == 12) {
            eph = 0;
            const int fb1 = 9 * gi + 4 * c2 + 2 * rank, sb2 = 4 * gi + 2 * c2;
            int pft = dt, pfj = 4 * (PF0 + PFS * dt);
            #pragma unroll 1
            for (int j = 16; j < 128; j += 4) {
                RING_STEP(A_BYTES, OFF_A, tma4(dst, &tm_w1a, 0, 0, j, fb1, fb));
                if (j < 64) { if (j & 4) RING_STEP(A_BYTES, OFF_A, tma4(dst, &tm_w1b, 0, 0, 64 * rank + j - 4, 9 * gi + 8, fb)); }
                if (RP1 && __any_sync(~0u, (j & 12) == 4 * dt && j + 4 * RP1 < 128) && elect())
                    asm volatile("cp.async.bulk.prefetch.tensor.4d.L2.global [%0, {%1, %1, %2, %3}];" :: "l"(&tm_w1a), "r"(0), "r"(j + 4 * RP1), "r"(fb1) : "memory");
                if (RPX && __any_sync(~0u, (j & 4) == 0 && j + 8 * RPX < 64 && ((j >> 3) & 7) == (role & 7)) && elect())
                    asm volatile("cp.async.bulk.prefetch.tensor.4d.L2.global [%0, {%1, %1, %2, %3}];" :: "l"(&tm_w1b), "r"(0), "r"(64 * (int)rank + j + 8 * RPX), "r"(9 * gi + 8) : "memory");
                if (__any_sync(~0u, j == pfj && pft < PFN)) {
                    const int kb = KB(pft); pft += 4; pfj += 16 * PFS;
                    if (elect()) asm volatile("cp.async.bulk.prefetch.tensor.3d.L2.global [%0, {%1, %2, %3}];" :: "l"(&tm_w2), "r"(0), "r"(kb), "r"(sb2) : "memory");
                }
            }
            #pragma unroll 1
            for (int n = 0; n < 36; n++) {
                const int kb = KB(n);
                RING_STEP(A_BYTES, OFF_A, tma3(dst, &tm_w2, 0, kb, sb2, fb));
            }
        } else if (warp == 13) {
            const uint32_t e1 = __shfl_sync(~0u, epoch + 1, 0);
            fence_async_s();
            if (lane == 0) mbar_expect(bars + 8 * BAR_FULL, B_BYTES);
            wait_count<0>(g_cnt + CNT_H3 * 32, e1 * 128); fence_async_g();
            if (elect()) tma3(sm + OFF_B, &tm_h3a, 0, 18 * dt, 0, bars + 8 * BAR_FULL);
            so = 8;
            if (lane == 0) PROFT(14);
            #pragma unroll 1
            for (int j = 4; j < 128; j += 4) {
                RING_STEP(B_BYTES, OFF_B, tma3(dst, &tm_h3a, 0, 18 * dt, j, fb));
                if (j < 64 && (j & 4)) RING_STEP(B_BYTES, OFF_B, tma3(dst, &tm_h3b, 0, 18 * dt + 9 * c2, 64 * rank + j - 4, fb));
            }
            mbar_wait(bars + 8 * BAR_UOK, 0); fence_async_g();
            if (lane == 0) PROFT(22);
            #pragma unroll 1
            for (int n = 0; n < 4; n++) { const uint32_t o = KB(n); RING_STEP(B_BYTES, OFF_B, bulk_load(dst, (const char*)g_U + o, B_BYTES, fb)); }
            {
                constexpr int S5 = (IT_G2 + 5) % NST; static_assert(S5 > 0 && S5 < NST - 1, "no wrap");
                const char* src = (const char*)g_U + KB(5);
                mbar_wait(bars + 8 * (BAR_EMPTY + S5), eph);
                if (lane == 0) mbar_expect(bars + 8 * (BAR_FULL + S5), B_BYTES);
                mbar_wait(bars + 8 * (BAR_UOK + 1), 0);
                wait_count<0>(g_cnt + (CNT_U + 8) * 32, e1 * 128); fence_async_g();
                if (elect()) bulk_load(sm + OFF_B + S5 * B_BYTES, src, B_BYTES, bars + 8 * (BAR_FULL + S5));
                so = 8 * (S5 + 1);
                if (lane == 0) PROFT(19);
            }
            #pragma unroll 1
            for (int n = 6; n < 36; n++) {
                const uint32_t o = KB(n);
                if (n == 21) { mbar_wait(bars + 8 * (BAR_UOK + 2), 0); fence_async_g(); }
                RING_STEP(B_BYTES, OFF_B, bulk_load(dst, (const char*)g_U + o, B_BYTES, fb));
            }
            if (role == 0 && rank == 0 && lane == 0) st_relaxed(g_cnt + CNT_EPOCH * 32, e1);
        } else if (warp == 15) {
            if (!rowcta && elect()) mbar_arrive_remote(mapa(bars + 8 * BAR_HOLD, rank ^ 1));
            __syncwarp();
            bar_sync(6, 160);
            if (elect()) mbar_arrive(bars + 8 * (BAR_FULL + (IT_G2 + 4) % NST));
            __syncwarp();
            mbar_wait(bars + 8 * BAR_W1GO, 0);
            if (elect()) {
                char* dst = (char*)(g_U + ((9 * gi + 4 * c2 + 2 * rank + 1) * 4 + dt) * 1152);
                #pragma unroll 1
                for (int i = 0; i < W1N; i++) {
                    asm volatile("cp.async.bulk.global.shared::cta.bulk_group [%0], [%1], %2;" :: "l"(dst + i * (18432 / W1N)), "r"(sm + OFF_X1 + i * (18432 / W1N)), "n"(18432 / W1N) : "memory");
                    const uint32_t t1 = clk32(); while ((int)(clk32() - t1) < W1P) {}
                }
                asm volatile("cp.async.bulk.commit_group;" ::: "memory");
                asm volatile("cp.async.bulk.wait_group 0;" ::: "memory");
                fence_async_g(); red_release(g_cnt + (CNT_U + 16) * 32);
                #pragma unroll 1
                for (int n = 0; n < 4; n++) { __nanosleep(300); tma2(sm + OFF_X1 + n * 4608, &tm_o, 144 * dt, 256 * gi + 128 * c2 + 64 * (rank ^ 1) + 16 * n, bars + 8 * BAR_XT); }
            }
        } else {
            const uint32_t e1 = epoch + 1;
            if (lane == 0) {
                __nanosleep(4000);
                wait_count<200>(g_cnt + CNT_NC * 32, e1 * 4); wait_count<200>(g_cnt + (CNT_NC + 1) * 32, e1 * 2);
                fence_async_g();
                mbar_expect(bars + 8 * BAR_GB, 1152);
                bulk_load(sm + OFF_GB, p.scr->modc + 896, 1152, bars + 8 * BAR_GB);
                wait_count<200>(g_cnt + CNT_X1 * 32, e1 * 128);
                if (role * 2 + rank < 108) {
                    uint4* z = (uint4*)p.scr->modc + (role * 2 + rank) * 2; z[0] = z[1] = make_uint4(0, 0, 0, 0);
                }
                wait_count<50>(g_cnt + (CNT_U + dt * 2 + rank) * 32, e1 * 16);
                mbar_arrive(bars + 8 * BAR_UOK);
            }
            __syncwarp();
            bar_sync(4, 160);
            if (tid == 448) {
                fence_async_g(); red_release(g_cnt + (CNT_U + 8) * 32);
                PROFT(17);
                mbar_arrive(bars + 8 * (BAR_UOK + 1));
                __nanosleep(2000);
                wait_count<100>(g_cnt + (CNT_U + 16) * 32, e1 * 128);
                mbar_arrive(bars + 8 * (BAR_UOK + 2));
            }
        }
    } else if (wg == 2) {
        float d0[36];
        const float bias = bf_lo(ldg_nc16(p.b1 + 576 * gi + 512 + 16 * wi + g + 8 * rank));
        #pragma unroll 1
        for (int it = 0; it < 200 && !__any_sync(~0u, mbar_test(bars + 8 * BAR_FULL, 0)); it++) { hb(); __nanosleep(100); }
        const bool lead = wi == 0 && elect();
        #pragma unroll 1
        for (int i = 0; i < 8; i++) {
            const uint32_t s = P2S + 3 * (i & 1);
            mbar_wait(bars + 8 * BAR_FULL + 8 * s, (i >> 1) & 1);
            const uint32_t da = desc_lo(OFF_A, 8192) + s * (A_BYTES / 16), db = desc_lo(OFF_B, 128) + s * (B_BYTES / 16);
            WG_FENCE();
            wgmma72(d0, da, db, i);
            #pragma unroll
            for (int k = 1; k < 9; k++) {
                if (k == P2K) asm volatile("{.reg .pred p; setp.ne.u32 p, %1, 0; @p mbarrier.arrive.shared::cta.b64 _, [%0];}" :: "r"(bars + 8 * (BAR_P2N + (i & 1))), "r"((uint32_t)lead) : "memory");
                if (k < 8) wgmma72(d0, da + k * 128, db + k * 144, 1);
            }
            WG_COMMIT();
            WG_WAIT(0);
            if (lead) mbar_arrive_n(bars + 8 * BAR_EMPTY + 8 * s, 2);
        }
        if (lead) PROFT(18);
        const uint32_t slot = sm + OFF_P2R + (tid & 127) * 16, ra = mapa(slot, rank ^ 1), rb = mapa(bars + 8 * BAR_P2R, rank ^ 1);
        float sv[18];
        #pragma unroll
        for (int i = 0; i < 18; i++) { const float lo = d0[4 * (i >> 1) + (i & 1)], hi = d0[4 * (i >> 1) + 2 + (i & 1)];
            sv[i] = rank ? lo : hi; d0[4 * (i >> 1) + (i & 1)] = (rank ? hi : lo) + bias; }
        mbar_wait(bars + 8 * BAR_HOLD, 0);
        #pragma unroll
        for (int i = 0; i < 4; i++)
            asm volatile("st.async.weak.shared::cluster.mbarrier::complete_tx::bytes.v4.f32 [%0], {%1,%2,%3,%4}, [%5];"
                :: "r"(ra + i * 2048), "f"(sv[4 * i]), "f"(sv[4 * i + 1]), "f"(sv[4 * i + 2]), "f"(sv[4 * i + 3]), "r"(rb) : "memory");
        asm volatile("st.async.weak.shared::cluster.mbarrier::complete_tx::bytes.v2.f32 [%0], {%1,%2}, [%3];" :: "r"(ra + 8192), "f"(sv[16]), "f"(sv[17]), "r"(rb) : "memory");
        mbar_wait(bars + 8 * BAR_P2R, 0);
        #pragma unroll
        for (int i = 0; i < 5; i++) {
            const uint4 v = lds128(slot + i * 2048);
            d0[8 * i] += __uint_as_float(v.x); d0[8 * i + 1] += __uint_as_float(v.y);
            if (i < 4) { d0[8 * i + 4] += __uint_as_float(v.z); d0[8 * i + 5] += __uint_as_float(v.w); }
        }
        asm volatile("bar.arrive 5, 256;" ::: "memory");
        gelu_store<0>(d0, (char*)(g_U + ((9 * gi + 8) * 4 + dt) * 1152) + wi * 4608 + rank * 2304 + c2 * 1152 + g * 16, q);
        bar_sync(8, 128);
        if (lead) { fence_async_g(); red_release(g_cnt + (CNT_U + dt * 2 + (gi >> 2)) * 32); PROFT(26); }
    } else {
        float d[72];
        const bool lead = wi == 0 && elect();
        const uint32_t da0 = desc_lo(OFF_A, 8192) + wg * 512;
        const bool owner = (uint32_t)wg == rank;
        const int srow = 256 * gi + 128 * c2 + 64 * wg + 16 * wi;
        const uint32_t b2w0 = ldg_nc16(p.b2 + srow + g), b2w1 = ldg_nc16(p.b2 + srow + g + 8);
        const int fr = 576 * gi + 256 * c2 + 128 * rank + 64 * wg + 16 * wi + g;
        const float bias0 = bf_lo(ldg_nc16(p.b1 + fr)), bias1 = bf_lo(ldg_nc16(p.b1 + fr + 8));
        {
            #pragma unroll
            for (int i = 0; i < 72; i++) d[i] = (i & 2) ? bias1 : bias0;
            constexpr uint32_t db1 = desc_lo(OFF_B, 128);
            static_assert(IT_G2 - LEAD1 == 6 * NST && IT_P1 == 4 * NST && P2S == 2, "loop structure");
            #define REL(s_) if (lead) mbar_arrive(bars + 8 * (BAR_EMPTY + (s_)))
            mma_block<DHI_H3, 0>(d, bars, da0, db1, 0);
            #pragma unroll 1
            for (int c = 0; c < 4; c++) {
                const uint32_t ph = c & 1;
                mma_block<DHI_H3, 1>(d, bars, da0, db1, ph); REL(0);
                mbar_wait(bars + 8 * (P2K ? BAR_P2N : BAR_FULL + 2), ph);
                mma_block<DHI_H3, 3>(d, bars, da0, db1, ph); REL(1);
                mma_block<DHI_H3, 4>(d, bars, da0, db1, ph); REL(3);
                mbar_wait(bars + 8 * (P2K ? BAR_P2N + 1 : BAR_FULL + 5), ph);
                mma_block<DHI_H3, 0>(d, bars, da0, db1, ph ^ 1); REL(4);
            }
            #pragma unroll 1
            for (uint32_t ph = 0; ph < 2; ph++) {
                mma_block<DHI_H3, 1>(d, bars, da0, db1, ph); REL(0);
                mma_block<DHI_H3, 2>(d, bars, da0, db1, ph); REL(1);
                mma_block<DHI_H3, 3>(d, bars, da0, db1, ph); REL(2);
                mma_block<DHI_H3, 4>(d, bars, da0, db1, ph); REL(3);
                mma_block<DHI_H3, 5>(d, bars, da0, db1, ph); REL(4);
                const bool pause = ph && wg == 1;
                if (pause) { WG_WAIT(0); REL(5); bar_sync(9, 256); }
                mma_block<DHI_H3, 0>(d, bars, da0, db1, ph ^ 1); if (!pause) REL(5);
            }
            #pragma unroll
            for (int i = IT_G2 - LEAD1 + 1; i < IT_G2; i++) {
                mbar_wait(bars + 8 * (BAR_FULL + i % NST), (i / NST) & 1);
                WG_FENCE();
                #pragma unroll
                for (int k = 0; k < 4; k++) {
                    if (i == IT_G2 - 1 && k == HOK1) WG_COMMIT();
                    wgmma144<DHI_H3>(d, da0 + (i % NST) * (A_BYTES / 16) + k * 128, db1 + (i % NST) * (B_BYTES / 16) + k * 288, 1);
                }
                WG_COMMIT();
                if (i == IT_G2 - 1 && HOK1 < 4) WG_WAIT(2); else WG_WAIT(1);
                REL((i - 1) % NST);
            }
            if (wg == 0) { WG_WAIT(1); asm volatile("bar.arrive 9, 256;" ::: "memory"); }
            WG_WAIT(0);
            if (lead) mbar_arrive(bars + 8 * (BAR_EMPTY + (IT_G2 - 1) % NST));
            PROF0(16);
            if (wg == 1) bar_sync(5, 256);
            char* const ub = (wg == 0 ? (char*)(g_U + ((9 * gi + 4 * c2 + 2 * rank) * 4 + dt) * 1152) : (char*)__cvta_shared_to_generic(sm + OFF_X1)) + wi * 4608 + g * 16;
            gelu_store<0>(d, ub, q); gelu_store<2>(d, ub + 2304, q); gelu_store<36>(d, ub + 1152, q); gelu_store<38>(d, ub + 3456, q);
            PROF0(27);
            if (wg == 0) asm volatile("bar.arrive 4, 160;" ::: "memory");
            else { fence_async_s(); asm volatile("bar.arrive 6, 160;" ::: "memory"); }
        }
        constexpr uint32_t db0 = desc_lo(OFF_B, 2304);
        const bool keep = role < 0;
        constexpr int IT_L = IT_END - NST;
        #pragma unroll
        for (int i = IT_G2; i <= IT_G2 + W1S; i++) {
            const uint32_t db = db0 + (i == IT_G2 + 4 ? OFF_X1 - OFF_B : (i % NST) * B_BYTES) / 16;
            mbar_wait(bars + 8 * (BAR_FULL + i % NST), (i / NST) & 1);
            WG_FENCE();
            #pragma unroll
            for (int k = 0; k < 4; k++) wgmma144<DHI_U>(d, da0 + (i % NST) * (A_BYTES / 16) + k * 128, db + k * 288, i > IT_G2 || k > 0 || keep);
            WG_COMMIT();
            if (i > IT_G2) { WG_WAIT(1); if (lead) mbar_arrive(bars + 8 * (BAR_EMPTY + (i - 1) % NST)); }
        }
        if (lead) mbar_arrive(bars + 8 * BAR_W1GO);
        const uint32_t ga0 = sm + OFF_GB + (144 * dt + 8 * q) * 2, tile = sm + OFF_X1 + wi * 4608, to = g * 288 + q * 16;
        #define QOFF(i_) (((i_) >> 2) * 2304 + 144 * (((i_) >> 1) & 1) + 64 * ((i_) & 1))
        #define SOFF(k_) (((k_) >> 1) * 2304 + 144 * ((k_) & 1) + 128 - 12 * q)
        #define DIDX(i_, k_) ((i_) < 8 ? 36 * (((i_) >> 1) & 1) + 16 * ((i_) & 1) + 4 * (k_) + 2 * ((i_) >> 2) : 36 * ((k_) & 1) + 32 + 2 * ((k_) >> 1))
        #define FIN(k_, f_) bfma2(g4.f_, pack_bf(d[DIDX(i, k_)], d[DIDX(i, k_) + 1]), xq[i].f_)
        uint4 xq[9];
        auto load_g = [&](int i) { uint4 r; if (i < 4) r = lds128(ga0 + QOFF(i)); else { r.x = r.z = lds32(ga0 + SOFF(0)); r.y = r.w = lds32(ga0 + SOFF(1)); } return r; };
        static_assert(W1S == 5 && (IT_G2 + 6) % NST == 4 && ((IT_G2 + 6) / NST) % 2 == 1 && IT_L == IT_G2 + 30, "loop structure");
        #pragma unroll 1
        for (int c = 0; c < 4; c++) {
            const uint32_t ph = c & 1, xa = tile + to; const bool xl = c == 3 && !owner;
            mma_block<DHI_U, 4>(d, bars, da0, db0, ph ^ 1); REL(3);
            mma_block<DHI_U, 5>(d, bars, da0, db0, ph ^ 1); REL(4);
            mma_block<DHI_U, 0>(d, bars, da0, db0, ph); REL(5);
            if (xl) { mbar_wait(bars + 8 * BAR_XT, 0); xq[0] = lds128(xa + QOFF(0)); xq[4] = lds128(xa + QOFF(4)); xq[1] = lds128(xa + QOFF(1)); }
            mma_block<DHI_U, 1>(d, bars, da0, db0, ph); REL(0);
            if (xl) { xq[5] = lds128(xa + QOFF(5)); xq[2] = lds128(xa + QOFF(2)); xq[6] = lds128(xa + QOFF(6)); }
            mma_block<DHI_U, 2>(d, bars, da0, db0, ph); REL(1);
            if (xl) { xq[3] = lds128(xa + QOFF(3)); xq[7] = lds128(xa + QOFF(7));
                      xq[8] = make_uint4(lds32(xa + SOFF(0)), lds32(xa + SOFF(1)), lds32(xa + SOFF(2)), lds32(xa + SOFF(3))); }
            mma_block<DHI_U, 3>(d, bars, da0, db0, ph); REL(2);
        }
        if (!owner && elect()) mbar_arrive_remote(mapa(bars + 8 * BAR_DONE, rank ^ 1));
        if (owner) { WG_WAIT(0); if (lead) mbar_arrive(bars + 8 * (BAR_EMPTY + (IT_L - 1) % NST)); bar_sync(7, 256); }
        #pragma unroll
        for (int i = IT_L; i < IT_END; i++) {
            mbar_wait(bars + 8 * (BAR_FULL + i % NST), (i / NST) & 1);
            WG_FENCE();
            #pragma unroll
            for (int k = 0; k < 4; k++) {
                if (i == IT_END - 1 && k == HOK) WG_COMMIT();
                wgmma144<DHI_U>(d, da0 + (i % NST) * (A_BYTES / 16) + k * 128, db0 + (i % NST) * (B_BYTES / 16) + k * 288, 1);
            }
            WG_COMMIT();
            if (i == IT_L) { WG_WAIT(1); if (lead && !owner) mbar_arrive(bars + 8 * (BAR_EMPTY + (IT_L - 1) % NST)); }
        }
        PROF0(9);
        mbar_wait(bars + 8 * BAR_GB, 0);
        if (!owner) {
            const uint32_t ra = mapa(tile + lane * 16, rank ^ 1), rb = mapa(bars + 8 * BAR_RECV, rank ^ 1);
            mbar_wait(bars + 8 * BAR_DONE, 0);
            uint4 gn = load_g(0);
            WG_WAIT(1);
            asm volatile("bar.arrive 7, 256;" ::: "memory");
            WG_WAIT(0);
            #pragma unroll
            for (int i = 0; i < 72; i++) d[i] = fmaf(bf_lo((i & 2) ? b2w1 : b2w0), 2.f, d[i]);
            #pragma unroll
            for (int j = 0; j < 5; j++) {
                const uint4 g4 = gn;
                if (j < 4) gn = load_g(j + 1);
                #pragma unroll
                for (int i = j < 4 ? j : 8; i < 9; i += 4) if (i < 8 || j == 4)
                    asm volatile("st.async.weak.shared::cluster.mbarrier::complete_tx::bytes.v4.b32 [%0], {%1,%2,%3,%4}, [%5];"
                        :: "r"(ra + i * 512), "r"(FIN(0, x)), "r"(FIN(1, y)), "r"(FIN(2, z)), "r"(FIN(3, w)), "r"(rb) : "memory");
            }
            PROF0(6);
            if (warp == 0) PROFDUMP();
            return;
        }
        PROF0(24);
        mbar_wait(bars + 8 * BAR_RECV, 0);
        #pragma unroll
        for (int i = 0; i < 9; i++) xq[i] = lds128(tile + lane * 16 + i * 512);
        uint4 gn = load_g(0);
        WG_WAIT(0);
        __syncwarp();
        PROF0(21);
        #pragma unroll
        for (int j = 0; j < 5; j++) {
            const uint4 g4 = gn;
            if (j < 4) gn = load_g(j + 1);
            #pragma unroll
            for (int i = j < 4 ? j : 8; i < 9; i += 4) if (i < 8 || j == 4) {
                const uint4 o = make_uint4(FIN(0, x), FIN(1, y), FIN(2, z), FIN(3, w));
                if (i < 8) sts128(tile + to + QOFF(i), o);
                else { sts32(tile + to + SOFF(0), o.x); sts32(tile + to + SOFF(1), o.y); sts32(tile + to + SOFF(2), o.z); sts32(tile + to + SOFF(3), o.w); }
            }
        }
        fence_async_s();
        __syncwarp();
        if (elect()) {
            asm volatile("cp.async.bulk.tensor.2d.global.shared::cta.bulk_group [%0, {%2, %3}], [%1];" :: "l"(&tm_o), "r"(tile), "r"(144 * dt), "r"(srow) : "memory");
            asm volatile("cp.async.bulk.commit_group;" ::: "memory");
            asm volatile("cp.async.bulk.wait_group.read 0;" ::: "memory");
        }
        PROF0(23);
        if (warp == 0) { __syncwarp(); PROFDUMP(); }
    }
}

typedef CUresult (*EncodeFn)(CUtensorMap*, CUtensorMapDataType, cuuint32_t, void*, const cuuint64_t*, const cuuint64_t*, const cuuint32_t*,
                             const cuuint32_t*, CUtensorMapInterleave, CUtensorMapSwizzle, CUtensorMapL2promotion, CUtensorMapFloatOOBfill);

void encode(EncodeFn fn, CUtensorMap* m, CUtensorMapDataType dt, int rank, const void* ptr, const cuuint64_t* dims, const cuuint64_t* strides,
            const cuuint32_t* box, CUtensorMapSwizzle sw, CUtensorMapL2promotion promo = CU_TENSOR_MAP_L2_PROMOTION_L2_128B) {
    const cuuint32_t es[5] = {1, 1, 1, 1, 1};
    fn(m, dt, rank, (void*)ptr, dims, strides, box, es, CU_TENSOR_MAP_INTERLEAVE_NONE, sw, promo, CU_TENSOR_MAP_FLOAT_OOB_FILL_NONE);
}

}

extern "C" void kernel_launch(void* const* d_in, const int* in_sizes, int n_in, void* d_out, int out_size) {
    (void)in_sizes; (void)n_in; (void)out_size;
    Params p;
    p.x = (const uint16_t*)d_in[0]; p.wr = (const uint16_t*)d_in[1]; p.wi = (const uint16_t*)d_in[2];
    p.w1 = (const uint16_t*)d_in[4]; p.b1 = (const uint16_t*)d_in[5]; p.w2 = (const uint16_t*)d_in[6]; p.b2 = (const uint16_t*)d_in[7];
    p.c = (const uint16_t*)d_in[8]; p.wmod = (const uint16_t*)d_in[9]; p.out = (uint16_t*)d_out;

    void* fnp = nullptr; cudaDriverEntryPointQueryResult qr;
    cudaGetDriverEntryPoint("cuTensorMapEncodeTiled", &fnp, cudaEnableDefault, &qr);
    EncodeFn fn = (EncodeFn)fnp;
    cudaGetSymbolAddress((void**)&p.scr, g_scr); cudaGetSymbolAddress((void**)&p.tab, g_tab);
    void* h3p = p.scr->h3;
    CUtensorMap tw1a, tw1b, tw2, th3a, th3b, twr, twi, twm, tt, ttx, to, th3s, tws;
    {
        const cuuint64_t dims[4] = {64, 16, 128, 72}, st[3] = {128ull * F_ * 2, (cuuint64_t)F_ * 2, 128};
        const cuuint32_t ba[4] = {64, 16, 4, 2}, bb[4] = {64, 16, 8, 1};
        encode(fn, &tw1a, CU_TENSOR_MAP_DATA_TYPE_BFLOAT16, 4, p.w1, dims, st, ba, CU_TENSOR_MAP_SWIZZLE_128B);
        encode(fn, &tw1b, CU_TENSOR_MAP_DATA_TYPE_BFLOAT16, 4, p.w1, dims, st, bb, CU_TENSOR_MAP_SWIZZLE_128B);
    }
    {
        const cuuint64_t dims[3] = {64, F_, 32}, st[2] = {(cuuint64_t)S_ * 2, 128};
        const cuuint32_t bx[3] = {64, 64, 2};
        encode(fn, &tw2, CU_TENSOR_MAP_DATA_TYPE_BFLOAT16, 3, p.w2, dims, st, bx, CU_TENSOR_MAP_SWIZZLE_128B);
    }
    {
        const cuuint64_t dims[3] = {64, 72, 128}, st[2] = {256, 18432};
        const cuuint32_t ba[3] = {64, 18, 4}, bb[3] = {64, 9, 8};
        encode(fn, &th3a, CU_TENSOR_MAP_DATA_TYPE_UINT32, 3, h3p, dims, st, ba, CU_TENSOR_MAP_SWIZZLE_NONE);
        encode(fn, &th3b, CU_TENSOR_MAP_DATA_TYPE_UINT32, 3, h3p, dims, st, bb, CU_TENSOR_MAP_SWIZZLE_NONE);
    }
    {
        const cuuint64_t dims[4] = {32, 72, 2, 128}, st[3] = {256, 128, 18432};
        const cuuint32_t bx[4] = {32, 72, 2, 1};
        encode(fn, &th3s, CU_TENSOR_MAP_DATA_TYPE_UINT32, 4, h3p, dims, st, bx, CU_TENSOR_MAP_SWIZZLE_128B, CU_TENSOR_MAP_L2_PROMOTION_NONE);
    }
    {
        const cuuint64_t dims[3] = {4624, 4, 32}, st[2] = {9248 * 32, 9248};
        const cuuint32_t bx[3] = {56, 4, 32};
        encode(fn, &twr, CU_TENSOR_MAP_DATA_TYPE_BFLOAT16, 3, p.wr, dims, st, bx, CU_TENSOR_MAP_SWIZZLE_NONE);
        encode(fn, &twi, CU_TENSOR_MAP_DATA_TYPE_BFLOAT16, 3, p.wi, dims, st, bx, CU_TENSOR_MAP_SWIZZLE_NONE);
    }
    {
        const cuuint64_t dims[2] = {3456, 576}, st[1] = {6912};
        const cuuint32_t bx[2] = {32, 144};
        encode(fn, &tws, CU_TENSOR_MAP_DATA_TYPE_BFLOAT16, 2, p.wmod, dims, st, bx, CU_TENSOR_MAP_SWIZZLE_64B);
    }
    {
        const cuuint64_t dims[3] = {64, 576, 54}, st[2] = {6912, 128};
        const cuuint32_t bx[3] = {64, 32, 7};
        encode(fn, &twm, CU_TENSOR_MAP_DATA_TYPE_BFLOAT16, 3, p.wmod, dims, st, bx, CU_TENSOR_MAP_SWIZZLE_128B);
    }
    {
        const cuuint64_t dims[2] = {TP, 128}, st[1] = {TP * 4};
        const cuuint32_t ba[2] = {32, 128}, bb[2] = {8, 128};
        encode(fn, &tt, CU_TENSOR_MAP_DATA_TYPE_UINT32, 2, p.scr->T, dims, st, ba, CU_TENSOR_MAP_SWIZZLE_128B, CU_TENSOR_MAP_L2_PROMOTION_NONE);
        encode(fn, &ttx, CU_TENSOR_MAP_DATA_TYPE_UINT32, 2, p.scr->T, dims, st, bb, CU_TENSOR_MAP_SWIZZLE_32B, CU_TENSOR_MAP_L2_PROMOTION_NONE);
    }
    {
        const cuuint64_t dims[2] = {D_, S_}, st[1] = {D_ * 2};
        const cuuint32_t bx[2] = {144, 16};
        encode(fn, &to, CU_TENSOR_MAP_DATA_TYPE_BFLOAT16, 2, p.out, dims, st, bx, CU_TENSOR_MAP_SWIZZLE_NONE, CU_TENSOR_MAP_L2_PROMOTION_NONE);
    }
    cudaFuncSetAttribute(fused_kernel, cudaFuncAttributeMaxDynamicSharedMemorySize, SMEM_BYTES);
    cudaLaunchConfig_t cfg = {};
    cfg.gridDim = dim3(NCTA); cfg.blockDim = dim3(NTHR); cfg.dynamicSmemBytes = SMEM_BYTES; cfg.stream = cudaStreamPerThread;
    cudaLaunchAttribute at[1];
    at[0].id = cudaLaunchAttributeClusterDimension; at[0].val.clusterDim.x = 2; at[0].val.clusterDim.y = 1; at[0].val.clusterDim.z = 1;
    cfg.attrs = at; cfg.numAttrs = 1;
    int nclusters = 0;
    cudaOccupancyMaxActiveClusters(&nclusters, fused_kernel, &cfg);
    at[0].id = cudaLaunchAttributeCooperative; at[0].val.cooperative = 1;
    cfg.numAttrs = nclusters * 2 >= NCTA ? 0 : 1;
    cudaLaunchKernelEx(&cfg, fused_kernel, p, tw1a, tw1b, tw2, th3a, th3b, twr, twi, twm, tt, ttx, to, th3s, tws);
}
```

```cpp
#include <cuda_runtime.h>
#include <cuda_bf16.h>
#include <cuda_fp16.h>
#include <cuda.h>
#include <stdint.h>

namespace {

constexpr int S_ = 2048, D_ = 576, F_ = 4608;
constexpr int NCTA = 132, NTHR = 512;
constexpr int TP = 4736;
constexpr int SPEC_P = 296;
constexpr int NST = 6;
constexpr int A_BYTES = 16384, B_BYTES = 18432;
constexpr int IT_P1 = 24, IT_G2 = 40, IT_END = 76;
constexpr int SPIN_LIMIT = 1 << 22;
#define X2D 1350
constexpr int P2S = 2;
#define LEAD1 4
#define W1N 8
#define W1P 100
#define W1S 5
#define XDELAY 1100
#define HOK 2
#define HOK1 2
#define NCP 11300
#define P2K 4
#define RP1 2
#define RPX 1
#define W1L 1
#define PK2 1
#define SLP 64
#define X1D 2100
#define PF0 4
#define PFS 3
#define PFN 9
#define X1DELAY 2000
#define X1PACE 400

constexpr int OFF_A = 0;
constexpr int OFF_B = NST * A_BYTES;
constexpr int OFF_P = OFF_B + NST * B_BYTES;
constexpr int OFF_BAR = OFF_P;
constexpr int OFF_EPOCH = OFF_P + 480;
constexpr int OFF_MISC = OFF_P + 496;
constexpr int OFF_GB = OFF_P + 512;
constexpr int OFF_P2R = OFF_P + 1664;
constexpr int OFF_X1 = OFF_P2R;
constexpr int OFF_PROF = OFF_X1 + 18432;
constexpr int SMEM_BYTES = OFF_PROF + 512;
constexpr int QA = 13, QB = 7, QC = 13;
constexpr int TAB_BYTES = (QA + QB + QC) * 512;
constexpr int OFF_STAGE = OFF_B;
constexpr int OFF_STX = OFF_STAGE + 16384;
constexpr int OFF_TAB = OFF_STAGE + 20480;
constexpr int OFF_SPEC = OFF_TAB + TAB_BYTES;
constexpr int OFF_WRAW = OFF_SPEC + 19072;
constexpr int OFF_B3 = OFF_WRAW + 28672;
constexpr int OFF_MODA = OFF_B3 + 4096;
constexpr int OFF_MODC = OFF_MODA + 2560;
constexpr int OFF_RED = OFF_MODC + 3584;
constexpr int OFF_HEXP = OFF_RED + 512;
constexpr int OFF_SILU = OFF_RED + 1536;
static_assert(OFF_SILU + 1152 <= OFF_P && 6 * 28672 <= OFF_B3, "scratch overflow");
constexpr int OFF_STRIP = OFF_A;
static_assert(OFF_WRAW % 128 == 0 && OFF_STAGE % 128 == 0 && OFF_STX % 128 == 0, "align");
constexpr int BAR_FULL = 0, BAR_EMPTY = 6, BAR_TAB = 12, BAR_W = 13, BAR_P2N = 14, BAR_P2R = 16,
              BAR_XT = 17, BAR_RECV = 18, BAR_ROLE = 19, BAR_NC = 20, BAR_TAB2 = 21, BAR_XB = 22, BAR_GB = 23, BAR_HOLD = 24, BAR_W1GO = 25, BAR_UOK = 26, BAR_DONE = 30, BAR_X = 31, BAR_ST = 47;

struct Cos1152 { double c[1152]; };
constexpr double cx_cos(double x) { double t = 1, s = 1; for (int i = 1; i < 14; i++) { t *= -x * x / ((2 * i - 1) * (2 * i)); s += t; } return s; }
constexpr Cos1152 make_cos() {
    Cos1152 r{};
    for (int i = 0; i <= 288; i++) {
        double v = (i == 288) ? 0.0 : cx_cos(3.14159265358979323846 * 2.0 * i / 1152.0);
        r.c[i] = v; r.c[576 - i] = -v; r.c[576 + i] = -v; r.c[(1152 - i) % 1152] = v;
    }
    return r;
}
constexpr uint32_t cx_f2h(double v) {
    uint32_t s = v < 0 ? 0x8000u : 0u; double a = v < 0 ? -v : v;
    if (a < 1e-9) return 0;
    int e = 0;
    while (a >= 2.0) { a *= 0.5; e++; }
    while (a < 1.0 && e > -14) { a *= 2.0; e--; }
    double m = a * 1024.0; uint32_t mi = (uint32_t)m; double fr = m - mi;
    if (fr > 0.5 || (fr == 0.5 && (mi & 1))) mi++;
    return s | (uint32_t)(((e + 14) << 10) + mi);
}
struct Tab { uint32_t w[(QA + QB + QC) * 128]; };
constexpr Tab make_tab() {
    Tab t{};
    Cos1152 ct = make_cos();
    auto C = [&](int num, int den) { return ct.c[(num % den) * (1152 / den)]; };
    auto Sn = [&](int num, int den) { return ct.c[((num % den) * (1152 / den) + 864) % 1152]; };
    auto put = [&](int q0, int idx, int lane, double lo, double hi) { t.w[((q0 + idx / 4) * 32 + lane) * 4 + idx % 4] = cx_f2h(lo) | (cx_f2h(hi) << 16); };
    for (int lane = 0; lane < 32; lane++) {
        const int g = lane >> 2, q = lane & 3;
        for (int mt = 0; mt < 3; mt++) {
            const int ka = 8 * mt + g;
            for (int r = 0; r < 10; r++) {
                const int im = r & 1, i0 = (r >> 1) * 2;
                double v[2] = {0, 0};
                for (int e = 0; e < 2; e++) { int i = i0 + e, d1 = 4 * i + q; if (i < 9 && ka <= 18) v[e] = (im ? -Sn(ka * d1, 36) : C(ka * d1, 36)) / 8; }
                put(0, r < 8 ? mt * 8 + r : 16 + 2 * mt + r, lane, v[0], v[1]);
            }
            for (int v = 0; v < 2; v++) {
                const int d2 = 4 * q + v;
                put(0, 30 + (mt * 2 + v) * 2, lane, C(ka * d2, 576) * 4 / 3, C(ka * (d2 + 2), 576) * 4 / 3);
                put(0, 31 + (mt * 2 + v) * 2, lane, Sn(ka * d2, 576) * 4 / 3, Sn(ka * (d2 + 2), 576) * 4 / 3);
            }
        }
        for (int v = 0; v < 2; v++) for (int nt = 0; nt < 2; nt++) {
            const int kb = 2 * (g >> 1) + nt, part = g & 1;
            double b0[2] = {0, 0}, b1[2] = {0, 0};
            for (int e = 0; e < 2; e++) { int d2 = 4 * q + 2 * e + v; double c = C(kb * d2, 16) / 4, s = Sn(kb * d2, 16) / 4;
                b0[e] = part ? -s : c; b1[e] = part ? c : s; }
            put(0, 42 + (v * 2 + nt) * 2, lane, b0[0], b0[1]); put(0, 43 + (v * 2 + nt) * 2, lane, b1[0], b1[1]);
        }
        t.w[((QA - 1) * 32 + lane) * 4 + 2] = 0x3F803F80u;
        for (int par = 0; par < 2; par++) for (int a = 0; a < 4; a++) {
            const int ja = 2 * (q + 4 * (a >> 1)) + par; const double c = C(g * ja, 16) / 4, s = Sn(g * ja, 16) / 4;
            put(QA, par * 4 + a, lane, (a & 1) ? -s : c, (a & 1) ? c : s);
        }
        for (int h = 0; h < 2; h++) {
            put(QA, 8 + 2 * h, lane, C((g + 8 * h) * (2 * q), 128) / 2, C((g + 8 * h) * (2 * q + 1), 128) / 2);
            put(QA, 9 + 2 * h, lane, Sn((g + 8 * h) * (2 * q), 128) / 2, Sn((g + 8 * h) * (2 * q + 1), 128) / 2);
            put(QA, 16 + 2 * h, lane, C(g * (8 * h + 2 * q), 128), C(g * (8 * h + 2 * q + 1), 128));
            put(QA, 17 + 2 * h, lane, Sn(g * (8 * h + 2 * q), 128), Sn(g * (8 * h + 2 * q + 1), 128));
        }
        put(QA, 12, lane, C(g * 2 * q, 8) / 2, C(g * (2 * q + 1), 8) / 2);
        put(QA, 15, lane, C(g * 2 * q, 8) / 2, C(g * (2 * q + 1), 8) / 2);
        put(QA, 13, lane, Sn(g * 2 * q, 8) / 2, Sn(g * (2 * q + 1), 8) / 2);
        put(QA, 14, lane, -Sn(g * 2 * q, 8) / 2, -Sn(g * (2 * q + 1), 8) / 2);
        for (int u = 0; u < 4; u++) {
            const int ja = 2 * ((g >> 1) + 4 * (u & 1)) + (u >> 1), part = g & 1; double b0[2] = {0, 0}, b1[2] = {0, 0};
            for (int e = 0; e < 2; e++) { int ka = 2 * q + e; double c = C(ja * ka, 16) / 4, s = Sn(ja * ka, 16) / 4;
                b0[e] = part ? s : c; b1[e] = part ? c : -s; }
            put(QA, 20 + u * 2, lane, b0[0], b0[1]); put(QA, 21 + u * 2, lane, b1[0], b1[1]);
        }
        for (int m2 = 0; m2 < 2; m2++) {
            const int d2 = 2 * g + m2;
            for (int a = 0; a < 4; a++) {
                const int kb = 2 * q + (a >> 1); const double c = C(d2 * kb, 16) / 4, s = Sn(d2 * kb, 16) / 4;
                put(QA + QB, m2 * 4 + a, lane, (a & 1) ? s : c, (a & 1) ? c : -s);
            }
            for (int mt = 0; mt < 3; mt++) {
                const int ka = 8 * mt + 2 * q;
                put(QA + QB, 8 + (m2 * 3 + mt) * 2, lane, C(ka * d2, 576) * 4 / 3, C((ka + 1) * d2, 576) * 4 / 3);
                put(QA + QB, 9 + (m2 * 3 + mt) * 2, lane, Sn(ka * d2, 576) * 4 / 3, Sn((ka + 1) * d2, 576) * 4 / 3);
            }
        }
        for (int mt = 0; mt < 3; mt++) for (int nt = 0; nt < 5; nt++) {
            const int i = 2 * nt + (g & 1), d1 = 4 * i + (g >> 1); double b0[2] = {0, 0}, b1[2] = {0, 0};
            for (int e = 0; e < 2; e++) { int ka = 8 * mt + 2 * q + e;
                if (ka <= 18 && i < 9) { double wt = (ka == 0 || ka == 18) ? 0.125 : 0.25; b0[e] = wt * C(ka * d1, 36); b1[e] = -wt * Sn(ka * d1, 36); } }
            const int o = (QA + QB + 5) * 128 + (mt * 5 + nt) * 64 + lane;
            t.w[o] = cx_f2h(b0[0]) | (cx_f2h(b0[1]) << 16); t.w[o + 32] = cx_f2h(b1[0]) | (cx_f2h(b1[1]) << 16);
        }
    }
    return t;
}
__device__ __align__(128) const Tab g_tab = make_tab();

struct Scratch {
    uint32_t cnt[30 * 32];
    uint32_t slot[96];
    uint32_t mod[2304];
    uint32_t modc[896 + 288];
    uint32_t T[128 * TP];
    uint4 h3[128 * 1152];
    uint4 U[72 * 4 * 1152];
};
__device__ __align__(1024) Scratch g_scr;
#define g_cnt (p.scr->cnt)
#define g_slot (p.scr->slot)
#define g_mod (p.scr->mod)
#define g_T (p.scr->T)
#define g_h3 (p.scr->h3)
#define g_U (p.scr->U)
constexpr int CNT_EPOCH = 0, CNT_H3 = 1, CNT_X1 = 26, CNT_NC = 27, CNT_U = 2;
#define PROFT(i) do {} while (0)
#define PROFDUMP() do {} while (0)
#define PROF0(i) do {} while (0)

__device__ __forceinline__ void mbar_init(uint32_t bar, uint32_t cnt) { asm volatile("mbarrier.init.shared::cta.b64 [%0], %1;" :: "r"(bar), "r"(cnt) : "memory"); }
__device__ __forceinline__ void mbar_expect(uint32_t bar, uint32_t bytes) { asm volatile("mbarrier.arrive.expect_tx.shared::cta.b64 _, [%0], %1;" :: "r"(bar), "r"(bytes) : "memory"); }
__device__ __forceinline__ void mbar_arrive(uint32_t bar) { asm volatile("mbarrier.arrive.shared::cta.b64 _, [%0];" :: "r"(bar) : "memory"); }
__device__ __forceinline__ void mbar_arrive_n(uint32_t bar, uint32_t n) { asm volatile("mbarrier.arrive.shared::cta.b64 _, [%0], %1;" :: "r"(bar), "r"(n) : "memory"); }
__device__ __forceinline__ void mbar_arrive_remote(uint32_t rbar) { asm volatile("mbarrier.arrive.relaxed.cluster.shared::cluster.b64 _, [%0];" :: "r"(rbar) : "memory"); }
__device__ __forceinline__ void mbar_wait(uint32_t bar, uint32_t parity) {
    asm volatile("{.reg .pred p; .reg .u32 c;\n"
        "mbarrier.try_wait.parity.shared::cta.b64 p, [%0], %1;\n@p bra.uni DONE;\nmov.u32 c, 0;\n"
        "LOOP: mbarrier.try_wait.parity.shared::cta.b64 p, [%0], %1;\n@p bra.uni DONE;\n"
        "add.u32 c, c, 1;\nsetp.lt.u32 p, c, %2;\n@p bra.uni LOOP;\ntrap;\nDONE:}" :: "r"(bar), "r"(parity), "n"(SPIN_LIMIT) : "memory");
}
__device__ __forceinline__ bool mbar_test(uint32_t bar, uint32_t parity) {
    uint32_t ok; asm volatile("{.reg .pred p; mbarrier.test_wait.parity.shared::cta.b64 p, [%1], %2; selp.u32 %0, 1, 0, p;}" : "=r"(ok) : "r"(bar), "r"(parity) : "memory"); return ok; }
__device__ __forceinline__ uint32_t mapa(uint32_t a, uint32_t rank) { uint32_t r; asm("mapa.shared::cluster.u32 %0, %1, %2;" : "=r"(r) : "r"(a), "r"(rank)); return r; }
__device__ __forceinline__ uint32_t clk32() { uint32_t r; asm volatile("mov.u32 %0, %%clock;" : "=r"(r)); return r; }
__device__ __forceinline__ void hb() {
    asm volatile("{.reg .b32 a, b; .reg .pred p; mma.sync.aligned.m16n8k8.row.col.f16.f16.f16.f16 {a, b}, {%0,%0}, {%0}, {%0,%0};\n"
                 "setp.ne.u32 p, a, 0; @p trap;}" :: "r"(0));
}
__device__ __forceinline__ void spin_until(uint32_t t) {
    #pragma unroll 1
    while (__any_sync(~0u, (int)(clk32() - t) < -SLP * 4)) { __nanosleep(SLP); hb(); }
    #pragma unroll 1
    while (__any_sync(~0u, (int)(clk32() - t) < 0)) {}
}
__device__ __forceinline__ bool elect() { uint32_t r; asm volatile("{.reg .pred p; elect.sync _|p, 0xffffffff; selp.u32 %0, 1, 0, p;}" : "=r"(r)); return r; }
__device__ __forceinline__ void bar_sync(int id, int n) { asm volatile("bar.sync %0, %1;" :: "r"(id), "r"(n) : "memory"); }
__device__ __forceinline__ void bulk_load(uint32_t dst, const void* src, uint32_t bytes, uint32_t bar) {
    asm volatile("cp.async.bulk.shared::cluster.global.mbarrier::complete_tx::bytes [%0], [%1], %2, [%3];" :: "r"(dst), "l"(src), "r"(bytes), "r"(bar) : "memory"); }
__device__ __forceinline__ void tma2(uint32_t dst, const CUtensorMap* m, int c0, int c1, uint32_t bar) {
    asm volatile("cp.async.bulk.tensor.2d.shared::cluster.global.mbarrier::complete_tx::bytes [%0], [%1, {%3, %4}], [%2];" :: "r"(dst), "l"(m), "r"(bar), "r"(c0), "r"(c1) : "memory"); }
__device__ __forceinline__ void tma3(uint32_t dst, const CUtensorMap* m, int c0, int c1, int c2, uint32_t bar) {
    asm volatile("cp.async.bulk.tensor.3d.shared::cluster.global.mbarrier::complete_tx::bytes [%0], [%1, {%3, %4, %5}], [%2];" :: "r"(dst), "l"(m), "r"(bar), "r"(c0), "r"(c1), "r"(c2) : "memory"); }
__device__ __forceinline__ void tma4(uint32_t dst, const CUtensorMap* m, int c0, int c1, int c2, int c3, uint32_t bar) {
    asm volatile("cp.async.bulk.tensor.4d.shared::cluster.global.mbarrier::complete_tx::bytes [%0], [%1, {%3, %4, %5, %6}], [%2];" :: "r"(dst), "l"(m), "r"(bar), "r"(c0), "r"(c1), "r"(c2), "r"(c3) : "memory"); }
__device__ __forceinline__ void fence_async_g() { asm volatile("fence.proxy.async.global;" ::: "memory"); }
__device__ __forceinline__ void fence_async_s() { asm volatile("fence.proxy.async.shared::cta;" ::: "memory"); }
__device__ __forceinline__ uint4 lds128(uint32_t a) { uint4 v; asm volatile("ld.shared.v4.u32 {%0,%1,%2,%3}, [%4];" : "=r"(v.x), "=r"(v.y), "=r"(v.z), "=r"(v.w) : "r"(a) : "memory"); return v; }
__device__ __forceinline__ uint32_t lds32(uint32_t a) { uint32_t v; asm volatile("ld.shared.u32 %0, [%1];" : "=r"(v) : "r"(a) : "memory"); return v; }
__device__ __forceinline__ void sts128(uint32_t a, uint4 v) { asm volatile("st.shared.v4.u32 [%0], {%1,%2,%3,%4};" :: "r"(a), "r"(v.x), "r"(v.y), "r"(v.z), "r"(v.w) : "memory"); }
__device__ __forceinline__ void sts32(uint32_t a, uint32_t v) { asm volatile("st.shared.u32 [%0], %1;" :: "r"(a), "r"(v) : "memory"); }
__device__ __forceinline__ void sts16(uint32_t a, uint32_t v) { asm volatile("st.shared.u16 [%0], %1;" :: "r"(a), "h"((uint16_t)v) : "memory"); }
__device__ __forceinline__ uint4 ldx128(const void* p) {
    uint4 v; asm volatile("{.reg .b128 t; .reg .b64 a, b; ld.relaxed.gpu.global.b128 t, [%4]; mov.b128 {a, b}, t; mov.b64 {%0,%1}, a; mov.b64 {%2,%3}, b;}"
        : "=r"(v.x), "=r"(v.y), "=r"(v.z), "=r"(v.w) : "l"(p) : "memory"); return v; }
__device__ __forceinline__ void stx128(void* p, uint4 v) {
    asm volatile("{.reg .b128 t; .reg .b64 a, b; mov.b64 a, {%1,%2}; mov.b64 b, {%3,%4}; mov.b128 t, {a, b}; st.relaxed.gpu.global.b128 [%0], t;}"
        :: "l"(p), "r"(v.x), "r"(v.y), "r"(v.z), "r"(v.w) : "memory"); }
__device__ __forceinline__ uint32_t ld_acquire(const uint32_t* p) { uint32_t v; asm volatile("ld.acquire.gpu.global.u32 %0, [%1];" : "=r"(v) : "l"(p) : "memory"); return v; }
__device__ __forceinline__ void st_relaxed(uint32_t* p, uint32_t v) { asm volatile("st.relaxed.gpu.global.u32 [%0], %1;" :: "l"(p), "r"(v) : "memory"); }
__device__ __forceinline__ void red_release(uint32_t* p) { asm volatile("red.release.gpu.global.add.u32 [%0], 1;" :: "l"(p) : "memory"); }
template <int SLEEP> __device__ __forceinline__ void wait_count(const uint32_t* p, uint32_t target) {
    int it = 0; while ((int)(ld_acquire(p) - target) < 0) { if (SLEEP) __nanosleep(SLEEP); if (++it > SPIN_LIMIT) __trap(); }
}
__device__ __forceinline__ uint32_t ldg_nc32(const void* p) { uint32_t v; asm volatile("ld.global.nc.L1::no_allocate.u32 %0, [%1];" : "=r"(v) : "l"(p)); return v; }
__device__ __forceinline__ uint32_t ldg_nc16(const void* p) { uint16_t v; asm volatile("ld.global.nc.u16 %0, [%1];" : "=h"(v) : "l"(p)); return v; }
__device__ __forceinline__ float bf_lo(uint32_t w) { return __uint_as_float(w << 16); }
__device__ __forceinline__ float bf_hi(uint32_t w) { return __uint_as_float(w & 0xFFFF0000u); }
__device__ __forceinline__ uint32_t pack_bf(float lo, float hi) { uint32_t r; asm("cvt.rn.bf16x2.f32 %0, %1, %2;" : "=r"(r) : "f"(hi), "f"(lo)); return r; }
__device__ __forceinline__ uint32_t pack_h(float lo, float hi) { uint32_t r; asm("cvt.rn.f16x2.f32 %0, %1, %2;" : "=r"(r) : "f"(hi), "f"(lo)); return r; }
__device__ __forceinline__ float bf_round(float v) { return bf_lo(pack_bf(v, 0.f)); }
__device__ __forceinline__ uint32_t hmul2(uint32_t a, uint32_t b) { uint32_t r; asm("mul.rn.f16x2 %0, %1, %2;" : "=r"(r) : "r"(a), "r"(b)); return r; }
__device__ __forceinline__ uint32_t hfma2(uint32_t a, uint32_t b, uint32_t c) { uint32_t r; asm("fma.rn.f16x2 %0, %1, %2, %3;" : "=r"(r) : "r"(a), "r"(b), "r"(c)); return r; }
__device__ __forceinline__ uint32_t hfms2(uint32_t a, uint32_t b, uint32_t c) { uint32_t r; asm("{.reg .b32 t; neg.f16x2 t, %3; fma.rn.f16x2 %0, %1, %2, t;}" : "=r"(r) : "r"(a), "r"(b), "r"(c)); return r; }
__device__ __forceinline__ uint32_t hadd2(uint32_t a, uint32_t b) { uint32_t r; asm("add.rn.f16x2 %0, %1, %2;" : "=r"(r) : "r"(a), "r"(b)); return r; }
__device__ __forceinline__ uint32_t hsub2(uint32_t a, uint32_t b) { uint32_t r; asm("sub.rn.f16x2 %0, %1, %2;" : "=r"(r) : "r"(a), "r"(b)); return r; }
__device__ __forceinline__ void cmul_neg(uint32_t& re, uint32_t& im, uint32_t c, uint32_t s) { uint32_t a = hfma2(re, c, hmul2(im, s)), b = hfms2(im, c, hmul2(re, s)); re = a; im = b; }
__device__ __forceinline__ void cmul_pos(uint32_t& re, uint32_t& im, uint32_t c, uint32_t s) { uint32_t a = hfms2(re, c, hmul2(im, s)), b = hfma2(im, c, hmul2(re, s)); re = a; im = b; }
__device__ __forceinline__ void mma_h(uint32_t& d0, uint32_t& d1, uint32_t a0, uint32_t a1, uint32_t a2, uint32_t a3, uint32_t b0, uint32_t b1) {
    asm("mma.sync.aligned.m16n8k16.row.col.f16.f16.f16.f16 {%0,%1}, {%2,%3,%4,%5}, {%6,%7}, {%0,%1};" : "+r"(d0), "+r"(d1) : "r"(a0), "r"(a1), "r"(a2), "r"(a3), "r"(b0), "r"(b1)); }
__device__ __forceinline__ void mma_h8(uint32_t& d0, uint32_t& d1, uint32_t a0, uint32_t a1, uint32_t b0) {
    asm("mma.sync.aligned.m16n8k8.row.col.f16.f16.f16.f16 {%0,%1}, {%2,%3}, {%4}, {%0,%1};" : "+r"(d0), "+r"(d1) : "r"(a0), "r"(a1), "r"(b0)); }
template <int NQ> __device__ __forceinline__ void load_tab(uint32_t (&r)[NQ * 4], uint32_t addr) {
    #pragma unroll
    for (int i = 0; i < NQ; i++) { uint4 v = lds128(addr + i * 512); r[4 * i] = v.x; r[4 * i + 1] = v.y; r[4 * i + 2] = v.z; r[4 * i + 3] = v.w; }
}
__device__ __forceinline__ float gelu2(float x) {
    float t = x * fmaf(x * x, 0.044715f * 0.7978845608028654f, 0.7978845608028654f), th;
    asm volatile("tanh.approx.f32 %0, %1;" : "=f"(th) : "f"(t));
    return fmaf(x, th, x);
}
constexpr uint32_t SM0 = 1024;
__device__ __forceinline__ constexpr uint32_t desc_lo(uint32_t off, uint32_t lbo) { return ((SM0 + off) >> 4) | ((lbo >> 4) << 16); }
constexpr uint32_t DHI_A = (1024 >> 4) | (1u << 30), DHI_H3 = 256 >> 4, DHI_U = 128 >> 4;
#define WG_FENCE() asm volatile("wgmma.fence.sync.aligned;" ::: "memory")
#define WG_COMMIT() asm volatile("wgmma.commit_group.sync.aligned;" ::: "memory")
#define WG_WAIT(n) asm volatile("wgmma.wait_group.sync.aligned %0;" :: "n"(n) : "memory")
#define R4(b) "+f"(d[b]), "+f"(d[b + 1]), "+f"(d[b + 2]), "+f"(d[b + 3])
#define R12(b) R4(b), R4(b + 4), R4(b + 8)
#define R36(b) R12(b), R12(b + 12), R12(b + 24)
template <uint32_t BHI> __device__ __forceinline__ void wgmma144(float (&d)[72], uint32_t da, uint32_t db, int acc) {
    asm volatile("{.reg .pred p; .reg .b64 a, b; setp.ne.b32 p, %74, 0; mov.b64 a, {%72, %75}; mov.b64 b, {%73, %76};\n"
        "wgmma.mma_async.sync.aligned.m64n144k16.f32.bf16.bf16 {%0,%1,%2,%3,%4,%5,%6,%7,%8,%9,%10,%11,%12,%13,%14,%15,%16,%17,%18,%19,%20,%21,%22,%23,"
        "%24,%25,%26,%27,%28,%29,%30,%31,%32,%33,%34,%35,%36,%37,%38,%39,%40,%41,%42,%43,%44,%45,%46,%47,"
        "%48,%49,%50,%51,%52,%53,%54,%55,%56,%57,%58,%59,%60,%61,%62,%63,%64,%65,%66,%67,%68,%69,%70,%71}, a, b, p, 1, 1, 1, 1;}\n"
        : R36(0), R36(36) : "r"(da), "r"(db), "r"(acc), "n"(DHI_A), "n"(BHI));
}
__device__ __forceinline__ void wgmma40_rs(float (&d)[20], uint32_t a0, uint32_t a1, uint32_t a2, uint32_t a3, uint32_t db, int acc) {
    asm volatile("{.reg .pred p; .reg .b64 b; setp.ne.b32 p, %25, 0; mov.b64 b, {%24, %26};\n"
        "wgmma.mma_async.sync.aligned.m64n40k16.f32.f16.f16 {%0,%1,%2,%3,%4,%5,%6,%7,%8,%9,%10,%11,%12,%13,%14,%15,%16,%17,%18,%19}, {%20,%21,%22,%23}, b, p, 1, 1, 0;}\n"
        : R12(0), R4(12), R4(16) : "r"(a0), "r"(a1), "r"(a2), "r"(a3), "r"(db), "r"(acc), "n"(DHI_H3));
}
__device__ __forceinline__ void wgmma72(float (&d)[36], uint32_t da, uint32_t db, int acc) {
    asm volatile("{.reg .pred p; .reg .b64 a, b; setp.ne.b32 p, %38, 0; mov.b64 a, {%36, %39}; mov.b64 b, {%37, %40};\n"
        "wgmma.mma_async.sync.aligned.m64n72k16.f32.bf16.bf16 {%0,%1,%2,%3,%4,%5,%6,%7,%8,%9,%10,%11,%12,%13,%14,%15,%16,%17,%18,%19,%20,%21,%22,%23,"
        "%24,%25,%26,%27,%28,%29,%30,%31,%32,%33,%34,%35}, a, b, p, 1, 1, 1, 1;}\n"
        : R36(0) : "r"(da), "r"(db), "r"(acc), "n"(DHI_A), "n"(DHI_H3));
}

__device__ __forceinline__ int g2_kb(int n, int kh, int gi, int c2) {
    if (n < 4) return 36 * kh + 9 * n + 8;
    if (n == 4) return 9 * gi + 4 * c2 + 2 * kh + 1;
    const int w = n > 20, m = n - (w ? 19 : 5);
    return 9 * ((gi * w + (m >> 1)) & 7) + 4 * (n == 35 ? 1 - c2 : m & 1) + 2 * kh + w;
}

template <uint32_t BHI, int S> __device__ __forceinline__ void mma_block(float (&d)[72], uint32_t bars, uint32_t da0, uint32_t db0, uint32_t ph) {
    mbar_wait(bars + 8 * (BAR_FULL + S), ph);
    WG_FENCE();
    #pragma unroll
    for (int k = 0; k < 4; k++) wgmma144<BHI>(d, da0 + S * (A_BYTES / 16) + k * 128, db0 + S * (B_BYTES / 16) + k * 288, 1);
    WG_COMMIT();
    WG_WAIT(1);
}

struct Params {
    const uint16_t *wmod, *c, *x;
    Scratch* scr;
    const Tab* tab;
    const uint16_t *wr, *wi, *w1, *b1, *w2, *b2;
    uint16_t* out;
};

__device__ __forceinline__ void mma_bf(float (&d)[4], const uint32_t (&a)[4], uint32_t b0, uint32_t b1) {
    asm("mma.sync.aligned.m16n8k16.row.col.f32.bf16.bf16.f32 {%0,%1,%2,%3}, {%4,%5,%6,%7}, {%8,%9}, {%0,%1,%2,%3};"
        : "+f"(d[0]), "+f"(d[1]), "+f"(d[2]), "+f"(d[3]) : "r"(a[0]), "r"(a[1]), "r"(a[2]), "r"(a[3]), "r"(b0), "r"(b1)); }
__device__ __forceinline__ void ldsm4t(uint32_t (&a)[4], uint32_t addr) {
    asm volatile("ldmatrix.sync.aligned.m8n8.x4.trans.shared.b16 {%0,%1,%2,%3}, [%4];" : "=r"(a[0]), "=r"(a[1]), "=r"(a[2]), "=r"(a[3]) : "r"(addr) : "memory"); }
__device__ __forceinline__ void ln_stats(const uint32_t (&w)[9], const uint32_t (&one)[9], int g, int q, float& r, float& mr) {
    float c[2][4] = {};
    #pragma unroll
    for (int p = 0; p < 9; p++)
        asm("mma.sync.aligned.m16n8k8.row.col.f32.bf16.bf16.f32 {%0,%1,%2,%3}, {%4,%5}, {%4}, {%0,%1,%2,%3};"
            : "+f"(c[p & 1][0]), "+f"(c[p & 1][1]), "+f"(c[p & 1][2]), "+f"(c[p & 1][3]) : "r"(w[p]), "r"(one[p]));
    const float t = (g & 1) ? c[0][1] + c[1][1] : c[0][0] + c[1][0];
    float s1 = (c[0][2] + c[1][2]) + (c[0][3] + c[1][3]), s2 = __shfl_sync(~0u, t, 9 * q) + __shfl_sync(~0u, t, 9 * q + 4);
    #pragma unroll
    for (int o = 1; o < 4; o <<= 1) { s1 += __shfl_xor_sync(~0u, s1, o); s2 += __shfl_xor_sync(~0u, s2, o); }
    const float m = s1 * (1.f / D_);
    asm("rsqrt.approx.ftz.f32 %0, %1;" : "=f"(r) : "f"(fmaxf(fmaf(s2, 1.f / D_, -m * m), 0.f) + 1e-5f));
    mr = -m * r;
}
__device__ __forceinline__ float silu(float v) { return __fdividef(v, 1.f + __expf(-v)); }
__device__ __forceinline__ uint32_t bfma2(uint32_t a, uint32_t b, uint32_t c) { uint32_t r; asm("fma.rn.bf16x2 %0, %1, %2, %3;" : "=r"(r) : "r"(a), "r"(b), "r"(c)); return r; }
__device__ __forceinline__ void radix16(const uint4 (&V)[4], const uint32_t (&B)[16], uint4 (&o)[4]) {
    #pragma unroll
    for (int nt = 0; nt < 4; nt++) o[nt] = make_uint4(0, 0, 0, 0);
    #pragma unroll
    for (int u = 0; u < 4; u++)
        #pragma unroll
        for (int nt = 0; nt < 4; nt++) {
            const uint32_t b = B[((u >> 1) * 4 + nt) * 2 + (u & 1)];
            mma_h8(o[nt].x, o[nt].y, V[u].x, V[u].y, b); mma_h8(o[nt].z, o[nt].w, V[u].z, V[u].w, b);
        }
}
template <int OFF, int N> __device__ __forceinline__ void gelu_store(const float (&d)[N], char* p, int q) {
    uint32_t w[9];
    #pragma unroll
    for (int blk = 0; blk < 9; blk++) w[blk] = pack_bf(gelu2(d[OFF + 4 * blk]), gelu2(d[OFF + 4 * blk + 1]));
    asm volatile("st.v4.u32 [%0], {%1,%2,%3,%4};" :: "l"(p + q * 128), "r"(w[0]), "r"(w[1]), "r"(w[2]), "r"(w[3]) : "memory");
    asm volatile("st.v4.u32 [%0+512], {%1,%2,%3,%4};" :: "l"(p + q * 128), "r"(w[4]), "r"(w[5]), "r"(w[6]), "r"(w[7]) : "memory");
    asm volatile("st.u32 [%0+1024], %1;" :: "l"(p + q * 4), "r"(w[8]) : "memory");
}

__global__ void __cluster_dims__(2, 1, 1) __launch_bounds__(NTHR, 1)
fused_kernel(const Params p,
             const __grid_constant__ CUtensorMap tm_w1a, const __grid_constant__ CUtensorMap tm_w1b, const __grid_constant__ CUtensorMap tm_w2,
             const __grid_constant__ CUtensorMap tm_h3a, const __grid_constant__ CUtensorMap tm_h3b,
             const __grid_constant__ CUtensorMap tm_wr, const __grid_constant__ CUtensorMap tm_wi, const __grid_constant__ CUtensorMap tm_wm,
             const __grid_constant__ CUtensorMap tm_t, const __grid_constant__ CUtensorMap tm_tx, const __grid_constant__ CUtensorMap tm_o,
             const __grid_constant__ CUtensorMap tm_h3s, const __grid_constant__ CUtensorMap tm_ws)
{
    extern __shared__ __align__(1024) char smem_raw[];
    const uint32_t t0 = clk32();
    const uint32_t sm = __shfl_sync(~0u, ((uint32_t)__cvta_generic_to_shared(smem_raw) + 1023u) & ~1023u, 0);
    const int tid = threadIdx.x, warp = __shfl_sync(~0u, tid >> 5, 0), lane = tid & 31, g = lane >> 2, q = lane & 3;
    const int b = blockIdx.x;
    const uint32_t rank = b & 1;
    const uint32_t bars = sm + OFF_BAR;
    const bool rowcta = b < 128;

    auto nc_issue = [&](int st, uint32_t sl) {
        const int pass = st >= 18;
        mbar_expect(bars + 8 * (BAR_X + sl), 28672);
        tma3(sm + sl * 28672, &tm_wm, 0, 32 * (st - 18 * pass), 18 + 28 * pass + 7 * (b - 128), bars + 8 * (BAR_X + sl));
    };
    uint32_t epoch;
    const bool strip = b < 72 && !(b & 1);
    const bool sil = (warp >> 2) == 2 && lane < 24 && (strip || !rowcta);
    uint32_t cw[3];
    if (elect()) {
        mbar_init(bars + 8 * (BAR_X + warp), rowcta || warp < 6 ? 1 : 14);
        if (warp >= 12) {
            if (strip) { const uint32_t sb = bars + 8 * (BAR_ST + warp - 12);
                mbar_init(sb, 1); mbar_expect(sb, 9216); tma2(sm + OFF_STRIP + (warp - 12) * 9216, &tm_ws, 16 * b, 144 * (warp - 12), sb); }
        } else if (warp == 7) {
            mbar_init(bars + 8 * BAR_TAB, 1); mbar_expect(bars + 8 * BAR_TAB, rowcta ? QA * 512 + 16 : 16);
            bulk_load(sm + OFF_EPOCH, g_cnt + CNT_EPOCH * 32, 16, bars + 8 * BAR_TAB);
            if (rowcta) bulk_load(sm + OFF_TAB, p.tab, QA * 512, bars + 8 * BAR_TAB);
        } else if (b + 132 * warp < 576) {
            asm volatile("cp.async.bulk.prefetch.L2.global [%0], 2304;" :: "l"(p.wmod + (b + 132 * warp) * 3456) : "memory");
        }
    }
    if (sil) {
        #pragma unroll
        for (int u = 0; u < 3; u++) cw[u] = ldg_nc32(p.c + 144 * (warp - 8) + 48 * u + 2 * lane);
    }
    if (warp == 6) hb();
    __syncthreads();
    if (!rowcta) { if (warp < 6 && elect()) nc_issue(warp, warp); }
    if (warp == 5 || warp == 6) {
        if (elect()) {
            if (warp == 5) {
                for (int i = BAR_W; i < BAR_X; i++) mbar_init(bars + 8 * i, i == BAR_DONE || i == BAR_NC ? 4 : i == BAR_W1GO ? 2 : 1);
                mbar_expect(bars + 8 * BAR_W, 28672); mbar_expect(bars + 8 * BAR_TAB2, (QB + QC) * 512);
                mbar_expect(bars + 8 * BAR_ROLE, 4); mbar_expect(bars + 8 * BAR_P2R, 9216); mbar_expect(bars + 8 * BAR_RECV, 18432); mbar_expect(bars + 8 * BAR_XT, 18432);
            } else {
                for (int i = 0; i < 2 * NST; i++) mbar_init(bars + 8 * i, 2);
                for (int i = 0; i < NST; i++) mbar_expect(bars + 8 * (BAR_FULL + i), A_BYTES);
            }
            asm volatile("fence.mbarrier_init.release.cluster;" ::: "memory");
        }
    } else if (warp >= 12 && elect())
        asm volatile("prefetch.tensormap [%0];" :: "l"(warp == 12 ? &tm_wr : warp == 13 ? &tm_wi : warp == 14 ? &tm_t : &tm_tx) : "memory");
    uint32_t sb[18];
    if ((warp >> 2) == 2) {
        if (sil) {
            #pragma unroll
            for (int u = 0; u < 3; u++) sts32(sm + OFF_SILU + (72 * (warp - 8) + 24 * u + lane) * 4, pack_bf(silu(bf_lo(cw[u])), silu(bf_hi(cw[u]))));
        }
        __syncwarp();
        if (strip) {
            #pragma unroll
            for (int u = 0; u < 18; u++) sb[u] = lds32(sm + OFF_SILU + (72 * (warp - 8) + 4 * u + q) * 4);
        }
    }
    if (rowcta && elect()) {
        if (XDELAY) while ((int)(clk32() - t0) < XDELAY) {}
        mbar_expect(bars + 8 * (BAR_X + warp), 1152);
        bulk_load(sm + OFF_STAGE + warp * 1152, p.x + (size_t)(b + 128 * warp) * D_, 1152, bars + 8 * (BAR_X + warp));
    }
    __syncwarp();
    hb();

    const int trow = 4 * (b & 7) + ((b >> 4) & 3) + 64 * ((b >> 3) & 1) + 32 * (b >> 6);
    uint32_t* const tptr = g_T + (size_t)trow * TP + (warp < 9 ? q * 288 + 32 * warp : 4608 + 8 * q) + 4 * g;
    const int tstr = warp < 9 ? 1152 : 32;
    const uint32_t scol = sm + OFF_SPEC + (q * SPEC_P + (warp < 8 ? 72 * (warp >> 1) + 40 * (warp & 1) + 4 * g : warp == 8 ? 72 * (g >> 1) + 32 + 4 * (g & 1) : 288 + 4 * g)) * 4;
    const int wc0 = (b >> 3) * 289 + 72 * ((b & 7) >> 1) + 40 * (b & 1);

    uint32_t xw[9], one[9], t_st = t0, hexp = 0;
    if (!rowcta) {
        const int nst = b < 130 ? 36 : 18;
        __syncthreads();
        asm volatile("barrier.cluster.arrive.relaxed.aligned;" ::: "memory");
        mbar_wait(bars + 8 * BAR_TAB, 0);
        epoch = lds32(sm + OFF_EPOCH);
        if (warp == 14) {
            uint32_t sl = 0, ph = 0;
            #pragma unroll 1
            for (int st = 6; st < nst; st++) {
                mbar_wait(bars + 8 * (BAR_X + 6 + sl), ph);
                if (elect()) nc_issue(st, sl);
                if (++sl == 6) { sl = 0; ph ^= 1; }
            }
        } else if (warp < 14) {
            uint32_t sl = 0, ph = 0;
            const uint32_t ad0 = sm + (warp >> 1) * 4096 + ((lane & 7) + 8 * (lane >> 4)) * 128, ch = (warp & 1) * 4 + ((lane >> 3) & 1);
            #pragma unroll 1
            for (int pass = 0; pass * 18 < nst; pass++) {
                float acc[2][4] = {};
                #pragma unroll 1
                for (int st = 0; st < 18; st++) {
                    const uint32_t sa = sm + OFF_SILU + (16 * st + q) * 4;
                    const uint32_t b0 = lds32(sa), b1 = lds32(sa + 16), b2 = lds32(sa + 32), b3 = lds32(sa + 48);
                    mbar_wait(bars + 8 * (BAR_X + sl), ph);
                    #pragma unroll
                    for (int m = 0; m < 2; m++) {
                        uint32_t a[4], a2[4];
                        const uint32_t ad = ad0 + sl * 28672 + ((ch + 2 * m) ^ (lane & 7)) * 16;
                        ldsm4t(a, ad); ldsm4t(a2, ad + 2048);
                        mma_bf(acc[m], a, b0, b1); mma_bf(acc[m], a2, b2, b3);
                    }
                    if (elect()) mbar_arrive(bars + 8 * (BAR_X + 6 + sl));
                    if (++sl == 6) { sl = 0; ph ^= 1; }
                }
                const int cb = 28 * pass + 7 * (b - 128) + (warp >> 1), gg = (g >> 1) + 4 * q;
                uint32_t w[2];
                #pragma unroll
                for (int m = 0; m < 2; m++) {
                    float v = bf_round(q ? acc[m][2] : acc[m][0]); if (cb >= 27) v *= 0.5f; else if (cb >= 18) v += 1.f;
                    w[m] = max(pack_bf(v, __shfl_xor_sync(~0u, v, 4)), 1u);
                }
                if (q < 2 && !(g & 1)) {
                    const int qq = (warp & 1) * 2;
                    if (cb < 27) asm volatile("st.relaxed.gpu.global.v2.u32 [%0], {%1, %2};" :: "l"(p.scr->modc + 32 * cb + 8 * qq + 2 * gg), "r"(w[0]), "r"(w[1]) : "memory");
                    else if (cb < 36) { uint32_t* o = p.scr->modc + 896 + 32 * (cb - 27) + 8 * qq + gg; o[0] = w[0]; o[8] = w[1]; }
                }
                if (tid == 0 && pass == 0) PROFT(25);
                bar_sync(1, 448);
                if (tid == 0) { fence_async_g(); red_release(g_cnt + (CNT_NC + pass) * 32); }
                __syncwarp();
            }
            fence_async_s();
        }
        __syncthreads();
    } else {
        uint32_t ta[QA * 4];
        if (strip && (warp >> 2) == 2) {
            const int w = warp - 8;
            const uint32_t ra = sm + OFF_STRIP + (144 * w + (lane & 7) + 8 * (lane >> 4)) * 64, sw = (lane >> 1) & 3, ch = (lane >> 3) & 1;
            float acc[2][2][4] = {};
            mbar_wait(bars + 8 * (BAR_ST + w), 0);
            #pragma unroll
            for (int u = 0; u < 9; u++)
                #pragma unroll
                for (int m = 0; m < 2; m++) { uint32_t a[4]; ldsm4t(a, ra + u * 1024 + ((ch + 2 * m) ^ sw) * 16); mma_bf(acc[u & 1][m], a, sb[2 * u], sb[2 * u + 1]); }
            #define PICK(a_) ((q & 2) ? ((q & 1) ? a_[1][2] : a_[1][0]) : ((q & 1) ? a_[0][2] : a_[0][0]))
            sts32(sm + OFF_RED + ((8 * q + g) * 4 + w) * 4, __float_as_uint(PICK(acc[0]) + PICK(acc[1])));
            if (tid == 256) PROFT(0);
            bar_sync(10, 128);
            if (warp == 8) {
                mbar_wait(bars + 8 * BAR_TAB, 0);
                const uint4 v = lds128(sm + OFF_RED + lane * 16);
                float sum = bf_round((__uint_as_float(v.x) + __uint_as_float(v.y)) + (__uint_as_float(v.z) + __uint_as_float(v.w)));
                if (b >= 36) sum = bf_round(1.f + sum);
                st_relaxed(g_mod + b * 16 + (lane & 16) + (lane & 1) * 8 + ((lane & 15) >> 1), (fabsf(sum) < 8.f ? pack_h(0.f, sum) : __float_as_uint(sum) | 0x8000u) | ((lds32(sm + OFF_EPOCH) + 1) & 0x7FFFu));
                asm volatile("bar.arrive 11, 416;" ::: "memory");
                if (tid == 256) PROFT(1);
            }
        }
        mbar_wait(bars + 8 * BAR_TAB, 0);
        load_tab<QA>(ta, sm + OFF_TAB + lane * 16);
        epoch = lds32(sm + OFF_EPOCH);
        const uint32_t tag = (epoch + 1) & 0x7FFFu;
        auto w_prefetch = [&]() {
            if (warp >= 14 && elect()) asm volatile("cp.async.bulk.prefetch.L2.global [%0], 9248;" :: "l"((warp == 14 ? p.wr : p.wi) + b * 4624) : "memory");
            __syncwarp();
        };
        uint32_t nb[2][5];
        uint4 mv = make_uint4(tag, tag, tag, tag);
        const bool poller = warp < 8 || warp == 12;
        const int mc = warp < 8 ? tid : tid - 128, mst = (mc >> 2) % 36, midx = (mc < 144 ? 10 : 0) + 5 * ((mc >> 1) & 1) + (mst >> 3);
        const uint32_t* mp = g_mod + mc * 4;
        const uint32_t ma = sm + OFF_MODA + ((midx >> 2) * 32 + (mc & 1) * 16 + (mst & 3)) * 16 + (midx & 3) * 4 + ((mst >> 2) & 1) * 2;
        #define MOD_MISSING ((((mv.x ^ tag) | (mv.y ^ tag) | (mv.z ^ tag) | (mv.w ^ tag)) & 0x7FFFu) != 0)
        if (strip && (warp >> 2) != 2) bar_sync(11, 416);
        #pragma unroll
        for (int i = 0; i < 9; i++) one[i] = lds32(sm + OFF_TAB + (QA - 1) * 512 + i * 16 + 8);
        hb();
        mbar_wait(bars + 8 * (BAR_X + warp), 0);
        if (poller) mv = ldx128(mp);
        PROF0(28);
        #pragma unroll
        for (int i = 0; i < 9; i++) xw[i] = lds32(sm + OFF_STAGE + warp * 1152 + (32 * i + 8 * q + g) * 4);
        {
            float r, mr;
            ln_stats(xw, one, g, q, r, mr);
            #pragma unroll
            for (int pp = 0; pp < 5; pp++) {
                nb[0][pp] = pack_h(fmaf(bf_lo(xw[2 * pp]), r, mr), pp < 4 ? fmaf(bf_lo(xw[pp < 4 ? 2 * pp + 1 : 0]), r, mr) : 0.f);
                nb[1][pp] = pack_h(fmaf(bf_hi(xw[2 * pp]), r, mr), pp < 4 ? fmaf(bf_hi(xw[pp < 4 ? 2 * pp + 1 : 0]), r, mr) : 0.f);
            }
        }
        PROF0(2);
        w_prefetch();
        if (poller && MOD_MISSING) mv = ldx128(mp);
        if (warp < 8) {
            if (warp >= 4) sts16(sm + OFF_MODA + ((warp - 3) * 32 + lane) * 16 + (warp - 4) * 4 + 2, 0);
            const int k1 = tid & 15, s1 = tid >> 4;
            float s, c;
            __sincosf((float)(((k1 * (128 * s1 + b) + 1024) & 2047) - 1024) * (3.14159265358979f / 1024.f), &s, &c); s *= 0.25f; c *= 0.25f;
            const int rf = ((s1 >> 3) * 4 + (k1 >> 2)) * 2 + ((s1 >> 2) & 1), ri = ((k1 >> 3) * 4 + (s1 >> 2)) * 2 + ((k1 >> 2) & 1);
            const uint32_t af = sm + OFF_B3 + ((rf >> 2) * 32 + (k1 & 3) * 8 + (s1 & 3)) * 16 + (rf & 3) * 4;
            const uint32_t ai = sm + OFF_B3 + 2048 + ((ri >> 2) * 32 + (s1 & 3) * 8 + (k1 & 3)) * 16 + (ri & 3) * 4;
            sts32(af, pack_h(c, s)); sts32(af + 64, pack_h(-s, c)); sts32(ai, pack_h(c, -s)); sts32(ai + 64, pack_h(s, c));
        }
        if (poller) {
            #pragma unroll 1
            for (int it = 0; __any_sync(~0u, MOD_MISSING); it++) { if (MOD_MISSING) mv = ldx128(mp); hb(); if (it > SPIN_LIMIT) __trap(); }
            sts16(ma, mv.x >> 16); sts16(ma + 64, mv.y >> 16); sts16(ma + 128, mv.z >> 16); sts16(ma + 192, mv.w >> 16);
        }
        uint32_t redo = 0; asm volatile("" : "+r"(redo));
        #pragma unroll 1
        do { if (redo) {
            const uint32_t w[4] = {mv.x, mv.y, mv.z, mv.w}; float f[4]; uint32_t big = 0;
            #pragma unroll
            for (int e = 0; e < 4; e++) { f[e] = (w[e] & 0x8000u) ? bf_hi(w[e]) : __half2float(__ushort_as_half(w[e] >> 16)); big = max(big, __float_as_uint(f[e]) << 1 >> 24); }
            sts32(sm + OFF_HEXP + warp * 4, __reduce_max_sync(~0u, big));
            __syncthreads();
            hexp = min(__reduce_max_sync(~0u, lds32(sm + OFF_HEXP + (lane & 15) * 4)), 253u) - 127;
            const float sc = __uint_as_float((127 - hexp) << 23);
            if (poller) {
                #pragma unroll
                for (int e = 0; e < 4; e++) sts16(ma + 64 * e, pack_h(f[e] * sc, 0.f));
            }
            mv = make_uint4(0, 0, 0, 0);
          }
          redo = __syncthreads_or((mv.x | mv.y | mv.z | mv.w) & 0x8000u);
          asm volatile("" : "+r"(redo));
        } while (redo);
        PROF0(3);
        asm volatile("barrier.cluster.arrive.relaxed.aligned;" ::: "memory");
        if (warp >= 13 && elect()) {
            if (warp == 15) bulk_load(sm + OFF_TAB + QA * 512, p.tab->w + QA * 128, (QB + QC) * 512, bars + 8 * BAR_TAB2);
            else tma3(sm + OFF_WRAW + (warp - 13) * 14336, warp == 13 ? &tm_wr : &tm_wi, wc0 & ~7, 0, 0, bars + 8 * BAR_W);
        }
        __syncwarp();
        {
            uint32_t md[20];
            load_tab<5>(md, sm + OFF_MODA + lane * 16);
            #pragma unroll
            for (int v = 0; v < 2; v++)
                #pragma unroll
                for (int pp = 0; pp < 5; pp++) nb[v][pp] = hfma2(nb[v][pp], md[v * 5 + pp], md[10 + v * 5 + pp]);
        }
        uint32_t re[3][2], im[3][2];
        #pragma unroll
        for (int mt = 0; mt < 3; mt++)
            #pragma unroll
            for (int v = 0; v < 2; v++) {
                re[mt][v] = 0; im[mt][v] = 0;
                mma_h8(re[mt][v], im[mt][v], ta[24 + 2 * mt], ta[25 + 2 * mt], nb[v][4]);
                mma_h(re[mt][v], im[mt][v], ta[mt * 8], ta[mt * 8 + 1], ta[mt * 8 + 2], ta[mt * 8 + 3], nb[v][0], nb[v][1]);
                mma_h(re[mt][v], im[mt][v], ta[mt * 8 + 4], ta[mt * 8 + 5], ta[mt * 8 + 6], ta[mt * 8 + 7], nb[v][2], nb[v][3]);
                cmul_neg(re[mt][v], im[mt][v], ta[30 + (mt * 2 + v) * 2], ta[31 + (mt * 2 + v) * 2]);
            }
        const uint32_t srow = sm + OFF_SPEC + warp * (SPEC_P * 4);
        #pragma unroll
        for (int nt = 0; nt < 2; nt++) {
            uint32_t o[2][4];
            #pragma unroll
            for (int v = 0; v < 2; v++) {
                const uint32_t b0 = ta[42 + (v * 2 + nt) * 2], b1 = ta[43 + (v * 2 + nt) * 2];
                o[v][0] = o[v][1] = o[v][2] = o[v][3] = 0;
                mma_h(o[v][0], o[v][1], re[0][v], re[1][v], im[0][v], im[1][v], b0, b1);
                mma_h(o[v][2], o[v][3], re[2][0], re[2][1], im[2][0], im[2][1], b0, b1);
            }
            const uint32_t a = srow + (g + 72 * q + 36 * nt) * 4, a2 = srow + (288 - g - 72 * q - 36 * nt) * 4;
            sts32(a, hadd2(o[0][0], o[1][0])); sts32(a + 32, hadd2(o[0][1], o[1][1])); if (g < 3) sts32(a + 64, hadd2(o[0][2], o[1][3]));
            if (g > 0 || (q == 0 && nt == 0)) sts32(a2, hsub2(o[0][0], o[1][0]) ^ 0x80000000u);
            sts32(a2 - 32, hsub2(o[0][1], o[1][1]) ^ 0x80000000u); if (g < 2) sts32(a2 - 64, hsub2(o[0][2], o[1][3]) ^ 0x80000000u);
        }
        uint32_t b3[16];
        if (warp < 10) load_tab<4>(b3, sm + OFF_B3 + lane * 16);
        __syncthreads();
        if (warp == 10) t_st = clk32();
        PROF0(4);
        if (warp < 10) {
            uint4 V[4], o[4];
            #pragma unroll
            for (int u = 0; u < 4; u++) V[u] = lds128(scol + u * (16 * SPEC_P));
            radix16(V, b3, o);
            #pragma unroll
            for (int nt = 0; nt < 4; nt++) { o[nt].x |= 1u; if (warp < 9 || g < 2) stx128(tptr + nt * tstr, o[nt]); }
        }
        PROF0(5);
    }

    int role = 0;
    asm volatile("barrier.cluster.wait.aligned;" ::: "memory");
    if (warp >= 12) {
        const int t = tid - 384;
        if (warp == 14 && rank == 0) {
            uint32_t smid; asm volatile("mov.u32 %0, %%smid;" : "=r"(smid));
            const uint32_t tp = smid >> 1;
            uint32_t pr = tp < 32 ? (tp & 7) * 8 + (tp >> 3) : tp < 60 ? (1 + (tp - 32) % 7) * 8 + 4 + (tp - 32) / 7 : tp < 62 ? 4 + tp : tp < 66 ? tp - 58 : 0;
            #pragma unroll 1
            for (;;) {
                uint32_t old = 0; if (lane == 0) old = atomicExch(g_slot + pr, epoch + 1);
                if (!__any_sync(~0u, lane == 0 && old == epoch + 1)) break;
                pr = pr == 65 ? 0 : pr + 1;
            }
            if (lane < 2) asm volatile("st.async.weak.shared::cluster.mbarrier::complete_tx::bytes.u32 [%0], %1, [%2];" :: "r"(mapa(sm + OFF_MISC, lane)), "r"(pr), "r"(mapa(bars + 8 * BAR_ROLE, lane)) : "memory");
        }
        __syncwarp();
        if (t == 0) {
            asm volatile("prefetch.tensormap [%0];" :: "l"(&tm_w1a) : "memory");
            asm volatile("prefetch.tensormap [%0];" :: "l"(&tm_h3a) : "memory"); asm volatile("prefetch.tensormap [%0];" :: "l"(&tm_w1b) : "memory");
            asm volatile("prefetch.tensormap [%0];" :: "l"(&tm_h3b) : "memory"); asm volatile("prefetch.tensormap [%0];" :: "l"(&tm_w2) : "memory");
            asm volatile("prefetch.tensormap [%0];" :: "l"(&tm_o) : "memory"); asm volatile("prefetch.tensormap [%0];" :: "l"(&tm_h3s) : "memory");
        }
        __syncwarp();
        if (rowcta) {
            spin_until(t0 + NCP);
            uint4 v[2];
            v[1] = make_uint4(1, 1, 1, 1);
            #pragma unroll 1
            for (int it = 0;; it++) {
                v[0] = ldx128(p.scr->modc + 4 * t); if (t < 88) v[1] = ldx128(p.scr->modc + 512 + 4 * t);
                if (__all_sync(~0u, min(min(min(v[0].x, v[0].y), min(v[0].z, v[0].w)), min(min(v[1].x, v[1].y), min(v[1].z, v[1].w))) != 0)) break;
                __nanosleep(100); if (it > SPIN_LIMIT) __trap();
            }
            if (t < 72) { const uint32_t sc = ((127 + hexp) << 7) * 0x10001u;
                v[0] = make_uint4(bfma2(v[0].x, sc, 0x80008000u), bfma2(v[0].y, sc, 0x80008000u), bfma2(v[0].z, sc, 0x80008000u), bfma2(v[0].w, sc, 0x80008000u)); }
            #pragma unroll
            for (int u = 0; u < 2; u++) if (u == 0 || t < 88) {
                const uint32_t a = sm + OFF_MODC + (((t >> 5) + 4 * u) * 32 + 8 * (t & 3) + ((t >> 1) & 2)) * 16 + ((t >> 3) & 3) * 4;
                sts32(a, v[u].x); sts32(a + 16, v[u].y); sts32(a + 64, v[u].z); sts32(a + 80, v[u].w);
            }
            __syncwarp();
            if (elect()) mbar_arrive(bars + 8 * BAR_NC);
            if (t == 0) PROFT(29);
        }
    } else if (rowcta && warp < 11) {
        const int nw = !(b & 1) ? 10 : (b & 7) == 7 ? 9 : 8;
        const int cm = (b >> 3) * 288 + (b & 7) * 32, cx = (b & 1) ? 4608 + 8 * (b >> 3) : (b >> 3) * 288 + 256 + 4 * (b & 7);
        auto load_in = [&]() {
            if (elect()) {
                mbar_expect(bars + 8 * BAR_XB, nw > 8 ? 20480 : 16384);
                tma2(sm + OFF_STAGE, &tm_t, cm, 0, bars + 8 * BAR_XB);
                if (nw > 8) tma2(sm + OFF_STX, &tm_tx, cx, 0, bars + 8 * BAR_XB);
            }
            __syncwarp();
        };
        if (warp == 10) { fence_async_s(); spin_until(t_st + X1D); load_in(); }
        uint32_t tb[QB * 4], wre[4][2], wim[4][2];
        if (warp < nw) {
            mbar_wait(bars + 8 * BAR_TAB2, 0);
            load_tab<QB>(tb, sm + OFF_TAB + QA * 512 + lane * 16);
            mbar_wait(bars + 8 * BAR_W, 0);
            const int off = wc0 & 7;
            const uint32_t wa = sm + OFF_WRAW + lane * 112 + ((off >> 1) + 2 * warp) * 4, sh = (off & 1) * 16;
            #pragma unroll
            for (int c = 0; c < 2; c++)
                #pragma unroll
                for (int h = 0; h < 2; h++) {
                    uint32_t y[2][2];
                    #pragma unroll
                    for (int e = 0; e < 2; e++) {
                        const uint32_t a = wa + c * 14336 + (h + 2 * e) * 3584, x0 = lds32(a), x1 = lds32(a + 4), x2 = lds32(a + 8);
                        y[e][0] = __funnelshift_r(x0, x1, sh); y[e][1] = __funnelshift_r(x1, x2, sh);
                    }
                    #pragma unroll
                    for (int x = 0; x < 4; x++) {
                        const uint32_t v = (x & 1) ? pack_h(bf_hi(y[0][x >> 1]), bf_hi(y[1][x >> 1])) : pack_h(bf_lo(y[0][x >> 1]), bf_lo(y[1][x >> 1]));
                        if (c) wim[x][h] = v; else wre[x][h] = v;
                    }
                }
        }
        const uint32_t ca = warp < 8 ? sm + OFF_STAGE + lane * 128 + (warp ^ (lane & 7)) * 16 : sm + OFF_STX + lane * 32 + ((warp ^ g) & 1) * 16, cs = warp < 8 ? 4096 : 1024;
        uint32_t V[4][4];
        #pragma unroll 1
        for (int it = 0;; it++) {
            mbar_wait(bars + 8 * BAR_XB, it & 1);
            uint32_t ok = 1;
            if (warp < nw) {
                #pragma unroll
                for (int u = 0; u < 4; u++) { uint4 t4 = lds128(ca + u * cs); V[u][0] = t4.x; V[u][1] = t4.y; V[u][2] = t4.z; V[u][3] = t4.w; ok &= t4.x; }
            }
            asm volatile("{.reg .pred p; setp.ne.u32 p, %0, 0; bar.red.and.pred p, 1, 352, p; selp.u32 %0, 1, 0, p;}" : "+r"(ok) :: "memory");
            if (ok) break;
            if (warp == 10) { load_in(); hb(); }
            if (it > SPIN_LIMIT / 64) __trap();
        }
        PROF0(7);
        if (warp < nw) {
            uint32_t zr[4][2], zi[4][2];
            #pragma unroll
            for (int x = 0; x < 4; x++) {
                uint32_t er = 0, ei = 0, or_ = 0, oi = 0;
                mma_h(er, ei, tb[0], tb[1], tb[2], tb[3], V[0][x], V[1][x]);
                mma_h(or_, oi, tb[4], tb[5], tb[6], tb[7], V[2][x], V[3][x]);
                uint32_t r0 = hadd2(er, or_), r1 = hsub2(er, or_), i0 = hadd2(ei, oi), i1 = hsub2(ei, oi);
                cmul_neg(r0, i0, tb[8], tb[9]); cmul_neg(r1, i1, tb[10], tb[11]);
                uint32_t xr0 = 0, xr1 = 0, xi0 = 0, xi1 = 0;
                mma_h(xr0, xr1, r0, r1, i0, i1, tb[12], tb[13]);
                mma_h(xi0, xi1, r0, r1, i0, i1, tb[14], tb[15]);
                cmul_pos(xr0, xi0, wre[x][0], wim[x][0]); cmul_pos(xr1, xi1, wre[x][1], wim[x][1]);
                r0 = 0; i0 = 0; r1 = 0; i1 = 0;
                mma_h(r0, i0, tb[12], tb[13], tb[14], tb[15], xr0, xi0);
                mma_h(r1, i1, tb[12], tb[13], tb[14], tb[15], xr1, xi1);
                cmul_pos(r0, i0, tb[16], tb[17]); cmul_pos(r1, i1, tb[18], tb[19]);
                zr[x][0] = hadd2(r0, r1); zr[x][1] = hsub2(r0, r1); zi[x][0] = hadd2(i0, i1); zi[x][1] = hsub2(i0, i1);
            }
            #pragma unroll
            for (int nt = 0; nt < 4; nt++) {
                uint4 o = make_uint4(0, 0, 0, 0);
                const int h = nt >> 1;
                mma_h(o.x, o.y, zr[0][h], zr[1][h], zi[0][h], zi[1][h], tb[20 + 2 * nt], tb[21 + 2 * nt]);
                mma_h(o.z, o.w, zr[2][h], zr[3][h], zi[2][h], zi[3][h], tb[20 + 2 * nt], tb[21 + 2 * nt]);
                o.x &= ~1u;
                sts128(ca + nt * cs, o);
            }
        }
        fence_async_s();
        bar_sync(1, 352);
        if (warp < 10) t_st = clk32();
        PROF0(8);
        if (warp == 10 && elect()) {
            asm volatile("cp.async.bulk.tensor.2d.global.shared::cta.bulk_group [%0, {%2, %3}], [%1];" :: "l"(&tm_t), "r"(sm + OFF_STAGE), "r"(cm), "r"(0) : "memory");
            if (nw > 8) asm volatile("cp.async.bulk.tensor.2d.global.shared::cta.bulk_group [%0, {%2, %3}], [%1];" :: "l"(&tm_tx), "r"(sm + OFF_STX), "r"(cx), "r"(0) : "memory");
            asm volatile("cp.async.bulk.commit_group;" ::: "memory");
            asm volatile("cp.async.bulk.wait_group.read 0;" ::: "memory");
        }
        __syncwarp();
    }

    if (warp >= 10) { mbar_wait(bars + 8 * BAR_ROLE, 0); role = __shfl_sync(~0u, lds32(sm + OFF_MISC), 0); fence_async_s(); }
    auto first_a = [&]() {
        if (warp >= 10 && role < 64 && elect()) {
            const int it = warp - 10, hi = it >= 3; const bool p2 = it - 3 * hi == 2;
            tma4(sm + OFF_A + it * A_BYTES, p2 ? &tm_w1b : &tm_w1a, 0, 0, p2 ? 64 * rank + 8 * hi : 4 * (it - hi),
                 9 * (role >> 3) + (p2 ? 8 : (role & 4) + 2 * rank), bars + 8 * (BAR_FULL + it));
        }
        __syncwarp();
    };
    if (!rowcta) first_a();
    else {
        uint32_t tc[20], md[28];
        mbar_wait(bars + 8 * BAR_TAB2, 0);
        load_tab<5>(tc, sm + OFF_TAB + (QA + QB) * 512 + lane * 16);
        bool md_early = warp >= 10;
        if (md_early) { mbar_wait(bars + 8 * BAR_NC, 0); load_tab<7>(md, sm + OFF_MODC + lane * 16); }
        if (warp < 10) {
            uint32_t b3[16];
            load_tab<4>(b3, sm + OFF_B3 + 2048 + lane * 16);
            uint4 V[4], o[4];
            const bool tact = warp < 9 || g == 0;
            spin_until(t_st + X2D);
            #pragma unroll
            for (int u = 0; u < 4; u++) { V[u] = make_uint4(0, 0, 0, 0); if (tact) V[u] = ldx128(tptr + u * tstr); }
            md_early = __any_sync(~0u, mbar_test(bars + 8 * BAR_NC, 0));
            if (md_early) load_tab<7>(md, sm + OFF_MODC + lane * 16);
            #pragma unroll 1
            for (int it = 0; __any_sync(~0u, (V[0].x | V[1].x | V[2].x | V[3].x) & 1u); it++) {
                #pragma unroll
                for (int u = 0; u < 4; u++) if (V[u].x & 1u) V[u] = ldx128(tptr + u * tstr);
                hb();
                if (it > SPIN_LIMIT) __trap();
            }
            PROF0(10);
            radix16(V, b3, o);
            if (tact) {
                #pragma unroll
                for (int nt = 0; nt < 4; nt++) sts128(scol + nt * (16 * SPEC_P), o[nt]);
            }
        }
        __syncthreads();
        PROF0(11);
        first_a();
        const uint32_t srow = sm + OFF_SPEC + warp * (SPEC_P * 4);
        uint32_t re[2][3], im[2][3];
        #pragma unroll
        for (int mt = 0; mt < 3; mt++) {
            const uint32_t a = srow + (g + 72 * q + 8 * mt) * 4, a2 = srow + (288 - g - 72 * q - 8 * mt) * 4;
            const uint32_t z0 = lds32(a), z1 = lds32(a + 144), z2 = lds32(a2), z3 = lds32(a2 - 144);
            #pragma unroll
            for (int m2 = 0; m2 < 2; m2++) {
                re[m2][mt] = 0; im[m2][mt] = 0;
                const uint32_t sg = m2 ? 0x3C00BC00u : 0xBC003C00u;
                mma_h(re[m2][mt], im[m2][mt], tc[m2 * 4], tc[m2 * 4 + 1], tc[m2 * 4 + 2], tc[m2 * 4 + 3], hfma2(z2, sg, z0), hfma2(z3, sg, z1));
                cmul_pos(re[m2][mt], im[m2][mt], tc[8 + (m2 * 3 + mt) * 2], tc[9 + (m2 * 3 + mt) * 2]);
            }
        }
        float y[20];
        WG_FENCE();
        #pragma unroll
        for (int mt = 0; mt < 3; mt++)
            wgmma40_rs(y, re[0][mt], re[1][mt], im[0][mt], im[1][mt], desc_lo(OFF_TAB + (QA + QB + 5) * 512 + mt * 1280, 128), mt);
        WG_COMMIT();
        if (!md_early) { mbar_wait(bars + 8 * BAR_NC, 0); load_tab<7>(md, sm + OFF_MODC + lane * 16); }
        WG_WAIT(0);
        #pragma unroll
        for (int i = 0; i < 9; i++) xw[i] = bfma2(md[i], pack_bf(y[4 * (i >> 1) + (i & 1)], y[4 * (i >> 1) + 2 + (i & 1)]), xw[i]);
        float r, mr;
        ln_stats(xw, one, g, q, r, mr);
        uint32_t r2 = pack_bf(r, r), m2 = pack_bf(mr, mr);
        #pragma unroll
        for (int i = 0; i < 9; i++) {
            sts32(sm + OFF_X1 + warp * 1152 + (32 * i + 8 * q + g) * 4, xw[i]);
            xw[i] = bfma2(bfma2(xw[i], r2, m2), md[18 + i], md[9 + i]);
        }
        ln_stats(xw, one, g, q, r, mr);
        r2 = pack_bf(r, r); m2 = pack_bf(mr, mr);
        {
            const int n7 = 2 * q + (g >> 2);
            const uint32_t a = sm + OFF_STAGE + (warp >> 3) * 9216 + n7 * 128 + ((warp & 7) ^ n7) * 16 + (g & 3) * 4;
            #pragma unroll
            for (int i = 0; i < 9; i++) sts32(a + i * 1024, bfma2(xw[i], r2, m2));
        }
        fence_async_s();
        __syncthreads();
        PROF0(12);
        if (tid == 0) {
            asm volatile("cp.async.bulk.tensor.4d.global.shared::cta.bulk_group [%0, {%2, %2, %2, %3}], [%1];" :: "l"(&tm_h3s), "r"(sm + OFF_STAGE), "r"(0), "r"(b) : "memory");
            asm volatile("cp.async.bulk.commit_group;" ::: "memory");
        }
    }
    if (!rowcta) __syncthreads();
    else {
        if (tid == 0) { asm volatile("cp.async.bulk.wait_group 0;" ::: "memory"); fence_async_g(); red_release(g_cnt + CNT_H3 * 32); }
        PROF0(13);
        if (warp == 15) {
            __nanosleep(X1DELAY);
            #pragma unroll 1
            for (int r = 0; r < 16; r++) {
                if (lane == 0) asm volatile("cp.async.bulk.global.shared::cta.bulk_group [%0], [%1], 1152;" :: "l"(p.out + (size_t)(b + 128 * r) * D_), "r"(sm + OFF_X1 + r * 1152) : "memory");
                const uint32_t t1 = clk32();
                #pragma unroll 1
                while (__any_sync(~0u, (int)(clk32() - t1) < X1PACE)) __nanosleep(50);
            }
            if (lane == 0) {
                asm volatile("cp.async.bulk.commit_group;" ::: "memory");
                asm volatile("cp.async.bulk.wait_group 0;" ::: "memory");
                if (role < 64) mbar_arrive_remote(mapa(bars + 8 * BAR_HOLD, rank ^ 1));
                fence_async_g(); red_release(g_cnt + CNT_X1 * 32);
            }
        }
    }
    role = __shfl_sync(~0u, lds32(sm + OFF_MISC), 0);
    if ((sm & 0xFFFFFFu) != SM0) __trap();
    if (role >= 64) { if (warp == 0) PROFDUMP(); return; }

    const int gi = role >> 3, dt = role & 3, c2 = (role >> 2) & 1;
    const int wg = warp >> 2, wi = warp & 3;
    if (wg == 3) {
        uint32_t so = 0, eph = 1;
        #define RING_STEP(BYTES, OFF, ISSUE) do { \
            mbar_wait(bars + 8 * BAR_EMPTY + so, eph); \
            if (elect()) { const uint32_t fb = bars + 8 * BAR_FULL + so, dst = sm + (OFF) + so * ((BYTES) / 8); mbar_expect(fb, BYTES); ISSUE; } \
            so += 8; if (so == 8 * NST) { so = 0; eph ^= 1; } } while (0)
        const uint32_t kbm = warp == 12 ? 64 : 4 * B_BYTES, kba = warp == 12 ? 0 : dt * B_BYTES;
        const uint32_t kb0 = g2_kb(lane, rank, gi, c2) * kbm + kba, kb1 = g2_kb(32 + (lane & 3), rank, gi, c2) * kbm + kba;
        #define KB(n_) __shfl_sync(~0u, (n_) < 32 ? kb0 : kb1, (n_) & 31)
        if (warp == 12) {
            eph = 0;
            const int fb1 = 9 * gi + 4 * c2 + 2 * rank, sb2 = 4 * gi + 2 * c2;
            int pft = dt, pfj = 4 * (PF0 + PFS * dt);
            #pragma unroll 1
            for (int j = 16; j < 128; j += 4) {
                RING_STEP(A_BYTES, OFF_A, tma4(dst, &tm_w1a, 0, 0, j, fb1, fb));
                if (j < 64) { if (j & 4) RING_STEP(A_BYTES, OFF_A, tma4(dst, &tm_w1b, 0, 0, 64 * rank + j - 4, 9 * gi + 8, fb)); }
                if (RP1 && __any_sync(~0u, (j & 12) == 4 * dt && j + 4 * RP1 < 128) && elect())
                    asm volatile("cp.async.bulk.prefetch.tensor.4d.L2.global [%0, {%1, %1, %2, %3}];" :: "l"(&tm_w1a), "r"(0), "r"(j + 4 * RP1), "r"(fb1) : "memory");
                if (RPX && __any_sync(~0u, (j & 4) == 0 && j + 8 * RPX < 64 && ((j >> 3) & 7) == (role & 7)) && elect())
                    asm volatile("cp.async.bulk.prefetch.tensor.4d.L2.global [%0, {%1, %1, %2, %3}];" :: "l"(&tm_w1b), "r"(0), "r"(64 * (int)rank + j + 8 * RPX), "r"(9 * gi + 8) : "memory");
                if (__any_sync(~0u, j == pfj && pft < PFN)) {
                    const int kb = KB(pft); pft += 4; pfj += 16 * PFS;
                    if (elect()) asm volatile("cp.async.bulk.prefetch.tensor.3d.L2.global [%0, {%1, %2, %3}];" :: "l"(&tm_w2), "r"(0), "r"(kb), "r"(sb2) : "memory");
                }
            }
            #pragma unroll 1
            for (int n = 0; n < 36; n++) {
                const int kb = KB(n);
                RING_STEP(A_BYTES, OFF_A, tma3(dst, &tm_w2, 0, kb, sb2, fb));
            }
        } else if (warp == 13) {
            const uint32_t e1 = __shfl_sync(~0u, epoch + 1, 0);
            fence_async_s();
            if (lane == 0) mbar_expect(bars + 8 * BAR_FULL, B_BYTES);
            wait_count<0>(g_cnt + CNT_H3 * 32, e1 * 128); fence_async_g();
            if (elect()) tma3(sm + OFF_B, &tm_h3a, 0, 18 * dt, 0, bars + 8 * BAR_FULL);
            so = 8;
            if (lane == 0) PROFT(14);
            #pragma unroll 1
            for (int j = 4; j < 128; j += 4) {
                RING_STEP(B_BYTES, OFF_B, tma3(dst, &tm_h3a, 0, 18 * dt, j, fb));
                if (j < 64 && (j & 4)) RING_STEP(B_BYTES, OFF_B, tma3(dst, &tm_h3b, 0, 18 * dt + 9 * c2, 64 * rank + j - 4, fb));
            }
            mbar_wait(bars + 8 * BAR_UOK, 0); fence_async_g();
            if (lane == 0) PROFT(22);
            #pragma unroll 1
            for (int n = 0; n < 4; n++) { const uint32_t o = KB(n); RING_STEP(B_BYTES, OFF_B, bulk_load(dst, (const char*)g_U + o, B_BYTES, fb)); }
            {
                constexpr int S5 = (IT_G2 + 5) % NST; static_assert(S5 > 0 && S5 < NST - 1, "no wrap");
                const char* src = (const char*)g_U + KB(5);
                mbar_wait(bars + 8 * (BAR_EMPTY + S5), eph);
                if (lane == 0) mbar_expect(bars + 8 * (BAR_FULL + S5), B_BYTES);
                mbar_wait(bars + 8 * (BAR_UOK + 1), 0);
                wait_count<0>(g_cnt + (CNT_U + 8) * 32, e1 * 128); fence_async_g();
                if (elect()) bulk_load(sm + OFF_B + S5 * B_BYTES, src, B_BYTES, bars + 8 * (BAR_FULL + S5));
                so = 8 * (S5 + 1);
                if (lane == 0) PROFT(19);
            }
            #pragma unroll 1
            for (int n = 6; n < 36; n++) {
                const uint32_t o = KB(n);
                if (n == 21) { mbar_wait(bars + 8 * (BAR_UOK + 2), 0); fence_async_g(); }
                RING_STEP(B_BYTES, OFF_B, bulk_load(dst, (const char*)g_U + o, B_BYTES, fb));
            }
            if (role == 0 && rank == 0 && lane == 0) st_relaxed(g_cnt + CNT_EPOCH * 32, e1);
        } else if (warp == 15) {
            if (!rowcta && elect()) mbar_arrive_remote(mapa(bars + 8 * BAR_HOLD, rank ^ 1));
            __syncwarp();
            bar_sync(6, 160);
            if (elect()) mbar_arrive(bars + 8 * (BAR_FULL + (IT_G2 + 4) % NST));
            __syncwarp();
            mbar_wait(bars + 8 * BAR_W1GO, 0);
            if (elect()) {
                char* dst = (char*)(g_U + ((9 * gi + 4 * c2 + 2 * rank + 1) * 4 + dt) * 1152);
                #pragma unroll 1
                for (int i = 0; i < W1N; i++) {
                    asm volatile("cp.async.bulk.global.shared::cta.bulk_group [%0], [%1], %2;" :: "l"(dst + i * (18432 / W1N)), "r"(sm + OFF_X1 + i * (18432 / W1N)), "n"(18432 / W1N) : "memory");
                    const uint32_t t1 = clk32(); while ((int)(clk32() - t1) < W1P) {}
                }
                asm volatile("cp.async.bulk.commit_group;" ::: "memory");
                asm volatile("cp.async.bulk.wait_group 0;" ::: "memory");
                fence_async_g(); red_release(g_cnt + (CNT_U + 16) * 32);
                #pragma unroll 1
                for (int n = 0; n < 4; n++) { __nanosleep(300); tma2(sm + OFF_X1 + n * 4608, &tm_o, 144 * dt, 256 * gi + 128 * c2 + 64 * (rank ^ 1) + 16 * n, bars + 8 * BAR_XT); }
            }
        } else {
            const uint32_t e1 = epoch + 1;
            if (lane == 0) {
                __nanosleep(4000);
                wait_count<200>(g_cnt + CNT_NC * 32, e1 * 4); wait_count<200>(g_cnt + (CNT_NC + 1) * 32, e1 * 2);
                fence_async_g();
                mbar_expect(bars + 8 * BAR_GB, 1152);
                bulk_load(sm + OFF_GB, p.scr->modc + 896, 1152, bars + 8 * BAR_GB);
                wait_count<200>(g_cnt + CNT_X1 * 32, e1 * 128);
                if (role * 2 + rank < 108) {
                    uint4* z = (uint4*)p.scr->modc + (role * 2 + rank) * 2; z[0] = z[1] = make_uint4(0, 0, 0, 0);
                }
                wait_count<50>(g_cnt + (CNT_U + dt * 2 + rank) * 32, e1 * 16);
                mbar_arrive(bars + 8 * BAR_UOK);
            }
            __syncwarp();
            bar_sync(4, 160);
            if (tid == 448) {
                fence_async_g(); red_release(g_cnt + (CNT_U + 8) * 32);
                PROFT(17);
                mbar_arrive(bars + 8 * (BAR_UOK + 1));
                __nanosleep(2000);
                wait_count<100>(g_cnt + (CNT_U + 16) * 32, e1 * 128);
                mbar_arrive(bars + 8 * (BAR_UOK + 2));
            }
        }
    } else if (wg == 2) {
        float d0[36];
        const float bias = bf_lo(ldg_nc16(p.b1 + 576 * gi + 512 + 16 * wi + g + 8 * rank));
        #pragma unroll 1
        for (int it = 0; it < 200 && !__any_sync(~0u, mbar_test(bars + 8 * BAR_FULL, 0)); it++) { hb(); __nanosleep(100); }
        const bool lead = wi == 0 && elect();
        #pragma unroll 1
        for (int i = 0; i < 8; i++) {
            const uint32_t s = P2S + 3 * (i & 1);
            mbar_wait(bars + 8 * BAR_FULL + 8 * s, (i >> 1) & 1);
            const uint32_t da = desc_lo(OFF_A, 8192) + s * (A_BYTES / 16), db = desc_lo(OFF_B, 128) + s * (B_BYTES / 16);
            WG_FENCE();
            wgmma72(d0, da, db, i);
            #pragma unroll
            for (int k = 1; k < 9; k++) {
                if (k == P2K) asm volatile("{.reg .pred p; setp.ne.u32 p, %1, 0; @p mbarrier.arrive.shared::cta.b64 _, [%0];}" :: "r"(bars + 8 * (BAR_P2N + (i & 1))), "r"((uint32_t)lead) : "memory");
                if (k < 8) wgmma72(d0, da + k * 128, db + k * 144, 1);
            }
            WG_COMMIT();
            WG_WAIT(0);
            if (lead) mbar_arrive_n(bars + 8 * BAR_EMPTY + 8 * s, 2);
        }
        if (lead) PROFT(18);
        const uint32_t slot = sm + OFF_P2R + (tid & 127) * 16, ra = mapa(slot, rank ^ 1), rb = mapa(bars + 8 * BAR_P2R, rank ^ 1);
        float sv[18];
        #pragma unroll
        for (int i = 0; i < 18; i++) { const float lo = d0[4 * (i >> 1) + (i & 1)], hi = d0[4 * (i >> 1) + 2 + (i & 1)];
            sv[i] = rank ? lo : hi; d0[4 * (i >> 1) + (i & 1)] = (rank ? hi : lo) + bias; }
        mbar_wait(bars + 8 * BAR_HOLD, 0);
        #pragma unroll
        for (int i = 0; i < 4; i++)
            asm volatile("st.async.weak.shared::cluster.mbarrier::complete_tx::bytes.v4.f32 [%0], {%1,%2,%3,%4}, [%5];"
                :: "r"(ra + i * 2048), "f"(sv[4 * i]), "f"(sv[4 * i + 1]), "f"(sv[4 * i + 2]), "f"(sv[4 * i + 3]), "r"(rb) : "memory");
        asm volatile("st.async.weak.shared::cluster.mbarrier::complete_tx::bytes.v2.f32 [%0], {%1,%2}, [%3];" :: "r"(ra + 8192), "f"(sv[16]), "f"(sv[17]), "r"(rb) : "memory");
        mbar_wait(bars + 8 * BAR_P2R, 0);
        #pragma unroll
        for (int i = 0; i < 5; i++) {
            const uint4 v = lds128(slot + i * 2048);
            d0[8 * i] += __uint_as_float(v.x); d0[8 * i + 1] += __uint_as_float(v.y);
            if (i < 4) { d0[8 * i + 4] += __uint_as_float(v.z); d0[8 * i + 5] += __uint_as_float(v.w); }
        }
        asm volatile("bar.arrive 5, 256;" ::: "memory");
        gelu_store<0>(d0, (char*)(g_U + ((9 * gi + 8) * 4 + dt) * 1152) + wi * 4608 + rank * 2304 + c2 * 1152 + g * 16, q);
        bar_sync(8, 128);
        if (lead) { fence_async_g(); red_release(g_cnt + (CNT_U + dt * 2 + (gi >> 2)) * 32); PROFT(26); }
    } else {
        float d[72];
        const bool lead = wi == 0 && elect();
        const uint32_t da0 = desc_lo(OFF_A, 8192) + wg * 512;
        const bool owner = (uint32_t)wg == rank;
        const int srow = 256 * gi + 128 * c2 + 64 * wg + 16 * wi;
        const uint32_t b2w0 = ldg_nc16(p.b2 + srow + g), b2w1 = ldg_nc16(p.b2 + srow + g + 8);
        const int fr = 576 * gi + 256 * c2 + 128 * rank + 64 * wg + 16 * wi + g;
        const float bias0 = bf_lo(ldg_nc16(p.b1 + fr)), bias1 = bf_lo(ldg_nc16(p.b1 + fr + 8));
        uint32_t g2rdy;
        {
            #pragma unroll
            for (int i = 0; i < 72; i++) d[i] = (i & 2) ? bias1 : bias0;
            constexpr uint32_t db1 = desc_lo(OFF_B, 128);
            static_assert(IT_G2 - LEAD1 == 6 * NST && IT_P1 == 4 * NST && P2S == 2, "loop structure");
            #define REL(s_) if (lead) mbar_arrive(bars + 8 * (BAR_EMPTY + (s_)))
            mma_block<DHI_H3, 0>(d, bars, da0, db1, 0);
            #pragma unroll 1
            for (int c = 0; c < 4; c++) {
                const uint32_t ph = c & 1;
                mma_block<DHI_H3, 1>(d, bars, da0, db1, ph); REL(0);
                mbar_wait(bars + 8 * (P2K ? BAR_P2N : BAR_FULL + 2), ph);
                mma_block<DHI_H3, 3>(d, bars, da0, db1, ph); REL(1);
                mma_block<DHI_H3, 4>(d, bars, da0, db1, ph); REL(3);
                mbar_wait(bars + 8 * (P2K ? BAR_P2N + 1 : BAR_FULL + 5), ph);
                mma_block<DHI_H3, 0>(d, bars, da0, db1, ph ^ 1); REL(4);
            }
            #pragma unroll 1
            for (uint32_t ph = 0; ph < 2; ph++) {
                mma_block<DHI_H3, 1>(d, bars, da0, db1, ph); REL(0);
                mma_block<DHI_H3, 2>(d, bars, da0, db1, ph); REL(1);
                mma_block<DHI_H3, 3>(d, bars, da0, db1, ph); REL(2);
                mma_block<DHI_H3, 4>(d, bars, da0, db1, ph); REL(3);
                mma_block<DHI_H3, 5>(d, bars, da0, db1, ph); REL(4);
                const bool pause = ph && wg == 1;
                if (pause) { WG_WAIT(0); REL(5); bar_sync(9, 256); }
                mma_block<DHI_H3, 0>(d, bars, da0, db1, ph ^ 1); if (!pause) REL(5);
            }
            #pragma unroll
            for (int i = IT_G2 - LEAD1 + 1; i < IT_G2; i++) {
                mbar_wait(bars + 8 * (BAR_FULL + i % NST), (i / NST) & 1);
                WG_FENCE();
                #pragma unroll
                for (int k = 0; k < 4; k++) {
                    if (i == IT_G2 - 1 && k == HOK1) WG_COMMIT();
                    wgmma144<DHI_H3>(d, da0 + (i % NST) * (A_BYTES / 16) + k * 128, db1 + (i % NST) * (B_BYTES / 16) + k * 288, 1);
                }
                WG_COMMIT();
                if (i == IT_G2 - 1 && HOK1 < 4) WG_WAIT(2); else WG_WAIT(1);
                REL((i - 1) % NST);
            }
            g2rdy = __shfl_sync(~0u, (uint32_t)mbar_test(bars + 8 * (BAR_FULL + IT_G2 % NST), (IT_G2 / NST) & 1), 0);
            if (wg == 0) { WG_WAIT(1); asm volatile("bar.arrive 9, 256;" ::: "memory"); }
            WG_WAIT(0);
            if (lead) mbar_arrive(bars + 8 * (BAR_EMPTY + (IT_G2 - 1) % NST));
            PROF0(16);
            if (wg == 1) bar_sync(5, 256);
            char* const ub = (wg == 0 ? (char*)(g_U + ((9 * gi + 4 * c2 + 2 * rank) * 4 + dt) * 1152) : (char*)__cvta_shared_to_generic(sm + OFF_X1)) + wi * 4608 + g * 16;
            gelu_store<0>(d, ub, q); gelu_store<2>(d, ub + 2304, q); gelu_store<36>(d, ub + 1152, q); gelu_store<38>(d, ub + 3456, q);
            PROF0(27);
            if (wg == 0) asm volatile("bar.arrive 4, 160;" ::: "memory");
            else if (!W1L) { fence_async_s(); asm volatile("bar.arrive 6, 160;" ::: "memory"); }
        }
        constexpr uint32_t db0 = desc_lo(OFF_B, 2304);
        const bool keep = role < 0;
        constexpr int IT_L = IT_END - NST;
        #pragma unroll
        for (int i = IT_G2; i <= IT_G2 + W1S; i++) {
            const uint32_t db = db0 + (i == IT_G2 + 4 ? OFF_X1 - OFF_B : (i % NST) * B_BYTES) / 16;
            if (i > IT_G2 || !PK2 || !g2rdy) mbar_wait(bars + 8 * (BAR_FULL + i % NST), (i / NST) & 1);
            WG_FENCE();
            #pragma unroll
            for (int k = 0; k < 4; k++) wgmma144<DHI_U>(d, da0 + (i % NST) * (A_BYTES / 16) + k * 128, db + k * 288, i > IT_G2 || k > 0 || keep);
            WG_COMMIT();
            if (W1L && i == IT_G2 && wg == 1) { fence_async_s(); asm volatile("bar.arrive 6, 160;" ::: "memory"); }
            if (i > IT_G2) { WG_WAIT(1); if (lead) mbar_arrive(bars + 8 * (BAR_EMPTY + (i - 1) % NST)); }
        }
        if (lead) mbar_arrive(bars + 8 * BAR_W1GO);
        const uint32_t ga0 = sm + OFF_GB + (144 * dt + 8 * q) * 2, tile = sm + OFF_X1 + wi * 4608, to = g * 288 + q * 16;
        #define QOFF(i_) (((i_) >> 2) * 2304 + 144 * (((i_) >> 1) & 1) + 64 * ((i_) & 1))
        #define SOFF(k_) (((k_) >> 1) * 2304 + 144 * ((k_) & 1) + 128 - 12 * q)
        #define DIDX(i_, k_) ((i_) < 8 ? 36 * (((i_) >> 1) & 1) + 16 * ((i_) & 1) + 4 * (k_) + 2 * ((i_) >> 2) : 36 * ((k_) & 1) + 32 + 2 * ((k_) >> 1))
        #define FIN(k_, f_) bfma2(g4.f_, pack_bf(d[DIDX(i, k_)], d[DIDX(i, k_) + 1]), xq[i].f_)
        uint4 xq[9];
        auto load_g = [&](int i) { uint4 r; if (i < 4) r = lds128(ga0 + QOFF(i)); else { r.x = r.z = lds32(ga0 + SOFF(0)); r.y = r.w = lds32(ga0 + SOFF(1)); } return r; };
        static_assert(W1S == 5 && (IT_G2 + 6) % NST == 4 && ((IT_G2 + 6) / NST) % 2 == 1 && IT_L == IT_G2 + 30, "loop structure");
        #pragma unroll 1
        for (int c = 0; c < 4; c++) {
            const uint32_t ph = c & 1, xa = tile + to; const bool xl = c == 3 && !owner;
            mma_block<DHI_U, 4>(d, bars, da0, db0, ph ^ 1); REL(3);
            mma_block<DHI_U, 5>(d, bars, da0, db0, ph ^ 1); REL(4);
            mma_block<DHI_U, 0>(d, bars, da0, db0, ph); REL(5);
            if (xl) { mbar_wait(bars + 8 * BAR_XT, 0); xq[0] = lds128(xa + QOFF(0)); xq[4] = lds128(xa + QOFF(4)); xq[1] = lds128(xa + QOFF(1)); }
            mma_block<DHI_U, 1>(d, bars, da0, db0, ph); REL(0);
            if (xl) { xq[5] = lds128(xa + QOFF(5)); xq[2] = lds128(xa + QOFF(2)); xq[6] = lds128(xa + QOFF(6)); }
            mma_block<DHI_U, 2>(d, bars, da0, db0, ph); REL(1);
            if (xl) { xq[3] = lds128(xa + QOFF(3)); xq[7] = lds128(xa + QOFF(7));
                      xq[8] = make_uint4(lds32(xa + SOFF(0)), lds32(xa + SOFF(1)), lds32(xa + SOFF(2)), lds32(xa + SOFF(3))); }
            mma_block<DHI_U, 3>(d, bars, da0, db0, ph); REL(2);
        }
        if (!owner && elect()) mbar_arrive_remote(mapa(bars + 8 * BAR_DONE, rank ^ 1));
        if (owner) { WG_WAIT(0); if (lead) mbar_arrive(bars + 8 * (BAR_EMPTY + (IT_L - 1) % NST)); bar_sync(7, 256); }
        #pragma unroll
        for (int i = IT_L; i < IT_END; i++) {
            mbar_wait(bars + 8 * (BAR_FULL + i % NST), (i / NST) & 1);
            WG_FENCE();
            #pragma unroll
            for (int k = 0; k < 4; k++) {
                if (i == IT_END - 1 && k == HOK) WG_COMMIT();
                wgmma144<DHI_U>(d, da0 + (i % NST) * (A_BYTES / 16) + k * 128, db0 + (i % NST) * (B_BYTES / 16) + k * 288, 1);
            }
            WG_COMMIT();
            if (i == IT_L) { WG_WAIT(1); if (lead && !owner) mbar_arrive(bars + 8 * (BAR_EMPTY + (IT_L - 1) % NST)); }
        }
        PROF0(9);
        mbar_wait(bars + 8 * BAR_GB, 0);
        if (!owner) {
            const uint32_t ra = mapa(tile + lane * 16, rank ^ 1), rb = mapa(bars + 8 * BAR_RECV, rank ^ 1);
            mbar_wait(bars + 8 * BAR_DONE, 0);
            uint4 gn = load_g(0);
            WG_WAIT(1);
            asm volatile("bar.arrive 7, 256;" ::: "memory");
            WG_WAIT(0);
            #pragma unroll
            for (int i = 0; i < 72; i++) d[i] = fmaf(bf_lo((i & 2) ? b2w1 : b2w0), 2.f, d[i]);
            #pragma unroll
            for (int j = 0; j < 5; j++) {
                const uint4 g4 = gn;
                if (j < 4) gn = load_g(j + 1);
                #pragma unroll
                for (int i = j < 4 ? j : 8; i < 9; i += 4) if (i < 8 || j == 4)
                    asm volatile("st.async.weak.shared::cluster.mbarrier::complete_tx::bytes.v4.b32 [%0], {%1,%2,%3,%4}, [%5];"
                        :: "r"(ra + i * 512), "r"(FIN(0, x)), "r"(FIN(1, y)), "r"(FIN(2, z)), "r"(FIN(3, w)), "r"(rb) : "memory");
            }
            PROF0(6);
            if (warp == 0) PROFDUMP();
            return;
        }
        PROF0(24);
        mbar_wait(bars + 8 * BAR_RECV, 0);
        #pragma unroll
        for (int i = 0; i < 9; i++) xq[i] = lds128(tile + lane * 16 + i * 512);
        uint4 gn = load_g(0);
        WG_WAIT(0);
        __syncwarp();
        PROF0(21);
        #pragma unroll
        for (int j = 0; j < 5; j++) {
            const uint4 g4 = gn;
            if (j < 4) gn = load_g(j + 1);
            #pragma unroll
            for (int i = j < 4 ? j : 8; i < 9; i += 4) if (i < 8 || j == 4) {
                const uint4 o = make_uint4(FIN(0, x), FIN(1, y), FIN(2, z), FIN(3, w));
                if (i < 8) sts128(tile + to + QOFF(i), o);
                else { sts32(tile + to + SOFF(0), o.x); sts32(tile + to + SOFF(1), o.y); sts32(tile + to + SOFF(2), o.z); sts32(tile + to + SOFF(3), o.w); }
            }
        }
        fence_async_s();
        __syncwarp();
        if (elect()) {
            asm volatile("cp.async.bulk.tensor.2d.global.shared::cta.bulk_group [%0, {%2, %3}], [%1];" :: "l"(&tm_o), "r"(tile), "r"(144 * dt), "r"(srow) : "memory");
            asm volatile("cp.async.bulk.commit_group;" ::: "memory");
            asm volatile("cp.async.bulk.wait_group.read 0;" ::: "memory");
        }
        PROF0(23);
        if (warp == 0) { __syncwarp(); PROFDUMP(); }
    }
}

typedef CUresult (*EncodeFn)(CUtensorMap*, CUtensorMapDataType, cuuint32_t, void*, const cuuint64_t*, const cuuint64_t*, const cuuint32_t*,
                             const cuuint32_t*, CUtensorMapInterleave, CUtensorMapSwizzle, CUtensorMapL2promotion, CUtensorMapFloatOOBfill);

void encode(EncodeFn fn, CUtensorMap* m, CUtensorMapDataType dt, int rank, const void* ptr, const cuuint64_t* dims, const cuuint64_t* strides,
            const cuuint32_t* box, CUtensorMapSwizzle sw, CUtensorMapL2promotion promo = CU_TENSOR_MAP_L2_PROMOTION_L2_128B) {
    const cuuint32_t es[5] = {1, 1, 1, 1, 1};
    fn(m, dt, rank, (void*)ptr, dims, strides, box, es, CU_TENSOR_MAP_INTERLEAVE_NONE, sw, promo, CU_TENSOR_MAP_FLOAT_OOB_FILL_NONE);
}

}

extern "C" void kernel_launch(void* const* d_in, const int* in_sizes, int n_in, void* d_out, int out_size) {
    (void)in_sizes; (void)n_in; (void)out_size;
    Params p;
    p.x = (const uint16_t*)d_in[0]; p.wr = (const uint16_t*)d_in[1]; p.wi = (const uint16_t*)d_in[2];
    p.w1 = (const uint16_t*)d_in[4]; p.b1 = (const uint16_t*)d_in[5]; p.w2 = (const uint16_t*)d_in[6]; p.b2 = (const uint16_t*)d_in[7];
    p.c = (const uint16_t*)d_in[8]; p.wmod = (const uint16_t*)d_in[9]; p.out = (uint16_t*)d_out;

    void* fnp = nullptr; cudaDriverEntryPointQueryResult qr;
    cudaGetDriverEntryPoint("cuTensorMapEncodeTiled", &fnp, cudaEnableDefault, &qr);
    EncodeFn fn = (EncodeFn)fnp;
    cudaGetSymbolAddress((void**)&p.scr, g_scr); cudaGetSymbolAddress((void**)&p.tab, g_tab);
    void* h3p = p.scr->h3;
    CUtensorMap tw1a, tw1b, tw2, th3a, th3b, twr, twi, twm, tt, ttx, to, th3s, tws;
    {
        const cuuint64_t dims[4] = {64, 16, 128, 72}, st[3] = {128ull * F_ * 2, (cuuint64_t)F_ * 2, 128};
        const cuuint32_t ba[4] = {64, 16, 4, 2}, bb[4] = {64, 16, 8, 1};
        encode(fn, &tw1a, CU_TENSOR_MAP_DATA_TYPE_BFLOAT16, 4, p.w1, dims, st, ba, CU_TENSOR_MAP_SWIZZLE_128B);
        encode(fn, &tw1b, CU_TENSOR_MAP_DATA_TYPE_BFLOAT16, 4, p.w1, dims, st, bb, CU_TENSOR_MAP_SWIZZLE_128B);
    }
    {
        const cuuint64_t dims[3] = {64, F_, 32}, st[2] = {(cuuint64_t)S_ * 2, 128};
        const cuuint32_t bx[3] = {64, 64, 2};
        encode(fn, &tw2, CU_TENSOR_MAP_DATA_TYPE_BFLOAT16, 3, p.w2, dims, st, bx, CU_TENSOR_MAP_SWIZZLE_128B);
    }
    {
        const cuuint64_t dims[3] = {64, 72, 128}, st[2] = {256, 18432};
        const cuuint32_t ba[3] = {64, 18, 4}, bb[3] = {64, 9, 8};
        encode(fn, &th3a, CU_TENSOR_MAP_DATA_TYPE_UINT32, 3, h3p, dims, st, ba, CU_TENSOR_MAP_SWIZZLE_NONE);
        encode(fn, &th3b, CU_TENSOR_MAP_DATA_TYPE_UINT32, 3, h3p, dims, st, bb, CU_TENSOR_MAP_SWIZZLE_NONE);
    }
    {
        const cuuint64_t dims[4] = {32, 72, 2, 128}, st[3] = {256, 128, 18432};
        const cuuint32_t bx[4] = {32, 72, 2, 1};
        encode(fn, &th3s, CU_TENSOR_MAP_DATA_TYPE_UINT32, 4, h3p, dims, st, bx, CU_TENSOR_MAP_SWIZZLE_128B, CU_TENSOR_MAP_L2_PROMOTION_NONE);
    }
    {
        const cuuint64_t dims[3] = {4624, 4, 32}, st[2] = {9248 * 32, 9248};
        const cuuint32_t bx[3] = {56, 4, 32};
        encode(fn, &twr, CU_TENSOR_MAP_DATA_TYPE_BFLOAT16, 3, p.wr, dims, st, bx, CU_TENSOR_MAP_SWIZZLE_NONE);
        encode(fn, &twi, CU_TENSOR_MAP_DATA_TYPE_BFLOAT16, 3, p.wi, dims, st, bx, CU_TENSOR_MAP_SWIZZLE_NONE);
    }
    {
        const cuuint64_t dims[2] = {3456, 576}, st[1] = {6912};
        const cuuint32_t bx[2] = {32, 144};
        encode(fn, &tws, CU_TENSOR_MAP_DATA_TYPE_BFLOAT16, 2, p.wmod, dims, st, bx, CU_TENSOR_MAP_SWIZZLE_64B);
    }
    {
        const cuuint64_t dims[3] = {64, 576, 54}, st[2] = {6912, 128};
        const cuuint32_t bx[3] = {64, 32, 7};
        encode(fn, &twm, CU_TENSOR_MAP_DATA_TYPE_BFLOAT16, 3, p.wmod, dims, st, bx, CU_TENSOR_MAP_SWIZZLE_128B);
    }
    {
        const cuuint64_t dims[2] = {TP, 128}, st[1] = {TP * 4};
        const cuuint32_t ba[2] = {32, 128}, bb[2] = {8, 128};
        encode(fn, &tt, CU_TENSOR_MAP_DATA_TYPE_UINT32, 2, p.scr->T, dims, st, ba, CU_TENSOR_MAP_SWIZZLE_128B, CU_TENSOR_MAP_L2_PROMOTION_NONE);
        encode(fn, &ttx, CU_TENSOR_MAP_DATA_TYPE_UINT32, 2, p.scr->T, dims, st, bb, CU_TENSOR_MAP_SWIZZLE_32B, CU_TENSOR_MAP_L2_PROMOTION_NONE);
    }
    {
        const cuuint64_t dims[2] = {D_, S_}, st[1] = {D_ * 2};
        const cuuint32_t bx[2] = {144, 16};
        encode(fn, &to, CU_TENSOR_MAP_DATA_TYPE_BFLOAT16, 2, p.out, dims, st, bx, CU_TENSOR_MAP_SWIZZLE_NONE, CU_TENSOR_MAP_L2_PROMOTION_NONE);
    }
    cudaFuncSetAttribute(fused_kernel, cudaFuncAttributeMaxDynamicSharedMemorySize, SMEM_BYTES);
    cudaLaunchConfig_t cfg = {};
    cfg.gridDim = dim3(NCTA); cfg.blockDim = dim3(NTHR); cfg.dynamicSmemBytes = SMEM_BYTES; cfg.stream = cudaStreamPerThread;
    cudaLaunchAttribute at[1];
    at[0].id = cudaLaunchAttributeClusterDimension; at[0].val.clusterDim.x = 2; at[0].val.clusterDim.y = 1; at[0].val.clusterDim.z = 1;
    cfg.attrs = at; cfg.numAttrs = 1;
    int nclusters = 0;
    cudaOccupancyMaxActiveClusters(&nclusters, fused_kernel, &cfg);
    at[0].id = cudaLaunchAttributeCooperative; at[0].val.cooperative = 1;
    cfg.numAttrs = nclusters * 2 >= NCTA ? 0 : 1;
    cudaLaunchKernelEx(&cfg, fused_kernel, p, tw1a, tw1b, tw2, th3a, th3b, twr, twi, twm, tt, ttx, to, th3s, tws);
}
```
